```python
import torch

def _softmax(x, axis=-1):
    return torch.softmax(x, dim=axis)
def _gelu(x):
    return torch.nn.functional.gelu(x, approximate="tanh")
def _silu(x):
    return torch.nn.functional.silu(x)
def _sigmoid(x):
    return torch.sigmoid(x)
def _layernorm(x, axis=-1, eps=1e-5):
    m = x.mean(dim=axis, keepdim=True)
    v = x.var(dim=axis, keepdim=True, unbiased=False)
    return (x - m) / torch.sqrt(v + eps)
def _scatter_add(tgt, idx, src, axis=0):
    return tgt.clone().index_add_(axis, idx, src)
def _segment_sum(src, seg, n):
    out = torch.zeros((n,) + src.shape[1:], dtype=src.dtype)
    return out.index_add_(0, seg, src)
def _pad(x, pw):
    flat = tuple(v for pair in reversed(pw) for v in pair)
    return torch.nn.functional.pad(x, flat)

kernel_name = 'gated_mix__ssm_conv_h3__sliding_local_dilated__prompt'

def setup_inputs():

    _w = (lambda a: (lambda t: t.to(torch.bfloat16) if t.is_floating_point() else t)(torch.as_tensor(a)))
    def _A_setup():
        B, S, D = 1, 2048, 640
        ks = 4
        return {
            "q": _w((lambda *s: torch.randn(*s, dtype=torch.bfloat16) * 0.05)(B, S, D)),
            "k": _w((lambda *s: torch.randn(*s, dtype=torch.bfloat16) * 0.8)(B, S, D)),
            "v": _w((lambda *s: torch.randn(*s, dtype=torch.bfloat16) * 0.8)(B, S, D)),
            "shift_k": _w((lambda *s: torch.randn(*s, dtype=torch.bfloat16) * 0.8)(D, ks) * 0.5),
            "ssm_k": _w((lambda *s: torch.randn(*s, dtype=torch.bfloat16) * 3.2)(D, S) * (1.0 / S ** 0.5)),
            "ssm_D": _w((lambda *s: torch.randn(*s, dtype=torch.bfloat16) * 0.8)(D)),
        }
    _A_in = _A_setup()

    def _B_setup():
        B, S, D = 1, 2048, 640
        return {
            "x": _w((lambda *s: torch.randn(*s, dtype=torch.bfloat16) * 0.05)(B, S, D)),
            "wqkv": _w((lambda *s: torch.randn(*s, dtype=torch.bfloat16) * 0.8)(D, 3 * D)),
            "wo": _w((lambda *s: torch.randn(*s, dtype=torch.bfloat16) * 0.05)(D, D)),
        }
    _B_in = _B_setup()

    return {
        "A_q": _A_in["q"],
        "A_k": _A_in["k"],
        "A_v": _A_in["v"],
        "A_shift_k": _A_in["shift_k"],
        "A_ssm_k": _A_in["ssm_k"],
        "A_ssm_D": _A_in["ssm_D"],
        "B_x": _B_in["x"],
        "B_wqkv": _B_in["wqkv"],
        "B_wo": _B_in["wo"],
        "gate_w": _w((lambda *s: torch.randn(*s, dtype=torch.bfloat16) * 0.05)(640) * 16.0),
    }

def reference(A_q, A_k, A_v, A_shift_k, A_ssm_k, A_ssm_D, B_x, B_wqkv, B_wo, gate_w):
    def _A_ref(q, k, v, shift_k, ssm_k, ssm_D):
        B, S, D = q.shape
        ks = shift_k.shape[-1]
        k_pad = _pad(k, ((0, 0), (ks - 1, 0), (0, 0)))
        k_shift = torch.zeros_like(k)
        for t in range(ks):
            k_shift = k_shift + k_pad[:, t:t + S, :] * shift_k[:, ks - 1 - t][None, None, :]
        kv = k_shift * v
        L = 2 * S
        kv_pad = _pad(kv, ((0, 0), (0, S), (0, 0)))
        kf_pad = _pad(ssm_k, ((0, 0), (0, S)))
        kv_f = (lambda x, axes=(-2,-1): torch.fft.rfft2(x.float(), dim=axes))(kv_pad[:, None, :, :], axes=(1, 2))
        kf_f = (lambda x, axes=(-2,-1): torch.fft.rfft2(x.float(), dim=axes))(kf_pad[:, None, :], axes=(1, 2))
        kf_f = (lambda x, *d: x.permute(*d))(kf_f, 1, 2, 0)
        y_f = kv_f * kf_f[None, :, :, :]
        y = (lambda x, s, axes=(-2,-1): torch.fft.irfft2(x, s=s, dim=axes).to(torch.bfloat16))(y_f, (1, L), axes=(1, 2))[:, 0, :S, :]
        y = y + kv * ssm_D[None, None, :]
        return q * y

    def _B_ref(x, wqkv, wo):
        B, S, D = x.shape
        H = 32; Dh = D // H
        W, dil = 8, 2
        qkv = (lambda x, *d: x.permute(*d))((x @ wqkv).reshape(B, S, 3, H, Dh), 2, 0, 3, 1, 4)
        q, k, v = qkv[0], qkv[1], qkv[2]
        scale = Dh ** -0.5
        pos = torch.arange(S)
        off = torch.arange(W) * dil
        idx = pos[:, None] - off[None, :]
        mask = idx >= 0
        idx_c = torch.where(mask, idx, 0).reshape(-1)
        kg = k[:, :, idx_c, :].reshape(B, H, S, W, Dh)
        vg = v[:, :, idx_c, :].reshape(B, H, S, W, Dh)
        logits = torch.einsum("bhsd,bhswd->bhsw", q, kg) * scale
        logits = torch.where(mask[None, None, :, :], logits, -1e9)
        attn = _softmax(logits, axis=-1)
        o = torch.einsum("bhsw,bhswd->bhsd", attn, vg)
        return (lambda x, *d: x.permute(*d))(o, 0, 2, 1, 3).reshape(B, S, D) @ wo

    x = A_q
    g = _sigmoid((x * gate_w).sum(-1, keepdims=True))
    a = _A_ref(x, A_k, A_v, A_shift_k, A_ssm_k, A_ssm_D)
    b = _B_ref(x, B_wqkv, B_wo)
    return g * a + (1 - g) * b
```

```cpp
#include <cuda_runtime.h>
#include <cuda_bf16.h>
#include <cuda.h>
#include <stdint.h>

#define DEVI __device__ __forceinline__
#define PT1 900
#define PTD 400
#define PTE 100
#define KT0 1500
#define KTD 1500
#define RC 192
#define RH 96
#define RP 32
#define SNOOZE 100
#define P1U 7
#define LEAD 3

DEVI uint32_t smem_u32(const void* p) { return (uint32_t)__cvta_generic_to_shared(p); }
DEVI void wg_fence() { asm volatile("wgmma.fence.sync.aligned;" ::: "memory"); }
DEVI void wg_commit() { asm volatile("wgmma.commit_group.sync.aligned;" ::: "memory"); }
template <int N> DEVI void wg_wait() { asm volatile("wgmma.wait_group.sync.aligned %0;" ::"n"(N) : "memory"); }
template <int S> DEVI void fence_regs(float (&d)[S]) {
#pragma unroll
  for (int i = 0; i < S; i++) asm volatile("" : "+f"(d[i])::"memory");
}
DEVI uint64_t mkdesc(uint32_t addr, uint32_t lbo, uint32_t sbo, int swz) {
  return (uint64_t)((addr & 0x3FFFF) >> 4) | ((uint64_t)(lbo >> 4) << 16) | ((uint64_t)(sbo >> 4) << 32) | ((uint64_t)swz << 62);
}
DEVI void mbar_init(uint32_t bar, uint32_t cnt) { asm volatile("mbarrier.init.shared::cta.b64 [%0], %1;" ::"r"(bar), "r"(cnt) : "memory"); }
DEVI void mbar_expect_tx(uint32_t bar, uint32_t bytes) { asm volatile("mbarrier.arrive.expect_tx.shared::cta.b64 _, [%0], %1;" ::"r"(bar), "r"(bytes) : "memory"); }
DEVI void mbar_arrive(uint32_t bar) { asm volatile("mbarrier.arrive.shared::cta.b64 _, [%0];" ::"r"(bar) : "memory"); }
DEVI void mbar_wait(uint32_t bar, uint32_t parity) {
  asm volatile("{\n.reg .pred p;\nLAB_WAIT:\nmbarrier.try_wait.parity.shared::cta.b64 p, [%0], %1;\n@!p bra LAB_WAIT;\n}" ::"r"(bar), "r"(parity) : "memory");
}
DEVI void mbar_wait_wd(uint32_t bar, uint32_t parity, uint32_t t0) {
  asm volatile("{\n.reg .pred p;\n.reg .u32 c;\nLAB_WAIT:\nmbarrier.try_wait.parity.shared::cta.b64 p, [%0], %1;\n@p bra DONE;\nmov.u32 c, %%clock;\nsub.u32 c, c, %2;\nsetp.lt.u32 p, c, 0x70000000;\n@p bra LAB_WAIT;\ntrap;\nDONE:\n}" ::"r"(bar), "r"(parity), "r"(t0) : "memory");
}
DEVI void flag_wait(const unsigned* p, unsigned target) {
  asm volatile("{\n.reg .pred p;\n.reg .s32 v;\nLAB_WAIT:\nld.relaxed.gpu.global.u32 v, [%0];\nsub.s32 v, v, %1;\nsetp.lt.s32 p, v, 0;\n@p bra LAB_WAIT;\n}" ::"l"(p), "r"(target) : "memory");
}
DEVI void flag_add(unsigned* p, unsigned v) { asm volatile("red.relaxed.gpu.global.add.u32 [%0], %1;" ::"l"(p), "r"(v) : "memory"); }
DEVI void fence_async_smem() { asm volatile("fence.proxy.async.shared::cta;" ::: "memory"); }
DEVI bool elect_one() { uint32_t p; asm volatile("{\n.reg .pred P;\nelect.sync _|P, 0xffffffff;\nselp.u32 %0, 1, 0, P;\n}" : "=r"(p)); return p; }
DEVI void bar_sync(int id, int n) { asm volatile("bar.sync %0, %1;" ::"r"(id), "r"(n) : "memory"); }
DEVI void bar_arrive(int id, int n) { asm volatile("bar.arrive %0, %1;" ::"r"(id), "r"(n) : "memory"); }
DEVI void tma2(uint32_t dst, const CUtensorMap* m, int c0, int c1, uint32_t bar) {
  asm volatile("cp.async.bulk.tensor.2d.shared::cluster.global.mbarrier::complete_tx::bytes [%0], [%1, {%3, %4}], [%2];" ::"r"(dst), "l"(m), "r"(bar), "r"(c0), "r"(c1) : "memory");
}
DEVI void tma3(uint32_t dst, const CUtensorMap* m, int c0, int c1, int c2, uint32_t bar) {
  asm volatile("cp.async.bulk.tensor.3d.shared::cluster.global.mbarrier::complete_tx::bytes [%0], [%1, {%3, %4, %5}], [%2];" ::"r"(dst), "l"(m), "r"(bar), "r"(c0), "r"(c1), "r"(c2) : "memory");
}
DEVI void tma3_mc(uint32_t dst, const CUtensorMap* m, int c0, int c1, int c2, uint32_t bar) {
  asm volatile("cp.async.bulk.tensor.3d.shared::cluster.global.mbarrier::complete_tx::bytes.multicast::cluster [%0], [%1, {%3, %4, %5}], [%2], %6;" ::"r"(dst), "l"(m), "r"(bar), "r"(c0), "r"(c1), "r"(c2), "h"((uint16_t)3) : "memory");
}
DEVI void tma2_mc(uint32_t dst, const CUtensorMap* m, int c0, int c1, uint32_t bar) {
  asm volatile("cp.async.bulk.tensor.2d.shared::cluster.global.mbarrier::complete_tx::bytes.multicast::cluster [%0], [%1, {%3, %4}], [%2], %5;" ::"r"(dst), "l"(m), "r"(bar), "r"(c0), "r"(c1), "h"((uint16_t)3) : "memory");
}
DEVI void mbar_arrive_remote(uint32_t bar, uint32_t cta) {
  asm volatile("{\n.reg .b32 ra;\nmapa.shared::cluster.u32 ra, %0, %1;\nmbarrier.arrive.shared::cluster.b64 _, [ra];\n}" ::"r"(bar), "r"(cta) : "memory");
}
DEVI void tma3_store(const CUtensorMap* m, int c0, int c1, int c2, uint32_t src) {
  asm volatile("cp.async.bulk.tensor.3d.global.shared::cta.bulk_group [%0, {%2, %3, %4}], [%1];" ::"l"(m), "r"(src), "r"(c0), "r"(c1), "r"(c2) : "memory");
}
DEVI void bulk_load(uint32_t dst, const void* src, uint32_t bytes, uint32_t bar) {
  asm volatile("cp.async.bulk.shared::cluster.global.mbarrier::complete_tx::bytes [%0], [%1], %2, [%3];" ::"r"(dst), "l"(src), "r"(bytes), "r"(bar) : "memory");
}
DEVI void bulk_store(void* dst, uint32_t src, uint32_t bytes) {
  asm volatile("cp.async.bulk.global.shared::cta.bulk_group [%0], [%1], %2;" ::"l"(dst), "r"(src), "r"(bytes) : "memory");
}
DEVI void pf_l2(const void* p) { asm volatile("prefetch.global.L2 [%0];" ::"l"(p)); }
template <int OFF> DEVI uint32_t ldg_v(const void* p) { uint32_t v; asm volatile("ld.volatile.global.b32 %0, [%1 + %2];" : "=r"(v) : "l"(p), "n"(OFF)); return v; }
DEVI void bulk_commit() { asm volatile("cp.async.bulk.commit_group;" ::: "memory"); }
DEVI void bulk_wait_all() { asm volatile("cp.async.bulk.wait_group 0;" ::: "memory"); }
DEVI void bulk_wait_read() { asm volatile("cp.async.bulk.wait_group.read 0;" ::: "memory"); }
template <int R> DEVI void reg_inc() { asm volatile("setmaxnreg.inc.sync.aligned.u32 %0;" ::"n"(R)); }
template <int R> DEVI void reg_dec() { asm volatile("setmaxnreg.dec.sync.aligned.u32 %0;" ::"n"(R)); }
DEVI uint32_t prmt(uint32_t a, uint32_t b, uint32_t s) { uint32_t r; asm("prmt.b32 %0,%1,%2,%3;" : "=r"(r) : "r"(a), "r"(b), "r"(s)); return r; }
DEVI uint32_t lds32(uint32_t a) { uint32_t r; asm volatile("ld.shared.b32 %0,[%1];" : "=r"(r) : "r"(a)); return r; }
DEVI void sts32(uint32_t a, uint32_t x) { asm volatile("st.shared.b32 [%0],%1;" ::"r"(a), "r"(x) : "memory"); }
DEVI void sts128(uint32_t a, uint32_t x, uint32_t y, uint32_t z, uint32_t w) { asm volatile("st.shared.v4.b32 [%0],{%1,%2,%3,%4};" ::"r"(a), "r"(x), "r"(y), "r"(z), "r"(w) : "memory"); }
DEVI void sts128v(uint32_t a, uint32_t x, uint32_t y, uint32_t z, uint32_t w) { asm volatile("st.volatile.shared.v4.b32 [%0],{%1,%2,%3,%4};" ::"r"(a), "r"(x), "r"(y), "r"(z), "r"(w) : "memory"); }
DEVI void lds128(uint32_t a, uint32_t& x, uint32_t& y, uint32_t& z, uint32_t& w) { asm volatile("ld.shared.v4.b32 {%0,%1,%2,%3},[%4];" : "=r"(x), "=r"(y), "=r"(z), "=r"(w) : "r"(a) : "memory"); }
DEVI void ldsm4(uint32_t& r0, uint32_t& r1, uint32_t& r2, uint32_t& r3, uint32_t addr) {
  asm volatile("ldmatrix.sync.aligned.m8n8.x4.shared.b16 {%0,%1,%2,%3}, [%4];" : "=r"(r0), "=r"(r1), "=r"(r2), "=r"(r3) : "r"(addr) : "memory");
}
DEVI void ldsm4t(uint32_t& r0, uint32_t& r1, uint32_t& r2, uint32_t& r3, uint32_t addr) {
  asm volatile("ldmatrix.sync.aligned.m8n8.x4.trans.shared.b16 {%0,%1,%2,%3}, [%4];" : "=r"(r0), "=r"(r1), "=r"(r2), "=r"(r3) : "r"(addr) : "memory");
}
DEVI void stsm4(uint32_t addr, uint32_t r0, uint32_t r1, uint32_t r2, uint32_t r3) {
  asm volatile("stmatrix.sync.aligned.m8n8.x4.shared.b16 [%0], {%1,%2,%3,%4};" ::"r"(addr), "r"(r0), "r"(r1), "r"(r2), "r"(r3) : "memory");
}
DEVI void stsm4t(uint32_t addr, uint32_t r0, uint32_t r1, uint32_t r2, uint32_t r3) {
  asm volatile("stmatrix.sync.aligned.m8n8.x4.trans.shared.b16 [%0], {%1,%2,%3,%4};" ::"r"(addr), "r"(r0), "r"(r1), "r"(r2), "r"(r3) : "memory");
}
DEVI uint32_t movm(uint32_t a) { uint32_t r; asm volatile("movmatrix.sync.aligned.m8n8.trans.b16 %0, %1;" : "=r"(r) : "r"(a)); return r; }
DEVI uint32_t pack_bf16(float lo, float hi) { uint32_t r; asm("cvt.rn.bf16x2.f32 %0, %1, %2;" : "=r"(r) : "f"(hi), "f"(lo)); return r; }
DEVI uint32_t hmul2(uint32_t a, uint32_t b) { uint32_t r; asm("mul.rn.bf16x2 %0,%1,%2;" : "=r"(r) : "r"(a), "r"(b)); return r; }
DEVI uint32_t hadd2(uint32_t a, uint32_t b) { uint32_t r; asm("add.rn.bf16x2 %0,%1,%2;" : "=r"(r) : "r"(a), "r"(b)); return r; }
DEVI float bf_lo(uint32_t a) { return __uint_as_float(prmt(a, 0, 0x1044)); }
DEVI float bf_hi(uint32_t a) { return __uint_as_float(a & 0xFFFF0000u); }
DEVI void mma16(float (&c)[4], uint32_t a0, uint32_t a1, uint32_t a2, uint32_t a3, uint32_t b0, uint32_t b1) {
  asm("mma.sync.aligned.m16n8k16.row.col.f32.bf16.bf16.f32 {%0,%1,%2,%3},{%4,%5,%6,%7},{%8,%9},{%0,%1,%2,%3};"
      : "+f"(c[0]), "+f"(c[1]), "+f"(c[2]), "+f"(c[3]) : "r"(a0), "r"(a1), "r"(a2), "r"(a3), "r"(b0), "r"(b1));
}
DEVI void mma8(float (&c)[4], uint32_t a0, uint32_t a1, uint32_t b0) {
  asm("mma.sync.aligned.m16n8k8.row.col.f32.bf16.bf16.f32 {%0,%1,%2,%3},{%4,%5},{%6},{%0,%1,%2,%3};"
      : "+f"(c[0]), "+f"(c[1]), "+f"(c[2]), "+f"(c[3]) : "r"(a0), "r"(a1), "r"(b0));
}
DEVI float ex2(float x) { float r; asm("ex2.approx.ftz.f32 %0, %1;" : "=f"(r) : "f"(x)); return r; }

DEVI uint32_t clk() { uint32_t c; asm volatile("mov.u32 %0, %%clock;" : "=r"(c)); return c; }
DEVI void wait_until(uint32_t t0, int dt) { while ((int)(clk() - t0) < dt) __nanosleep(40); }
DEVI void spin_until(uint32_t t0, int dt) { while ((int)(clk() - t0) < dt) {} }
DEVI uint32_t hfma2(uint32_t a, uint32_t b, uint32_t c) { uint32_t r; asm("fma.rn.bf16x2 %0,%1,%2,%3;" : "=r"(r) : "r"(a), "r"(b), "r"(c)); return r; }
DEVI void bar_sync_p(int on, int id, int n) { asm volatile("{\n.reg .pred p;\nsetp.ne.b32 p, %0, 0;\n@p bar.sync %1, %2;\n}" ::"r"(on), "r"(id), "r"(n) : "memory"); }
DEVI void bar_arrive_p(int on, int id, int n) { asm volatile("{\n.reg .pred p;\nsetp.ne.b32 p, %0, 0;\n@p bar.arrive %1, %2;\n}" ::"r"(on), "r"(id), "r"(n) : "memory"); }
DEVI void mbar_arrive_p(int on, uint32_t bar) { asm volatile("{\n.reg .pred p;\nsetp.ne.b32 p, %1, 0;\n@p mbarrier.arrive.shared::cta.b64 _, [%0];\n}" ::"r"(bar), "r"(on) : "memory"); }
DEVI void mbar_arrive2_p(int on, uint32_t bar, uint32_t rbar) {
  asm volatile("{\n.reg .pred p;\nsetp.ne.b32 p, %2, 0;\n@p mbarrier.arrive.shared::cta.b64 _, [%0];\n@p mbarrier.arrive.shared::cluster.b64 _, [%1];\n}" ::"r"(bar), "r"(rbar), "r"(on) : "memory");
}
DEVI uint32_t mapa(uint32_t a, uint32_t cta) { uint32_t r; asm("mapa.shared::cluster.u32 %0, %1, %2;" : "=r"(r) : "r"(a), "r"(cta)); return r; }
DEVI void st_async128(uint32_t a, uint32_t x, uint32_t y, uint32_t z, uint32_t w, uint32_t bar) {
  asm volatile("st.async.weak.shared::cluster.mbarrier::complete_tx::bytes.v4.b32 [%0], {%1,%2,%3,%4}, [%5];" ::"r"(a), "r"(x), "r"(y), "r"(z), "r"(w), "r"(bar) : "memory");
}

template<int OFF, int TB, int S> __device__ __forceinline__ void wgmma_rs_n192(float (&d)[S], uint32_t a0, uint32_t a1, uint32_t a2, uint32_t a3, uint64_t db, int sd) {
  asm volatile("{\n.reg .pred p;\nsetp.ne.b32 p, %101, 0;\n"
    "wgmma.mma_async.sync.aligned.m64n192k16.f32.bf16.bf16 {%0, %1, %2, %3, %4, %5, %6, %7, %8, %9, %10, %11, %12, %13, %14, %15, %16, %17, %18, %19, %20, %21, %22, %23, %24, %25, %26, %27, %28, %29, %30, %31, %32, %33, %34, %35, %36, %37, %38, %39, %40, %41, %42, %43, %44, %45, %46, %47, %48, %49, %50, %51, %52, %53, %54, %55, %56, %57, %58, %59, %60, %61, %62, %63, %64, %65, %66, %67, %68, %69, %70, %71, %72, %73, %74, %75, %76, %77, %78, %79, %80, %81, %82, %83, %84, %85, %86, %87, %88, %89, %90, %91, %92, %93, %94, %95}, {%96, %97, %98, %99}, %100, p, 1, 1, %102;\n}\n"
    : "+f"(d[OFF+0]), "+f"(d[OFF+1]), "+f"(d[OFF+2]), "+f"(d[OFF+3]), "+f"(d[OFF+4]), "+f"(d[OFF+5]), "+f"(d[OFF+6]), "+f"(d[OFF+7]), "+f"(d[OFF+8]), "+f"(d[OFF+9]), "+f"(d[OFF+10]), "+f"(d[OFF+11]), "+f"(d[OFF+12]), "+f"(d[OFF+13]), "+f"(d[OFF+14]), "+f"(d[OFF+15]), "+f"(d[OFF+16]), "+f"(d[OFF+17]), "+f"(d[OFF+18]), "+f"(d[OFF+19]), "+f"(d[OFF+20]), "+f"(d[OFF+21]), "+f"(d[OFF+22]), "+f"(d[OFF+23]), "+f"(d[OFF+24]), "+f"(d[OFF+25]), "+f"(d[OFF+26]), "+f"(d[OFF+27]), "+f"(d[OFF+28]), "+f"(d[OFF+29]), "+f"(d[OFF+30]), "+f"(d[OFF+31]), "+f"(d[OFF+32]), "+f"(d[OFF+33]), "+f"(d[OFF+34]), "+f"(d[OFF+35]), "+f"(d[OFF+36]), "+f"(d[OFF+37]), "+f"(d[OFF+38]), "+f"(d[OFF+39]), "+f"(d[OFF+40]), "+f"(d[OFF+41]), "+f"(d[OFF+42]), "+f"(d[OFF+43]), "+f"(d[OFF+44]), "+f"(d[OFF+45]), "+f"(d[OFF+46]), "+f"(d[OFF+47]), "+f"(d[OFF+48]), "+f"(d[OFF+49]), "+f"(d[OFF+50]), "+f"(d[OFF+51]), "+f"(d[OFF+52]), "+f"(d[OFF+53]), "+f"(d[OFF+54]), "+f"(d[OFF+55]), "+f"(d[OFF+56]), "+f"(d[OFF+57]), "+f"(d[OFF+58]), "+f"(d[OFF+59]), "+f"(d[OFF+60]), "+f"(d[OFF+61]), "+f"(d[OFF+62]), "+f"(d[OFF+63]), "+f"(d[OFF+64]), "+f"(d[OFF+65]), "+f"(d[OFF+66]), "+f"(d[OFF+67]), "+f"(d[OFF+68]), "+f"(d[OFF+69]), "+f"(d[OFF+70]), "+f"(d[OFF+71]), "+f"(d[OFF+72]), "+f"(d[OFF+73]), "+f"(d[OFF+74]), "+f"(d[OFF+75]), "+f"(d[OFF+76]), "+f"(d[OFF+77]), "+f"(d[OFF+78]), "+f"(d[OFF+79]), "+f"(d[OFF+80]), "+f"(d[OFF+81]), "+f"(d[OFF+82]), "+f"(d[OFF+83]), "+f"(d[OFF+84]), "+f"(d[OFF+85]), "+f"(d[OFF+86]), "+f"(d[OFF+87]), "+f"(d[OFF+88]), "+f"(d[OFF+89]), "+f"(d[OFF+90]), "+f"(d[OFF+91]), "+f"(d[OFF+92]), "+f"(d[OFF+93]), "+f"(d[OFF+94]), "+f"(d[OFF+95]) : "r"(a0), "r"(a1), "r"(a2), "r"(a3), "l"(db), "r"(sd), "n"(TB));
}
template<int OFF, int TB, int S> __device__ __forceinline__ void wgmma_rs_n48(float (&d)[S], uint32_t a0, uint32_t a1, uint32_t a2, uint32_t a3, uint64_t db, int sd) {
  asm volatile("{\n.reg .pred p;\nsetp.ne.b32 p, %29, 0;\n"
    "wgmma.mma_async.sync.aligned.m64n48k16.f32.bf16.bf16 {%0, %1, %2, %3, %4, %5, %6, %7, %8, %9, %10, %11, %12, %13, %14, %15, %16, %17, %18, %19, %20, %21, %22, %23}, {%24, %25, %26, %27}, %28, p, 1, 1, %30;\n}\n"
    : "+f"(d[OFF+0]), "+f"(d[OFF+1]), "+f"(d[OFF+2]), "+f"(d[OFF+3]), "+f"(d[OFF+4]), "+f"(d[OFF+5]), "+f"(d[OFF+6]), "+f"(d[OFF+7]), "+f"(d[OFF+8]), "+f"(d[OFF+9]), "+f"(d[OFF+10]), "+f"(d[OFF+11]), "+f"(d[OFF+12]), "+f"(d[OFF+13]), "+f"(d[OFF+14]), "+f"(d[OFF+15]), "+f"(d[OFF+16]), "+f"(d[OFF+17]), "+f"(d[OFF+18]), "+f"(d[OFF+19]), "+f"(d[OFF+20]), "+f"(d[OFF+21]), "+f"(d[OFF+22]), "+f"(d[OFF+23]) : "r"(a0), "r"(a1), "r"(a2), "r"(a3), "l"(db), "r"(sd), "n"(TB));
}
template<int OFF, int TB, int S> __device__ __forceinline__ void wgmma_rs_n16(float (&d)[S], uint32_t a0, uint32_t a1, uint32_t a2, uint32_t a3, uint64_t db, int sd) {
  asm volatile("{\n.reg .pred p;\nsetp.ne.b32 p, %13, 0;\n"
    "wgmma.mma_async.sync.aligned.m64n16k16.f32.bf16.bf16 {%0, %1, %2, %3, %4, %5, %6, %7}, {%8, %9, %10, %11}, %12, p, 1, 1, %14;\n}\n"
    : "+f"(d[OFF+0]), "+f"(d[OFF+1]), "+f"(d[OFF+2]), "+f"(d[OFF+3]), "+f"(d[OFF+4]), "+f"(d[OFF+5]), "+f"(d[OFF+6]), "+f"(d[OFF+7]) : "r"(a0), "r"(a1), "r"(a2), "r"(a3), "l"(db), "r"(sd), "n"(TB));
}
template<int OFF, int TA, int TB, int S> __device__ __forceinline__ void wgmma_ss_n160(float (&d)[S], uint64_t da, uint64_t db, int sd) {
  asm volatile("{\n.reg .pred p;\nsetp.ne.b32 p, %82, 0;\n"
    "wgmma.mma_async.sync.aligned.m64n160k16.f32.bf16.bf16 {%0, %1, %2, %3, %4, %5, %6, %7, %8, %9, %10, %11, %12, %13, %14, %15, %16, %17, %18, %19, %20, %21, %22, %23, %24, %25, %26, %27, %28, %29, %30, %31, %32, %33, %34, %35, %36, %37, %38, %39, %40, %41, %42, %43, %44, %45, %46, %47, %48, %49, %50, %51, %52, %53, %54, %55, %56, %57, %58, %59, %60, %61, %62, %63, %64, %65, %66, %67, %68, %69, %70, %71, %72, %73, %74, %75, %76, %77, %78, %79}, %80, %81, p, 1, 1, %83, %84;\n}\n"
    : "+f"(d[OFF+0]), "+f"(d[OFF+1]), "+f"(d[OFF+2]), "+f"(d[OFF+3]), "+f"(d[OFF+4]), "+f"(d[OFF+5]), "+f"(d[OFF+6]), "+f"(d[OFF+7]), "+f"(d[OFF+8]), "+f"(d[OFF+9]), "+f"(d[OFF+10]), "+f"(d[OFF+11]), "+f"(d[OFF+12]), "+f"(d[OFF+13]), "+f"(d[OFF+14]), "+f"(d[OFF+15]), "+f"(d[OFF+16]), "+f"(d[OFF+17]), "+f"(d[OFF+18]), "+f"(d[OFF+19]), "+f"(d[OFF+20]), "+f"(d[OFF+21]), "+f"(d[OFF+22]), "+f"(d[OFF+23]), "+f"(d[OFF+24]), "+f"(d[OFF+25]), "+f"(d[OFF+26]), "+f"(d[OFF+27]), "+f"(d[OFF+28]), "+f"(d[OFF+29]), "+f"(d[OFF+30]), "+f"(d[OFF+31]), "+f"(d[OFF+32]), "+f"(d[OFF+33]), "+f"(d[OFF+34]), "+f"(d[OFF+35]), "+f"(d[OFF+36]), "+f"(d[OFF+37]), "+f"(d[OFF+38]), "+f"(d[OFF+39]), "+f"(d[OFF+40]), "+f"(d[OFF+41]), "+f"(d[OFF+42]), "+f"(d[OFF+43]), "+f"(d[OFF+44]), "+f"(d[OFF+45]), "+f"(d[OFF+46]), "+f"(d[OFF+47]), "+f"(d[OFF+48]), "+f"(d[OFF+49]), "+f"(d[OFF+50]), "+f"(d[OFF+51]), "+f"(d[OFF+52]), "+f"(d[OFF+53]), "+f"(d[OFF+54]), "+f"(d[OFF+55]), "+f"(d[OFF+56]), "+f"(d[OFF+57]), "+f"(d[OFF+58]), "+f"(d[OFF+59]), "+f"(d[OFF+60]), "+f"(d[OFF+61]), "+f"(d[OFF+62]), "+f"(d[OFF+63]), "+f"(d[OFF+64]), "+f"(d[OFF+65]), "+f"(d[OFF+66]), "+f"(d[OFF+67]), "+f"(d[OFF+68]), "+f"(d[OFF+69]), "+f"(d[OFF+70]), "+f"(d[OFF+71]), "+f"(d[OFF+72]), "+f"(d[OFF+73]), "+f"(d[OFF+74]), "+f"(d[OFF+75]), "+f"(d[OFF+76]), "+f"(d[OFF+77]), "+f"(d[OFF+78]), "+f"(d[OFF+79]) : "l"(da), "l"(db), "r"(sd), "n"(TA), "n"(TB));
}

__device__ __align__(1024) uint16_t g_kvT[640 * 2048];
__device__ __align__(1024) uint16_t g_y2T[640 * 2048];
__device__ __align__(1024) uint16_t g_o[2048 * 640];
__device__ __align__(1024) uint16_t g_gate[2080];
__device__ __align__(1024) uint4 g_halo[128 * 10 * 32];
__device__ __align__(1024) unsigned g_cnt[46 * 32];
__device__ __align__(1024) unsigned g_launch[132];
#define CNT_KV(i) (g_cnt + 32 * (i))
#define CNT_O(i) (g_cnt + 32 * (10 + (i)))
#define CNT_Y(i) (g_cnt + 32 * (26 + (i)))
#define PT(i) do {} while (0)
#define PTP(on, i) do {} while (0)

constexpr uint32_t SB = 1024;
constexpr uint32_t STG = 23552, WST = 15360;
DEVI constexpr uint32_t o_px(int ks) { return (((ks >> 1) + 1) & 3) * 2 * STG; }
DEVI constexpr uint32_t o_pw(int ks) { return o_px(ks) + 16384 + (ks & 1) * WST; }
constexpr uint32_t O_HALO = 0, O_OST = STG;
constexpr uint32_t P3S = 28672;
constexpr uint32_t HC = 8320, UC = 4624, UZ = 528;
constexpr uint32_t O_H0 = 5 * P3S, O_U2 = O_H0 + 3 * HC, O_H3 = O_U2 + UC, O_U0 = O_H3 + 2 * HC;
DEVI constexpr uint32_t o_h(int c) { return O_H0 + c * HC + (c > 2 ? UC : 0); }
DEVI constexpr uint32_t o_u(int c) { return c == 2 ? O_U2 : O_U0 + (c > 2 ? c - 1 : c) * UC; }
constexpr uint32_t O_Y = 208896;
DEVI constexpr uint32_t o_x(int c) { return c < 2 ? O_Y + c * 5120 : O_U0 + (c & 1) * UC; }
constexpr uint32_t O_HIN = O_U0 + 3 * UC + UZ;
constexpr uint32_t O_BT = 4 * P3S;
constexpr uint32_t O_GT = O_Y + 20480, O_GW = O_GT + 320;
constexpr uint32_t O_BAR = 231040;
constexpr uint32_t B_FULL = O_BAR, B_EMPTY = O_BAR + 8 * 8, B_P3E = O_BAR + 8 * 16, B_HX = O_BAR + 8 * 23, B_AD = O_BAR + 8 * 31, B_P3F = O_BAR + 8 * 32,
                   B_P3R = O_BAR + 8 * 38, B_G = O_BAR + 8 * 39, B_U = O_BAR + 8 * 40, B_HR = O_BAR + 8 * 45, B_Y = O_BAR + 8 * 50, B_EP = O_BAR + 8 * 52,
                   B_LAST = O_BAR + 8 * 53, B_GW = O_BAR + 8 * 54, B_DONE = O_BAR + 8 * 55, B_P1E = O_BAR + 8 * 56, B_YF = O_BAR + 8 * 60;
constexpr uint64_t BAR_COUNTS = 0x4111111111226611ull;
constexpr uint32_t B_S13 = B_EMPTY + 8 * 5, B_S15 = B_EMPTY + 8 * 7, B_S19 = B_EMPTY + 8 * 3;
constexpr uint32_t O_GP = O_BAR + 512, O_EPOCH = O_GW + 1280;
constexpr uint32_t SMEM_BYTES = 232448;
static_assert(O_U0 + 4 * UC <= O_Y && O_EPOCH + 4 <= O_BAR && O_U0 >= 8 * STG, "smem map");
enum { NB_LEAD = 1, NB_HELP = 2, NB_HALO = 3, NB_ATT = 4, NB_G = 5, NB_TOK = 6, NB_RFULL = 8, NB_RFREE = 10 };

struct Maps { CUtensorMap x_par, w_main, w_tail, o_st, kv_st, wo, o_ld, y_ld; };

template <int M> DEVI void conv_step(float (&acc)[128], uint32_t a0, uint32_t a1, uint32_t a2, uint32_t a3, uint32_t dl) {
  auto D = [&](int off) { return ((uint64_t)8 << 32) | (uint64_t)(uint32_t)(dl + off - 16 * M); };
  if constexpr (M == 0) wgmma_rs_n16<0, 0>(acc, a0, a1, a2, a3, D(0), 0);
  if constexpr (M <= 3) wgmma_rs_n48<8, 0>(acc, a0, a1, a2, a3, D(16), M == 0 ? 0 : 1);
  if constexpr (M <= 6) wgmma_rs_n48<32, 0>(acc, a0, a1, a2, a3, D(64), M == 0 ? 0 : 1);
  if constexpr (M <= 9) wgmma_rs_n48<56, 0>(acc, a0, a1, a2, a3, D(112), M == 0 ? 0 : 1);
  if constexpr (M <= 12) wgmma_rs_n48<80, 0>(acc, a0, a1, a2, a3, D(160), M == 0 ? 0 : 1);
  wgmma_rs_n48<104, 0>(acc, a0, a1, a2, a3, D(208), M == 0 ? 0 : 1);
}
template <int P> DEVI void load_pair(uint32_t (&a)[8], uint32_t ab) {
#pragma unroll
  for (int i = 0; i < 2; i++) {
    const int m = i ? 15 - P : P;
    a[4 * i + 0] = lds32(ab - 4 * (64 * m));
    a[4 * i + 1] = lds32(ab - 4 * (64 * m + 32));
    a[4 * i + 2] = lds32(ab - 4 * (64 * m - 4));
    a[4 * i + 3] = lds32(ab - 4 * (64 * m + 28));
  }
}
template <int P> DEVI void mma_pair(float (&acc)[128], uint32_t (&a)[8], uint32_t db) {
  wg_fence();
  conv_step<P>(acc, a[0], a[1], a[2], a[3], db);
  conv_step<15 - P>(acc, a[4], a[5], a[6], a[7], db);
  wg_commit();
}

DEVI void conv_reduce(uint32_t sb, int c, int ht, int chan) {
  const uint32_t a0 = sb + o_h(c) + ht * 16, a2 = sb + o_u(c) + ht * 16, a3 = sb + o_x(c) + ht * 16;
  uint4* yp = (uint4*)(g_y2T + (size_t)chan * 2048) + ht;
#pragma unroll
  for (int i = 0; i < 2; i++) {
    uint4 p, q, r, s;
    lds128(a0 + i * 2048, p.x, p.y, p.z, p.w); lds128(a0 + 4160 + i * 2048, q.x, q.y, q.z, q.w);
    lds128(a2 + i * 2048, r.x, r.y, r.z, r.w); lds128(a3 + i * 2048, s.x, s.y, s.z, s.w);
    yp[i * 128] = make_uint4(hadd2(hadd2(p.x, q.x), hadd2(r.x, s.x)), hadd2(hadd2(p.y, q.y), hadd2(r.y, s.y)),
                             hadd2(hadd2(p.z, q.z), hadd2(r.z, s.z)), hadd2(hadd2(p.w, q.w), hadd2(r.w, s.w)));
  }
}

template <int I> DEVI void ld_rows(uint32_t (&kk)[32], uint32_t (&vv)[32], const char* kp, const char* vp) {
  if constexpr (I < 32) { kk[I] = ldg_v<I * 1280>(kp); vv[I] = ldg_v<I * 1280>(vp); ld_rows<I + 1>(kk, vv, kp, vp); }
}

template <int ODD, int PART> DEVI void pack_qkv(const float (&acc)[120], uint32_t (&Q)[10][2], uint32_t (&K)[10][2], uint32_t (&V)[10][2]) {
#pragma unroll
  for (int f = 0; f < 10; f++) {
    const bool tail = ODD ? (f < 2) : (f >= 8);
    const int fm = ODD ? f - 2 : f, ft = ODD ? f : f - 8;
    const int nq = tail ? 24 + ft : fm, nk = tail ? 26 + ft : 8 + fm, nv = tail ? 28 + ft : 16 + fm;
    if (PART == 0) {
      V[f][1] = pack_bf16(acc[4 * nv + 2], acc[4 * nv + 3]);
      K[f][1] = pack_bf16(acc[4 * nk + 2], acc[4 * nk + 3]);
    } else {
      Q[f][0] = pack_bf16(acc[4 * nq], acc[4 * nq + 1]); Q[f][1] = pack_bf16(acc[4 * nq + 2], acc[4 * nq + 3]);
      K[f][0] = pack_bf16(acc[4 * nk], acc[4 * nk + 1]); V[f][0] = pack_bf16(acc[4 * nv], acc[4 * nv + 1]);
    }
  }
}
template <int R> DEVI void softmax8(float (&l)[R][2], uint32_t (&P)[R]) {
  const float C = 0.22360679774997896f * 1.4426950408889634f;
  float m[R], s[R];
#pragma unroll
  for (int j = 0; j < R; j++) m[j] = fmaxf(l[j][0], l[j][1]);
#pragma unroll
  for (int j = 0; j < R; j++) m[j] = fmaxf(m[j], __shfl_xor_sync(~0u, m[j], 1));
#pragma unroll
  for (int j = 0; j < R; j++) m[j] = fmaxf(m[j], __shfl_xor_sync(~0u, m[j], 2));
#pragma unroll
  for (int j = 0; j < R; j++) { const float mc = m[j] * C; l[j][0] = ex2(fmaf(l[j][0], C, -mc)); l[j][1] = ex2(fmaf(l[j][1], C, -mc)); s[j] = l[j][0] + l[j][1]; }
#pragma unroll
  for (int j = 0; j < R; j++) s[j] += __shfl_xor_sync(~0u, s[j], 1);
#pragma unroll
  for (int j = 0; j < R; j++) s[j] += __shfl_xor_sync(~0u, s[j], 2);
#pragma unroll
  for (int j = 0; j < R; j++) {
    float r; asm("rcp.approx.ftz.f32 %0, %1;" : "=f"(r) : "f"(s[j]));
    P[j] = pack_bf16(l[j][0] * r, l[j][1] * r);
  }
}

DEVI uint32_t make_ctx() {
  int b; asm volatile("mov.u32 %0, %%ctaid.x;" : "=r"(b));
  b += threadIdx.y;
  const int c = b >> 1, d = c - 36;
  const int p = c < 4 ? 32 + 8 * c : c < 36 ? c - 4 : 33 + d + ((37 * d) >> 8);
  const int j = b < 128 ? 8 * (p & 7) + (p >> 3) : 64, cp = (j * 79) >> 10;
  return ((2 * p + (b & 1)) & 255) | (j - 13 * cp) << 8 | (2 * cp + (b & 1)) << 12 | (b >> 7) << 16;
}
#define CTX() asm volatile("" : "+r"(ctx)); CTXU()
#define CTXU() int tid; asm volatile("mov.u32 %0, %%tid.x;" : "=r"(tid)); \
  const int lane = tid & 31, vb = ctx & 255, hg = (ctx >> 4) & 7, rt = ctx & 15, par = (ctx >> 3) & 1, mt = ctx & 7, rank = ctx & 1, \
  tb = (ctx >> 8) & 15, cb = (ctx >> 12) & 15; const bool main_cta = ctx < 65536; \
  (void)tid; (void)lane; (void)vb; (void)hg; (void)rt; (void)par; (void)mt; (void)rank; (void)tb; (void)cb; (void)main_cta
#define CTXW() CTX(); const int wg = warp >> 2, w = warp & 3, g = lane >> 2, t = lane & 3; const bool lead = (tid & 127) == 0; \
  (void)wg; (void)w; (void)g; (void)t; (void)lead

__global__ void __cluster_dims__(2, 1, 1) __launch_bounds__(512, 1)
fused_kernel(const uint16_t* __restrict__ xq, const uint16_t* __restrict__ wqkv, const __grid_constant__ Maps M, const uint16_t* __restrict__ shift_k, const uint16_t* __restrict__ ssm_k, const uint16_t* __restrict__ ssm_D,
             const uint16_t* __restrict__ gate_w, const uint16_t* __restrict__ kin, const uint16_t* __restrict__ vin, uint16_t* __restrict__ outp) {
  extern __shared__ __align__(1024) uint8_t smem_raw[];
  const uint32_t sb = smem_u32(smem_raw);
  const uint32_t t0 = clk();
  auto get_epoch = [&]() { mbar_wait(sb + B_EP, 0); return lds32(sb + O_EPOCH); };

  if (threadIdx.x < 32) {
    const unsigned b = blockIdx.x, l = threadIdx.x;
    if (b < 128 && l < 31) pf_l2(l < 16 ? xq + (16 * b + l) * 640 : wqkv + (15 * b + l - 16) * 64);
  }
  const int warp = __shfl_sync(~0u, threadIdx.x >> 5, 0);
  if (elect_one()) {
    const uint32_t cnt = (uint32_t)(BAR_COUNTS >> (4 * (warp ^ 15))) & 15;
#pragma unroll
    for (int s = 0; s < 4; s++) mbar_init(sb + O_BAR + 32 * (warp ^ 15) + 8 * s, cnt);
    asm volatile("fence.mbarrier_init.release.cluster;" ::: "memory");
  }
  __syncwarp();
  asm volatile("barrier.cluster.arrive.relaxed.aligned;" ::: "memory");
  uint32_t ctx = make_ctx();
  if (warp == 15) {
    const uint32_t cu = __shfl_sync(~0u, ctx, 0);
    if (cu < 65536 && elect_one()) {
      const int hg = (cu >> 4) & 7, cm = hg * 80 + ((hg & 1) ? 16 : 0), ct = hg * 80 + ((hg & 1) ? 0 : 64);
#pragma unroll 1
      for (int i = 0; i < 2; i++) {
        const uint32_t st = sb + o_pw(0), fb = sb + B_FULL;
        if (!i) { mbar_expect_tx(fb, 16384 + WST); tma3(sb + o_px(0), &M.x_par, 0, (cu >> 3) & 1, (cu & 7) * 128, fb); }
        tma3(st + i * 6144, &M.w_main, cm, i * 16, 0, fb); tma3(st + 12288 + i * 1536, &M.w_tail, ct, i * 16, 0, fb);
        PT(100);
      }
    }
    __syncwarp();
  }
  asm volatile("barrier.cluster.wait.aligned;" ::: "memory");
  if (threadIdx.x == 384) PT(1);

  if (warp < 8) {
    if (SNOOZE) __nanosleep(SNOOZE);
    reg_inc<RC>();
    if (blockIdx.x < 128) {
      {
        uint32_t Q[10][2], K[10][2], V[10][2];
        {
          {
            float acc[120];
            unsigned epoch;
            {
              CTXW();
              const uint32_t aa = sb + (warp * 16 + (lane & 15)) * 128 + (((lane >> 4) ^ (lane & 7)) << 4);
              const uint32_t rsb = mapa(sb, (blockIdx.x & 1) ^ 1);
              uint32_t a0[8], a1[8], a2[8];
              auto load_a = [&](uint32_t (&r)[8], int ks) {
                mbar_wait(sb + B_FULL + 8 * (ks & 7), (ks >> 3) & 1);
                PTP(lead && (wg || !(ks & 3)), wg ? 60 + ks : 80 + (ks >> 2));
                ldsm4(r[0], r[1], r[2], r[3], (aa ^ ((ks & 1) * 64)) + o_px(ks)); ldsm4(r[4], r[5], r[6], r[7], (aa ^ ((ks & 1) * 64 + 32)) + o_px(ks));
              };
              auto stage = [&](uint32_t (&r)[8], uint32_t (&nx)[8], int ks, int u) {
                const uint32_t dl = o_pw(ks) >> 4;
                const uint64_t db = mkdesc(SB, 2048, 1024, 1), dt = mkdesc(SB + 12288, 512, 256, 3);
                auto D = [&](uint64_t d) { return (d & ~0xFFFFFFFFull) | (uint32_t)((uint32_t)d + dl); };
                if (LEAD && u == (20 - LEAD) % 3) bar_sync_p(wg == 0 && ks == 20 - LEAD, NB_LEAD, 256);
                wg_fence();
                wgmma_rs_n192<0, 1>(acc, r[0], r[1], r[2], r[3], D(db), 1);
                wgmma_rs_n48<96, 1>(acc, r[0], r[1], r[2], r[3], D(dt), 1);
                wg_commit();
                if (LEAD && u == 1) bar_arrive_p(wg && ks == 19, NB_LEAD, 256);
                load_a(nx, u == 1 ? min(ks + 1, 19) : ks + 1);
                wg_fence();
                wgmma_rs_n192<0, 1>(acc, r[4], r[5], r[6], r[7], D(db + 384), 1);
                wgmma_rs_n48<96, 1>(acc, r[4], r[5], r[6], r[7], D(dt + 96), 1);
                wg_commit();
                wg_wait<2>();
                mbar_arrive2_p(lead && (u || ks), sb + B_EMPTY + 8 * ((ks - 1) & 7), rsb + B_EMPTY + 8 * ((ks - 1) & 7));
              };
#pragma unroll
              for (int i = 0; i < 120; i++) acc[i] = 0.f;
              fence_regs(acc);
              load_a(a0, 0);
              constexpr int p1u = P1U;
#pragma unroll p1u
              for (int ks = 0; ks < 21; ks += 3) {
                stage(a0, a1, ks, 0);
                stage(a1, a2, ks + 1, 1);
                if (ks == 18) break;
                stage(a2, a0, ks + 2, 2);
              }
              epoch = get_epoch();
              mbar_wait(sb + B_S15, 1);
              wg_wait<0>();
              fence_regs(acc);
              mbar_arrive_p(tid == 0, sb + B_P1E);
              mbar_arrive2_p(lead, sb + B_S19, rsb + B_S19);
              PTP(lead, 50 + wg);
            }
            CTXW();
            if (hg & 1) pack_qkv<1, 0>(acc, Q, K, V); else pack_qkv<0, 0>(acc, Q, K, V);
#pragma unroll
            for (int f = 0; f < 10; f++) V[f][1] = movm(V[f][1]);
            const uint32_t ho = sb + O_HALO + warp * 2560 + lane * 16;
            if (warp == 7) {
              if (!rank) {
                const uint32_t ra = mapa(sb + O_HIN + lane * 16, 1), rb = mapa(sb + B_HX, 1);
#pragma unroll
                for (int i = 0; i < 2; i++) {
                  st_async128(ra + i * 512, K[5 * i][1], K[5 * i + 1][1], K[5 * i + 3][1], K[5 * i + 4][1], rb);
                  st_async128(ra + 1024 + i * 512, V[5 * i][1], V[5 * i + 1][1], V[5 * i + 3][1], V[5 * i + 4][1], rb);
                }
                st_async128(ra + 2048, K[2][1], K[7][1], V[2][1], V[7][1], rb);
              } else if (mt < 7) {
                const uint64_t tag = (uint64_t)epoch << 32;
                uint4* hp = g_halo + (size_t)vb * 320 + lane;
                auto put = [&](int i, uint32_t x, uint32_t y) { asm volatile("st.relaxed.gpu.global.v2.b64 [%0], {%1, %2};" ::"l"(hp + 32 * i), "l"(tag | x), "l"(tag | y) : "memory"); };
                put(0, K[0][1], K[1][1]); put(1, K[3][1], K[4][1]); put(2, K[5][1], K[6][1]); put(3, K[8][1], K[9][1]); put(4, K[2][1], K[7][1]);
                put(5, V[0][1], V[1][1]); put(6, V[3][1], V[4][1]); put(7, V[5][1], V[6][1]); put(8, V[8][1], V[9][1]); put(9, V[2][1], V[7][1]);
              }
            } else {
#pragma unroll
              for (int i = 0; i < 2; i++) {
                sts128(ho + i * 512, K[5 * i][1], K[5 * i + 1][1], K[5 * i + 3][1], K[5 * i + 4][1]);
                sts128(ho + 1024 + i * 512, V[5 * i][1], V[5 * i + 1][1], V[5 * i + 3][1], V[5 * i + 4][1]);
              }
              sts128(ho + 2048, K[2][1], K[7][1], V[2][1], V[7][1]);
              __syncwarp();
              if (lane == 0) mbar_arrive(sb + B_HX + 8 + 8 * warp);
            }
            if (hg & 1) pack_qkv<1, 1>(acc, Q, K, V); else pack_qkv<0, 1>(acc, Q, K, V);
#pragma unroll
            for (int f = 0; f < 10; f++) V[f][0] = movm(V[f][0]);
            if (lead) PT(52 + wg);
            if (wg) mbar_wait(sb + B_P1E, 0);
          }
          CTXW();
          const bool gt0 = 2 * t > g, gt1 = 2 * t + 1 > g;
          const uint32_t pmask = (gt0 ? 0xFFFFu : 0u) | (gt1 ? 0xFFFF0000u : 0u);
          uint32_t Qh[4][2];
          float lg[8][2];
#pragma unroll
          for (int j = 0; j < 4; j++) {
            const int fa = (j >> 1) * 5 + (j & 1) * 3, fh = (j >> 1) * 5 + 2;
            const bool mine = (j & 1) ? (t >= 2) : (t < 2);
            Qh[j][0] = mine ? Q[fh][0] : 0u; Qh[j][1] = mine ? Q[fh][1] : 0u;
            float c1[4] = {0.f, 0.f, 0.f, 0.f}, c2[4] = {0.f, 0.f, 0.f, 0.f};
            mma16(c1, Q[fa][0], Q[fa][1], Q[fa + 1][0], Q[fa + 1][1], K[fa][0], K[fa + 1][0]);
            mma16(c2, Q[fa][0], Q[fa][1], Q[fa + 1][0], Q[fa + 1][1], K[fa][1], K[fa + 1][1]);
            mma8(c1, Qh[j][0], Qh[j][1], K[fh][0]);
            mma8(c2, Qh[j][0], Qh[j][1], K[fh][1]);
            lg[j][0] = c1[0]; lg[j][1] = c1[1];
            lg[4 + j][0] = gt0 ? c1[2] : c2[2]; lg[4 + j][1] = gt1 ? c1[3] : c2[3];
          }
          if (lead) PT(54 + wg);
          mbar_wait(sb + B_HX + 8 * warp, 0);
          if (lead) PT(56 + wg);
          const uint32_t ha = sb + (warp ? O_HALO + (warp - 1) * 2560 : O_HIN) + lane * 16;
          uint32_t Kh[10], Vh[10];
#pragma unroll
          for (int i = 0; i < 2; i++) lds128(ha + i * 512, Kh[5 * i], Kh[5 * i + 1], Kh[5 * i + 3], Kh[5 * i + 4]);
          lds128(ha + 2048, Kh[2], Kh[7], Vh[2], Vh[7]);
#pragma unroll
          for (int i = 0; i < 2; i++) lds128(ha + 1024 + i * 512, Vh[5 * i], Vh[5 * i + 1], Vh[5 * i + 3], Vh[5 * i + 4]);
          const bool have_halo = warp > 0 || mt > 0;
#pragma unroll
          for (int j = 0; j < 4; j++) {
            const int fa = (j >> 1) * 5 + (j & 1) * 3, fh = (j >> 1) * 5 + 2;
            float c0[4] = {0.f, 0.f, 0.f, 0.f};
            mma16(c0, Q[fa][0], Q[fa][1], Q[fa + 1][0], Q[fa + 1][1], Kh[fa], Kh[fa + 1]);
            mma8(c0, Qh[j][0], Qh[j][1], Kh[fh]);
            if (!have_halo) c0[0] = c0[1] = -INFINITY;
            lg[j][0] = gt0 ? c0[0] : lg[j][0]; lg[j][1] = gt1 ? c0[1] : lg[j][1];
          }
          uint32_t Pv[8], O[10][2];
          softmax8<8>(lg, Pv);
#pragma unroll
          for (int j = 0; j < 4; j++) {
            const int fa = (j >> 1) * 5 + (j & 1) * 3, fh = (j >> 1) * 5 + 2;
            const uint32_t a0 = Pv[j] & pmask, a2 = Pv[j] & ~pmask, a3 = Pv[4 + j] & pmask, a5 = Pv[4 + j] & ~pmask;
#pragma unroll
            for (int q = 0; q < 3; q++) {
              const int f = q < 2 ? fa + q : fh;
              float o[4] = {0.f, 0.f, 0.f, 0.f};
              mma8(o, a0, 0u, Vh[f]);
              mma16(o, a2, a3, 0u, a5, V[f][0], V[f][1]);
              const uint32_t o0 = pack_bf16(o[0], o[1]), o1 = pack_bf16(o[2], o[3]);
              if (q < 2 || !(j & 1)) { O[f][0] = o0; O[f][1] = o1; }
              else { O[f][0] = t >= 2 ? o0 : O[f][0]; O[f][1] = t >= 2 ? o1 : O[f][1]; }
            }
          }
          const uint32_t oa = sb + O_OST + (warp * 16 + (lane & 15)) * 160 + (lane >> 4) * 16;
#pragma unroll
          for (int i = 0; i < 5; i++) stsm4(oa + i * 32, O[2 * i][0], O[2 * i][1], O[2 * i + 1][0], O[2 * i + 1][1]);
        }
      }
      {
        CTXW();
        bar_arrive_p(wg == 0, NB_HALO, 256);
        mbar_arrive_p(tid == 0, sb + B_AD);
        fence_async_smem();
        bar_arrive(NB_ATT, 288);
        if (lead) PT(58 + wg);
        const uint32_t abase = sb + (g & 1) * 4160 + 4 * (1023 - 4 - 8 * w - (g >> 1) + t);
        float acc[128];
        uint32_t a0[8], a1[8], a2[8], a3[8];
#pragma unroll 1
        for (int c = wg ^ 1; c < 5; c += 2) {
          const uint32_t ab = abase + o_h(c);
          const uint32_t db = __shfl_sync(~0u, ((SB + o_u(c) + UZ - 16) >> 4) | 0x10000u, 0);
          mbar_wait(sb + B_HR + 8 * c, 0);
          load_pair<0>(a0, ab); load_pair<1>(a1, ab); load_pair<2>(a2, ab); load_pair<3>(a3, ab);
          mbar_wait(sb + B_U + 8 * c, 0);
          if (lead) PT(85 + c);
          bar_sync(c ? NB_TOK + wg : NB_HALO, 256);
          fence_regs(acc);
          if (lead) PT(90 + c);
          mma_pair<0>(acc, a0, db);
          mma_pair<1>(acc, a1, db); wg_wait<1>();  load_pair<4>(a0, ab);
          mma_pair<2>(acc, a2, db); wg_wait<1>();  load_pair<5>(a1, ab);
          mma_pair<3>(acc, a3, db); wg_wait<1>();  load_pair<6>(a2, ab);
          mma_pair<4>(acc, a0, db); wg_wait<1>();  load_pair<7>(a3, ab);
          mma_pair<5>(acc, a1, db);
          mma_pair<6>(acc, a2, db);
          bar_arrive(NB_TOK + (wg ^ 1), 256);
          mma_pair<7>(acc, a3, db);
          wg_wait<0>();
          fence_regs(acc);
          if (lead) PT(95 + c);
          bar_sync(NB_RFREE + wg, 256);
          const uint32_t pb = sb + (w < 2 ? o_h(c) + w * 4160 : w == 2 ? o_u(c) : o_x(c)) + lane * 16;
          if (lane < 2 * w) sts128(pb, 0, 0, 0, 0);
#pragma unroll
          for (int q = 0; q < 8; q++) {
            uint32_t p[4];
#pragma unroll
            for (int i = 0; i < 4; i++) {
              const int nu = 4 * q + i;
              float v0 = acc[4 * nu], v1 = acc[4 * nu + 1];
              if (nu > 0) { v0 += acc[4 * nu - 2]; v1 += acc[4 * nu - 1]; }
              p[i] = pack_bf16(v0, v1);
            }
            stsm4t(pb + w * 32 + q * 512, p[0], p[1], p[2], p[3]);
          }
          bar_arrive(NB_RFULL + wg, 256);
          if (lead) PT(140 + c);
        }
      }
    }
    if (warp < 4) {
      CTXW();
      const uint32_t rsb = mapa(sb, (blockIdx.x & 1) ^ 1);
      const uint32_t ba = sb + O_BT + ((lane >> 4) * 8 + (lane & 7)) * 128 + (((2 * w + ((lane >> 3) & 1)) ^ ((lane & 1) << 2 | (lane >> 1 & 3))) << 4);
      mbar_wait(sb + B_P3F, 0);
      if (lead) PT(145);
      if (blockIdx.x < 128) bar_sync(NB_TOK, 256);
      float acc[80];
#pragma unroll 1
      for (int ks = 0; ks < 10; ks++) {
        PTP(lead, 146 + ks);
        const uint32_t dl = (ks < 6 ? ks : ks - 6) * (P3S >> 4);
        const uint64_t da = mkdesc(SB, 1024, 1024, 1), db = mkdesc(SB + 8192, 16, 1024, 1);
        auto D = [&](uint64_t d) { return (d & ~0xFFFFFFFFull) | (uint32_t)((uint32_t)d + dl); };
        wg_fence();
#pragma unroll
        for (int j = 0; j < 4; j++) wgmma_ss_n160<0, 1, 0>(acc, D(da + j * 128), D(db + j * 2), j ? 1 : ks);
        wg_commit();
        wg_wait<1>();
        mbar_arrive2_p(lead && ks >= 1 && ks <= 4, sb + B_P3E + 8 * (ks - 1), rsb + B_P3E + 8 * (ks - 1));
        mbar_wait(sb + B_P3F + 8 * (ks < 5 ? ks + 1 : ks - 5), ks >= 5 && ks < 9);
      }
      wg_wait<0>();
      fence_regs(acc);
      if (lead) PT(156);
#pragma unroll
      for (int i = 0; i < 10; i++) {
        stsm4t(ba + i * 2048, pack_bf16(acc[8 * i], acc[8 * i + 1]), pack_bf16(acc[8 * i + 2], acc[8 * i + 3]),
               pack_bf16(acc[8 * i + 4], acc[8 * i + 5]), pack_bf16(acc[8 * i + 6], acc[8 * i + 7]));
        if (i & 1) bar_arrive(1 + (i >> 1), 256);
      }
      if (lead) PT(157);
    }
  } else if (warp < 12) {
    reg_dec<RH>();
    if (SNOOZE) __nanosleep(SNOOZE);
    const int hw = warp - 8;
    ctx = __shfl_sync(~0u, ctx, 0);
    if (ctx < 65536) {
      CTXU();
#pragma unroll 1
      for (int c = hw; c < 5; c += 4) {
        const int kb = 2 * c + (vb >> 6), r0 = (vb & 63) * 32;
        const uint4 sk = __ldg((const uint4*)(shift_k + (size_t)(kb * 64 + 2 * lane) * 4));
        wait_until(t0, KT0 + c * KTD + ((((vb * 37) & 127) * KTD) >> 7));
        if (lane == 0) PT(20 + c);
        const char* kp = (const char*)kin + (size_t)r0 * 1280 + kb * 128 + lane * 4;
        const char* vp = (const char*)vin + (size_t)r0 * 1280 + kb * 128 + lane * 4;
        uint32_t k0 = 0, k1 = 0, k2 = 0, kk[32], vv[32];
        if (r0 > 0) { k0 = ldg_v<-3 * 1280>(kp); k1 = ldg_v<-2 * 1280>(kp); k2 = ldg_v<-1280>(kp); }
        ld_rows<0>(kk, vv, kp, vp);
        const uint32_t zz = vv[31] & (uint32_t)(threadIdx.y);
        const uint32_t w0 = prmt(sk.x, sk.z, 0x5410) | zz, w1 = prmt(sk.x, sk.z, 0x7632), w2 = prmt(sk.y, sk.w, 0x5410), w3 = prmt(sk.y, sk.w, 0x7632) | zz;
        const int odd = (lane >> 2) & 1;
        const uint32_t sel0 = odd ? 0x7632 : 0x5410, sel1 = odd ? 0x5410 : 0x7632;
        const uint32_t st = sb + O_Y + c * 4096;
        PTP(lane == 0 && c == 1, 40 + zz);
#pragma unroll
        for (int ch = 0; ch < 4; ch++) {
          uint32_t o[8];
#pragma unroll
          for (int i = 0; i < 8; i++) {
            const uint32_t k3 = kk[8 * ch + i];
            o[i] = hmul2(hfma2(k3, w0, hfma2(k2, w1, hfma2(k1, w2, hmul2(k0, w3)))), vv[8 * ch + i]);
            k0 = k1; k1 = k2; k2 = k3;
          }
          const uint32_t oa = st + (2 * lane) * 64 + ((ch ^ (lane & 3)) << 4);
          sts128v(oa + odd * 64, prmt(o[0], o[1], sel0), prmt(o[2], o[3], sel0), prmt(o[4], o[5], sel0), prmt(o[6], o[7], sel0));
          sts128v(oa + 64 - odd * 64, prmt(o[0], o[1], sel1), prmt(o[2], o[3], sel1), prmt(o[4], o[5], sel1), prmt(o[6], o[7], sel1));
        }
        fence_async_smem();
        __syncwarp();
        if (elect_one()) {
          PT(25 + c);
          tma3_store(&M.kv_st, 0, kb * 64, vb & 63, st);
          bulk_commit(); bulk_wait_all();
          flag_add(CNT_KV(kb), 1);
          PT(30 + c);
        }
        __syncwarp();
      }
      mbar_wait(sb + B_LAST, 0);
#pragma unroll 1
      for (int c = hw ? hw - 1 : 5; c < 5; c += 3) {
        const uint4* hp = (const uint4*)(ssm_k + (size_t)(128 * c + vb) * 2048) + lane;
        uint4 u[8];
#pragma unroll
        for (int q = 0; q < 8; q++) asm volatile("ld.volatile.global.v4.b32 {%0,%1,%2,%3}, [%4];" : "=r"(u[q].x), "=r"(u[q].y), "=r"(u[q].z), "=r"(u[q].w) : "l"(hp + 32 * q));
        const uint32_t d = __ldg(ssm_D + 128 * c + vb);
        mbar_wait(sb + B_S13, 1);
        const uint32_t o = sb + o_h(c) + (255 - lane) * 16;
        if (lane == 0) u[0].x = prmt(pack_bf16(bf_lo(u[0].x) + bf_lo(d), 0.f), u[0].x, 0x7610);
#pragma unroll
        for (int q = 0; q < 8; q++) {
          const uint32_t up = __shfl_sync(~0u, lane == 31 ? (q ? u[q ? q - 1 : 0].w : 0u) : u[q].w, lane + 31);
          sts128(o - q * 512, prmt(u[q].w, u[q].z, 0x7610), prmt(u[q].z, u[q].y, 0x7610), prmt(u[q].y, u[q].x, 0x7610), prmt(u[q].x, up, 0x7610));
          sts128(o - q * 512 + 4160, prmt(u[q].w, 0, 0x1032), prmt(u[q].z, 0, 0x1032), prmt(u[q].y, 0, 0x1032), prmt(u[q].x, 0, 0x1032));
        }
        if (lane < 2) sts128(sb + o_h(c) + lane * 4160 + 4096, 0, 0, 0, 0);
        __syncwarp();
        if (lane == 0) { mbar_arrive(sb + B_HR + 8 * c); PT(35 + c); }
      }
    }
    CTXU();
    const int g = lane >> 2, t = lane & 3, row = 8 * hw + g;
    const uint32_t go = (tb * 160 + row) * 80 + cb * 8 + t;
    uint4 T[10];
#pragma unroll
    for (int i = 0; i < 10; i++) {
      T[i] = make_uint4(0, 0, 0, 0);
      if (i < 8 || tb < 12) asm volatile("ld.volatile.global.v4.b32 {%0,%1,%2,%3}, [%4];" : "=r"(T[i].x), "=r"(T[i].y), "=r"(T[i].z), "=r"(T[i].w) : "l"((const uint4*)xq + go + (i >> 1) * 2560 + (i & 1) * 4));
    }
    if (main_cta) {
      bar_arrive(NB_RFREE, 256);
      bar_arrive(NB_RFREE + 1, 256);
      const int yrow = (vb & 0x61) | (vb & 6) << 2 | (vb >> 2 & 6);
#pragma unroll 1
      for (int c = 0; c < 5; c++) {
        const int wg = (c & 1) ^ 1;
        bar_sync(NB_RFULL + wg, 256);
        conv_reduce(sb, c, tid - 256, 128 * c + yrow);
        __syncwarp();
        if (lane == 0) flag_add(CNT_Y(4 * c + (vb >> 5)), 1);
        if (tid == 256) PT(41 + c);
        if (c < 3) bar_arrive(NB_RFREE + wg, 256);
        if (c == 1 && lane == 0) mbar_arrive(sb + B_YF);
        if (c == 2) {
          bar_sync(NB_HELP, 128);
          if (tid == 256) { mbar_arrive(sb + B_P3E + 32); mbar_arrive_remote(sb + B_P3E + 32, rank ^ 1); }
        }
      }
    }
    uint32_t G[5];
    mbar_wait(sb + B_G, 0);
#pragma unroll
    for (int q = 0; q < 5; q++) { uint16_t v; asm volatile("ld.shared.u16 %0, [%1];" : "=h"(v) : "r"(sb + O_GT + (32 * q + row) * 2)); G[q] = prmt(v, 0, 0x1010); }
#pragma unroll
    for (int i = 0; i < 10; i++) { const uint32_t c = G[i >> 1]; T[i] = make_uint4(hmul2(T[i].x, c), hmul2(T[i].y, c), hmul2(T[i].z, c), hmul2(T[i].w, c)); }
#pragma unroll
    for (int h = 0; h < 2; h++) {
      mbar_wait(sb + B_Y + 8 * h, 0);
      if (tid == 256) PT(46);
#pragma unroll
      for (int q = 0; q < 5; q++) {
        uint32_t y0, y1, y2, y3;
        ldsm4t(y0, y1, y2, y3, sb + O_Y + h * 10240 + q * 2048 + lane * 64 + ((hw ^ ((lane >> 1) & 3)) << 4));
        uint4& r = T[2 * q + h];
        r = make_uint4(hmul2(r.x, y0), hmul2(r.y, y1), hmul2(r.z, y2), hmul2(r.w, y3));
      }
    }
    const uint32_t so = sb + O_BT + row * 128 + ((t ^ ((g & 1) << 2 | g >> 1)) << 4);
    if (tid == 256) PT(47);
#pragma unroll
    for (int q = 0; q < 5; q++) {
      const uint32_t c = hfma2(G[q], 0xBF80BF80u, 0x3F803F80u);
      bar_sync(1 + q, 256);
      if (q == 4) mbar_arrive_p(tid == 256, sb + B_DONE);
#pragma unroll
      for (int h = 0; h < 2; h++) {
        uint4 u;
        lds128((so ^ (h * 64)) + q * 4096, u.x, u.y, u.z, u.w);
        const uint4& r = T[2 * q + h];
        if (q < 4 || tb < 12) ((uint4*)outp)[go + q * 2560 + h * 4] = make_uint4(hfma2(u.x, c, r.x), hfma2(u.y, c, r.y), hfma2(u.z, c, r.z), hfma2(u.w, c, r.w));
      }
    }
  } else {
    reg_dec<RP>();
    ctx = __shfl_sync(~0u, ctx, 0);
    CTXU();
    if (warp == 15) {
      if (SNOOZE) __nanosleep(SNOOZE);
      unsigned epoch = 0;
      if (lane == 0) {
        if ((sb & 0xFFFFFF) != SB) __trap();
        mbar_expect_tx(sb + B_GW, 1280);
        bulk_load(sb + O_GW, gate_w, 1280, sb + B_GW);
        epoch = *(volatile unsigned*)(g_launch + blockIdx.x) + 1;
        *(volatile unsigned*)(g_launch + blockIdx.x) = epoch;
        sts32(sb + O_EPOCH, epoch);
        mbar_arrive(sb + B_EP);
#pragma unroll 1
        for (int i = 3; i < 8; i++) asm volatile("prefetch.tensormap [%0];" ::"l"(&M.x_par + i) : "memory");
      }
      __syncwarp();
      if (main_cta) {
        mbar_wait(sb + B_LAST, 0);
        mbar_wait(sb + B_S13, 1);
#pragma unroll
        for (int c = 0; c < 5; c++) sts128(sb + o_u(c) + lane * 16, 0, 0, 0, 0);
        if (lane < 5) sts128(sb + o_u(lane) + 512, 0, 0, 0, 0);
        fence_async_smem();
        __syncwarp();
        if (lane == 0) {
#pragma unroll 1
          for (int c = 0; c < 5; c++) {
            if (c == 4) mbar_wait(sb + B_AD, 0);
            flag_wait(CNT_KV(2 * c + (vb >> 6)), 64 * epoch);
            mbar_expect_tx(sb + B_U + 8 * c, 4096);
            bulk_load(sb + o_u(c) + UZ, g_kvT + (size_t)(128 * c + vb) * 2048, 4096, sb + B_U + 8 * c);
            PT(10 + c);
          }
        }
      }
    } else if (warp != 12) {
      if (SNOOZE) __nanosleep(SNOOZE);
      const int r = warp - 13;
      if (main_cta) {
        if (rank) {
#pragma unroll
          for (int f = 0; f < 5; f++)
            asm volatile("st.relaxed.gpu.global.v2.b64 [%0], {%1, %1};" ::"l"(g_halo + (size_t)vb * 320 + r * 160 + lane + 32 * f), "l"(0ull) : "memory");
          if (lane == 0) mbar_expect_tx(sb + B_HX, 1280);
        }
        const int t = lane & 3, grow = hg * 16 + (lane & 15);
        const uint32_t ga = sb + grow * 128 + (((4 * r + (lane >> 4)) ^ (lane & 7)) << 4);
        const uint32_t gp = sb + O_GW + 64 * r + 4 * t;
        float s0 = 0.f, s1 = 0.f;
        mbar_wait_wd(sb + B_GW, 0, t0);
#pragma unroll 1
        for (int ks = 0; ks < 20; ks += 2) {
          uint32_t x[8], gw[4];
#pragma unroll
          for (int i = 0; i < 4; i++) gw[i] = lds32(gp + ks * 64 + i * 16);
          mbar_wait_wd(sb + B_FULL + 8 * (ks & 7), (ks >> 3) & 1, t0);
          if (r == 0 && lane == 0) PT(120 + ks);
          ldsm4(x[0], x[1], x[2], x[3], ga + o_px(ks)); ldsm4(x[4], x[5], x[6], x[7], (ga ^ 32) + o_px(ks));
#pragma unroll
          for (int i = 0; i < 8; i++) x[i] = hmul2(x[i], gw[i >> 1]);
          if (lane < 2) mbar_arrive(sb + B_EMPTY + 8 * (ks & 7) + 8 * lane + (x[0] & x[7] & threadIdx.y));
#pragma unroll
          for (int i = 0; i < 8; i += 4) {
            s0 += (bf_lo(x[i]) + bf_hi(x[i])) + (bf_lo(x[i + 2]) + bf_hi(x[i + 2]));
            s1 += (bf_lo(x[i + 1]) + bf_hi(x[i + 1])) + (bf_lo(x[i + 3]) + bf_hi(x[i + 3]));
          }
        }
        s0 += __shfl_xor_sync(~0u, s0, 1); s1 += __shfl_xor_sync(~0u, s1, 1);
        s0 += __shfl_xor_sync(~0u, s0, 2); s1 += __shfl_xor_sync(~0u, s1, 2);
        if (t < 2) sts32(sb + O_GP + r * 64 + (8 * t + (lane >> 2)) * 4, __float_as_uint(t ? s1 : s0));
        if (r == 0) bar_arrive(NB_G, 64);
        if (!rank) {
          const uint32_t ha = sb + O_HIN + lane * 16 + r * 1024, hb = sb + O_HIN + lane * 16 + 2048 + r * 8;
          uint32_t d[10];
          if (mt > 0) {
            const uint4* hp = g_halo + (size_t)(vb - 1) * 320 + r * 160 + lane;
            mbar_wait_wd(sb + B_HX + 56, 0, t0);
            const unsigned epoch = lds32(sb + O_EPOCH);
            for (;;) {
              uint64_t u[10];
#pragma unroll
              for (int f = 0; f < 5; f++) asm volatile("ld.relaxed.gpu.global.v2.b64 {%0, %1}, [%2];" : "=l"(u[2 * f]), "=l"(u[2 * f + 1]) : "l"(hp + 32 * f) : "memory");
              uint32_t bad = 0;
#pragma unroll
              for (int f = 0; f < 10; f++) { d[f] = (uint32_t)u[f]; bad |= (uint32_t)(u[f] >> 32) ^ epoch; }
              if (__all_sync(~0u, bad == 0)) break;
              if (clk() - t0 > 0x70000000u) __trap();
            }
          } else {
#pragma unroll
            for (int f = 0; f < 10; f++) d[f] = 0u;
          }
          sts128(ha, d[0], d[1], d[2], d[3]); sts128(ha + 512, d[4], d[5], d[6], d[7]);
          sts32(hb, d[8]); sts32(hb + 4, d[9]);
          __syncwarp();
          if (lane == 0) { mbar_arrive(sb + B_HX); PT(15 + r); }
        }
        if (r == 1) {
          bar_sync(NB_G, 64);
          if (lane < 16) {
            const uint32_t pa = sb + O_GP + lane * 4;
            const float z = __uint_as_float(lds32(pa)) + __uint_as_float(lds32(pa + 64));
            g_gate[2 * (mt * 128 + hg * 16 + lane) + par] = (uint16_t)pack_bf16(__fdividef(1.f, 1.f + __expf(-bf_lo(pack_bf16(z, 0.f)))), 0.f);
          }
          __syncwarp();
          if (lane == 0) flag_add(CNT_O(rt), 1);
        }
      }
      if (elect_one()) {
        mbar_wait_wd(sb + B_EP, 0, t0);
        const unsigned epoch = lds32(sb + O_EPOCH);
        if (main_cta) mbar_wait_wd(sb + B_YF, 0, t0);
        unsigned v;
        do {
          asm volatile("ld.relaxed.gpu.global.u32 %0, [%1];" : "=r"(v) : "l"(CNT_Y(2 * cb + r)) : "memory");
          if (clk() - t0 > 0x70000000u) __trap();
        } while ((int)(v - 128 * epoch) < 0);
        mbar_expect_tx(sb + B_Y + 8 * r, 10240);
        tma3(sb + O_Y + r * 10240, &M.y_ld, 0, cb * 64 + 32 * r, tb * 5, sb + B_Y + 8 * r);
        PT(17 + r);
        mbar_wait_wd(sb + B_DONE, 0, t0);
      }
    } else {
      if (main_cta && elect_one()) {
        const int cm = hg * 80 + ((hg & 1) ? 16 : 0), ct = hg * 80 + ((hg & 1) ? 0 : 64);
#pragma unroll 1
        for (int ks = 1; ks < 20; ks++) {
          const uint32_t st = sb + o_pw(ks), fb = sb + B_FULL + 8 * (ks & 7);
          mbar_wait(sb + B_EMPTY + 8 * (ks & 7), ((ks >> 3) & 1) ^ 1);
          spin_until(t0, PT1 + (ks - 1) * PTD - ((ks & 1) ? 0 : PTE));
          PT(100 + ks);
          mbar_expect_tx(fb, (ks & 1) ? WST : 16384 + WST);
          if (!(ks & 1)) tma3(st - 16384, &M.x_par, ks * 32, par, mt * 128, fb);
          tma3_mc(st + rank * 6144, &M.w_main, cm, ks * 32 + rank * 16, 0, fb);
          tma3_mc(st + 12288 + rank * 1536, &M.w_tail, ct, ks * 32 + rank * 16, 0, fb);
        }
        mbar_arrive(sb + B_LAST);
        mbar_wait(sb + B_S19, 0);
      }
      __syncwarp();
      const unsigned epoch = get_epoch();
      if (main_cta) bar_sync(NB_ATT, 288);
      if (elect_one()) {
        if (main_cta) {
          tma3_store(&M.o_st, hg * 80, par, mt * 128, sb + O_OST);
          bulk_commit(); bulk_wait_all();
          flag_add(CNT_O(rt), 1);
        }
        mbar_arrive_remote(sb + B_P3R, rank ^ 1);
        PT(3);
      }
      __syncwarp();
      if (lane < 4) flag_wait(CNT_O(8 * (lane & 1) + min(7, (80 * tb + 79 * (lane >> 1)) >> 7)), 16 * epoch);
      __syncwarp();
      if (elect_one()) {
        PT(4);
        mbar_expect_tx(sb + B_G, 320);
        bulk_load(sb + O_GT, g_gate + tb * 160, 320, sb + B_G);
        mbar_wait(sb + B_P3R, 0);
#pragma unroll 1
        for (int ks = 0; ks < 10; ks++) {
          const int q = ks < 6 ? ks : ks - 6;
          if (ks > 5 || (ks == 5 && main_cta)) mbar_wait(sb + B_P3E + 8 * (ks == 5 ? 4 : q), 0);
          PTP(ks >= 5, ks);
          mbar_expect_tx(sb + B_P3F + 8 * q, P3S);
          tma2(sb + q * P3S, &M.wo, cb * 64, ks * 64, sb + B_P3F + 8 * q);
          tma2_mc(sb + q * P3S + 8192 + rank * 10240, &M.o_ld, ks * 64, tb * 160 + rank * 80, sb + B_P3F + 8 * q);
        }
      }
    }
  }
}

typedef CUresult (*PFN_enc)(CUtensorMap*, CUtensorMapDataType, cuuint32_t, void*, const cuuint64_t*, const cuuint64_t*, const cuuint32_t*,
                            const cuuint32_t*, CUtensorMapInterleave, CUtensorMapSwizzle, CUtensorMapL2promotion, CUtensorMapFloatOOBfill);
static void enc(PFN_enc f, CUtensorMap* m, const void* base, int rank, const cuuint64_t* dims, const cuuint64_t* strides, const cuuint32_t* box,
                CUtensorMapSwizzle sw) {
  const cuuint32_t es[5] = {1, 1, 1, 1, 1};
  f(m, CU_TENSOR_MAP_DATA_TYPE_BFLOAT16, rank, (void*)base, dims, strides, box, es, CU_TENSOR_MAP_INTERLEAVE_NONE, sw,
    CU_TENSOR_MAP_L2_PROMOTION_NONE, CU_TENSOR_MAP_FLOAT_OOB_FILL_NONE);
}

extern "C" void kernel_launch(void* const* d_in, const int* in_sizes, int n_in, void* d_out, int out_size) {
  (void)in_sizes; (void)n_in; (void)out_size;
  static PFN_enc f = nullptr;
  static void *kvT, *y2T, *o;
  if (!f) {
    void* p = nullptr;
    cudaDriverEntryPointQueryResult q;
    cudaGetDriverEntryPoint("cuTensorMapEncodeTiled", &p, cudaEnableDefault, &q);
    f = (PFN_enc)p;
    cudaGetSymbolAddress(&kvT, g_kvT); cudaGetSymbolAddress(&y2T, g_y2T); cudaGetSymbolAddress(&o, g_o);
    cudaFuncSetAttribute(fused_kernel, cudaFuncAttributeMaxDynamicSharedMemorySize, SMEM_BYTES);
  }
  Maps M;
  const CUtensorMapSwizzle S0 = CU_TENSOR_MAP_SWIZZLE_NONE, S32 = CU_TENSOR_MAP_SWIZZLE_32B, S64 = CU_TENSOR_MAP_SWIZZLE_64B, S128 = CU_TENSOR_MAP_SWIZZLE_128B;
  const cuuint64_t dpar[3] = {640, 2, 1024}, spar[2] = {1280, 2560};
  const cuuint64_t dw[3] = {640, 640, 3}, sw[2] = {3840, 1280};
  const cuuint64_t dnat[2] = {640, 2048}, snat[1] = {1280};
  const cuuint64_t dT[3] = {32, 640, 64}, sT[2] = {4096, 64};
  const cuuint64_t dwo[2] = {640, 640};
  { const cuuint32_t bx[3] = {64, 1, 128}; enc(f, &M.x_par, d_in[0], 3, dpar, spar, bx, S128); }
  { const cuuint32_t bx[3] = {64, 16, 3}; enc(f, &M.w_main, d_in[7], 3, dw, sw, bx, S128); }
  { const cuuint32_t bx[3] = {16, 16, 3}; enc(f, &M.w_tail, d_in[7], 3, dw, sw, bx, S32); }
  { const cuuint32_t bx[3] = {80, 1, 128}; enc(f, &M.o_st, o, 3, dpar, spar, bx, S0); }
  { const cuuint32_t bx[3] = {32, 64, 1}; enc(f, &M.kv_st, kvT, 3, dT, sT, bx, S64); }
  { const cuuint32_t bx[3] = {32, 32, 5}; enc(f, &M.y_ld, y2T, 3, dT, sT, bx, S64); }
  { const cuuint32_t bx[2] = {64, 64}; enc(f, &M.wo, d_in[8], 2, dwo, snat, bx, S128); }
  { const cuuint32_t bx[2] = {64, 80}; enc(f, &M.o_ld, o, 2, dnat, snat, bx, S128); }
  fused_kernel<<<130, 512, SMEM_BYTES, cudaStreamPerThread>>>((const uint16_t*)d_in[0], (const uint16_t*)d_in[7], M, (const uint16_t*)d_in[3], (const uint16_t*)d_in[4], (const uint16_t*)d_in[5], (const uint16_t*)d_in[9],
                                                              (const uint16_t*)d_in[1], (const uint16_t*)d_in[2], (uint16_t*)d_out);
}
```

```cpp
#include <cuda_runtime.h>
#include <cuda_bf16.h>
#include <cuda.h>
#include <stdint.h>

#define DEVI __device__ __forceinline__
#define PT1 900
#define PTD 460
#define PTE 100
#define KT0 1500
#define KTD 1500
#define RC 192
#define RH 96
#define RP 32
#define SNOOZE 100
#define P1U 7
#define LEAD 3

DEVI uint32_t smem_u32(const void* p) { return (uint32_t)__cvta_generic_to_shared(p); }
DEVI void wg_fence() { asm volatile("wgmma.fence.sync.aligned;" ::: "memory"); }
DEVI void wg_commit() { asm volatile("wgmma.commit_group.sync.aligned;" ::: "memory"); }
template <int N> DEVI void wg_wait() { asm volatile("wgmma.wait_group.sync.aligned %0;" ::"n"(N) : "memory"); }
template <int S> DEVI void fence_regs(float (&d)[S]) {
#pragma unroll
  for (int i = 0; i < S; i++) asm volatile("" : "+f"(d[i])::"memory");
}
DEVI uint64_t mkdesc(uint32_t addr, uint32_t lbo, uint32_t sbo, int swz) {
  return (uint64_t)((addr & 0x3FFFF) >> 4) | ((uint64_t)(lbo >> 4) << 16) | ((uint64_t)(sbo >> 4) << 32) | ((uint64_t)swz << 62);
}
DEVI void mbar_init(uint32_t bar, uint32_t cnt) { asm volatile("mbarrier.init.shared::cta.b64 [%0], %1;" ::"r"(bar), "r"(cnt) : "memory"); }
DEVI void mbar_expect_tx(uint32_t bar, uint32_t bytes) { asm volatile("mbarrier.arrive.expect_tx.shared::cta.b64 _, [%0], %1;" ::"r"(bar), "r"(bytes) : "memory"); }
DEVI void mbar_arrive(uint32_t bar) { asm volatile("mbarrier.arrive.shared::cta.b64 _, [%0];" ::"r"(bar) : "memory"); }
DEVI void mbar_wait(uint32_t bar, uint32_t parity) {
  asm volatile("{\n.reg .pred p;\nLAB_WAIT:\nmbarrier.try_wait.parity.shared::cta.b64 p, [%0], %1;\n@!p bra LAB_WAIT;\n}" ::"r"(bar), "r"(parity) : "memory");
}
DEVI void mbar_wait_wd(uint32_t bar, uint32_t parity, uint32_t t0) {
  asm volatile("{\n.reg .pred p;\n.reg .u32 c;\nLAB_WAIT:\nmbarrier.try_wait.parity.shared::cta.b64 p, [%0], %1;\n@p bra DONE;\nmov.u32 c, %%clock;\nsub.u32 c, c, %2;\nsetp.lt.u32 p, c, 0x70000000;\n@p bra LAB_WAIT;\ntrap;\nDONE:\n}" ::"r"(bar), "r"(parity), "r"(t0) : "memory");
}
DEVI void flag_wait(const unsigned* p, unsigned target) {
  asm volatile("{\n.reg .pred p;\n.reg .s32 v;\nLAB_WAIT:\nld.relaxed.gpu.global.u32 v, [%0];\nsub.s32 v, v, %1;\nsetp.lt.s32 p, v, 0;\n@p bra LAB_WAIT;\n}" ::"l"(p), "r"(target) : "memory");
}
DEVI void flag_add(unsigned* p, unsigned v) { asm volatile("red.relaxed.gpu.global.add.u32 [%0], %1;" ::"l"(p), "r"(v) : "memory"); }
DEVI void fence_async_smem() { asm volatile("fence.proxy.async.shared::cta;" ::: "memory"); }
DEVI bool elect_one() { uint32_t p; asm volatile("{\n.reg .pred P;\nelect.sync _|P, 0xffffffff;\nselp.u32 %0, 1, 0, P;\n}" : "=r"(p)); return p; }
DEVI void bar_sync(int id, int n) { asm volatile("bar.sync %0, %1;" ::"r"(id), "r"(n) : "memory"); }
DEVI void bar_arrive(int id, int n) { asm volatile("bar.arrive %0, %1;" ::"r"(id), "r"(n) : "memory"); }
DEVI void tma2(uint32_t dst, const CUtensorMap* m, int c0, int c1, uint32_t bar) {
  asm volatile("cp.async.bulk.tensor.2d.shared::cluster.global.mbarrier::complete_tx::bytes [%0], [%1, {%3, %4}], [%2];" ::"r"(dst), "l"(m), "r"(bar), "r"(c0), "r"(c1) : "memory");
}
DEVI void tma3(uint32_t dst, const CUtensorMap* m, int c0, int c1, int c2, uint32_t bar) {
  asm volatile("cp.async.bulk.tensor.3d.shared::cluster.global.mbarrier::complete_tx::bytes [%0], [%1, {%3, %4, %5}], [%2];" ::"r"(dst), "l"(m), "r"(bar), "r"(c0), "r"(c1), "r"(c2) : "memory");
}
DEVI void tma3_mc(uint32_t dst, const CUtensorMap* m, int c0, int c1, int c2, uint32_t bar) {
  asm volatile("cp.async.bulk.tensor.3d.shared::cluster.global.mbarrier::complete_tx::bytes.multicast::cluster [%0], [%1, {%3, %4, %5}], [%2], %6;" ::"r"(dst), "l"(m), "r"(bar), "r"(c0), "r"(c1), "r"(c2), "h"((uint16_t)3) : "memory");
}
DEVI void tma2_mc(uint32_t dst, const CUtensorMap* m, int c0, int c1, uint32_t bar) {
  asm volatile("cp.async.bulk.tensor.2d.shared::cluster.global.mbarrier::complete_tx::bytes.multicast::cluster [%0], [%1, {%3, %4}], [%2], %5;" ::"r"(dst), "l"(m), "r"(bar), "r"(c0), "r"(c1), "h"((uint16_t)3) : "memory");
}
DEVI void mbar_arrive_remote(uint32_t bar, uint32_t cta) {
  asm volatile("{\n.reg .b32 ra;\nmapa.shared::cluster.u32 ra, %0, %1;\nmbarrier.arrive.shared::cluster.b64 _, [ra];\n}" ::"r"(bar), "r"(cta) : "memory");
}
DEVI void tma3_store(const CUtensorMap* m, int c0, int c1, int c2, uint32_t src) {
  asm volatile("cp.async.bulk.tensor.3d.global.shared::cta.bulk_group [%0, {%2, %3, %4}], [%1];" ::"l"(m), "r"(src), "r"(c0), "r"(c1), "r"(c2) : "memory");
}
DEVI void bulk_load(uint32_t dst, const void* src, uint32_t bytes, uint32_t bar) {
  asm volatile("cp.async.bulk.shared::cluster.global.mbarrier::complete_tx::bytes [%0], [%1], %2, [%3];" ::"r"(dst), "l"(src), "r"(bytes), "r"(bar) : "memory");
}
DEVI void bulk_store(void* dst, uint32_t src, uint32_t bytes) {
  asm volatile("cp.async.bulk.global.shared::cta.bulk_group [%0], [%1], %2;" ::"l"(dst), "r"(src), "r"(bytes) : "memory");
}
DEVI void pf_l2(const void* p) { asm volatile("prefetch.global.L2 [%0];" ::"l"(p)); }
template <int OFF> DEVI uint32_t ldg_v(const void* p) { uint32_t v; asm volatile("ld.volatile.global.b32 %0, [%1 + %2];" : "=r"(v) : "l"(p), "n"(OFF)); return v; }
DEVI void bulk_commit() { asm volatile("cp.async.bulk.commit_group;" ::: "memory"); }
DEVI void bulk_wait_all() { asm volatile("cp.async.bulk.wait_group 0;" ::: "memory"); }
DEVI void bulk_wait_read() { asm volatile("cp.async.bulk.wait_group.read 0;" ::: "memory"); }
template <int R> DEVI void reg_inc() { asm volatile("setmaxnreg.inc.sync.aligned.u32 %0;" ::"n"(R)); }
template <int R> DEVI void reg_dec() { asm volatile("setmaxnreg.dec.sync.aligned.u32 %0;" ::"n"(R)); }
DEVI uint32_t prmt(uint32_t a, uint32_t b, uint32_t s) { uint32_t r; asm("prmt.b32 %0,%1,%2,%3;" : "=r"(r) : "r"(a), "r"(b), "r"(s)); return r; }
DEVI uint32_t lds32(uint32_t a) { uint32_t r; asm volatile("ld.shared.b32 %0,[%1];" : "=r"(r) : "r"(a)); return r; }
DEVI void sts32(uint32_t a, uint32_t x) { asm volatile("st.shared.b32 [%0],%1;" ::"r"(a), "r"(x) : "memory"); }
DEVI void sts128(uint32_t a, uint32_t x, uint32_t y, uint32_t z, uint32_t w) { asm volatile("st.shared.v4.b32 [%0],{%1,%2,%3,%4};" ::"r"(a), "r"(x), "r"(y), "r"(z), "r"(w) : "memory"); }
DEVI void sts128v(uint32_t a, uint32_t x, uint32_t y, uint32_t z, uint32_t w) { asm volatile("st.volatile.shared.v4.b32 [%0],{%1,%2,%3,%4};" ::"r"(a), "r"(x), "r"(y), "r"(z), "r"(w) : "memory"); }
DEVI void lds128(uint32_t a, uint32_t& x, uint32_t& y, uint32_t& z, uint32_t& w) { asm volatile("ld.shared.v4.b32 {%0,%1,%2,%3},[%4];" : "=r"(x), "=r"(y), "=r"(z), "=r"(w) : "r"(a) : "memory"); }
DEVI void ldsm4(uint32_t& r0, uint32_t& r1, uint32_t& r2, uint32_t& r3, uint32_t addr) {
  asm volatile("ldmatrix.sync.aligned.m8n8.x4.shared.b16 {%0,%1,%2,%3}, [%4];" : "=r"(r0), "=r"(r1), "=r"(r2), "=r"(r3) : "r"(addr) : "memory");
}
DEVI void ldsm4t(uint32_t& r0, uint32_t& r1, uint32_t& r2, uint32_t& r3, uint32_t addr) {
  asm volatile("ldmatrix.sync.aligned.m8n8.x4.trans.shared.b16 {%0,%1,%2,%3}, [%4];" : "=r"(r0), "=r"(r1), "=r"(r2), "=r"(r3) : "r"(addr) : "memory");
}
DEVI void stsm4(uint32_t addr, uint32_t r0, uint32_t r1, uint32_t r2, uint32_t r3) {
  asm volatile("stmatrix.sync.aligned.m8n8.x4.shared.b16 [%0], {%1,%2,%3,%4};" ::"r"(addr), "r"(r0), "r"(r1), "r"(r2), "r"(r3) : "memory");
}
DEVI void stsm4t(uint32_t addr, uint32_t r0, uint32_t r1, uint32_t r2, uint32_t r3) {
  asm volatile("stmatrix.sync.aligned.m8n8.x4.trans.shared.b16 [%0], {%1,%2,%3,%4};" ::"r"(addr), "r"(r0), "r"(r1), "r"(r2), "r"(r3) : "memory");
}
DEVI uint32_t movm(uint32_t a) { uint32_t r; asm volatile("movmatrix.sync.aligned.m8n8.trans.b16 %0, %1;" : "=r"(r) : "r"(a)); return r; }
DEVI uint32_t pack_bf16(float lo, float hi) { uint32_t r; asm("cvt.rn.bf16x2.f32 %0, %1, %2;" : "=r"(r) : "f"(hi), "f"(lo)); return r; }
DEVI uint32_t hmul2(uint32_t a, uint32_t b) { uint32_t r; asm("mul.rn.bf16x2 %0,%1,%2;" : "=r"(r) : "r"(a), "r"(b)); return r; }
DEVI uint32_t hadd2(uint32_t a, uint32_t b) { uint32_t r; asm("add.rn.bf16x2 %0,%1,%2;" : "=r"(r) : "r"(a), "r"(b)); return r; }
DEVI float bf_lo(uint32_t a) { return __uint_as_float(prmt(a, 0, 0x1044)); }
DEVI float bf_hi(uint32_t a) { return __uint_as_float(a & 0xFFFF0000u); }
DEVI void mma16(float (&c)[4], uint32_t a0, uint32_t a1, uint32_t a2, uint32_t a3, uint32_t b0, uint32_t b1) {
  asm("mma.sync.aligned.m16n8k16.row.col.f32.bf16.bf16.f32 {%0,%1,%2,%3},{%4,%5,%6,%7},{%8,%9},{%0,%1,%2,%3};"
      : "+f"(c[0]), "+f"(c[1]), "+f"(c[2]), "+f"(c[3]) : "r"(a0), "r"(a1), "r"(a2), "r"(a3), "r"(b0), "r"(b1));
}
DEVI void mma8(float (&c)[4], uint32_t a0, uint32_t a1, uint32_t b0) {
  asm("mma.sync.aligned.m16n8k8.row.col.f32.bf16.bf16.f32 {%0,%1,%2,%3},{%4,%5},{%6},{%0,%1,%2,%3};"
      : "+f"(c[0]), "+f"(c[1]), "+f"(c[2]), "+f"(c[3]) : "r"(a0), "r"(a1), "r"(b0));
}
DEVI float ex2(float x) { float r; asm("ex2.approx.ftz.f32 %0, %1;" : "=f"(r) : "f"(x)); return r; }

DEVI uint32_t clk() { uint32_t c; asm volatile("mov.u32 %0, %%clock;" : "=r"(c)); return c; }
DEVI void wait_until(uint32_t t0, int dt) { while ((int)(clk() - t0) < dt) __nanosleep(40); }
DEVI void spin_until(uint32_t t0, int dt) { while ((int)(clk() - t0) < dt) {} }
DEVI uint32_t hfma2(uint32_t a, uint32_t b, uint32_t c) { uint32_t r; asm("fma.rn.bf16x2 %0,%1,%2,%3;" : "=r"(r) : "r"(a), "r"(b), "r"(c)); return r; }
DEVI void bar_sync_p(int on, int id, int n) { asm volatile("{\n.reg .pred p;\nsetp.ne.b32 p, %0, 0;\n@p bar.sync %1, %2;\n}" ::"r"(on), "r"(id), "r"(n) : "memory"); }
DEVI void bar_arrive_p(int on, int id, int n) { asm volatile("{\n.reg .pred p;\nsetp.ne.b32 p, %0, 0;\n@p bar.arrive %1, %2;\n}" ::"r"(on), "r"(id), "r"(n) : "memory"); }
DEVI void mbar_arrive_p(int on, uint32_t bar) { asm volatile("{\n.reg .pred p;\nsetp.ne.b32 p, %1, 0;\n@p mbarrier.arrive.shared::cta.b64 _, [%0];\n}" ::"r"(bar), "r"(on) : "memory"); }
DEVI void mbar_arrive2_p(int on, uint32_t bar, uint32_t rbar) {
  asm volatile("{\n.reg .pred p;\nsetp.ne.b32 p, %2, 0;\n@p mbarrier.arrive.shared::cta.b64 _, [%0];\n@p mbarrier.arrive.shared::cluster.b64 _, [%1];\n}" ::"r"(bar), "r"(rbar), "r"(on) : "memory");
}
DEVI uint32_t mapa(uint32_t a, uint32_t cta) { uint32_t r; asm("mapa.shared::cluster.u32 %0, %1, %2;" : "=r"(r) : "r"(a), "r"(cta)); return r; }
DEVI void st_async128(uint32_t a, uint32_t x, uint32_t y, uint32_t z, uint32_t w, uint32_t bar) {
  asm volatile("st.async.weak.shared::cluster.mbarrier::complete_tx::bytes.v4.b32 [%0], {%1,%2,%3,%4}, [%5];" ::"r"(a), "r"(x), "r"(y), "r"(z), "r"(w), "r"(bar) : "memory");
}

template<int OFF, int TB, int S> __device__ __forceinline__ void wgmma_rs_n192(float (&d)[S], uint32_t a0, uint32_t a1, uint32_t a2, uint32_t a3, uint64_t db, int sd) {
  asm volatile("{\n.reg .pred p;\nsetp.ne.b32 p, %101, 0;\n"
    "wgmma.mma_async.sync.aligned.m64n192k16.f32.bf16.bf16 {%0, %1, %2, %3, %4, %5, %6, %7, %8, %9, %10, %11, %12, %13, %14, %15, %16, %17, %18, %19, %20, %21, %22, %23, %24, %25, %26, %27, %28, %29, %30, %31, %32, %33, %34, %35, %36, %37, %38, %39, %40, %41, %42, %43, %44, %45, %46, %47, %48, %49, %50, %51, %52, %53, %54, %55, %56, %57, %58, %59, %60, %61, %62, %63, %64, %65, %66, %67, %68, %69, %70, %71, %72, %73, %74, %75, %76, %77, %78, %79, %80, %81, %82, %83, %84, %85, %86, %87, %88, %89, %90, %91, %92, %93, %94, %95}, {%96, %97, %98, %99}, %100, p, 1, 1, %102;\n}\n"
    : "+f"(d[OFF+0]), "+f"(d[OFF+1]), "+f"(d[OFF+2]), "+f"(d[OFF+3]), "+f"(d[OFF+4]), "+f"(d[OFF+5]), "+f"(d[OFF+6]), "+f"(d[OFF+7]), "+f"(d[OFF+8]), "+f"(d[OFF+9]), "+f"(d[OFF+10]), "+f"(d[OFF+11]), "+f"(d[OFF+12]), "+f"(d[OFF+13]), "+f"(d[OFF+14]), "+f"(d[OFF+15]), "+f"(d[OFF+16]), "+f"(d[OFF+17]), "+f"(d[OFF+18]), "+f"(d[OFF+19]), "+f"(d[OFF+20]), "+f"(d[OFF+21]), "+f"(d[OFF+22]), "+f"(d[OFF+23]), "+f"(d[OFF+24]), "+f"(d[OFF+25]), "+f"(d[OFF+26]), "+f"(d[OFF+27]), "+f"(d[OFF+28]), "+f"(d[OFF+29]), "+f"(d[OFF+30]), "+f"(d[OFF+31]), "+f"(d[OFF+32]), "+f"(d[OFF+33]), "+f"(d[OFF+34]), "+f"(d[OFF+35]), "+f"(d[OFF+36]), "+f"(d[OFF+37]), "+f"(d[OFF+38]), "+f"(d[OFF+39]), "+f"(d[OFF+40]), "+f"(d[OFF+41]), "+f"(d[OFF+42]), "+f"(d[OFF+43]), "+f"(d[OFF+44]), "+f"(d[OFF+45]), "+f"(d[OFF+46]), "+f"(d[OFF+47]), "+f"(d[OFF+48]), "+f"(d[OFF+49]), "+f"(d[OFF+50]), "+f"(d[OFF+51]), "+f"(d[OFF+52]), "+f"(d[OFF+53]), "+f"(d[OFF+54]), "+f"(d[OFF+55]), "+f"(d[OFF+56]), "+f"(d[OFF+57]), "+f"(d[OFF+58]), "+f"(d[OFF+59]), "+f"(d[OFF+60]), "+f"(d[OFF+61]), "+f"(d[OFF+62]), "+f"(d[OFF+63]), "+f"(d[OFF+64]), "+f"(d[OFF+65]), "+f"(d[OFF+66]), "+f"(d[OFF+67]), "+f"(d[OFF+68]), "+f"(d[OFF+69]), "+f"(d[OFF+70]), "+f"(d[OFF+71]), "+f"(d[OFF+72]), "+f"(d[OFF+73]), "+f"(d[OFF+74]), "+f"(d[OFF+75]), "+f"(d[OFF+76]), "+f"(d[OFF+77]), "+f"(d[OFF+78]), "+f"(d[OFF+79]), "+f"(d[OFF+80]), "+f"(d[OFF+81]), "+f"(d[OFF+82]), "+f"(d[OFF+83]), "+f"(d[OFF+84]), "+f"(d[OFF+85]), "+f"(d[OFF+86]), "+f"(d[OFF+87]), "+f"(d[OFF+88]), "+f"(d[OFF+89]), "+f"(d[OFF+90]), "+f"(d[OFF+91]), "+f"(d[OFF+92]), "+f"(d[OFF+93]), "+f"(d[OFF+94]), "+f"(d[OFF+95]) : "r"(a0), "r"(a1), "r"(a2), "r"(a3), "l"(db), "r"(sd), "n"(TB));
}
template<int OFF, int TB, int S> __device__ __forceinline__ void wgmma_rs_n48(float (&d)[S], uint32_t a0, uint32_t a1, uint32_t a2, uint32_t a3, uint64_t db, int sd) {
  asm volatile("{\n.reg .pred p;\nsetp.ne.b32 p, %29, 0;\n"
    "wgmma.mma_async.sync.aligned.m64n48k16.f32.bf16.bf16 {%0, %1, %2, %3, %4, %5, %6, %7, %8, %9, %10, %11, %12, %13, %14, %15, %16, %17, %18, %19, %20, %21, %22, %23}, {%24, %25, %26, %27}, %28, p, 1, 1, %30;\n}\n"
    : "+f"(d[OFF+0]), "+f"(d[OFF+1]), "+f"(d[OFF+2]), "+f"(d[OFF+3]), "+f"(d[OFF+4]), "+f"(d[OFF+5]), "+f"(d[OFF+6]), "+f"(d[OFF+7]), "+f"(d[OFF+8]), "+f"(d[OFF+9]), "+f"(d[OFF+10]), "+f"(d[OFF+11]), "+f"(d[OFF+12]), "+f"(d[OFF+13]), "+f"(d[OFF+14]), "+f"(d[OFF+15]), "+f"(d[OFF+16]), "+f"(d[OFF+17]), "+f"(d[OFF+18]), "+f"(d[OFF+19]), "+f"(d[OFF+20]), "+f"(d[OFF+21]), "+f"(d[OFF+22]), "+f"(d[OFF+23]) : "r"(a0), "r"(a1), "r"(a2), "r"(a3), "l"(db), "r"(sd), "n"(TB));
}
template<int OFF, int TB, int S> __device__ __forceinline__ void wgmma_rs_n16(float (&d)[S], uint32_t a0, uint32_t a1, uint32_t a2, uint32_t a3, uint64_t db, int sd) {
  asm volatile("{\n.reg .pred p;\nsetp.ne.b32 p, %13, 0;\n"
    "wgmma.mma_async.sync.aligned.m64n16k16.f32.bf16.bf16 {%0, %1, %2, %3, %4, %5, %6, %7}, {%8, %9, %10, %11}, %12, p, 1, 1, %14;\n}\n"
    : "+f"(d[OFF+0]), "+f"(d[OFF+1]), "+f"(d[OFF+2]), "+f"(d[OFF+3]), "+f"(d[OFF+4]), "+f"(d[OFF+5]), "+f"(d[OFF+6]), "+f"(d[OFF+7]) : "r"(a0), "r"(a1), "r"(a2), "r"(a3), "l"(db), "r"(sd), "n"(TB));
}
template<int OFF, int TA, int TB, int S> __device__ __forceinline__ void wgmma_ss_n160(float (&d)[S], uint64_t da, uint64_t db, int sd) {
  asm volatile("{\n.reg .pred p;\nsetp.ne.b32 p, %82, 0;\n"
    "wgmma.mma_async.sync.aligned.m64n160k16.f32.bf16.bf16 {%0, %1, %2, %3, %4, %5, %6, %7, %8, %9, %10, %11, %12, %13, %14, %15, %16, %17, %18, %19, %20, %21, %22, %23, %24, %25, %26, %27, %28, %29, %30, %31, %32, %33, %34, %35, %36, %37, %38, %39, %40, %41, %42, %43, %44, %45, %46, %47, %48, %49, %50, %51, %52, %53, %54, %55, %56, %57, %58, %59, %60, %61, %62, %63, %64, %65, %66, %67, %68, %69, %70, %71, %72, %73, %74, %75, %76, %77, %78, %79}, %80, %81, p, 1, 1, %83, %84;\n}\n"
    : "+f"(d[OFF+0]), "+f"(d[OFF+1]), "+f"(d[OFF+2]), "+f"(d[OFF+3]), "+f"(d[OFF+4]), "+f"(d[OFF+5]), "+f"(d[OFF+6]), "+f"(d[OFF+7]), "+f"(d[OFF+8]), "+f"(d[OFF+9]), "+f"(d[OFF+10]), "+f"(d[OFF+11]), "+f"(d[OFF+12]), "+f"(d[OFF+13]), "+f"(d[OFF+14]), "+f"(d[OFF+15]), "+f"(d[OFF+16]), "+f"(d[OFF+17]), "+f"(d[OFF+18]), "+f"(d[OFF+19]), "+f"(d[OFF+20]), "+f"(d[OFF+21]), "+f"(d[OFF+22]), "+f"(d[OFF+23]), "+f"(d[OFF+24]), "+f"(d[OFF+25]), "+f"(d[OFF+26]), "+f"(d[OFF+27]), "+f"(d[OFF+28]), "+f"(d[OFF+29]), "+f"(d[OFF+30]), "+f"(d[OFF+31]), "+f"(d[OFF+32]), "+f"(d[OFF+33]), "+f"(d[OFF+34]), "+f"(d[OFF+35]), "+f"(d[OFF+36]), "+f"(d[OFF+37]), "+f"(d[OFF+38]), "+f"(d[OFF+39]), "+f"(d[OFF+40]), "+f"(d[OFF+41]), "+f"(d[OFF+42]), "+f"(d[OFF+43]), "+f"(d[OFF+44]), "+f"(d[OFF+45]), "+f"(d[OFF+46]), "+f"(d[OFF+47]), "+f"(d[OFF+48]), "+f"(d[OFF+49]), "+f"(d[OFF+50]), "+f"(d[OFF+51]), "+f"(d[OFF+52]), "+f"(d[OFF+53]), "+f"(d[OFF+54]), "+f"(d[OFF+55]), "+f"(d[OFF+56]), "+f"(d[OFF+57]), "+f"(d[OFF+58]), "+f"(d[OFF+59]), "+f"(d[OFF+60]), "+f"(d[OFF+61]), "+f"(d[OFF+62]), "+f"(d[OFF+63]), "+f"(d[OFF+64]), "+f"(d[OFF+65]), "+f"(d[OFF+66]), "+f"(d[OFF+67]), "+f"(d[OFF+68]), "+f"(d[OFF+69]), "+f"(d[OFF+70]), "+f"(d[OFF+71]), "+f"(d[OFF+72]), "+f"(d[OFF+73]), "+f"(d[OFF+74]), "+f"(d[OFF+75]), "+f"(d[OFF+76]), "+f"(d[OFF+77]), "+f"(d[OFF+78]), "+f"(d[OFF+79]) : "l"(da), "l"(db), "r"(sd), "n"(TA), "n"(TB));
}

__device__ __align__(1024) uint16_t g_kvT[640 * 2048];
__device__ __align__(1024) uint16_t g_y2T[640 * 2048];
__device__ __align__(1024) uint16_t g_o[2048 * 640];
__device__ __align__(1024) uint16_t g_gate[2080];
__device__ __align__(1024) uint4 g_halo[128 * 10 * 32];
__device__ __align__(1024) unsigned g_cnt[46 * 32];
__device__ __align__(1024) unsigned g_launch[132];
#define CNT_KV(i) (g_cnt + 32 * (i))
#define CNT_O(i) (g_cnt + 32 * (10 + (i)))
#define CNT_Y(i) (g_cnt + 32 * (26 + (i)))
#define PT(i) do {} while (0)
#define PTP(on, i) do {} while (0)

constexpr uint32_t SB = 1024;
constexpr uint32_t STG = 23552, WST = 15360;
DEVI constexpr uint32_t o_px(int ks) { return (((ks >> 1) + 1) & 3) * 2 * STG; }
DEVI constexpr uint32_t o_pw(int ks) { return o_px(ks) + 16384 + (ks & 1) * WST; }
constexpr uint32_t O_HALO = 0, O_OST = STG;
constexpr uint32_t P3S = 28672;
constexpr uint32_t HC = 8320, UC = 4624, UZ = 528;
constexpr uint32_t O_H0 = 5 * P3S, O_U2 = O_H0 + 3 * HC, O_H3 = O_U2 + UC, O_U0 = O_H3 + 2 * HC;
DEVI constexpr uint32_t o_h(int c) { return O_H0 + c * HC + (c > 2 ? UC : 0); }
DEVI constexpr uint32_t o_u(int c) { return c == 2 ? O_U2 : O_U0 + (c > 2 ? c - 1 : c) * UC; }
constexpr uint32_t O_Y = 208896;
DEVI constexpr uint32_t o_x(int c) { return c < 2 ? O_Y + c * 5120 : O_U0 + (c & 1) * UC; }
constexpr uint32_t O_HIN = O_U0 + 3 * UC + UZ;
constexpr uint32_t O_BT = 4 * P3S;
constexpr uint32_t O_GT = O_Y + 20480, O_GW = O_GT + 320;
constexpr uint32_t O_BAR = 231040;
constexpr uint32_t B_FULL = O_BAR, B_P3F = O_BAR + 8 * 8, B_P3R = O_BAR + 8 * 14, B_G = O_BAR + 8 * 15, B_U = O_BAR + 8 * 16, B_HR = O_BAR + 8 * 21,
                   B_Y = O_BAR + 8 * 26, B_EP = O_BAR + 8 * 28, B_LAST = O_BAR + 8 * 29, B_GW = O_BAR + 8 * 30, B_DONE = O_BAR + 8 * 31, B_P1E = O_BAR + 8 * 32,
                   B_AD = O_BAR + 8 * 33, B_HX = O_BAR + 8 * 33  , B_EMPTY = O_BAR + 8 * 44, B_P3E = O_BAR + 8 * 52, B_HX0 = O_BAR + 8 * 57;
constexpr uint32_t B_S13 = B_EMPTY + 8 * 5, B_S15 = B_EMPTY + 8 * 7, B_S19 = B_EMPTY + 8 * 3;
constexpr uint32_t O_GP = O_BAR + 512, O_EPOCH = O_GW + 1280;
constexpr uint32_t SMEM_BYTES = 232448;
static_assert(O_U0 + 4 * UC <= O_Y && O_EPOCH + 4 <= O_BAR && O_U0 >= 8 * STG, "smem map");
enum { NB_LEAD = 1, NB_HELP = 2, NB_HALO = 3, NB_ATT = 4, NB_G = 5, NB_TOK = 6, NB_RFULL = 8, NB_RFREE = 10 };

struct Maps { CUtensorMap x_par, w_main, w_tail, o_st, kv_st, wo, o_ld, y_ld; };

template <int M> DEVI void conv_step(float (&acc)[128], uint32_t a0, uint32_t a1, uint32_t a2, uint32_t a3, uint32_t dl) {
  auto D = [&](int off) { return ((uint64_t)8 << 32) | (uint64_t)(uint32_t)(dl + off - 16 * M); };
  if constexpr (M == 0) wgmma_rs_n16<0, 0>(acc, a0, a1, a2, a3, D(0), 0);
  if constexpr (M <= 3) wgmma_rs_n48<8, 0>(acc, a0, a1, a2, a3, D(16), M == 0 ? 0 : 1);
  if constexpr (M <= 6) wgmma_rs_n48<32, 0>(acc, a0, a1, a2, a3, D(64), M == 0 ? 0 : 1);
  if constexpr (M <= 9) wgmma_rs_n48<56, 0>(acc, a0, a1, a2, a3, D(112), M == 0 ? 0 : 1);
  if constexpr (M <= 12) wgmma_rs_n48<80, 0>(acc, a0, a1, a2, a3, D(160), M == 0 ? 0 : 1);
  wgmma_rs_n48<104, 0>(acc, a0, a1, a2, a3, D(208), M == 0 ? 0 : 1);
}
template <int P> DEVI void load_pair(uint32_t (&a)[8], uint32_t ab) {
#pragma unroll
  for (int i = 0; i < 2; i++) {
    const int m = i ? 15 - P : P;
    a[4 * i + 0] = lds32(ab - 4 * (64 * m));
    a[4 * i + 1] = lds32(ab - 4 * (64 * m + 32));
    a[4 * i + 2] = lds32(ab - 4 * (64 * m - 4));
    a[4 * i + 3] = lds32(ab - 4 * (64 * m + 28));
  }
}
template <int P> DEVI void mma_pair(float (&acc)[128], uint32_t (&a)[8], uint32_t db) {
  wg_fence();
  conv_step<P>(acc, a[0], a[1], a[2], a[3], db);
  conv_step<15 - P>(acc, a[4], a[5], a[6], a[7], db);
  wg_commit();
}

DEVI void conv_reduce(uint32_t sb, int c, int ht, int chan) {
  const uint32_t a0 = sb + o_h(c) + ht * 16, a2 = sb + o_u(c) + ht * 16, a3 = sb + o_x(c) + ht * 16;
  uint4* yp = (uint4*)(g_y2T + (size_t)chan * 2048) + ht;
#pragma unroll
  for (int i = 0; i < 2; i++) {
    uint4 p, q, r, s;
    lds128(a0 + i * 2048, p.x, p.y, p.z, p.w); lds128(a0 + 4160 + i * 2048, q.x, q.y, q.z, q.w);
    lds128(a2 + i * 2048, r.x, r.y, r.z, r.w); lds128(a3 + i * 2048, s.x, s.y, s.z, s.w);
    yp[i * 128] = make_uint4(hadd2(hadd2(p.x, q.x), hadd2(r.x, s.x)), hadd2(hadd2(p.y, q.y), hadd2(r.y, s.y)),
                             hadd2(hadd2(p.z, q.z), hadd2(r.z, s.z)), hadd2(hadd2(p.w, q.w), hadd2(r.w, s.w)));
  }
}

template <int I> DEVI void ld_rows(uint32_t (&kk)[32], uint32_t (&vv)[32], const char* kp, const char* vp) {
  if constexpr (I < 32) { kk[I] = ldg_v<I * 1280>(kp); vv[I] = ldg_v<I * 1280>(vp); ld_rows<I + 1>(kk, vv, kp, vp); }
}

template <int ODD, int PART> DEVI void pack_qkv(const float (&acc)[120], uint32_t (&Q)[10][2], uint32_t (&K)[10][2], uint32_t (&V)[10][2]) {
#pragma unroll
  for (int f = 0; f < 10; f++) {
    const bool tail = ODD ? (f < 2) : (f >= 8);
    const int fm = ODD ? f - 2 : f, ft = ODD ? f : f - 8;
    const int nq = tail ? 24 + ft : fm, nk = tail ? 26 + ft : 8 + fm, nv = tail ? 28 + ft : 16 + fm;
    if (PART == 0) {
      V[f][1] = pack_bf16(acc[4 * nv + 2], acc[4 * nv + 3]);
      K[f][1] = pack_bf16(acc[4 * nk + 2], acc[4 * nk + 3]);
    } else {
      Q[f][0] = pack_bf16(acc[4 * nq], acc[4 * nq + 1]); Q[f][1] = pack_bf16(acc[4 * nq + 2], acc[4 * nq + 3]);
      K[f][0] = pack_bf16(acc[4 * nk], acc[4 * nk + 1]); V[f][0] = pack_bf16(acc[4 * nv], acc[4 * nv + 1]);
    }
  }
}
template <int R> DEVI void softmax8(float (&l)[R][2], uint32_t (&P)[R]) {
  const float C = 0.22360679774997896f * 1.4426950408889634f;
  float m[R], s[R];
#pragma unroll
  for (int j = 0; j < R; j++) m[j] = fmaxf(l[j][0], l[j][1]);
#pragma unroll
  for (int j = 0; j < R; j++) m[j] = fmaxf(m[j], __shfl_xor_sync(~0u, m[j], 1));
#pragma unroll
  for (int j = 0; j < R; j++) m[j] = fmaxf(m[j], __shfl_xor_sync(~0u, m[j], 2));
#pragma unroll
  for (int j = 0; j < R; j++) { const float mc = m[j] * C; l[j][0] = ex2(fmaf(l[j][0], C, -mc)); l[j][1] = ex2(fmaf(l[j][1], C, -mc)); s[j] = l[j][0] + l[j][1]; }
#pragma unroll
  for (int j = 0; j < R; j++) s[j] += __shfl_xor_sync(~0u, s[j], 1);
#pragma unroll
  for (int j = 0; j < R; j++) s[j] += __shfl_xor_sync(~0u, s[j], 2);
#pragma unroll
  for (int j = 0; j < R; j++) {
    float r; asm("rcp.approx.ftz.f32 %0, %1;" : "=f"(r) : "f"(s[j]));
    P[j] = pack_bf16(l[j][0] * r, l[j][1] * r);
  }
}

DEVI uint32_t make_ctx() {
  int b; asm volatile("mov.u32 %0, %%ctaid.x;" : "=r"(b));
  b += clk() & threadIdx.y;
  const int c = b >> 1, d = c - 36;
  const int p = c < 4 ? 32 + 8 * c : c < 36 ? c - 4 : 33 + d + ((37 * d) >> 8);
  const int j = b < 128 ? 8 * (p & 7) + (p >> 3) : 64, cp = (j * 79) >> 10;
  return ((2 * p + (b & 1)) & 255) | (j - 13 * cp) << 8 | (2 * cp + (b & 1)) << 12 | (b >> 7) << 16;
}
#define CTX() asm volatile("" : "+r"(ctx)); CTXU()
#define CTXU() int tid; asm volatile("mov.u32 %0, %%tid.x;" : "=r"(tid)); \
  const int lane = tid & 31, vb = ctx & 255, hg = (ctx >> 4) & 7, rt = ctx & 15, par = (ctx >> 3) & 1, mt = ctx & 7, rank = ctx & 1, \
  tb = (ctx >> 8) & 15, cb = (ctx >> 12) & 15; const bool main_cta = ctx < 65536; \
  (void)tid; (void)lane; (void)vb; (void)hg; (void)rt; (void)par; (void)mt; (void)rank; (void)tb; (void)cb; (void)main_cta
#define CTXW() CTX(); const int wg = warp >> 2, w = warp & 3, g = lane >> 2, t = lane & 3; const bool lead = (tid & 127) == 0; \
  (void)wg; (void)w; (void)g; (void)t; (void)lead

__global__ void __cluster_dims__(2, 1, 1) __launch_bounds__(512, 1)
fused_kernel(const uint16_t* __restrict__ xq, const uint16_t* __restrict__ wqkv, const __grid_constant__ Maps M, const uint16_t* __restrict__ shift_k, const uint16_t* __restrict__ ssm_k, const uint16_t* __restrict__ ssm_D,
             const uint16_t* __restrict__ gate_w, const uint16_t* __restrict__ kin, const uint16_t* __restrict__ vin, uint16_t* __restrict__ outp) {
  extern __shared__ __align__(1024) uint8_t smem_raw[];
  const uint32_t sb = smem_u32(smem_raw);
  const uint32_t t0 = clk();
  auto get_epoch = [&]() { mbar_wait(sb + B_EP, 0); return lds32(sb + O_EPOCH); };

  auto p1_load_x = [&](int ks, int p, int rank) {
    tma3(sb + o_px(ks), &M.x_par, ks * 32, (p >> 2) & 1, (p & 3) * 256 + rank * 128, sb + B_FULL + 8 * (ks & 7));
  };
  auto p1_load_w = [&](int ks, int p, int rank) {
    const uint32_t st = sb + o_pw(ks), fb = sb + B_FULL + 8 * (ks & 7);
    tma3_mc(st + rank * 6144, &M.w_main, (p >> 3) * 80 + 2 * (p & 8), ks * 32 + rank * 16, 0, fb);
    tma3_mc(st + 12288 + rank * 1536, &M.w_tail, (p >> 3) * 80 + 8 * (~p & 8), ks * 32 + rank * 16, 0, fb);
  };
  auto cta_pair = [&]() { const int c = blockIdx.x >> 1, d = c - 36; return c < 4 ? 32 + 8 * c : c < 36 ? c - 4 : 33 + d + ((37 * d) >> 8); };

  const int warp = __shfl_sync(~0u, threadIdx.x >> 5, 0);
  if (warp == 0) {
    asm volatile("barrier.cluster.arrive.relaxed.aligned;" ::: "memory");
    const unsigned b = blockIdx.x, l = threadIdx.x;
    if (b < 128 && l < 31) pf_l2(l < 16 ? xq + (16 * b + l) * 640 : wqkv + (15 * b + l - 16) * 64);
    __syncwarp();
  } else {
    if (elect_one()) {
      const uint32_t cnt = warp > 4 ? 1 : warp > 2 ? 6 : 2;
#pragma unroll
      for (int s = 0; s < 4; s++) mbar_init(sb + O_BAR + 480 - 32 * warp + 8 * s, cnt);
      asm volatile("fence.mbarrier_init.release.cluster;" ::: "memory");
    }
    __syncwarp();
    asm volatile("barrier.cluster.arrive.relaxed.aligned;" ::: "memory");
  }
  uint32_t ctx = 0;
  if (warp < 12) {
    asm volatile("barrier.cluster.wait.aligned;" ::: "memory");
    __nanosleep(SNOOZE);
    ctx = make_ctx();
  }

  if (warp < 8) {
    reg_inc<RC>();
    if (blockIdx.x < 128) {
      {
        uint32_t Q[10][2], K[10][2], V[10][2];
        {
          {
            float acc[120];
            unsigned epoch;
            {
              CTXW();
              const uint32_t aa = sb + (warp * 16 + (lane & 15)) * 128 + (((lane >> 4) ^ (lane & 7)) << 4);
              const uint32_t rsb = mapa(sb, (blockIdx.x & 1) ^ 1);
              uint32_t a0[8], a1[8], a2[8];
              auto load_a = [&](uint32_t (&r)[8], int ks) {
                mbar_wait(sb + B_FULL + 8 * (ks & 7), (ks >> 3) & 1);
                PTP(lead && (wg || !(ks & 3)), wg ? 60 + ks : 80 + (ks >> 2));
                ldsm4(r[0], r[1], r[2], r[3], (aa ^ ((ks & 1) * 64)) + o_px(ks)); ldsm4(r[4], r[5], r[6], r[7], (aa ^ ((ks & 1) * 64 + 32)) + o_px(ks));
              };
              auto stage = [&](uint32_t (&r)[8], uint32_t (&nx)[8], int ks, int u) {
                const uint32_t dl = o_pw(ks) >> 4;
                const uint64_t db = mkdesc(SB, 2048, 1024, 1), dt = mkdesc(SB + 12288, 512, 256, 3);
                auto D = [&](uint64_t d) { return (d & ~0xFFFFFFFFull) | (uint32_t)((uint32_t)d + dl); };
                if (LEAD && u == (20 - LEAD) % 3) bar_sync_p(wg == 0 && ks == 20 - LEAD, NB_LEAD, 256);
                wg_fence();
                wgmma_rs_n192<0, 1>(acc, r[0], r[1], r[2], r[3], D(db), 1);
                wgmma_rs_n48<96, 1>(acc, r[0], r[1], r[2], r[3], D(dt), 1);
                wg_commit();
                if (LEAD && u == 1) bar_arrive_p(wg && ks == 19, NB_LEAD, 256);
                load_a(nx, u == 1 ? min(ks + 1, 19) : ks + 1);
                wg_fence();
                wgmma_rs_n192<0, 1>(acc, r[4], r[5], r[6], r[7], D(db + 384), 1);
                wgmma_rs_n48<96, 1>(acc, r[4], r[5], r[6], r[7], D(dt + 96), 1);
                wg_commit();
                wg_wait<2>();
                mbar_arrive2_p(lead && (u || ks), sb + B_EMPTY + 8 * ((ks - 1) & 7), rsb + B_EMPTY + 8 * ((ks - 1) & 7));
              };
#pragma unroll
              for (int i = 0; i < 120; i++) acc[i] = 0.f;
              fence_regs(acc);
              load_a(a0, 0);
              constexpr int p1u = P1U;
#pragma unroll p1u
              for (int ks = 0; ks < 21; ks += 3) {
                stage(a0, a1, ks, 0);
                stage(a1, a2, ks + 1, 1);
                if (ks == 18) break;
                stage(a2, a0, ks + 2, 2);
              }
              epoch = get_epoch();
              mbar_wait(sb + B_S15, 1);
              wg_wait<0>();
              fence_regs(acc);
              mbar_arrive_p(tid == 0, sb + B_P1E);
              mbar_arrive2_p(lead, sb + B_S19, rsb + B_S19);
              PTP(lead, 50 + wg);
            }
            CTXW();
            if (hg & 1) pack_qkv<1, 0>(acc, Q, K, V); else pack_qkv<0, 0>(acc, Q, K, V);
#pragma unroll
            for (int f = 0; f < 10; f++) V[f][1] = movm(V[f][1]);
            const uint32_t ho = sb + O_HALO + warp * 2560 + lane * 16;
            if (warp == 7) {
              if (!rank) {
                const uint32_t ra = mapa(sb + O_HIN + lane * 16, 1), rb = mapa(sb + B_HX0, 1);
#pragma unroll
                for (int i = 0; i < 2; i++) {
                  st_async128(ra + i * 512, K[5 * i][1], K[5 * i + 1][1], K[5 * i + 3][1], K[5 * i + 4][1], rb);
                  st_async128(ra + 1024 + i * 512, V[5 * i][1], V[5 * i + 1][1], V[5 * i + 3][1], V[5 * i + 4][1], rb);
                }
                st_async128(ra + 2048, K[2][1], K[7][1], V[2][1], V[7][1], rb);
              } else if (mt < 7) {
                const uint64_t tag = (uint64_t)epoch << 32;
                uint4* hp = g_halo + (size_t)vb * 320 + lane;
                auto put = [&](int i, uint32_t x, uint32_t y) { asm volatile("st.relaxed.gpu.global.v2.b64 [%0], {%1, %2};" ::"l"(hp + 32 * i), "l"(tag | x), "l"(tag | y) : "memory"); };
                put(0, K[0][1], K[1][1]); put(1, K[3][1], K[4][1]); put(2, K[5][1], K[6][1]); put(3, K[8][1], K[9][1]); put(4, K[2][1], K[7][1]);
                put(5, V[0][1], V[1][1]); put(6, V[3][1], V[4][1]); put(7, V[5][1], V[6][1]); put(8, V[8][1], V[9][1]); put(9, V[2][1], V[7][1]);
              }
            } else {
#pragma unroll
              for (int i = 0; i < 2; i++) {
                sts128(ho + i * 512, K[5 * i][1], K[5 * i + 1][1], K[5 * i + 3][1], K[5 * i + 4][1]);
                sts128(ho + 1024 + i * 512, V[5 * i][1], V[5 * i + 1][1], V[5 * i + 3][1], V[5 * i + 4][1]);
              }
              sts128(ho + 2048, K[2][1], K[7][1], V[2][1], V[7][1]);
              __syncwarp();
              if (lane == 0) mbar_arrive(sb + B_HX + 8 + 8 * warp);
            }
            if (hg & 1) pack_qkv<1, 1>(acc, Q, K, V); else pack_qkv<0, 1>(acc, Q, K, V);
#pragma unroll
            for (int f = 0; f < 10; f++) V[f][0] = movm(V[f][0]);
            if (lead) PT(52 + wg);
            if (wg) mbar_wait(sb + B_P1E, 0);
          }
          CTXW();
          const bool gt0 = 2 * t > g, gt1 = 2 * t + 1 > g;
          const uint32_t pmask = (gt0 ? 0xFFFFu : 0u) | (gt1 ? 0xFFFF0000u : 0u);
          uint32_t Qh[4][2];
          float lg[8][2];
#pragma unroll
          for (int j = 0; j < 4; j++) {
            const int fa = (j >> 1) * 5 + (j & 1) * 3, fh = (j >> 1) * 5 + 2;
            const bool mine = (j & 1) ? (t >= 2) : (t < 2);
            Qh[j][0] = mine ? Q[fh][0] : 0u; Qh[j][1] = mine ? Q[fh][1] : 0u;
            float c1[4] = {0.f, 0.f, 0.f, 0.f}, c2[4] = {0.f, 0.f, 0.f, 0.f};
            mma16(c1, Q[fa][0], Q[fa][1], Q[fa + 1][0], Q[fa + 1][1], K[fa][0], K[fa + 1][0]);
            mma16(c2, Q[fa][0], Q[fa][1], Q[fa + 1][0], Q[fa + 1][1], K[fa][1], K[fa + 1][1]);
            mma8(c1, Qh[j][0], Qh[j][1], K[fh][0]);
            mma8(c2, Qh[j][0], Qh[j][1], K[fh][1]);
            lg[j][0] = c1[0]; lg[j][1] = c1[1];
            lg[4 + j][0] = gt0 ? c1[2] : c2[2]; lg[4 + j][1] = gt1 ? c1[3] : c2[3];
          }
          if (lead) PT(54 + wg);
          mbar_wait(sb + (warp ? B_HX + 8 * warp : B_HX0), 0);
          if (lead) PT(56 + wg);
          const uint32_t ha = sb + (warp ? O_HALO + (warp - 1) * 2560 : O_HIN) + lane * 16;
          uint32_t Kh[10], Vh[10];
#pragma unroll
          for (int i = 0; i < 2; i++) lds128(ha + i * 512, Kh[5 * i], Kh[5 * i + 1], Kh[5 * i + 3], Kh[5 * i + 4]);
          lds128(ha + 2048, Kh[2], Kh[7], Vh[2], Vh[7]);
#pragma unroll
          for (int i = 0; i < 2; i++) lds128(ha + 1024 + i * 512, Vh[5 * i], Vh[5 * i + 1], Vh[5 * i + 3], Vh[5 * i + 4]);
          const bool have_halo = warp > 0 || mt > 0;
#pragma unroll
          for (int j = 0; j < 4; j++) {
            const int fa = (j >> 1) * 5 + (j & 1) * 3, fh = (j >> 1) * 5 + 2;
            float c0[4] = {0.f, 0.f, 0.f, 0.f};
            mma16(c0, Q[fa][0], Q[fa][1], Q[fa + 1][0], Q[fa + 1][1], Kh[fa], Kh[fa + 1]);
            mma8(c0, Qh[j][0], Qh[j][1], Kh[fh]);
            if (!have_halo) c0[0] = c0[1] = -INFINITY;
            lg[j][0] = gt0 ? c0[0] : lg[j][0]; lg[j][1] = gt1 ? c0[1] : lg[j][1];
          }
          uint32_t Pv[8], O[10][2];
          softmax8<8>(lg, Pv);
#pragma unroll
          for (int j = 0; j < 4; j++) {
            const int fa = (j >> 1) * 5 + (j & 1) * 3, fh = (j >> 1) * 5 + 2;
            const uint32_t a0 = Pv[j] & pmask, a2 = Pv[j] & ~pmask, a3 = Pv[4 + j] & pmask, a5 = Pv[4 + j] & ~pmask;
#pragma unroll
            for (int q = 0; q < 3; q++) {
              const int f = q < 2 ? fa + q : fh;
              float o[4] = {0.f, 0.f, 0.f, 0.f};
              mma8(o, a0, 0u, Vh[f]);
              mma16(o, a2, a3, 0u, a5, V[f][0], V[f][1]);
              const uint32_t o0 = pack_bf16(o[0], o[1]), o1 = pack_bf16(o[2], o[3]);
              if (q < 2 || !(j & 1)) { O[f][0] = o0; O[f][1] = o1; }
              else { O[f][0] = t >= 2 ? o0 : O[f][0]; O[f][1] = t >= 2 ? o1 : O[f][1]; }
            }
          }
          const uint32_t oa = sb + O_OST + (warp * 16 + (lane & 15)) * 160 + (lane >> 4) * 16;
#pragma unroll
          for (int i = 0; i < 5; i++) stsm4(oa + i * 32, O[2 * i][0], O[2 * i][1], O[2 * i + 1][0], O[2 * i + 1][1]);
        }
      }
      {
        CTXW();
        bar_arrive_p(wg == 0, NB_HALO, 256);
        mbar_arrive_p(tid == 0, sb + B_AD);
        fence_async_smem();
        bar_arrive(NB_ATT, 288);
        if (lead) PT(58 + wg);
        const uint32_t abase = sb + (g & 1) * 4160 + 4 * (1023 - 4 - 8 * w - (g >> 1) + t);
        float acc[128];
        uint32_t a0[8], a1[8], a2[8], a3[8];
#pragma unroll 1
        for (int c = wg ^ 1; c < 5; c += 2) {
          const uint32_t ab = abase + o_h(c);
          const uint32_t db = __shfl_sync(~0u, ((SB + o_u(c) + UZ - 16) >> 4) | 0x10000u, 0);
          mbar_wait(sb + B_HR + 8 * c, 0);
          load_pair<0>(a0, ab); load_pair<1>(a1, ab); load_pair<2>(a2, ab); load_pair<3>(a3, ab);
          mbar_wait(sb + B_U + 8 * c, 0);
          if (lead) PT(85 + c);
          bar_sync(c ? NB_TOK + wg : NB_HALO, 256);
          fence_regs(acc);
          if (lead) PT(90 + c);
          mma_pair<0>(acc, a0, db);
          mma_pair<1>(acc, a1, db); wg_wait<1>();  load_pair<4>(a0, ab);
          mma_pair<2>(acc, a2, db); wg_wait<1>();  load_pair<5>(a1, ab);
          mma_pair<3>(acc, a3, db); wg_wait<1>();  load_pair<6>(a2, ab);
          mma_pair<4>(acc, a0, db); wg_wait<1>();  load_pair<7>(a3, ab);
          mma_pair<5>(acc, a1, db);
          mma_pair<6>(acc, a2, db);
          bar_arrive(NB_TOK + (wg ^ 1), 256);
          mma_pair<7>(acc, a3, db);
          wg_wait<0>();
          fence_regs(acc);
          if (lead) PT(95 + c);
          bar_sync(NB_RFREE + wg, 256);
          const uint32_t pb = sb + (w < 2 ? o_h(c) + w * 4160 : w == 2 ? o_u(c) : o_x(c)) + lane * 16;
          if (lane < 2 * w) sts128(pb, 0, 0, 0, 0);
#pragma unroll
          for (int q = 0; q < 8; q++) {
            uint32_t p[4];
#pragma unroll
            for (int i = 0; i < 4; i++) {
              const int nu = 4 * q + i;
              float v0 = acc[4 * nu], v1 = acc[4 * nu + 1];
              if (nu > 0) { v0 += acc[4 * nu - 2]; v1 += acc[4 * nu - 1]; }
              p[i] = pack_bf16(v0, v1);
            }
            stsm4t(pb + w * 32 + q * 512, p[0], p[1], p[2], p[3]);
          }
          bar_arrive(NB_RFULL + wg, 256);
          if (lead) PT(140 + c);
        }
      }
    }
    if (warp < 4) {
      CTXW();
      const uint32_t rsb = mapa(sb, (blockIdx.x & 1) ^ 1);
      const uint32_t ba = sb + O_BT + ((lane >> 4) * 8 + (lane & 7)) * 128 + (((2 * w + ((lane >> 3) & 1)) ^ ((lane & 1) << 2 | (lane >> 1 & 3))) << 4);
      mbar_wait(sb + B_P3F, 0);
      if (lead) PT(145);
      if (blockIdx.x < 128) bar_sync(NB_TOK, 256);
      float acc[80];
#pragma unroll 1
      for (int ks = 0; ks < 10; ks++) {
        PTP(lead, 146 + ks);
        const uint32_t dl = (ks < 6 ? ks : ks - 6) * (P3S >> 4);
        const uint64_t da = mkdesc(SB, 1024, 1024, 1), db = mkdesc(SB + 8192, 16, 1024, 1);
        auto D = [&](uint64_t d) { return (d & ~0xFFFFFFFFull) | (uint32_t)((uint32_t)d + dl); };
        wg_fence();
#pragma unroll
        for (int j = 0; j < 4; j++) wgmma_ss_n160<0, 1, 0>(acc, D(da + j * 128), D(db + j * 2), j ? 1 : ks);
        wg_commit();
        wg_wait<1>();
        mbar_arrive2_p(lead && ks >= 1 && ks <= 4, sb + B_P3E + 8 * (ks - 1), rsb + B_P3E + 8 * (ks - 1));
        mbar_wait(sb + B_P3F + 8 * (ks < 5 ? ks + 1 : ks - 5), ks >= 5 && ks < 9);
      }
      wg_wait<0>();
      fence_regs(acc);
      if (lead) PT(156);
#pragma unroll
      for (int i = 0; i < 10; i++) {
        stsm4t(ba + i * 2048, pack_bf16(acc[8 * i], acc[8 * i + 1]), pack_bf16(acc[8 * i + 2], acc[8 * i + 3]),
               pack_bf16(acc[8 * i + 4], acc[8 * i + 5]), pack_bf16(acc[8 * i + 6], acc[8 * i + 7]));
        if (i & 1) bar_arrive(1 + (i >> 1), 256);
      }
      if (lead) PT(157);
    }
  } else if (warp < 12) {
    reg_dec<RH>();
    const int hw = warp - 8;
    ctx = __shfl_sync(~0u, ctx, 0);
    if (ctx < 65536) {
      CTXU();
#pragma unroll 1
      for (int c = hw; c < 5; c += 4) {
        const int kb = 2 * c + (vb >> 6), r0 = (vb & 63) * 32;
        const uint4 sk = __ldg((const uint4*)(shift_k + (size_t)(kb * 64 + 2 * lane) * 4));
        wait_until(t0, KT0 + c * KTD + ((((vb * 37) & 127) * KTD) >> 7));
        if (lane == 0) PT(20 + c);
        const char* kp = (const char*)kin + (size_t)r0 * 1280 + kb * 128 + lane * 4;
        const char* vp = (const char*)vin + (size_t)r0 * 1280 + kb * 128 + lane * 4;
        uint32_t k0 = 0, k1 = 0, k2 = 0, kk[32], vv[32];
        if (r0 > 0) { k0 = ldg_v<-3 * 1280>(kp); k1 = ldg_v<-2 * 1280>(kp); k2 = ldg_v<-1280>(kp); }
        ld_rows<0>(kk, vv, kp, vp);
        const uint32_t zz = vv[31] & (uint32_t)(threadIdx.y);
        const uint32_t w0 = prmt(sk.x, sk.z, 0x5410) | zz, w1 = prmt(sk.x, sk.z, 0x7632), w2 = prmt(sk.y, sk.w, 0x5410), w3 = prmt(sk.y, sk.w, 0x7632) | zz;
        const int odd = (lane >> 2) & 1;
        const uint32_t sel0 = odd ? 0x7632 : 0x5410, sel1 = odd ? 0x5410 : 0x7632;
        const uint32_t st = sb + O_Y + c * 4096;
        PTP(lane == 0 && c == 1, 40 + zz);
#pragma unroll
        for (int ch = 0; ch < 4; ch++) {
          uint32_t o[8];
#pragma unroll
          for (int i = 0; i < 8; i++) {
            const uint32_t k3 = kk[8 * ch + i];
            o[i] = hmul2(hfma2(k3, w0, hfma2(k2, w1, hfma2(k1, w2, hmul2(k0, w3)))), vv[8 * ch + i]);
            k0 = k1; k1 = k2; k2 = k3;
          }
          const uint32_t oa = st + (2 * lane) * 64 + ((ch ^ (lane & 3)) << 4);
          sts128v(oa + odd * 64, prmt(o[0], o[1], sel0), prmt(o[2], o[3], sel0), prmt(o[4], o[5], sel0), prmt(o[6], o[7], sel0));
          sts128v(oa + 64 - odd * 64, prmt(o[0], o[1], sel1), prmt(o[2], o[3], sel1), prmt(o[4], o[5], sel1), prmt(o[6], o[7], sel1));
        }
        fence_async_smem();
        __syncwarp();
        if (elect_one()) {
          PT(25 + c);
          tma3_store(&M.kv_st, 0, kb * 64, vb & 63, st);
          bulk_commit(); bulk_wait_all();
          flag_add(CNT_KV(kb), 1);
          PT(30 + c);
        }
        __syncwarp();
      }
      mbar_wait(sb + B_LAST, 0);
#pragma unroll 1
      for (int c = hw ? hw - 1 : 5; c < 5; c += 3) {
        const uint4* hp = (const uint4*)(ssm_k + (size_t)(128 * c + vb) * 2048) + lane;
        uint4 u[8];
#pragma unroll
        for (int q = 0; q < 8; q++) asm volatile("ld.volatile.global.v4.b32 {%0,%1,%2,%3}, [%4];" : "=r"(u[q].x), "=r"(u[q].y), "=r"(u[q].z), "=r"(u[q].w) : "l"(hp + 32 * q));
        const uint32_t d = __ldg(ssm_D + 128 * c + vb);
        mbar_wait(sb + B_S13, 1);
        const uint32_t o = sb + o_h(c) + (255 - lane) * 16;
        if (lane == 0) u[0].x = prmt(pack_bf16(bf_lo(u[0].x) + bf_lo(d), 0.f), u[0].x, 0x7610);
#pragma unroll
        for (int q = 0; q < 8; q++) {
          const uint32_t up = __shfl_sync(~0u, lane == 31 ? (q ? u[q ? q - 1 : 0].w : 0u) : u[q].w, lane + 31);
          sts128(o - q * 512, prmt(u[q].w, u[q].z, 0x7610), prmt(u[q].z, u[q].y, 0x7610), prmt(u[q].y, u[q].x, 0x7610), prmt(u[q].x, up, 0x7610));
          sts128(o - q * 512 + 4160, prmt(u[q].w, 0, 0x1032), prmt(u[q].z, 0, 0x1032), prmt(u[q].y, 0, 0x1032), prmt(u[q].x, 0, 0x1032));
        }
        if (lane < 2) sts128(sb + o_h(c) + lane * 4160 + 4096, 0, 0, 0, 0);
        __syncwarp();
        if (lane == 0) { mbar_arrive(sb + B_HR + 8 * c); PT(35 + c); }
      }
    }
    CTXU();
    const int g = lane >> 2, t = lane & 3, row = 8 * hw + g;
    const uint32_t go = (tb * 160 + row) * 80 + cb * 8 + t;
    uint4 T[10];
#pragma unroll
    for (int i = 0; i < 10; i++) {
      T[i] = make_uint4(0, 0, 0, 0);
      if (i < 8 || tb < 12) asm volatile("ld.volatile.global.v4.b32 {%0,%1,%2,%3}, [%4];" : "=r"(T[i].x), "=r"(T[i].y), "=r"(T[i].z), "=r"(T[i].w) : "l"((const uint4*)xq + go + (i >> 1) * 2560 + (i & 1) * 4));
    }
    if (main_cta) {
      bar_arrive(NB_RFREE, 256);
      bar_arrive(NB_RFREE + 1, 256);
      const int yrow = (vb & 0x61) | (vb & 6) << 2 | (vb >> 2 & 6);
#pragma unroll 1
      for (int c = 0; c < 5; c++) {
        const int wg = (c & 1) ^ 1;
        bar_sync(NB_RFULL + wg, 256);
        conv_reduce(sb, c, tid - 256, 128 * c + yrow);
        __syncwarp();
        if (lane == 0) flag_add(CNT_Y(4 * c + (vb >> 5)), 1);
        if (tid == 256) PT(41 + c);
        if (c < 3) bar_arrive(NB_RFREE + wg, 256);
        if (c == 2) {
          bar_sync(NB_HELP, 128);
          if (tid == 256) { mbar_arrive(sb + B_P3E + 32); mbar_arrive_remote(sb + B_P3E + 32, rank ^ 1); }
        }
      }
    }
    uint32_t G[5];
    mbar_wait(sb + B_G, 0);
#pragma unroll
    for (int q = 0; q < 5; q++) { uint16_t v; asm volatile("ld.shared.u16 %0, [%1];" : "=h"(v) : "r"(sb + O_GT + (32 * q + row) * 2)); G[q] = prmt(v, 0, 0x1010); }
#pragma unroll
    for (int i = 0; i < 10; i++) { const uint32_t c = G[i >> 1]; T[i] = make_uint4(hmul2(T[i].x, c), hmul2(T[i].y, c), hmul2(T[i].z, c), hmul2(T[i].w, c)); }
#pragma unroll
    for (int h = 0; h < 2; h++) {
      mbar_wait(sb + B_Y + 8 * h, 0);
      if (tid == 256) PT(46);
#pragma unroll
      for (int q = 0; q < 5; q++) {
        uint32_t y0, y1, y2, y3;
        ldsm4t(y0, y1, y2, y3, sb + O_Y + h * 10240 + q * 2048 + lane * 64 + ((hw ^ ((lane >> 1) & 3)) << 4));
        uint4& r = T[2 * q + h];
        r = make_uint4(hmul2(r.x, y0), hmul2(r.y, y1), hmul2(r.z, y2), hmul2(r.w, y3));
      }
    }
    const uint32_t so = sb + O_BT + row * 128 + ((t ^ ((g & 1) << 2 | g >> 1)) << 4);
    if (tid == 256) PT(47);
#pragma unroll
    for (int q = 0; q < 5; q++) {
      const uint32_t c = hfma2(G[q], 0xBF80BF80u, 0x3F803F80u);
      bar_sync(1 + q, 256);
      if (q == 4) mbar_arrive_p(tid == 256, sb + B_DONE);
#pragma unroll
      for (int h = 0; h < 2; h++) {
        uint4 u;
        lds128((so ^ (h * 64)) + q * 4096, u.x, u.y, u.z, u.w);
        const uint4& r = T[2 * q + h];
        if (q < 4 || tb < 12) ((uint4*)outp)[go + q * 2560 + h * 4] = make_uint4(hfma2(u.x, c, r.x), hfma2(u.y, c, r.y), hfma2(u.z, c, r.z), hfma2(u.w, c, r.w));
      }
    }
  } else {
    reg_dec<RP>();
    if (warp == 15 && blockIdx.x < 128) {
      const int p = cta_pair(), rank = blockIdx.x & 1;
      if (elect_one()) { mbar_expect_tx(sb + B_FULL, 16384 + WST); p1_load_x(0, p, rank); PT(1); }
      __syncwarp();
      asm volatile("barrier.cluster.wait.aligned;" ::: "memory");
#pragma unroll 1
      for (int ks = 0; ks < 20; ks += 2) {
        if (elect_one()) { p1_load_w(ks, p, rank); PT(100 + ks); }
        mbar_wait(sb + B_EMPTY + 8 + 8 * (ks & 7), ((ks >> 3) & 1) ^ 1);
        spin_until(t0, PT1 + ks * PTD);
        if (elect_one()) { mbar_expect_tx(sb + B_FULL + 8 + 8 * (ks & 7), WST); p1_load_w(ks + 1, p, rank); PT(101 + ks); }
        if (ks == 18) break;
        mbar_wait(sb + B_EMPTY + 8 * ((ks + 2) & 7), (((ks + 2) >> 3) & 1) ^ 1);
        spin_until(t0, PT1 + (ks + 1) * PTD - PTE);
        if (elect_one()) { mbar_expect_tx(sb + B_FULL + 8 * ((ks + 2) & 7), 16384 + WST); p1_load_x(ks + 2, p, rank); }
      }
      if (elect_one()) mbar_arrive(sb + B_LAST);
      mbar_wait(sb + B_S19, 0);
    } else {
      asm volatile("barrier.cluster.wait.aligned;" ::: "memory");
      __nanosleep(SNOOZE);
    }
    ctx = __shfl_sync(~0u, make_ctx(), 0);
    CTXU();
    if (warp == 12) {
        unsigned epoch = 0;
      if (lane == 0) {
        if ((sb & 0xFFFFFF) != SB) __trap();
        mbar_expect_tx(sb + B_GW, 1280);
        bulk_load(sb + O_GW, gate_w, 1280, sb + B_GW);
        epoch = *(volatile unsigned*)(g_launch + blockIdx.x) + 1;
        *(volatile unsigned*)(g_launch + blockIdx.x) = epoch;
        sts32(sb + O_EPOCH, epoch);
        mbar_arrive(sb + B_EP);
#pragma unroll 1
        for (int i = 3; i < 8; i++) asm volatile("prefetch.tensormap [%0];" ::"l"(&M.x_par + i) : "memory");
      }
      __syncwarp();
      if (main_cta) {
        mbar_wait(sb + B_LAST, 0);
        mbar_wait(sb + B_S13, 1);
#pragma unroll
        for (int c = 0; c < 5; c++) sts128(sb + o_u(c) + lane * 16, 0, 0, 0, 0);
        if (lane < 5) sts128(sb + o_u(lane) + 512, 0, 0, 0, 0);
        fence_async_smem();
        __syncwarp();
        epoch = __shfl_sync(~0u, epoch, 0);
#pragma unroll 1
        for (int c = 0; c < 5; c++) {
          if (c == 4) mbar_wait(sb + B_AD, 0);
          flag_wait(CNT_KV(2 * c + (vb >> 6)), 64 * epoch);
          __syncwarp();
          if (elect_one()) {
            mbar_expect_tx(sb + B_U + 8 * c, 4096);
            bulk_load(sb + o_u(c) + UZ, g_kvT + (size_t)(128 * c + vb) * 2048, 4096, sb + B_U + 8 * c);
            PT(10 + c);
          }
        }
      }
    } else if (warp != 15) {
        const int r = warp - 13;
      if (main_cta) {
        if (rank) {
#pragma unroll
          for (int f = 0; f < 5; f++)
            asm volatile("st.relaxed.gpu.global.v2.b64 [%0], {%1, %1};" ::"l"(g_halo + (size_t)vb * 320 + r * 160 + lane + 32 * f), "l"(0ull) : "memory");
          if (lane == 0) mbar_expect_tx(sb + B_HX0, 1280);
        }
        const int t = lane & 3, grow = hg * 16 + (lane & 15);
        const uint32_t ga = sb + grow * 128 + (((4 * r + (lane >> 4)) ^ (lane & 7)) << 4);
        const uint32_t gp = sb + O_GW + 64 * r + 4 * t;
        float s0 = 0.f, s1 = 0.f;
        mbar_wait_wd(sb + B_GW, 0, t0);
#pragma unroll 1
        for (int ks = 0; ks < 20; ks += 2) {
          uint32_t x[8], gw[4];
#pragma unroll
          for (int i = 0; i < 4; i++) gw[i] = lds32(gp + ks * 64 + i * 16);
          mbar_wait_wd(sb + B_FULL + 8 * (ks & 7), (ks >> 3) & 1, t0);
          if (r == 0 && lane == 0) PT(120 + ks);
          ldsm4(x[0], x[1], x[2], x[3], ga + o_px(ks)); ldsm4(x[4], x[5], x[6], x[7], (ga ^ 32) + o_px(ks));
#pragma unroll
          for (int i = 0; i < 8; i++) x[i] = hmul2(x[i], gw[i >> 1]);
          if (lane < 2) mbar_arrive(sb + B_EMPTY + 8 * (ks & 7) + 8 * lane + (x[0] & x[7] & threadIdx.y));
#pragma unroll
          for (int i = 0; i < 8; i += 4) {
            s0 += (bf_lo(x[i]) + bf_hi(x[i])) + (bf_lo(x[i + 2]) + bf_hi(x[i + 2]));
            s1 += (bf_lo(x[i + 1]) + bf_hi(x[i + 1])) + (bf_lo(x[i + 3]) + bf_hi(x[i + 3]));
          }
        }
        s0 += __shfl_xor_sync(~0u, s0, 1); s1 += __shfl_xor_sync(~0u, s1, 1);
        s0 += __shfl_xor_sync(~0u, s0, 2); s1 += __shfl_xor_sync(~0u, s1, 2);
        if (t < 2) sts32(sb + O_GP + r * 64 + (8 * t + (lane >> 2)) * 4, __float_as_uint(t ? s1 : s0));
        if (r == 0) bar_arrive(NB_G, 64);
        if (!rank) {
          const uint32_t ha = sb + O_HIN + lane * 16 + r * 1024, hb = sb + O_HIN + lane * 16 + 2048 + r * 8;
          uint32_t d[10];
          if (mt > 0) {
            const uint4* hp = g_halo + (size_t)(vb - 1) * 320 + r * 160 + lane;
            mbar_wait_wd(sb + B_HX + 56, 0, t0);
            const unsigned epoch = lds32(sb + O_EPOCH);
            for (;;) {
              uint64_t u[10];
#pragma unroll
              for (int f = 0; f < 5; f++) asm volatile("ld.relaxed.gpu.global.v2.b64 {%0, %1}, [%2];" : "=l"(u[2 * f]), "=l"(u[2 * f + 1]) : "l"(hp + 32 * f) : "memory");
              uint32_t bad = 0;
#pragma unroll
              for (int f = 0; f < 10; f++) { d[f] = (uint32_t)u[f]; bad |= (uint32_t)(u[f] >> 32) ^ epoch; }
              if (__all_sync(~0u, bad == 0)) break;
              if (clk() - t0 > 0x70000000u) __trap();
            }
          } else {
#pragma unroll
            for (int f = 0; f < 10; f++) d[f] = 0u;
          }
          sts128(ha, d[0], d[1], d[2], d[3]); sts128(ha + 512, d[4], d[5], d[6], d[7]);
          sts32(hb, d[8]); sts32(hb + 4, d[9]);
          __syncwarp();
          if (lane == 0) { mbar_arrive(sb + B_HX0); PT(15 + r); }
        }
        if (r == 1) {
          bar_sync(NB_G, 64);
          if (lane < 16) {
            const uint32_t pa = sb + O_GP + lane * 4;
            const float z = __uint_as_float(lds32(pa)) + __uint_as_float(lds32(pa + 64));
            g_gate[2 * (mt * 128 + hg * 16 + lane) + par] = (uint16_t)pack_bf16(__fdividef(1.f, 1.f + __expf(-bf_lo(pack_bf16(z, 0.f)))), 0.f);
          }
          __syncwarp();
          if (lane == 0) flag_add(CNT_O(rt), 1);
        }
      }
      if (elect_one()) {
        mbar_wait_wd(sb + B_EP, 0, t0);
        const unsigned epoch = lds32(sb + O_EPOCH);
        if (main_cta) mbar_wait_wd(sb + B_P3E + 32, 0, t0);
        unsigned v;
        do {
          asm volatile("ld.relaxed.gpu.global.u32 %0, [%1];" : "=r"(v) : "l"(CNT_Y(2 * cb + r)) : "memory");
          if (clk() - t0 > 0x70000000u) __trap();
        } while ((int)(v - 128 * epoch) < 0);
        mbar_expect_tx(sb + B_Y + 8 * r, 10240);
        tma3(sb + O_Y + r * 10240, &M.y_ld, 0, cb * 64 + 32 * r, tb * 5, sb + B_Y + 8 * r);
        PT(17 + r);
        mbar_wait_wd(sb + B_DONE, 0, t0);
      }
    } else {
      const unsigned epoch = get_epoch();
      if (main_cta) bar_sync(NB_ATT, 288);
      if (elect_one()) {
        if (main_cta) {
          tma3_store(&M.o_st, hg * 80, par, mt * 128, sb + O_OST);
          bulk_commit(); bulk_wait_all();
          flag_add(CNT_O(rt), 1);
        }
        mbar_arrive_remote(sb + B_P3R, rank ^ 1);
        PT(3);
      }
      __syncwarp();
      if (lane < 4) flag_wait(CNT_O(8 * (lane & 1) + min(7, (80 * tb + 79 * (lane >> 1)) >> 7)), 16 * epoch);
      __syncwarp();
      if (elect_one()) {
        PT(4);
        mbar_expect_tx(sb + B_G, 320);
        bulk_load(sb + O_GT, g_gate + tb * 160, 320, sb + B_G);
      }
      mbar_wait(sb + B_P3R, 0);
#pragma unroll 1
      for (int ks = 0; ks < 10; ks++) {
        const int q = ks < 6 ? ks : ks - 6;
        if (ks > 5 || (ks == 5 && main_cta)) mbar_wait(sb + B_P3E + 8 * (ks == 5 ? 4 : q), 0);
        if (elect_one()) {
          PTP(ks >= 5, ks);
          mbar_expect_tx(sb + B_P3F + 8 * q, P3S);
          tma2(sb + q * P3S, &M.wo, cb * 64, ks * 64, sb + B_P3F + 8 * q);
          tma2_mc(sb + q * P3S + 8192 + rank * 10240, &M.o_ld, ks * 64, tb * 160 + rank * 80, sb + B_P3F + 8 * q);
        }
      }
    }
  }
}

typedef CUresult (*PFN_enc)(CUtensorMap*, CUtensorMapDataType, cuuint32_t, void*, const cuuint64_t*, const cuuint64_t*, const cuuint32_t*,
                            const cuuint32_t*, CUtensorMapInterleave, CUtensorMapSwizzle, CUtensorMapL2promotion, CUtensorMapFloatOOBfill);
static void enc(PFN_enc f, CUtensorMap* m, const void* base, int rank, const cuuint64_t* dims, const cuuint64_t* strides, const cuuint32_t* box,
                CUtensorMapSwizzle sw) {
  const cuuint32_t es[5] = {1, 1, 1, 1, 1};
  f(m, CU_TENSOR_MAP_DATA_TYPE_BFLOAT16, rank, (void*)base, dims, strides, box, es, CU_TENSOR_MAP_INTERLEAVE_NONE, sw,
    CU_TENSOR_MAP_L2_PROMOTION_NONE, CU_TENSOR_MAP_FLOAT_OOB_FILL_NONE);
}

extern "C" void kernel_launch(void* const* d_in, const int* in_sizes, int n_in, void* d_out, int out_size) {
  (void)in_sizes; (void)n_in; (void)out_size;
  static PFN_enc f = nullptr;
  static void *kvT, *y2T, *o;
  if (!f) {
    void* p = nullptr;
    cudaDriverEntryPointQueryResult q;
    cudaGetDriverEntryPoint("cuTensorMapEncodeTiled", &p, cudaEnableDefault, &q);
    f = (PFN_enc)p;
    cudaGetSymbolAddress(&kvT, g_kvT); cudaGetSymbolAddress(&y2T, g_y2T); cudaGetSymbolAddress(&o, g_o);
    cudaFuncSetAttribute(fused_kernel, cudaFuncAttributeMaxDynamicSharedMemorySize, SMEM_BYTES);
  }
  Maps M;
  const CUtensorMapSwizzle S0 = CU_TENSOR_MAP_SWIZZLE_NONE, S32 = CU_TENSOR_MAP_SWIZZLE_32B, S64 = CU_TENSOR_MAP_SWIZZLE_64B, S128 = CU_TENSOR_MAP_SWIZZLE_128B;
  const cuuint64_t dpar[3] = {640, 2, 1024}, spar[2] = {1280, 2560};
  const cuuint64_t dw[3] = {640, 640, 3}, sw[2] = {3840, 1280};
  const cuuint64_t dnat[2] = {640, 2048}, snat[1] = {1280};
  const cuuint64_t dT[3] = {32, 640, 64}, sT[2] = {4096, 64};
  const cuuint64_t dwo[2] = {640, 640};
  { const cuuint32_t bx[3] = {64, 1, 128}; enc(f, &M.x_par, d_in[0], 3, dpar, spar, bx, S128); }
  { const cuuint32_t bx[3] = {64, 16, 3}; enc(f, &M.w_main, d_in[7], 3, dw, sw, bx, S128); }
  { const cuuint32_t bx[3] = {16, 16, 3}; enc(f, &M.w_tail, d_in[7], 3, dw, sw, bx, S32); }
  { const cuuint32_t bx[3] = {80, 1, 128}; enc(f, &M.o_st, o, 3, dpar, spar, bx, S0); }
  { const cuuint32_t bx[3] = {32, 64, 1}; enc(f, &M.kv_st, kvT, 3, dT, sT, bx, S64); }
  { const cuuint32_t bx[3] = {32, 32, 5}; enc(f, &M.y_ld, y2T, 3, dT, sT, bx, S64); }
  { const cuuint32_t bx[2] = {64, 64}; enc(f, &M.wo, d_in[8], 2, dwo, snat, bx, S128); }
  { const cuuint32_t bx[2] = {64, 80}; enc(f, &M.o_ld, o, 2, dnat, snat, bx, S128); }
  fused_kernel<<<130, 512, SMEM_BYTES, cudaStreamPerThread>>>((const uint16_t*)d_in[0], (const uint16_t*)d_in[7], M, (const uint16_t*)d_in[3], (const uint16_t*)d_in[4], (const uint16_t*)d_in[5], (const uint16_t*)d_in[9],
                                                              (const uint16_t*)d_in[1], (const uint16_t*)d_in[2], (uint16_t*)d_out);
}
```

```cpp
#include <cuda_runtime.h>
#include <cuda_bf16.h>
#include <cuda.h>
#include <stdint.h>

#define DEVI __device__ __forceinline__
#define PT1 700
#define PTD 460
#define PTE 200
#define PF2 0
#define NPF 1
#define PFD 0
#define KT0 1500
#define KTD 1500
#define RC 192
#define RH 96
#define RP 32
#define HOLD 500
#define P1U 7
#define LEAD 3

DEVI uint32_t smem_u32(const void* p) { return (uint32_t)__cvta_generic_to_shared(p); }
DEVI void wg_fence() { asm volatile("wgmma.fence.sync.aligned;" ::: "memory"); }
DEVI void wg_commit() { asm volatile("wgmma.commit_group.sync.aligned;" ::: "memory"); }
template <int N> DEVI void wg_wait() { asm volatile("wgmma.wait_group.sync.aligned %0;" ::"n"(N) : "memory"); }
template <int S> DEVI void fence_regs(float (&d)[S]) {
#pragma unroll
  for (int i = 0; i < S; i++) asm volatile("" : "+f"(d[i])::"memory");
}
DEVI uint64_t mkdesc(uint32_t addr, uint32_t lbo, uint32_t sbo, int swz) {
  return (uint64_t)((addr & 0x3FFFF) >> 4) | ((uint64_t)(lbo >> 4) << 16) | ((uint64_t)(sbo >> 4) << 32) | ((uint64_t)swz << 62);
}
DEVI void mbar_init(uint32_t bar, uint32_t cnt) { asm volatile("mbarrier.init.shared::cta.b64 [%0], %1;" ::"r"(bar), "r"(cnt) : "memory"); }
DEVI void mbar_expect_tx(uint32_t bar, uint32_t bytes) { asm volatile("mbarrier.arrive.expect_tx.shared::cta.b64 _, [%0], %1;" ::"r"(bar), "r"(bytes) : "memory"); }
DEVI void mbar_arrive(uint32_t bar) { asm volatile("mbarrier.arrive.shared::cta.b64 _, [%0];" ::"r"(bar) : "memory"); }
DEVI void mbar_wait(uint32_t bar, uint32_t parity) {
  asm volatile("{\n.reg .pred p;\nLAB_WAIT:\nmbarrier.try_wait.parity.shared::cta.b64 p, [%0], %1;\n@!p bra LAB_WAIT;\n}" ::"r"(bar), "r"(parity) : "memory");
}
DEVI void mbar_wait_wd(uint32_t bar, uint32_t parity, uint32_t t0) {
  asm volatile("{\n.reg .pred p;\n.reg .u32 c;\nLAB_WAIT:\nmbarrier.try_wait.parity.shared::cta.b64 p, [%0], %1;\n@p bra DONE;\nmov.u32 c, %%clock;\nsub.u32 c, c, %2;\nsetp.lt.u32 p, c, 0x70000000;\n@p bra LAB_WAIT;\ntrap;\nDONE:\n}" ::"r"(bar), "r"(parity), "r"(t0) : "memory");
}
DEVI void flag_wait(const unsigned* p, unsigned target) {
  asm volatile("{\n.reg .pred p;\n.reg .s32 v;\nLAB_WAIT:\nld.relaxed.gpu.global.u32 v, [%0];\nsub.s32 v, v, %1;\nsetp.lt.s32 p, v, 0;\n@p bra LAB_WAIT;\n}" ::"l"(p), "r"(target) : "memory");
}
DEVI void flag_add(unsigned* p, unsigned v) { asm volatile("red.relaxed.gpu.global.add.u32 [%0], %1;" ::"l"(p), "r"(v) : "memory"); }
DEVI void fence_async_smem() { asm volatile("fence.proxy.async.shared::cta;" ::: "memory"); }
DEVI bool elect_one() { uint32_t p; asm volatile("{\n.reg .pred P;\nelect.sync _|P, 0xffffffff;\nselp.u32 %0, 1, 0, P;\n}" : "=r"(p)); return p; }
DEVI void bar_sync(int id, int n) { asm volatile("bar.sync %0, %1;" ::"r"(id), "r"(n) : "memory"); }
DEVI void bar_arrive(int id, int n) { asm volatile("bar.arrive %0, %1;" ::"r"(id), "r"(n) : "memory"); }
DEVI void tma2(uint32_t dst, const CUtensorMap* m, int c0, int c1, uint32_t bar) {
  asm volatile("cp.async.bulk.tensor.2d.shared::cluster.global.mbarrier::complete_tx::bytes [%0], [%1, {%3, %4}], [%2];" ::"r"(dst), "l"(m), "r"(bar), "r"(c0), "r"(c1) : "memory");
}
DEVI void tma3(uint32_t dst, const CUtensorMap* m, int c0, int c1, int c2, uint32_t bar) {
  asm volatile("cp.async.bulk.tensor.3d.shared::cluster.global.mbarrier::complete_tx::bytes [%0], [%1, {%3, %4, %5}], [%2];" ::"r"(dst), "l"(m), "r"(bar), "r"(c0), "r"(c1), "r"(c2) : "memory");
}
DEVI void tma3_mc(uint32_t dst, const CUtensorMap* m, int c0, int c1, int c2, uint32_t bar) {
  asm volatile("cp.async.bulk.tensor.3d.shared::cluster.global.mbarrier::complete_tx::bytes.multicast::cluster [%0], [%1, {%3, %4, %5}], [%2], %6;" ::"r"(dst), "l"(m), "r"(bar), "r"(c0), "r"(c1), "r"(c2), "h"((uint16_t)3) : "memory");
}
DEVI void tma2_mc(uint32_t dst, const CUtensorMap* m, int c0, int c1, uint32_t bar) {
  asm volatile("cp.async.bulk.tensor.2d.shared::cluster.global.mbarrier::complete_tx::bytes.multicast::cluster [%0], [%1, {%3, %4}], [%2], %5;" ::"r"(dst), "l"(m), "r"(bar), "r"(c0), "r"(c1), "h"((uint16_t)3) : "memory");
}
DEVI void mbar_arrive_remote(uint32_t bar, uint32_t cta) {
  asm volatile("{\n.reg .b32 ra;\nmapa.shared::cluster.u32 ra, %0, %1;\nmbarrier.arrive.shared::cluster.b64 _, [ra];\n}" ::"r"(bar), "r"(cta) : "memory");
}
DEVI void tma3_store(const CUtensorMap* m, int c0, int c1, int c2, uint32_t src) {
  asm volatile("cp.async.bulk.tensor.3d.global.shared::cta.bulk_group [%0, {%2, %3, %4}], [%1];" ::"l"(m), "r"(src), "r"(c0), "r"(c1), "r"(c2) : "memory");
}
DEVI void bulk_load(uint32_t dst, const void* src, uint32_t bytes, uint32_t bar) {
  asm volatile("cp.async.bulk.shared::cluster.global.mbarrier::complete_tx::bytes [%0], [%1], %2, [%3];" ::"r"(dst), "l"(src), "r"(bytes), "r"(bar) : "memory");
}
DEVI void bulk_store(void* dst, uint32_t src, uint32_t bytes) {
  asm volatile("cp.async.bulk.global.shared::cta.bulk_group [%0], [%1], %2;" ::"l"(dst), "r"(src), "r"(bytes) : "memory");
}
DEVI void pf_l2(const void* p) { asm volatile("prefetch.global.L2 [%0];" ::"l"(p)); }
template <int OFF> DEVI uint32_t ldg_v(const void* p) { uint32_t v; asm volatile("ld.volatile.global.b32 %0, [%1 + %2];" : "=r"(v) : "l"(p), "n"(OFF)); return v; }
DEVI void bulk_commit() { asm volatile("cp.async.bulk.commit_group;" ::: "memory"); }
DEVI void bulk_wait_all() { asm volatile("cp.async.bulk.wait_group 0;" ::: "memory"); }
DEVI void bulk_wait_read() { asm volatile("cp.async.bulk.wait_group.read 0;" ::: "memory"); }
template <int R> DEVI void reg_inc() { asm volatile("setmaxnreg.inc.sync.aligned.u32 %0;" ::"n"(R)); }
template <int R> DEVI void reg_dec() { asm volatile("setmaxnreg.dec.sync.aligned.u32 %0;" ::"n"(R)); }
DEVI uint32_t prmt(uint32_t a, uint32_t b, uint32_t s) { uint32_t r; asm("prmt.b32 %0,%1,%2,%3;" : "=r"(r) : "r"(a), "r"(b), "r"(s)); return r; }
DEVI uint32_t lds32(uint32_t a) { uint32_t r; asm volatile("ld.shared.b32 %0,[%1];" : "=r"(r) : "r"(a)); return r; }
DEVI void sts32(uint32_t a, uint32_t x) { asm volatile("st.shared.b32 [%0],%1;" ::"r"(a), "r"(x) : "memory"); }
DEVI void sts128(uint32_t a, uint32_t x, uint32_t y, uint32_t z, uint32_t w) { asm volatile("st.shared.v4.b32 [%0],{%1,%2,%3,%4};" ::"r"(a), "r"(x), "r"(y), "r"(z), "r"(w) : "memory"); }
DEVI void sts128v(uint32_t a, uint32_t x, uint32_t y, uint32_t z, uint32_t w) { asm volatile("st.volatile.shared.v4.b32 [%0],{%1,%2,%3,%4};" ::"r"(a), "r"(x), "r"(y), "r"(z), "r"(w) : "memory"); }
DEVI void lds128(uint32_t a, uint32_t& x, uint32_t& y, uint32_t& z, uint32_t& w) { asm volatile("ld.shared.v4.b32 {%0,%1,%2,%3},[%4];" : "=r"(x), "=r"(y), "=r"(z), "=r"(w) : "r"(a) : "memory"); }
DEVI void ldsm4(uint32_t& r0, uint32_t& r1, uint32_t& r2, uint32_t& r3, uint32_t addr) {
  asm volatile("ldmatrix.sync.aligned.m8n8.x4.shared.b16 {%0,%1,%2,%3}, [%4];" : "=r"(r0), "=r"(r1), "=r"(r2), "=r"(r3) : "r"(addr) : "memory");
}
DEVI void ldsm4t(uint32_t& r0, uint32_t& r1, uint32_t& r2, uint32_t& r3, uint32_t addr) {
  asm volatile("ldmatrix.sync.aligned.m8n8.x4.trans.shared.b16 {%0,%1,%2,%3}, [%4];" : "=r"(r0), "=r"(r1), "=r"(r2), "=r"(r3) : "r"(addr) : "memory");
}
DEVI void stsm4(uint32_t addr, uint32_t r0, uint32_t r1, uint32_t r2, uint32_t r3) {
  asm volatile("stmatrix.sync.aligned.m8n8.x4.shared.b16 [%0], {%1,%2,%3,%4};" ::"r"(addr), "r"(r0), "r"(r1), "r"(r2), "r"(r3) : "memory");
}
DEVI void stsm4t(uint32_t addr, uint32_t r0, uint32_t r1, uint32_t r2, uint32_t r3) {
  asm volatile("stmatrix.sync.aligned.m8n8.x4.trans.shared.b16 [%0], {%1,%2,%3,%4};" ::"r"(addr), "r"(r0), "r"(r1), "r"(r2), "r"(r3) : "memory");
}
DEVI uint32_t movm(uint32_t a) { uint32_t r; asm volatile("movmatrix.sync.aligned.m8n8.trans.b16 %0, %1;" : "=r"(r) : "r"(a)); return r; }
DEVI uint32_t pack_bf16(float lo, float hi) { uint32_t r; asm("cvt.rn.bf16x2.f32 %0, %1, %2;" : "=r"(r) : "f"(hi), "f"(lo)); return r; }
DEVI uint32_t hmul2(uint32_t a, uint32_t b) { uint32_t r; asm("mul.rn.bf16x2 %0,%1,%2;" : "=r"(r) : "r"(a), "r"(b)); return r; }
DEVI uint32_t hadd2(uint32_t a, uint32_t b) { uint32_t r; asm("add.rn.bf16x2 %0,%1,%2;" : "=r"(r) : "r"(a), "r"(b)); return r; }
DEVI float bf_lo(uint32_t a) { return __uint_as_float(prmt(a, 0, 0x1044)); }
DEVI float bf_hi(uint32_t a) { return __uint_as_float(a & 0xFFFF0000u); }
DEVI void mma16(float (&c)[4], uint32_t a0, uint32_t a1, uint32_t a2, uint32_t a3, uint32_t b0, uint32_t b1) {
  asm("mma.sync.aligned.m16n8k16.row.col.f32.bf16.bf16.f32 {%0,%1,%2,%3},{%4,%5,%6,%7},{%8,%9},{%0,%1,%2,%3};"
      : "+f"(c[0]), "+f"(c[1]), "+f"(c[2]), "+f"(c[3]) : "r"(a0), "r"(a1), "r"(a2), "r"(a3), "r"(b0), "r"(b1));
}
DEVI void mma8(float (&c)[4], uint32_t a0, uint32_t a1, uint32_t b0) {
  asm("mma.sync.aligned.m16n8k8.row.col.f32.bf16.bf16.f32 {%0,%1,%2,%3},{%4,%5},{%6},{%0,%1,%2,%3};"
      : "+f"(c[0]), "+f"(c[1]), "+f"(c[2]), "+f"(c[3]) : "r"(a0), "r"(a1), "r"(b0));
}
DEVI float ex2(float x) { float r; asm("ex2.approx.ftz.f32 %0, %1;" : "=f"(r) : "f"(x)); return r; }

DEVI uint32_t clk() { uint32_t c; asm volatile("mov.u32 %0, %%clock;" : "=r"(c)); return c; }
DEVI void wait_until(uint32_t t0, int dt) { while ((int)(clk() - t0) < dt) __nanosleep(40); }
DEVI void spin_until(uint32_t t0, int dt) { while ((int)(clk() - t0) < dt) {} }
DEVI uint32_t hfma2(uint32_t a, uint32_t b, uint32_t c) { uint32_t r; asm("fma.rn.bf16x2 %0,%1,%2,%3;" : "=r"(r) : "r"(a), "r"(b), "r"(c)); return r; }
DEVI void bar_sync_p(int on, int id, int n) { asm volatile("{\n.reg .pred p;\nsetp.ne.b32 p, %0, 0;\n@p bar.sync %1, %2;\n}" ::"r"(on), "r"(id), "r"(n) : "memory"); }
DEVI void bar_arrive_p(int on, int id, int n) { asm volatile("{\n.reg .pred p;\nsetp.ne.b32 p, %0, 0;\n@p bar.arrive %1, %2;\n}" ::"r"(on), "r"(id), "r"(n) : "memory"); }
DEVI void mbar_arrive_p(int on, uint32_t bar) { asm volatile("{\n.reg .pred p;\nsetp.ne.b32 p, %1, 0;\n@p mbarrier.arrive.shared::cta.b64 _, [%0];\n}" ::"r"(bar), "r"(on) : "memory"); }
DEVI void mbar_arrive2_p(int on, uint32_t bar, uint32_t rbar) {
  asm volatile("{\n.reg .pred p;\nsetp.ne.b32 p, %2, 0;\n@p mbarrier.arrive.shared::cta.b64 _, [%0];\n@p mbarrier.arrive.shared::cluster.b64 _, [%1];\n}" ::"r"(bar), "r"(rbar), "r"(on) : "memory");
}
DEVI uint32_t mapa(uint32_t a, uint32_t cta) { uint32_t r; asm("mapa.shared::cluster.u32 %0, %1, %2;" : "=r"(r) : "r"(a), "r"(cta)); return r; }
DEVI void st_async128(uint32_t a, uint32_t x, uint32_t y, uint32_t z, uint32_t w, uint32_t bar) {
  asm volatile("st.async.weak.shared::cluster.mbarrier::complete_tx::bytes.v4.b32 [%0], {%1,%2,%3,%4}, [%5];" ::"r"(a), "r"(x), "r"(y), "r"(z), "r"(w), "r"(bar) : "memory");
}

template<int OFF, int TB, int S> __device__ __forceinline__ void wgmma_rs_n192(float (&d)[S], uint32_t a0, uint32_t a1, uint32_t a2, uint32_t a3, uint64_t db, int sd) {
  asm volatile("{\n.reg .pred p;\nsetp.ne.b32 p, %101, 0;\n"
    "wgmma.mma_async.sync.aligned.m64n192k16.f32.bf16.bf16 {%0, %1, %2, %3, %4, %5, %6, %7, %8, %9, %10, %11, %12, %13, %14, %15, %16, %17, %18, %19, %20, %21, %22, %23, %24, %25, %26, %27, %28, %29, %30, %31, %32, %33, %34, %35, %36, %37, %38, %39, %40, %41, %42, %43, %44, %45, %46, %47, %48, %49, %50, %51, %52, %53, %54, %55, %56, %57, %58, %59, %60, %61, %62, %63, %64, %65, %66, %67, %68, %69, %70, %71, %72, %73, %74, %75, %76, %77, %78, %79, %80, %81, %82, %83, %84, %85, %86, %87, %88, %89, %90, %91, %92, %93, %94, %95}, {%96, %97, %98, %99}, %100, p, 1, 1, %102;\n}\n"
    : "+f"(d[OFF+0]), "+f"(d[OFF+1]), "+f"(d[OFF+2]), "+f"(d[OFF+3]), "+f"(d[OFF+4]), "+f"(d[OFF+5]), "+f"(d[OFF+6]), "+f"(d[OFF+7]), "+f"(d[OFF+8]), "+f"(d[OFF+9]), "+f"(d[OFF+10]), "+f"(d[OFF+11]), "+f"(d[OFF+12]), "+f"(d[OFF+13]), "+f"(d[OFF+14]), "+f"(d[OFF+15]), "+f"(d[OFF+16]), "+f"(d[OFF+17]), "+f"(d[OFF+18]), "+f"(d[OFF+19]), "+f"(d[OFF+20]), "+f"(d[OFF+21]), "+f"(d[OFF+22]), "+f"(d[OFF+23]), "+f"(d[OFF+24]), "+f"(d[OFF+25]), "+f"(d[OFF+26]), "+f"(d[OFF+27]), "+f"(d[OFF+28]), "+f"(d[OFF+29]), "+f"(d[OFF+30]), "+f"(d[OFF+31]), "+f"(d[OFF+32]), "+f"(d[OFF+33]), "+f"(d[OFF+34]), "+f"(d[OFF+35]), "+f"(d[OFF+36]), "+f"(d[OFF+37]), "+f"(d[OFF+38]), "+f"(d[OFF+39]), "+f"(d[OFF+40]), "+f"(d[OFF+41]), "+f"(d[OFF+42]), "+f"(d[OFF+43]), "+f"(d[OFF+44]), "+f"(d[OFF+45]), "+f"(d[OFF+46]), "+f"(d[OFF+47]), "+f"(d[OFF+48]), "+f"(d[OFF+49]), "+f"(d[OFF+50]), "+f"(d[OFF+51]), "+f"(d[OFF+52]), "+f"(d[OFF+53]), "+f"(d[OFF+54]), "+f"(d[OFF+55]), "+f"(d[OFF+56]), "+f"(d[OFF+57]), "+f"(d[OFF+58]), "+f"(d[OFF+59]), "+f"(d[OFF+60]), "+f"(d[OFF+61]), "+f"(d[OFF+62]), "+f"(d[OFF+63]), "+f"(d[OFF+64]), "+f"(d[OFF+65]), "+f"(d[OFF+66]), "+f"(d[OFF+67]), "+f"(d[OFF+68]), "+f"(d[OFF+69]), "+f"(d[OFF+70]), "+f"(d[OFF+71]), "+f"(d[OFF+72]), "+f"(d[OFF+73]), "+f"(d[OFF+74]), "+f"(d[OFF+75]), "+f"(d[OFF+76]), "+f"(d[OFF+77]), "+f"(d[OFF+78]), "+f"(d[OFF+79]), "+f"(d[OFF+80]), "+f"(d[OFF+81]), "+f"(d[OFF+82]), "+f"(d[OFF+83]), "+f"(d[OFF+84]), "+f"(d[OFF+85]), "+f"(d[OFF+86]), "+f"(d[OFF+87]), "+f"(d[OFF+88]), "+f"(d[OFF+89]), "+f"(d[OFF+90]), "+f"(d[OFF+91]), "+f"(d[OFF+92]), "+f"(d[OFF+93]), "+f"(d[OFF+94]), "+f"(d[OFF+95]) : "r"(a0), "r"(a1), "r"(a2), "r"(a3), "l"(db), "r"(sd), "n"(TB));
}
template<int OFF, int TB, int S> __device__ __forceinline__ void wgmma_rs_n48(float (&d)[S], uint32_t a0, uint32_t a1, uint32_t a2, uint32_t a3, uint64_t db, int sd) {
  asm volatile("{\n.reg .pred p;\nsetp.ne.b32 p, %29, 0;\n"
    "wgmma.mma_async.sync.aligned.m64n48k16.f32.bf16.bf16 {%0, %1, %2, %3, %4, %5, %6, %7, %8, %9, %10, %11, %12, %13, %14, %15, %16, %17, %18, %19, %20, %21, %22, %23}, {%24, %25, %26, %27}, %28, p, 1, 1, %30;\n}\n"
    : "+f"(d[OFF+0]), "+f"(d[OFF+1]), "+f"(d[OFF+2]), "+f"(d[OFF+3]), "+f"(d[OFF+4]), "+f"(d[OFF+5]), "+f"(d[OFF+6]), "+f"(d[OFF+7]), "+f"(d[OFF+8]), "+f"(d[OFF+9]), "+f"(d[OFF+10]), "+f"(d[OFF+11]), "+f"(d[OFF+12]), "+f"(d[OFF+13]), "+f"(d[OFF+14]), "+f"(d[OFF+15]), "+f"(d[OFF+16]), "+f"(d[OFF+17]), "+f"(d[OFF+18]), "+f"(d[OFF+19]), "+f"(d[OFF+20]), "+f"(d[OFF+21]), "+f"(d[OFF+22]), "+f"(d[OFF+23]) : "r"(a0), "r"(a1), "r"(a2), "r"(a3), "l"(db), "r"(sd), "n"(TB));
}
template<int OFF, int TB, int S> __device__ __forceinline__ void wgmma_rs_n16(float (&d)[S], uint32_t a0, uint32_t a1, uint32_t a2, uint32_t a3, uint64_t db, int sd) {
  asm volatile("{\n.reg .pred p;\nsetp.ne.b32 p, %13, 0;\n"
    "wgmma.mma_async.sync.aligned.m64n16k16.f32.bf16.bf16 {%0, %1, %2, %3, %4, %5, %6, %7}, {%8, %9, %10, %11}, %12, p, 1, 1, %14;\n}\n"
    : "+f"(d[OFF+0]), "+f"(d[OFF+1]), "+f"(d[OFF+2]), "+f"(d[OFF+3]), "+f"(d[OFF+4]), "+f"(d[OFF+5]), "+f"(d[OFF+6]), "+f"(d[OFF+7]) : "r"(a0), "r"(a1), "r"(a2), "r"(a3), "l"(db), "r"(sd), "n"(TB));
}
template<int OFF, int TA, int TB, int S> __device__ __forceinline__ void wgmma_ss_n160(float (&d)[S], uint64_t da, uint64_t db, int sd) {
  asm volatile("{\n.reg .pred p;\nsetp.ne.b32 p, %82, 0;\n"
    "wgmma.mma_async.sync.aligned.m64n160k16.f32.bf16.bf16 {%0, %1, %2, %3, %4, %5, %6, %7, %8, %9, %10, %11, %12, %13, %14, %15, %16, %17, %18, %19, %20, %21, %22, %23, %24, %25, %26, %27, %28, %29, %30, %31, %32, %33, %34, %35, %36, %37, %38, %39, %40, %41, %42, %43, %44, %45, %46, %47, %48, %49, %50, %51, %52, %53, %54, %55, %56, %57, %58, %59, %60, %61, %62, %63, %64, %65, %66, %67, %68, %69, %70, %71, %72, %73, %74, %75, %76, %77, %78, %79}, %80, %81, p, 1, 1, %83, %84;\n}\n"
    : "+f"(d[OFF+0]), "+f"(d[OFF+1]), "+f"(d[OFF+2]), "+f"(d[OFF+3]), "+f"(d[OFF+4]), "+f"(d[OFF+5]), "+f"(d[OFF+6]), "+f"(d[OFF+7]), "+f"(d[OFF+8]), "+f"(d[OFF+9]), "+f"(d[OFF+10]), "+f"(d[OFF+11]), "+f"(d[OFF+12]), "+f"(d[OFF+13]), "+f"(d[OFF+14]), "+f"(d[OFF+15]), "+f"(d[OFF+16]), "+f"(d[OFF+17]), "+f"(d[OFF+18]), "+f"(d[OFF+19]), "+f"(d[OFF+20]), "+f"(d[OFF+21]), "+f"(d[OFF+22]), "+f"(d[OFF+23]), "+f"(d[OFF+24]), "+f"(d[OFF+25]), "+f"(d[OFF+26]), "+f"(d[OFF+27]), "+f"(d[OFF+28]), "+f"(d[OFF+29]), "+f"(d[OFF+30]), "+f"(d[OFF+31]), "+f"(d[OFF+32]), "+f"(d[OFF+33]), "+f"(d[OFF+34]), "+f"(d[OFF+35]), "+f"(d[OFF+36]), "+f"(d[OFF+37]), "+f"(d[OFF+38]), "+f"(d[OFF+39]), "+f"(d[OFF+40]), "+f"(d[OFF+41]), "+f"(d[OFF+42]), "+f"(d[OFF+43]), "+f"(d[OFF+44]), "+f"(d[OFF+45]), "+f"(d[OFF+46]), "+f"(d[OFF+47]), "+f"(d[OFF+48]), "+f"(d[OFF+49]), "+f"(d[OFF+50]), "+f"(d[OFF+51]), "+f"(d[OFF+52]), "+f"(d[OFF+53]), "+f"(d[OFF+54]), "+f"(d[OFF+55]), "+f"(d[OFF+56]), "+f"(d[OFF+57]), "+f"(d[OFF+58]), "+f"(d[OFF+59]), "+f"(d[OFF+60]), "+f"(d[OFF+61]), "+f"(d[OFF+62]), "+f"(d[OFF+63]), "+f"(d[OFF+64]), "+f"(d[OFF+65]), "+f"(d[OFF+66]), "+f"(d[OFF+67]), "+f"(d[OFF+68]), "+f"(d[OFF+69]), "+f"(d[OFF+70]), "+f"(d[OFF+71]), "+f"(d[OFF+72]), "+f"(d[OFF+73]), "+f"(d[OFF+74]), "+f"(d[OFF+75]), "+f"(d[OFF+76]), "+f"(d[OFF+77]), "+f"(d[OFF+78]), "+f"(d[OFF+79]) : "l"(da), "l"(db), "r"(sd), "n"(TA), "n"(TB));
}

__device__ __align__(1024) uint16_t g_kvT[640 * 2048];
__device__ __align__(1024) uint16_t g_y2T[640 * 2048];
__device__ __align__(1024) uint16_t g_o[2048 * 640];
__device__ __align__(1024) uint16_t g_gate[2080];
__device__ __align__(1024) uint4 g_halo[128 * 10 * 32];
__device__ __align__(1024) unsigned g_cnt[46 * 32];
__device__ __align__(1024) unsigned g_launch[132];
#define CNT_KV(i) (g_cnt + 32 * (i))
#define CNT_O(i) (g_cnt + 32 * (10 + (i)))
#define CNT_Y(i) (g_cnt + 32 * (26 + (i)))
#define PT(i) do {} while (0)
#define PTP(on, i) do {} while (0)

constexpr uint32_t SB = 1024;
constexpr uint32_t STG = 23552, WST = 15360;
DEVI constexpr uint32_t o_px(int ks) { return (((ks >> 1) + 1) & 3) * 2 * STG; }
DEVI constexpr uint32_t o_pw(int ks) { return o_px(ks) + 16384 + (ks & 1) * WST; }
constexpr uint32_t O_HALO = 0, O_OST = STG;
constexpr uint32_t P3S = 28672;
constexpr uint32_t HC = 8320, UC = 4624, UZ = 528;
constexpr uint32_t O_H0 = 5 * P3S, O_U2 = O_H0 + 3 * HC, O_H3 = O_U2 + UC, O_U0 = O_H3 + 2 * HC;
DEVI constexpr uint32_t o_h(int c) { return O_H0 + c * HC + (c > 2 ? UC : 0); }
DEVI constexpr uint32_t o_u(int c) { return c == 2 ? O_U2 : O_U0 + (c > 2 ? c - 1 : c) * UC; }
constexpr uint32_t O_Y = 208896;
DEVI constexpr uint32_t o_x(int c) { return c < 2 ? O_Y + c * 5120 : O_U0 + (c & 1) * UC; }
constexpr uint32_t O_HIN = O_U0 + 3 * UC + UZ;
constexpr uint32_t O_BT = 4 * P3S;
constexpr uint32_t O_GT = O_Y + 20480, O_GW = O_GT + 320;
constexpr uint32_t O_BAR = 231040;
constexpr uint32_t B_FULL = O_BAR, B_EMPTY = O_BAR + 8 * 8, B_P3F = O_BAR + 8 * 16, B_P3R = O_BAR + 8 * 22, B_G = O_BAR + 8 * 23, B_U = O_BAR + 8 * 24,
                   B_HR = O_BAR + 8 * 29, B_Y = O_BAR + 8 * 34, B_EP = O_BAR + 8 * 36, B_LAST = O_BAR + 8 * 37, B_GW = O_BAR + 8 * 38, B_DONE = O_BAR + 8 * 39,
                   B_P1E = O_BAR + 8 * 40, B_AD = O_BAR + 8 * 41, B_HX = O_BAR + 8 * 41  , B_P3E = O_BAR + 8 * 52, B_HX0 = O_BAR + 8 * 57;
constexpr uint32_t B_S13 = B_EMPTY + 8 * 5, B_S15 = B_EMPTY + 8 * 7, B_S19 = B_EMPTY + 8 * 3;
constexpr uint32_t O_GP = O_BAR + 512, O_EPOCH = O_GW + 1280;
constexpr uint32_t SMEM_BYTES = 232448;
static_assert(O_U0 + 4 * UC <= O_Y && O_EPOCH + 4 <= O_BAR && O_U0 >= 8 * STG, "smem map");
enum { NB_LEAD = 1, NB_HELP = 2, NB_HALO = 3, NB_ATT = 4, NB_G = 5, NB_TOK = 6, NB_RFULL = 8, NB_RFREE = 10 };

struct Maps { CUtensorMap x_par, w_main, w_tail, o_st, kv_st, wo, o_ld, y_ld; };

template <int M> DEVI void conv_step(float (&acc)[128], uint32_t a0, uint32_t a1, uint32_t a2, uint32_t a3, uint32_t dl) {
  auto D = [&](int off) { return ((uint64_t)8 << 32) | (uint64_t)(uint32_t)(dl + off - 16 * M); };
  if constexpr (M == 0) wgmma_rs_n16<0, 0>(acc, a0, a1, a2, a3, D(0), 0);
  if constexpr (M <= 3) wgmma_rs_n48<8, 0>(acc, a0, a1, a2, a3, D(16), M == 0 ? 0 : 1);
  if constexpr (M <= 6) wgmma_rs_n48<32, 0>(acc, a0, a1, a2, a3, D(64), M == 0 ? 0 : 1);
  if constexpr (M <= 9) wgmma_rs_n48<56, 0>(acc, a0, a1, a2, a3, D(112), M == 0 ? 0 : 1);
  if constexpr (M <= 12) wgmma_rs_n48<80, 0>(acc, a0, a1, a2, a3, D(160), M == 0 ? 0 : 1);
  wgmma_rs_n48<104, 0>(acc, a0, a1, a2, a3, D(208), M == 0 ? 0 : 1);
}
template <int P> DEVI void load_pair(uint32_t (&a)[8], uint32_t ab) {
#pragma unroll
  for (int i = 0; i < 2; i++) {
    const int m = i ? 15 - P : P;
    a[4 * i + 0] = lds32(ab - 4 * (64 * m));
    a[4 * i + 1] = lds32(ab - 4 * (64 * m + 32));
    a[4 * i + 2] = lds32(ab - 4 * (64 * m - 4));
    a[4 * i + 3] = lds32(ab - 4 * (64 * m + 28));
  }
}
template <int P> DEVI void mma_pair(float (&acc)[128], uint32_t (&a)[8], uint32_t db) {
  wg_fence();
  conv_step<P>(acc, a[0], a[1], a[2], a[3], db);
  conv_step<15 - P>(acc, a[4], a[5], a[6], a[7], db);
  wg_commit();
}

DEVI void conv_reduce(uint32_t sb, int c, int ht, int chan) {
  const uint32_t a0 = sb + o_h(c) + ht * 16, a2 = sb + o_u(c) + ht * 16, a3 = sb + o_x(c) + ht * 16;
  uint4* yp = (uint4*)(g_y2T + (size_t)chan * 2048) + ht;
#pragma unroll
  for (int i = 0; i < 2; i++) {
    uint4 p, q, r, s;
    lds128(a0 + i * 2048, p.x, p.y, p.z, p.w); lds128(a0 + 4160 + i * 2048, q.x, q.y, q.z, q.w);
    lds128(a2 + i * 2048, r.x, r.y, r.z, r.w); lds128(a3 + i * 2048, s.x, s.y, s.z, s.w);
    yp[i * 128] = make_uint4(hadd2(hadd2(p.x, q.x), hadd2(r.x, s.x)), hadd2(hadd2(p.y, q.y), hadd2(r.y, s.y)),
                             hadd2(hadd2(p.z, q.z), hadd2(r.z, s.z)), hadd2(hadd2(p.w, q.w), hadd2(r.w, s.w)));
  }
}

template <int I> DEVI void ld_rows(uint32_t (&kk)[32], uint32_t (&vv)[32], const char* kp, const char* vp) {
  if constexpr (I < 32) { kk[I] = ldg_v<I * 1280>(kp); vv[I] = ldg_v<I * 1280>(vp); ld_rows<I + 1>(kk, vv, kp, vp); }
}

template <int ODD, int PART> DEVI void pack_qkv(const float (&acc)[120], uint32_t (&Q)[10][2], uint32_t (&K)[10][2], uint32_t (&V)[10][2]) {
#pragma unroll
  for (int f = 0; f < 10; f++) {
    const bool tail = ODD ? (f < 2) : (f >= 8);
    const int fm = ODD ? f - 2 : f, ft = ODD ? f : f - 8;
    const int nq = tail ? 24 + ft : fm, nk = tail ? 26 + ft : 8 + fm, nv = tail ? 28 + ft : 16 + fm;
    if (PART == 0) {
      V[f][1] = pack_bf16(acc[4 * nv + 2], acc[4 * nv + 3]);
      K[f][1] = pack_bf16(acc[4 * nk + 2], acc[4 * nk + 3]);
    } else {
      Q[f][0] = pack_bf16(acc[4 * nq], acc[4 * nq + 1]); Q[f][1] = pack_bf16(acc[4 * nq + 2], acc[4 * nq + 3]);
      K[f][0] = pack_bf16(acc[4 * nk], acc[4 * nk + 1]); V[f][0] = pack_bf16(acc[4 * nv], acc[4 * nv + 1]);
    }
  }
}
template <int R> DEVI void softmax8(float (&l)[R][2], uint32_t (&P)[R]) {
  const float C = 0.22360679774997896f * 1.4426950408889634f;
  float m[R], s[R];
#pragma unroll
  for (int j = 0; j < R; j++) m[j] = fmaxf(l[j][0], l[j][1]);
#pragma unroll
  for (int j = 0; j < R; j++) m[j] = fmaxf(m[j], __shfl_xor_sync(~0u, m[j], 1));
#pragma unroll
  for (int j = 0; j < R; j++) m[j] = fmaxf(m[j], __shfl_xor_sync(~0u, m[j], 2));
#pragma unroll
  for (int j = 0; j < R; j++) { const float mc = m[j] * C; l[j][0] = ex2(fmaf(l[j][0], C, -mc)); l[j][1] = ex2(fmaf(l[j][1], C, -mc)); s[j] = l[j][0] + l[j][1]; }
#pragma unroll
  for (int j = 0; j < R; j++) s[j] += __shfl_xor_sync(~0u, s[j], 1);
#pragma unroll
  for (int j = 0; j < R; j++) s[j] += __shfl_xor_sync(~0u, s[j], 2);
#pragma unroll
  for (int j = 0; j < R; j++) {
    float r; asm("rcp.approx.ftz.f32 %0, %1;" : "=f"(r) : "f"(s[j]));
    P[j] = pack_bf16(l[j][0] * r, l[j][1] * r);
  }
}

DEVI int pair_of(int c) {
  const int lo = 32 + 8 * c, hi = c - 4 + ((max(c - 29, 0) * 37) >> 8);
  int p; asm("{\n.reg .pred q;\nsetp.lt.s32 q, %1, 4;\nselp.b32 %0, %2, %3, q;\n}" : "=r"(p) : "r"(c), "r"(lo), "r"(hi));
  return p;
}
DEVI uint32_t make_ctx() {
  int b; asm volatile("mov.u32 %0, %%ctaid.x;" : "=r"(b));
  b += clk() & threadIdx.y;
  const int p = pair_of(b >> 1);
  const int j = b < 128 ? 8 * (p & 7) + (p >> 3) : 64, cp = (j * 79) >> 10;
  return ((2 * p + (b & 1)) & 255) | (j - 13 * cp) << 8 | (2 * cp + (b & 1)) << 12 | (b >> 7) << 16;
}
#define CTX() asm volatile("" : "+r"(ctx)); CTXU()
#define CTXU() int tid; asm volatile("mov.u32 %0, %%tid.x;" : "=r"(tid)); \
  const int lane = tid & 31, vb = ctx & 255, hg = (ctx >> 4) & 7, rt = ctx & 15, par = (ctx >> 3) & 1, mt = ctx & 7, rank = ctx & 1, \
  tb = (ctx >> 8) & 15, cb = (ctx >> 12) & 15; const bool main_cta = ctx < 65536; \
  (void)tid; (void)lane; (void)vb; (void)hg; (void)rt; (void)par; (void)mt; (void)rank; (void)tb; (void)cb; (void)main_cta
#define CTXW() CTX(); const int wg = warp >> 2, w = warp & 3, g = lane >> 2, t = lane & 3; const bool lead = (tid & 127) == 0; \
  (void)wg; (void)w; (void)g; (void)t; (void)lead

__global__ void __cluster_dims__(2, 1, 1) __launch_bounds__(512, 1)
fused_kernel(const uint16_t* __restrict__ xq, const uint16_t* __restrict__ wqkv, const __grid_constant__ Maps M, const uint16_t* __restrict__ shift_k, const uint16_t* __restrict__ ssm_k, const uint16_t* __restrict__ ssm_D,
             const uint16_t* __restrict__ gate_w, const uint16_t* __restrict__ kin, const uint16_t* __restrict__ vin, uint16_t* __restrict__ outp) {
  extern __shared__ __align__(1024) uint8_t smem_raw[];
  const uint32_t sb = smem_u32(smem_raw);
  const uint32_t t0 = clk();
  auto get_epoch = [&]() { mbar_wait(sb + B_EP, 0); return lds32(sb + O_EPOCH); };

  auto p1_load_x = [&](int ks, int p, int rank) {
    tma3(sb + o_px(ks), &M.x_par, ks * 32, (p >> 2) & 1, (p & 3) * 256 + rank * 128, sb + B_FULL + 8 * (ks & 7));
  };
  auto p1_load_w = [&](int ks, int p, int rank) {
    const uint32_t st = sb + o_pw(ks), fb = sb + B_FULL + 8 * (ks & 7);
    tma3_mc(st + rank * 6144, &M.w_main, (p >> 3) * 80 + 2 * (p & 8), ks * 32 + rank * 16, 0, fb);
    tma3_mc(st + 12288 + rank * 1536, &M.w_tail, (p >> 3) * 80 + 8 * (~p & 8), ks * 32 + rank * 16, 0, fb);
  };
  auto cta_pair = [&]() { return pair_of(blockIdx.x >> 1); };

  const uint16_t* pfp = nullptr;
  if (threadIdx.x < 32) {
    const unsigned b = blockIdx.x, l = threadIdx.x;
    pfp = l < 16 ? xq + (16 * b + l) * 640 : wqkv + (15 * b + l - 16) * 64;
    if ((l | b >> 7 << 5) < 31) pf_l2(pfp);
  }
  const int warp = __shfl_sync(~0u, threadIdx.x >> 5, 0);
  if ((warp & 14) == 8) {
    if (elect_one()) {
#pragma unroll
      for (int s = 0; s < 8; s++) mbar_init(sb + O_BAR - 512 + 64 * warp + 8 * s, 5 * warp - 39);
      asm volatile("fence.mbarrier_init.release.cluster;" ::: "memory");
    }
    __syncwarp();
  }
  asm volatile("barrier.cluster.arrive.relaxed.aligned;" ::: "memory");
  if (warp == 8 && blockIdx.x < 128) {
    const int p = cta_pair(), rank = blockIdx.x & 1;
    if (elect_one()) { mbar_expect_tx(sb + B_FULL, 16384 + WST); p1_load_x(0, p, rank); }
    __syncwarp();
    asm volatile("barrier.cluster.wait.aligned;" ::: "memory");
    if (elect_one()) { p1_load_w(0, p, rank); PT(100); }
    __syncwarp();
  } else if (warp != 15) {
    asm volatile("barrier.cluster.wait.aligned;" ::: "memory");
    spin_until(t0, HOLD);
  }
  auto init_rest = [&]() {
    if (warp >= 11 && elect_one()) {
#pragma unroll
      for (int s = 0; s < 12; s++) mbar_init(sb + O_BAR + 128 - 11 * 96 + 96 * warp + 8 * s, warp == 14 ? 2 : 1);
      asm volatile("fence.mbarrier_init.release.cluster;" ::: "memory");
    }
    __syncwarp();
    bar_sync(0, blockIdx.x < 128 ? 224 : 512);
  };
  uint32_t ctx = 0;

  if (warp < 8) {
    if (PF2 && warp == 0) {
#pragma unroll 1
      for (int i = 1; i <= NPF; i++) {
        spin_until(t0, PF2 + (i - 1) * PFD);
        if ((threadIdx.x | blockIdx.x >> 7 << 5) < 31) pf_l2(pfp + (threadIdx.x < 16 ? 64 : 64 * 1920) * i);
        __syncwarp();
      }
    }
    reg_inc<RC>();
    ctx = make_ctx();
    if (blockIdx.x >= 128) bar_sync(0, 512);
    else {
      {
        uint32_t Q[10][2], K[10][2], V[10][2];
        {
          {
            float acc[120];
            unsigned epoch;
            {
              CTXW();
              const uint32_t aa = sb + (warp * 16 + (lane & 15)) * 128 + (((lane >> 4) ^ (lane & 7)) << 4);
              const uint32_t rsb = mapa(sb, (blockIdx.x & 1) ^ 1);
              uint32_t a0[8], a1[8], a2[8];
              auto load_a = [&](uint32_t (&r)[8], int ks) {
                mbar_wait(sb + B_FULL + 8 * (ks & 7), (ks >> 3) & 1);
                PTP(lead && (wg || !(ks & 3)), wg ? 60 + ks : 80 + (ks >> 2));
                ldsm4(r[0], r[1], r[2], r[3], (aa ^ ((ks & 1) * 64)) + o_px(ks)); ldsm4(r[4], r[5], r[6], r[7], (aa ^ ((ks & 1) * 64 + 32)) + o_px(ks));
              };
              auto stage = [&](uint32_t (&r)[8], uint32_t (&nx)[8], int ks, int u) {
                const uint32_t dl = o_pw(ks) >> 4;
                const uint64_t db = mkdesc(SB, 2048, 1024, 1), dt = mkdesc(SB + 12288, 512, 256, 3);
                auto D = [&](uint64_t d) { return (d & ~0xFFFFFFFFull) | (uint32_t)((uint32_t)d + dl); };
                if (LEAD && u == (20 - LEAD) % 3) bar_sync_p(wg == 0 && ks == 20 - LEAD, NB_LEAD, 256);
                wg_fence();
                wgmma_rs_n192<0, 1>(acc, r[0], r[1], r[2], r[3], D(db), ks);
                wgmma_rs_n48<96, 1>(acc, r[0], r[1], r[2], r[3], D(dt), ks);
                wg_commit();
                if (LEAD && u == 1) bar_arrive_p(wg && ks == 19, NB_LEAD, 256);
                load_a(nx, u == 1 ? min(ks + 1, 19) : ks + 1);
                wg_fence();
                wgmma_rs_n192<0, 1>(acc, r[4], r[5], r[6], r[7], D(db + 384), 1);
                wgmma_rs_n48<96, 1>(acc, r[4], r[5], r[6], r[7], D(dt + 96), 1);
                wg_commit();
                wg_wait<2>();
                mbar_arrive2_p(lead && (u || ks), sb + B_EMPTY + 8 * ((ks - 1) & 7), rsb + B_EMPTY + 8 * ((ks - 1) & 7));
              };
              if (lead) PT(1 + wg);
              load_a(a0, 0);
              constexpr int p1u = P1U;
#pragma unroll p1u
              for (int ks = 0; ks < 21; ks += 3) {
                stage(a0, a1, ks, 0);
                stage(a1, a2, ks + 1, 1);
                if (ks == 18) break;
                stage(a2, a0, ks + 2, 2);
              }
              epoch = get_epoch();
              mbar_wait(sb + B_S15, 1);
              wg_wait<0>();
              fence_regs(acc);
              mbar_arrive_p(tid == 0, sb + B_P1E);
              mbar_arrive2_p(lead, sb + B_S19, rsb + B_S19);
              PTP(lead, 50 + wg);
            }
            CTXW();
            if (hg & 1) pack_qkv<1, 0>(acc, Q, K, V); else pack_qkv<0, 0>(acc, Q, K, V);
#pragma unroll
            for (int f = 0; f < 10; f++) V[f][1] = movm(V[f][1]);
            const uint32_t ho = sb + O_HALO + warp * 2560 + lane * 16;
            if (warp == 7) {
              if (!rank) {
                const uint32_t ra = mapa(sb + O_HIN + lane * 16, 1), rb = mapa(sb + B_HX0, 1);
#pragma unroll
                for (int i = 0; i < 2; i++) {
                  st_async128(ra + i * 512, K[5 * i][1], K[5 * i + 1][1], K[5 * i + 3][1], K[5 * i + 4][1], rb);
                  st_async128(ra + 1024 + i * 512, V[5 * i][1], V[5 * i + 1][1], V[5 * i + 3][1], V[5 * i + 4][1], rb);
                }
                st_async128(ra + 2048, K[2][1], K[7][1], V[2][1], V[7][1], rb);
              } else if (mt < 7) {
                const uint64_t tag = (uint64_t)epoch << 32;
                uint4* hp = g_halo + (size_t)vb * 320 + lane;
                auto put = [&](int i, uint32_t x, uint32_t y) { asm volatile("st.relaxed.gpu.global.v2.b64 [%0], {%1, %2};" ::"l"(hp + 32 * i), "l"(tag | x), "l"(tag | y) : "memory"); };
                put(0, K[0][1], K[1][1]); put(1, K[3][1], K[4][1]); put(2, K[5][1], K[6][1]); put(3, K[8][1], K[9][1]); put(4, K[2][1], K[7][1]);
                put(5, V[0][1], V[1][1]); put(6, V[3][1], V[4][1]); put(7, V[5][1], V[6][1]); put(8, V[8][1], V[9][1]); put(9, V[2][1], V[7][1]);
              }
            } else {
#pragma unroll
              for (int i = 0; i < 2; i++) {
                sts128(ho + i * 512, K[5 * i][1], K[5 * i + 1][1], K[5 * i + 3][1], K[5 * i + 4][1]);
                sts128(ho + 1024 + i * 512, V[5 * i][1], V[5 * i + 1][1], V[5 * i + 3][1], V[5 * i + 4][1]);
              }
              sts128(ho + 2048, K[2][1], K[7][1], V[2][1], V[7][1]);
              __syncwarp();
              if (lane == 0) mbar_arrive(sb + B_HX + 8 + 8 * warp);
            }
            if (hg & 1) pack_qkv<1, 1>(acc, Q, K, V); else pack_qkv<0, 1>(acc, Q, K, V);
#pragma unroll
            for (int f = 0; f < 10; f++) V[f][0] = movm(V[f][0]);
            if (lead) PT(52 + wg);
            if (wg) mbar_wait(sb + B_P1E, 0);
          }
          CTXW();
          const bool gt0 = 2 * t > g, gt1 = 2 * t + 1 > g;
          const uint32_t pmask = (gt0 ? 0xFFFFu : 0u) | (gt1 ? 0xFFFF0000u : 0u);
          uint32_t Qh[4][2];
          float lg[8][2];
#pragma unroll
          for (int j = 0; j < 4; j++) {
            const int fa = (j >> 1) * 5 + (j & 1) * 3, fh = (j >> 1) * 5 + 2;
            const bool mine = (j & 1) ? (t >= 2) : (t < 2);
            Qh[j][0] = mine ? Q[fh][0] : 0u; Qh[j][1] = mine ? Q[fh][1] : 0u;
            float c1[4] = {0.f, 0.f, 0.f, 0.f}, c2[4] = {0.f, 0.f, 0.f, 0.f};
            mma16(c1, Q[fa][0], Q[fa][1], Q[fa + 1][0], Q[fa + 1][1], K[fa][0], K[fa + 1][0]);
            mma16(c2, Q[fa][0], Q[fa][1], Q[fa + 1][0], Q[fa + 1][1], K[fa][1], K[fa + 1][1]);
            mma8(c1, Qh[j][0], Qh[j][1], K[fh][0]);
            mma8(c2, Qh[j][0], Qh[j][1], K[fh][1]);
            lg[j][0] = c1[0]; lg[j][1] = c1[1];
            lg[4 + j][0] = gt0 ? c1[2] : c2[2]; lg[4 + j][1] = gt1 ? c1[3] : c2[3];
          }
          if (lead) PT(54 + wg);
          mbar_wait(sb + (warp ? B_HX + 8 * warp : B_HX0), 0);
          if (lead) PT(56 + wg);
          const uint32_t ha = sb + (warp ? O_HALO + (warp - 1) * 2560 : O_HIN) + lane * 16;
          uint32_t Kh[10], Vh[10];
#pragma unroll
          for (int i = 0; i < 2; i++) lds128(ha + i * 512, Kh[5 * i], Kh[5 * i + 1], Kh[5 * i + 3], Kh[5 * i + 4]);
          lds128(ha + 2048, Kh[2], Kh[7], Vh[2], Vh[7]);
#pragma unroll
          for (int i = 0; i < 2; i++) lds128(ha + 1024 + i * 512, Vh[5 * i], Vh[5 * i + 1], Vh[5 * i + 3], Vh[5 * i + 4]);
          const bool have_halo = warp > 0 || mt > 0;
#pragma unroll
          for (int j = 0; j < 4; j++) {
            const int fa = (j >> 1) * 5 + (j & 1) * 3, fh = (j >> 1) * 5 + 2;
            float c0[4] = {0.f, 0.f, 0.f, 0.f};
            mma16(c0, Q[fa][0], Q[fa][1], Q[fa + 1][0], Q[fa + 1][1], Kh[fa], Kh[fa + 1]);
            mma8(c0, Qh[j][0], Qh[j][1], Kh[fh]);
            if (!have_halo) c0[0] = c0[1] = -INFINITY;
            lg[j][0] = gt0 ? c0[0] : lg[j][0]; lg[j][1] = gt1 ? c0[1] : lg[j][1];
          }
          uint32_t Pv[8], O[10][2];
          softmax8<8>(lg, Pv);
#pragma unroll
          for (int j = 0; j < 4; j++) {
            const int fa = (j >> 1) * 5 + (j & 1) * 3, fh = (j >> 1) * 5 + 2;
            const uint32_t a0 = Pv[j] & pmask, a2 = Pv[j] & ~pmask, a3 = Pv[4 + j] & pmask, a5 = Pv[4 + j] & ~pmask;
#pragma unroll
            for (int q = 0; q < 3; q++) {
              const int f = q < 2 ? fa + q : fh;
              float o[4] = {0.f, 0.f, 0.f, 0.f};
              mma8(o, a0, 0u, Vh[f]);
              mma16(o, a2, a3, 0u, a5, V[f][0], V[f][1]);
              const uint32_t o0 = pack_bf16(o[0], o[1]), o1 = pack_bf16(o[2], o[3]);
              if (q < 2 || !(j & 1)) { O[f][0] = o0; O[f][1] = o1; }
              else { O[f][0] = t >= 2 ? o0 : O[f][0]; O[f][1] = t >= 2 ? o1 : O[f][1]; }
            }
          }
          const uint32_t oa = sb + O_OST + (warp * 16 + (lane & 15)) * 160 + (lane >> 4) * 16;
#pragma unroll
          for (int i = 0; i < 5; i++) stsm4(oa + i * 32, O[2 * i][0], O[2 * i][1], O[2 * i + 1][0], O[2 * i + 1][1]);
        }
      }
      {
        CTXW();
        bar_arrive_p(wg == 0, NB_HALO, 256);
        mbar_arrive_p(tid == 0, sb + B_AD);
        fence_async_smem();
        bar_arrive(NB_ATT, 288);
        if (lead) PT(58 + wg);
        const uint32_t abase = sb + (g & 1) * 4160 + 4 * (1023 - 4 - 8 * w - (g >> 1) + t);
        float acc[128];
        uint32_t a0[8], a1[8], a2[8], a3[8];
#pragma unroll 1
        for (int c = wg ^ 1; c < 5; c += 2) {
          const uint32_t ab = abase + o_h(c);
          const uint32_t db = __shfl_sync(~0u, ((SB + o_u(c) + UZ - 16) >> 4) | 0x10000u, 0);
          mbar_wait(sb + B_HR + 8 * c, 0);
          load_pair<0>(a0, ab); load_pair<1>(a1, ab); load_pair<2>(a2, ab); load_pair<3>(a3, ab);
          mbar_wait(sb + B_U + 8 * c, 0);
          if (lead) PT(85 + c);
          bar_sync(c ? NB_TOK + wg : NB_HALO, 256);
          fence_regs(acc);
          if (lead) PT(90 + c);
          mma_pair<0>(acc, a0, db);
          mma_pair<1>(acc, a1, db); wg_wait<1>();  load_pair<4>(a0, ab);
          mma_pair<2>(acc, a2, db); wg_wait<1>();  load_pair<5>(a1, ab);
          mma_pair<3>(acc, a3, db); wg_wait<1>();  load_pair<6>(a2, ab);
          mma_pair<4>(acc, a0, db); wg_wait<1>();  load_pair<7>(a3, ab);
          mma_pair<5>(acc, a1, db);
          mma_pair<6>(acc, a2, db);
          bar_arrive(NB_TOK + (wg ^ 1), 256);
          mma_pair<7>(acc, a3, db);
          wg_wait<0>();
          fence_regs(acc);
          if (lead) PT(95 + c);
          bar_sync(NB_RFREE + wg, 256);
          const uint32_t pb = sb + (w < 2 ? o_h(c) + w * 4160 : w == 2 ? o_u(c) : o_x(c)) + lane * 16;
          if (lane < 2 * w) sts128(pb, 0, 0, 0, 0);
#pragma unroll
          for (int q = 0; q < 8; q++) {
            uint32_t p[4];
#pragma unroll
            for (int i = 0; i < 4; i++) {
              const int nu = 4 * q + i;
              float v0 = acc[4 * nu], v1 = acc[4 * nu + 1];
              if (nu > 0) { v0 += acc[4 * nu - 2]; v1 += acc[4 * nu - 1]; }
              p[i] = pack_bf16(v0, v1);
            }
            stsm4t(pb + w * 32 + q * 512, p[0], p[1], p[2], p[3]);
          }
          bar_arrive(NB_RFULL + wg, 256);
          if (lead) PT(140 + c);
        }
      }
    }
    if (warp < 4) {
      CTXW();
      const uint32_t rsb = mapa(sb, (blockIdx.x & 1) ^ 1);
      const uint32_t ba = sb + O_BT + ((lane >> 4) * 8 + (lane & 7)) * 128 + (((2 * w + ((lane >> 3) & 1)) ^ ((lane & 1) << 2 | (lane >> 1 & 3))) << 4);
      mbar_wait(sb + B_P3F, 0);
      if (lead) PT(145);
      if (blockIdx.x < 128) bar_sync(NB_TOK, 256);
      float acc[80];
#pragma unroll 1
      for (int ks = 0; ks < 10; ks++) {
        PTP(lead, 146 + ks);
        const uint32_t dl = (ks < 6 ? ks : ks - 6) * (P3S >> 4);
        const uint64_t da = mkdesc(SB, 1024, 1024, 1), db = mkdesc(SB + 8192, 16, 1024, 1);
        auto D = [&](uint64_t d) { return (d & ~0xFFFFFFFFull) | (uint32_t)((uint32_t)d + dl); };
        wg_fence();
#pragma unroll
        for (int j = 0; j < 4; j++) wgmma_ss_n160<0, 1, 0>(acc, D(da + j * 128), D(db + j * 2), j ? 1 : ks);
        wg_commit();
        wg_wait<1>();
        mbar_arrive2_p(lead && ks >= 1 && ks <= 4, sb + B_P3E + 8 * (ks - 1), rsb + B_P3E + 8 * (ks - 1));
        mbar_wait(sb + B_P3F + 8 * (ks < 5 ? ks + 1 : ks - 5), ks >= 5 && ks < 9);
      }
      wg_wait<0>();
      fence_regs(acc);
      if (lead) PT(156);
#pragma unroll
      for (int i = 0; i < 10; i++) {
        stsm4t(ba + i * 2048, pack_bf16(acc[8 * i], acc[8 * i + 1]), pack_bf16(acc[8 * i + 2], acc[8 * i + 3]),
               pack_bf16(acc[8 * i + 4], acc[8 * i + 5]), pack_bf16(acc[8 * i + 6], acc[8 * i + 7]));
        if (i & 1) bar_arrive(1 + (i >> 1), 256);
      }
      if (lead) PT(157);
    }
  } else if (warp < 12) {
    reg_dec<RH>();
    const int hw = warp - 8;
    init_rest();
    ctx = __shfl_sync(~0u, make_ctx(), 0);
    if (ctx < 65536) {
      CTXU();
#pragma unroll 1
      for (int c = hw; c < 5; c += 4) {
        const int kb = 2 * c + (vb >> 6), r0 = (vb & 63) * 32;
        const uint4 sk = __ldg((const uint4*)(shift_k + (size_t)(kb * 64 + 2 * lane) * 4));
        wait_until(t0, KT0 + c * KTD + ((((vb * 37) & 127) * KTD) >> 7));
        if (lane == 0) PT(20 + c);
        const char* kp = (const char*)kin + (size_t)r0 * 1280 + kb * 128 + lane * 4;
        const char* vp = (const char*)vin + (size_t)r0 * 1280 + kb * 128 + lane * 4;
        uint32_t k0 = 0, k1 = 0, k2 = 0, kk[32], vv[32];
        if (r0 > 0) { k0 = ldg_v<-3 * 1280>(kp); k1 = ldg_v<-2 * 1280>(kp); k2 = ldg_v<-1280>(kp); }
        ld_rows<0>(kk, vv, kp, vp);
        const uint32_t zz = vv[31] & (uint32_t)(threadIdx.y);
        const uint32_t w0 = prmt(sk.x, sk.z, 0x5410) | zz, w1 = prmt(sk.x, sk.z, 0x7632), w2 = prmt(sk.y, sk.w, 0x5410), w3 = prmt(sk.y, sk.w, 0x7632) | zz;
        const int odd = (lane >> 2) & 1;
        const uint32_t sel0 = odd ? 0x7632 : 0x5410, sel1 = odd ? 0x5410 : 0x7632;
        const uint32_t st = sb + O_Y + c * 4096;
        PTP(lane == 0 && c == 1, 40 + zz);
#pragma unroll
        for (int ch = 0; ch < 4; ch++) {
          uint32_t o[8];
#pragma unroll
          for (int i = 0; i < 8; i++) {
            const uint32_t k3 = kk[8 * ch + i];
            o[i] = hmul2(hfma2(k3, w0, hfma2(k2, w1, hfma2(k1, w2, hmul2(k0, w3)))), vv[8 * ch + i]);
            k0 = k1; k1 = k2; k2 = k3;
          }
          const uint32_t oa = st + (2 * lane) * 64 + ((ch ^ (lane & 3)) << 4);
          sts128v(oa + odd * 64, prmt(o[0], o[1], sel0), prmt(o[2], o[3], sel0), prmt(o[4], o[5], sel0), prmt(o[6], o[7], sel0));
          sts128v(oa + 64 - odd * 64, prmt(o[0], o[1], sel1), prmt(o[2], o[3], sel1), prmt(o[4], o[5], sel1), prmt(o[6], o[7], sel1));
        }
        fence_async_smem();
        __syncwarp();
        if (elect_one()) {
          PT(25 + c);
          tma3_store(&M.kv_st, 0, kb * 64, vb & 63, st);
          bulk_commit(); bulk_wait_all();
          flag_add(CNT_KV(kb), 1);
          PT(30 + c);
        }
        __syncwarp();
      }
      mbar_wait(sb + B_LAST, 0);
#pragma unroll 1
      for (int c = hw ? hw - 1 : 5; c < 5; c += 3) {
        const uint4* hp = (const uint4*)(ssm_k + (size_t)(128 * c + vb) * 2048) + lane;
        uint4 u[8];
#pragma unroll
        for (int q = 0; q < 8; q++) asm volatile("ld.volatile.global.v4.b32 {%0,%1,%2,%3}, [%4];" : "=r"(u[q].x), "=r"(u[q].y), "=r"(u[q].z), "=r"(u[q].w) : "l"(hp + 32 * q));
        const uint32_t d = __ldg(ssm_D + 128 * c + vb);
        mbar_wait(sb + B_S13, 1);
        const uint32_t o = sb + o_h(c) + (255 - lane) * 16;
        if (lane == 0) u[0].x = prmt(pack_bf16(bf_lo(u[0].x) + bf_lo(d), 0.f), u[0].x, 0x7610);
#pragma unroll
        for (int q = 0; q < 8; q++) {
          const uint32_t up = __shfl_sync(~0u, lane == 31 ? (q ? u[q ? q - 1 : 0].w : 0u) : u[q].w, lane + 31);
          sts128(o - q * 512, prmt(u[q].w, u[q].z, 0x7610), prmt(u[q].z, u[q].y, 0x7610), prmt(u[q].y, u[q].x, 0x7610), prmt(u[q].x, up, 0x7610));
          sts128(o - q * 512 + 4160, prmt(u[q].w, 0, 0x1032), prmt(u[q].z, 0, 0x1032), prmt(u[q].y, 0, 0x1032), prmt(u[q].x, 0, 0x1032));
        }
        if (lane < 2) sts128(sb + o_h(c) + lane * 4160 + 4096, 0, 0, 0, 0);
        __syncwarp();
        if (lane == 0) { mbar_arrive(sb + B_HR + 8 * c); PT(35 + c); }
      }
    }
    CTXU();
    const int g = lane >> 2, t = lane & 3, row = 8 * hw + g;
    const uint32_t go = (tb * 160 + row) * 80 + cb * 8 + t;
    uint4 T[10];
#pragma unroll
    for (int i = 0; i < 10; i++) {
      T[i] = make_uint4(0, 0, 0, 0);
      if (i < 8 || tb < 12) asm volatile("ld.volatile.global.v4.b32 {%0,%1,%2,%3}, [%4];" : "=r"(T[i].x), "=r"(T[i].y), "=r"(T[i].z), "=r"(T[i].w) : "l"((const uint4*)xq + go + (i >> 1) * 2560 + (i & 1) * 4));
    }
    if (main_cta) {
      bar_arrive(NB_RFREE, 256);
      bar_arrive(NB_RFREE + 1, 256);
      const int yrow = (vb & 0x61) | (vb & 6) << 2 | (vb >> 2 & 6);
#pragma unroll 1
      for (int c = 0; c < 5; c++) {
        const int wg = (c & 1) ^ 1;
        bar_sync(NB_RFULL + wg, 256);
        conv_reduce(sb, c, tid - 256, 128 * c + yrow);
        __syncwarp();
        if (lane == 0) flag_add(CNT_Y(4 * c + (vb >> 5)), 1);
        if (tid == 256) PT(41 + c);
        if (c < 3) bar_arrive(NB_RFREE + wg, 256);
        if (c == 2) {
          bar_sync(NB_HELP, 128);
          if (tid == 256) { mbar_arrive(sb + B_P3E + 32); mbar_arrive_remote(sb + B_P3E + 32, rank ^ 1); }
        }
      }
    }
    uint32_t G[5];
    mbar_wait(sb + B_G, 0);
#pragma unroll
    for (int q = 0; q < 5; q++) { uint16_t v; asm volatile("ld.shared.u16 %0, [%1];" : "=h"(v) : "r"(sb + O_GT + (32 * q + row) * 2)); G[q] = prmt(v, 0, 0x1010); }
#pragma unroll
    for (int i = 0; i < 10; i++) { const uint32_t c = G[i >> 1]; T[i] = make_uint4(hmul2(T[i].x, c), hmul2(T[i].y, c), hmul2(T[i].z, c), hmul2(T[i].w, c)); }
#pragma unroll
    for (int h = 0; h < 2; h++) {
      mbar_wait(sb + B_Y + 8 * h, 0);
      if (tid == 256) PT(46);
#pragma unroll
      for (int q = 0; q < 5; q++) {
        uint32_t y0, y1, y2, y3;
        ldsm4t(y0, y1, y2, y3, sb + O_Y + h * 10240 + q * 2048 + lane * 64 + ((hw ^ ((lane >> 1) & 3)) << 4));
        uint4& r = T[2 * q + h];
        r = make_uint4(hmul2(r.x, y0), hmul2(r.y, y1), hmul2(r.z, y2), hmul2(r.w, y3));
      }
    }
    const uint32_t so = sb + O_BT + row * 128 + ((t ^ ((g & 1) << 2 | g >> 1)) << 4);
    if (tid == 256) PT(47);
#pragma unroll
    for (int q = 0; q < 5; q++) {
      const uint32_t c = hfma2(G[q], 0xBF80BF80u, 0x3F803F80u);
      bar_sync(1 + q, 256);
      if (q == 4) mbar_arrive_p(tid == 256, sb + B_DONE);
#pragma unroll
      for (int h = 0; h < 2; h++) {
        uint4 u;
        lds128((so ^ (h * 64)) + q * 4096, u.x, u.y, u.z, u.w);
        const uint4& r = T[2 * q + h];
        if (q < 4 || tb < 12) ((uint4*)outp)[go + q * 2560 + h * 4] = make_uint4(hfma2(u.x, c, r.x), hfma2(u.y, c, r.y), hfma2(u.z, c, r.z), hfma2(u.w, c, r.w));
      }
    }
  } else {
    reg_dec<RP>();
    if (warp == 15) {
      const int p = cta_pair(), rank = blockIdx.x & 1;
      asm volatile("barrier.cluster.wait.aligned;" ::: "memory");
      if (blockIdx.x >= 128) bar_sync(0, 512);
      else {
#pragma unroll 1
        for (int ks = 1;; ks += 2) {
          mbar_wait(sb + B_EMPTY + 8 * (ks & 7), ((ks >> 3) & 1) ^ 1);
          spin_until(t0, PT1 + (ks - 1) * PTD);
          if (elect_one()) { mbar_expect_tx(sb + B_FULL + 8 * (ks & 7), WST); p1_load_w(ks, p, rank); PT(100 + ks); }
          if (ks == 19) break;
          const int kn = ks + 1;
          mbar_wait(sb + B_EMPTY + 8 * (kn & 7), ((kn >> 3) & 1) ^ 1);
          spin_until(t0, PT1 + ks * PTD - PTE);
          if (elect_one()) { mbar_expect_tx(sb + B_FULL + 8 * (kn & 7), 16384 + WST); p1_load_x(kn, p, rank); p1_load_w(kn, p, rank); PT(100 + kn); }
        }
        if (elect_one()) mbar_arrive(sb + B_LAST);
        mbar_wait(sb + B_S19, 0);
      }
    } else init_rest();
    ctx = __shfl_sync(~0u, make_ctx(), 0);
    CTXU();
    if (warp == 12) {
        unsigned epoch = 0;
      if (lane == 0) {
        if ((sb & 0xFFFFFF) != SB) __trap();
        mbar_expect_tx(sb + B_GW, 1280);
        bulk_load(sb + O_GW, gate_w, 1280, sb + B_GW);
        epoch = *(volatile unsigned*)(g_launch + blockIdx.x) + 1;
        *(volatile unsigned*)(g_launch + blockIdx.x) = epoch;
        sts32(sb + O_EPOCH, epoch);
        mbar_arrive(sb + B_EP);
#pragma unroll 1
        for (int i = 3; i < 8; i++) asm volatile("prefetch.tensormap [%0];" ::"l"(&M.x_par + i) : "memory");
      }
      __syncwarp();
      if (main_cta) {
        mbar_wait(sb + B_LAST, 0);
        mbar_wait(sb + B_S13, 1);
#pragma unroll
        for (int c = 0; c < 5; c++) sts128(sb + o_u(c) + lane * 16, 0, 0, 0, 0);
        if (lane < 5) sts128(sb + o_u(lane) + 512, 0, 0, 0, 0);
        fence_async_smem();
        __syncwarp();
        epoch = __shfl_sync(~0u, epoch, 0);
#pragma unroll 1
        for (int c = 0; c < 5; c++) {
          if (c == 4) mbar_wait(sb + B_AD, 0);
          flag_wait(CNT_KV(2 * c + (vb >> 6)), 64 * epoch);
          __syncwarp();
          if (elect_one()) {
            mbar_expect_tx(sb + B_U + 8 * c, 4096);
            bulk_load(sb + o_u(c) + UZ, g_kvT + (size_t)(128 * c + vb) * 2048, 4096, sb + B_U + 8 * c);
            PT(10 + c);
          }
        }
      }
    } else if (warp != 15) {
        const int r = warp - 13;
      if (main_cta) {
        if (rank) {
#pragma unroll
          for (int f = 0; f < 5; f++)
            asm volatile("st.relaxed.gpu.global.v2.b64 [%0], {%1, %1};" ::"l"(g_halo + (size_t)vb * 320 + r * 160 + lane + 32 * f), "l"(0ull) : "memory");
          if (lane == 0) mbar_expect_tx(sb + B_HX0, 1280);
        }
        const int t = lane & 3, grow = hg * 16 + (lane & 15);
        const uint32_t ga = sb + grow * 128 + (((4 * r + (lane >> 4)) ^ (lane & 7)) << 4);
        const uint32_t gp = sb + O_GW + 64 * r + 4 * t;
        float s0 = 0.f, s1 = 0.f;
        mbar_wait_wd(sb + B_GW, 0, t0);
#pragma unroll 1
        for (int ks = 0; ks < 20; ks += 2) {
          uint32_t x[8], gw[4];
#pragma unroll
          for (int i = 0; i < 4; i++) gw[i] = lds32(gp + ks * 64 + i * 16);
          mbar_wait_wd(sb + B_FULL + 8 * (ks & 7), (ks >> 3) & 1, t0);
          if (r == 0 && lane == 0) PT(120 + ks);
          ldsm4(x[0], x[1], x[2], x[3], ga + o_px(ks)); ldsm4(x[4], x[5], x[6], x[7], (ga ^ 32) + o_px(ks));
#pragma unroll
          for (int i = 0; i < 8; i++) x[i] = hmul2(x[i], gw[i >> 1]);
          if (lane < 2) mbar_arrive(sb + B_EMPTY + 8 * (ks & 7) + 8 * lane + (x[0] & x[7] & threadIdx.y));
#pragma unroll
          for (int i = 0; i < 8; i += 4) {
            s0 += (bf_lo(x[i]) + bf_hi(x[i])) + (bf_lo(x[i + 2]) + bf_hi(x[i + 2]));
            s1 += (bf_lo(x[i + 1]) + bf_hi(x[i + 1])) + (bf_lo(x[i + 3]) + bf_hi(x[i + 3]));
          }
        }
        s0 += __shfl_xor_sync(~0u, s0, 1); s1 += __shfl_xor_sync(~0u, s1, 1);
        s0 += __shfl_xor_sync(~0u, s0, 2); s1 += __shfl_xor_sync(~0u, s1, 2);
        if (t < 2) sts32(sb + O_GP + r * 64 + (8 * t + (lane >> 2)) * 4, __float_as_uint(t ? s1 : s0));
        if (r == 0) bar_arrive(NB_G, 64);
        if (!rank) {
          const uint32_t ha = sb + O_HIN + lane * 16 + r * 1024, hb = sb + O_HIN + lane * 16 + 2048 + r * 8;
          uint32_t d[10];
          if (mt > 0) {
            const uint4* hp = g_halo + (size_t)(vb - 1) * 320 + r * 160 + lane;
            mbar_wait_wd(sb + B_HX + 56, 0, t0);
            const unsigned epoch = lds32(sb + O_EPOCH);
            for (;;) {
              uint64_t u[10];
#pragma unroll
              for (int f = 0; f < 5; f++) asm volatile("ld.relaxed.gpu.global.v2.b64 {%0, %1}, [%2];" : "=l"(u[2 * f]), "=l"(u[2 * f + 1]) : "l"(hp + 32 * f) : "memory");
              uint32_t bad = 0;
#pragma unroll
              for (int f = 0; f < 10; f++) { d[f] = (uint32_t)u[f]; bad |= (uint32_t)(u[f] >> 32) ^ epoch; }
              if (__all_sync(~0u, bad == 0)) break;
              if (clk() - t0 > 0x70000000u) __trap();
            }
          } else {
#pragma unroll
            for (int f = 0; f < 10; f++) d[f] = 0u;
          }
          sts128(ha, d[0], d[1], d[2], d[3]); sts128(ha + 512, d[4], d[5], d[6], d[7]);
          sts32(hb, d[8]); sts32(hb + 4, d[9]);
          __syncwarp();
          if (lane == 0) { mbar_arrive(sb + B_HX0); PT(15 + r); }
        }
        if (r == 1) {
          bar_sync(NB_G, 64);
          if (lane < 16) {
            const uint32_t pa = sb + O_GP + lane * 4;
            const float z = __uint_as_float(lds32(pa)) + __uint_as_float(lds32(pa + 64));
            g_gate[2 * (mt * 128 + hg * 16 + lane) + par] = (uint16_t)pack_bf16(__fdividef(1.f, 1.f + __expf(-bf_lo(pack_bf16(z, 0.f)))), 0.f);
          }
          __syncwarp();
          if (lane == 0) flag_add(CNT_O(rt), 1);
        }
      }
      if (elect_one()) {
        mbar_wait_wd(sb + B_EP, 0, t0);
        const unsigned epoch = lds32(sb + O_EPOCH);
        if (main_cta) mbar_wait_wd(sb + B_P3E + 32, 0, t0);
        unsigned v;
        do {
          asm volatile("ld.relaxed.gpu.global.u32 %0, [%1];" : "=r"(v) : "l"(CNT_Y(2 * cb + r)) : "memory");
          if (clk() - t0 > 0x70000000u) __trap();
        } while ((int)(v - 128 * epoch) < 0);
        mbar_expect_tx(sb + B_Y + 8 * r, 10240);
        tma3(sb + O_Y + r * 10240, &M.y_ld, 0, cb * 64 + 32 * r, tb * 5, sb + B_Y + 8 * r);
        PT(17 + r);
        mbar_wait_wd(sb + B_DONE, 0, t0);
      }
    } else {
      const unsigned epoch = get_epoch();
      if (main_cta) bar_sync(NB_ATT, 288);
      if (elect_one()) {
        if (main_cta) {
          tma3_store(&M.o_st, hg * 80, par, mt * 128, sb + O_OST);
          bulk_commit(); bulk_wait_all();
          flag_add(CNT_O(rt), 1);
        }
        PT(3);
      }
      __syncwarp();
      if (lane < 4) flag_wait(CNT_O(8 * (lane & 1) + min(7, (80 * tb + 79 * (lane >> 1)) >> 7)), 16 * epoch);
      __syncwarp();
      if (elect_one()) {
        PT(4);
        mbar_arrive_remote(sb + B_P3R, rank ^ 1);
        mbar_expect_tx(sb + B_G, 320);
        bulk_load(sb + O_GT, g_gate + tb * 160, 320, sb + B_G);
      }
      mbar_wait(sb + B_P3R, 0);
#pragma unroll 1
      for (int ks = 0; ks < 10; ks++) {
        const int q = ks < 6 ? ks : ks - 6;
        if (ks > 5 || (ks == 5 && main_cta)) mbar_wait(sb + B_P3E + 8 * (ks == 5 ? 4 : q), 0);
        if (elect_one()) {
          PTP(ks >= 5, ks);
          mbar_expect_tx(sb + B_P3F + 8 * q, P3S);
          tma2(sb + q * P3S, &M.wo, cb * 64, ks * 64, sb + B_P3F + 8 * q);
          tma2_mc(sb + q * P3S + 8192 + rank * 10240, &M.o_ld, ks * 64, tb * 160 + rank * 80, sb + B_P3F + 8 * q);
        }
      }
    }
  }
}

typedef CUresult (*PFN_enc)(CUtensorMap*, CUtensorMapDataType, cuuint32_t, void*, const cuuint64_t*, const cuuint64_t*, const cuuint32_t*,
                            const cuuint32_t*, CUtensorMapInterleave, CUtensorMapSwizzle, CUtensorMapL2promotion, CUtensorMapFloatOOBfill);
static void enc(PFN_enc f, CUtensorMap* m, const void* base, int rank, const cuuint64_t* dims, const cuuint64_t* strides, const cuuint32_t* box,
                CUtensorMapSwizzle sw) {
  const cuuint32_t es[5] = {1, 1, 1, 1, 1};
  f(m, CU_TENSOR_MAP_DATA_TYPE_BFLOAT16, rank, (void*)base, dims, strides, box, es, CU_TENSOR_MAP_INTERLEAVE_NONE, sw,
    CU_TENSOR_MAP_L2_PROMOTION_NONE, CU_TENSOR_MAP_FLOAT_OOB_FILL_NONE);
}

extern "C" void kernel_launch(void* const* d_in, const int* in_sizes, int n_in, void* d_out, int out_size) {
  (void)in_sizes; (void)n_in; (void)out_size;
  static PFN_enc f = nullptr;
  static void *kvT, *y2T, *o;
  if (!f) {
    void* p = nullptr;
    cudaDriverEntryPointQueryResult q;
    cudaGetDriverEntryPoint("cuTensorMapEncodeTiled", &p, cudaEnableDefault, &q);
    f = (PFN_enc)p;
    cudaGetSymbolAddress(&kvT, g_kvT); cudaGetSymbolAddress(&y2T, g_y2T); cudaGetSymbolAddress(&o, g_o);
    cudaFuncSetAttribute(fused_kernel, cudaFuncAttributeMaxDynamicSharedMemorySize, SMEM_BYTES);
  }
  Maps M;
  const CUtensorMapSwizzle S0 = CU_TENSOR_MAP_SWIZZLE_NONE, S32 = CU_TENSOR_MAP_SWIZZLE_32B, S64 = CU_TENSOR_MAP_SWIZZLE_64B, S128 = CU_TENSOR_MAP_SWIZZLE_128B;
  const cuuint64_t dpar[3] = {640, 2, 1024}, spar[2] = {1280, 2560};
  const cuuint64_t dw[3] = {640, 640, 3}, sw[2] = {3840, 1280};
  const cuuint64_t dnat[2] = {640, 2048}, snat[1] = {1280};
  const cuuint64_t dT[3] = {32, 640, 64}, sT[2] = {4096, 64};
  const cuuint64_t dwo[2] = {640, 640};
  { const cuuint32_t bx[3] = {64, 1, 128}; enc(f, &M.x_par, d_in[0], 3, dpar, spar, bx, S128); }
  { const cuuint32_t bx[3] = {64, 16, 3}; enc(f, &M.w_main, d_in[7], 3, dw, sw, bx, S128); }
  { const cuuint32_t bx[3] = {16, 16, 3}; enc(f, &M.w_tail, d_in[7], 3, dw, sw, bx, S32); }
  { const cuuint32_t bx[3] = {80, 1, 128}; enc(f, &M.o_st, o, 3, dpar, spar, bx, S0); }
  { const cuuint32_t bx[3] = {32, 64, 1}; enc(f, &M.kv_st, kvT, 3, dT, sT, bx, S64); }
  { const cuuint32_t bx[3] = {32, 32, 5}; enc(f, &M.y_ld, y2T, 3, dT, sT, bx, S64); }
  { const cuuint32_t bx[2] = {64, 64}; enc(f, &M.wo, d_in[8], 2, dwo, snat, bx, S128); }
  { const cuuint32_t bx[2] = {64, 80}; enc(f, &M.o_ld, o, 2, dnat, snat, bx, S128); }
  fused_kernel<<<130, 512, SMEM_BYTES, cudaStreamPerThread>>>((const uint16_t*)d_in[0], (const uint16_t*)d_in[7], M, (const uint16_t*)d_in[3], (const uint16_t*)d_in[4], (const uint16_t*)d_in[5], (const uint16_t*)d_in[9],
                                                              (const uint16_t*)d_in[1], (const uint16_t*)d_in[2], (uint16_t*)d_out);
}
```

```cpp
#include <cuda_runtime.h>
#include <cuda_bf16.h>
#include <cuda.h>
#include <stdint.h>

#define DEVI __device__ __forceinline__
#define PT1 550
#define PTD 460
#define PTE 200
#define PF2 0
#define NPF 1
#define PFD 0
#define SSMASK 0
static_assert((SSMASK & 0xAAA) == 0, "an x tile is refilled as soon as its even stage is released");
#define HT 19
#define KPH 37
#define KT0 1500
#define KTD 1300
#define RC 192
#define RH 96
#define RP 32
#define HOLD 750
#define P1U 7
#define LEAD 3

DEVI uint32_t smem_u32(const void* p) { return (uint32_t)__cvta_generic_to_shared(p); }
DEVI void wg_fence() { asm volatile("wgmma.fence.sync.aligned;" ::: "memory"); }
DEVI void wg_commit() { asm volatile("wgmma.commit_group.sync.aligned;" ::: "memory"); }
template <int N> DEVI void wg_wait() { asm volatile("wgmma.wait_group.sync.aligned %0;" ::"n"(N) : "memory"); }
template <int S> DEVI void fence_regs(float (&d)[S]) {
#pragma unroll
  for (int i = 0; i < S; i++) asm volatile("" : "+f"(d[i])::"memory");
}
DEVI uint64_t mkdesc(uint32_t addr, uint32_t lbo, uint32_t sbo, int swz) {
  return (uint64_t)((addr & 0x3FFFF) >> 4) | ((uint64_t)(lbo >> 4) << 16) | ((uint64_t)(sbo >> 4) << 32) | ((uint64_t)swz << 62);
}
DEVI void mbar_init(uint32_t bar, uint32_t cnt) { asm volatile("mbarrier.init.shared::cta.b64 [%0], %1;" ::"r"(bar), "r"(cnt) : "memory"); }
DEVI void mbar_expect_tx(uint32_t bar, uint32_t bytes) { asm volatile("mbarrier.arrive.expect_tx.shared::cta.b64 _, [%0], %1;" ::"r"(bar), "r"(bytes) : "memory"); }
DEVI void mbar_arrive(uint32_t bar) { asm volatile("mbarrier.arrive.shared::cta.b64 _, [%0];" ::"r"(bar) : "memory"); }
DEVI void mbar_wait(uint32_t bar, uint32_t parity) {
  asm volatile("{\n.reg .pred p;\nLAB_WAIT:\nmbarrier.try_wait.parity.shared::cta.b64 p, [%0], %1;\n@!p bra LAB_WAIT;\n}" ::"r"(bar), "r"(parity) : "memory");
}
DEVI void mbar_wait_wd(uint32_t bar, uint32_t parity, uint32_t t0) {
  asm volatile("{\n.reg .pred p;\n.reg .u32 c;\nLAB_WAIT:\nmbarrier.try_wait.parity.shared::cta.b64 p, [%0], %1;\n@p bra DONE;\nmov.u32 c, %%clock;\nsub.u32 c, c, %2;\nsetp.lt.u32 p, c, 0x70000000;\n@p bra LAB_WAIT;\ntrap;\nDONE:\n}" ::"r"(bar), "r"(parity), "r"(t0) : "memory");
}
DEVI void flag_wait(const unsigned* p, unsigned target) {
  asm volatile("{\n.reg .pred p;\n.reg .s32 v;\nLAB_WAIT:\nld.relaxed.gpu.global.u32 v, [%0];\nsub.s32 v, v, %1;\nsetp.lt.s32 p, v, 0;\n@p bra LAB_WAIT;\n}" ::"l"(p), "r"(target) : "memory");
}
DEVI void flag_add(unsigned* p, unsigned v) { asm volatile("red.relaxed.gpu.global.add.u32 [%0], %1;" ::"l"(p), "r"(v) : "memory"); }
DEVI void fence_async_smem() { asm volatile("fence.proxy.async.shared::cta;" ::: "memory"); }
DEVI bool elect_one() { uint32_t p; asm volatile("{\n.reg .pred P;\nelect.sync _|P, 0xffffffff;\nselp.u32 %0, 1, 0, P;\n}" : "=r"(p)); return p; }
DEVI void bar_sync(int id, int n) { asm volatile("bar.sync %0, %1;" ::"r"(id), "r"(n) : "memory"); }
DEVI void bar_arrive(int id, int n) { asm volatile("bar.arrive %0, %1;" ::"r"(id), "r"(n) : "memory"); }
DEVI void tma2(uint32_t dst, const CUtensorMap* m, int c0, int c1, uint32_t bar) {
  asm volatile("cp.async.bulk.tensor.2d.shared::cluster.global.mbarrier::complete_tx::bytes [%0], [%1, {%3, %4}], [%2];" ::"r"(dst), "l"(m), "r"(bar), "r"(c0), "r"(c1) : "memory");
}
DEVI void tma3(uint32_t dst, const CUtensorMap* m, int c0, int c1, int c2, uint32_t bar) {
  asm volatile("cp.async.bulk.tensor.3d.shared::cluster.global.mbarrier::complete_tx::bytes [%0], [%1, {%3, %4, %5}], [%2];" ::"r"(dst), "l"(m), "r"(bar), "r"(c0), "r"(c1), "r"(c2) : "memory");
}
DEVI void tma3_mc(uint32_t dst, const CUtensorMap* m, int c0, int c1, int c2, uint32_t bar) {
  asm volatile("cp.async.bulk.tensor.3d.shared::cluster.global.mbarrier::complete_tx::bytes.multicast::cluster [%0], [%1, {%3, %4, %5}], [%2], %6;" ::"r"(dst), "l"(m), "r"(bar), "r"(c0), "r"(c1), "r"(c2), "h"((uint16_t)3) : "memory");
}
DEVI void tma2_mc(uint32_t dst, const CUtensorMap* m, int c0, int c1, uint32_t bar) {
  asm volatile("cp.async.bulk.tensor.2d.shared::cluster.global.mbarrier::complete_tx::bytes.multicast::cluster [%0], [%1, {%3, %4}], [%2], %5;" ::"r"(dst), "l"(m), "r"(bar), "r"(c0), "r"(c1), "h"((uint16_t)3) : "memory");
}
DEVI void mbar_arrive_remote(uint32_t bar, uint32_t cta) {
  asm volatile("{\n.reg .b32 ra;\nmapa.shared::cluster.u32 ra, %0, %1;\nmbarrier.arrive.shared::cluster.b64 _, [ra];\n}" ::"r"(bar), "r"(cta) : "memory");
}
DEVI void tma3_store(const CUtensorMap* m, int c0, int c1, int c2, uint32_t src) {
  asm volatile("cp.async.bulk.tensor.3d.global.shared::cta.bulk_group [%0, {%2, %3, %4}], [%1];" ::"l"(m), "r"(src), "r"(c0), "r"(c1), "r"(c2) : "memory");
}
DEVI void bulk_load(uint32_t dst, const void* src, uint32_t bytes, uint32_t bar) {
  asm volatile("cp.async.bulk.shared::cluster.global.mbarrier::complete_tx::bytes [%0], [%1], %2, [%3];" ::"r"(dst), "l"(src), "r"(bytes), "r"(bar) : "memory");
}
DEVI void bulk_store(void* dst, uint32_t src, uint32_t bytes) {
  asm volatile("cp.async.bulk.global.shared::cta.bulk_group [%0], [%1], %2;" ::"l"(dst), "r"(src), "r"(bytes) : "memory");
}
DEVI void pf_l2(const void* p) { asm volatile("prefetch.global.L2 [%0];" ::"l"(p)); }
template <int OFF> DEVI uint32_t ldg_v(const void* p) { uint32_t v; asm volatile("ld.volatile.global.b32 %0, [%1 + %2];" : "=r"(v) : "l"(p), "n"(OFF)); return v; }
DEVI void bulk_commit() { asm volatile("cp.async.bulk.commit_group;" ::: "memory"); }
DEVI void bulk_wait_all() { asm volatile("cp.async.bulk.wait_group 0;" ::: "memory"); }
DEVI void bulk_wait_read() { asm volatile("cp.async.bulk.wait_group.read 0;" ::: "memory"); }
template <int R> DEVI void reg_inc() { asm volatile("setmaxnreg.inc.sync.aligned.u32 %0;" ::"n"(R)); }
template <int R> DEVI void reg_dec() { asm volatile("setmaxnreg.dec.sync.aligned.u32 %0;" ::"n"(R)); }
DEVI uint32_t prmt(uint32_t a, uint32_t b, uint32_t s) { uint32_t r; asm("prmt.b32 %0,%1,%2,%3;" : "=r"(r) : "r"(a), "r"(b), "r"(s)); return r; }
DEVI uint32_t lds32(uint32_t a) { uint32_t r; asm volatile("ld.shared.b32 %0,[%1];" : "=r"(r) : "r"(a)); return r; }
DEVI void sts32(uint32_t a, uint32_t x) { asm volatile("st.shared.b32 [%0],%1;" ::"r"(a), "r"(x) : "memory"); }
DEVI void sts128(uint32_t a, uint32_t x, uint32_t y, uint32_t z, uint32_t w) { asm volatile("st.shared.v4.b32 [%0],{%1,%2,%3,%4};" ::"r"(a), "r"(x), "r"(y), "r"(z), "r"(w) : "memory"); }
DEVI void sts128v(uint32_t a, uint32_t x, uint32_t y, uint32_t z, uint32_t w) { asm volatile("st.volatile.shared.v4.b32 [%0],{%1,%2,%3,%4};" ::"r"(a), "r"(x), "r"(y), "r"(z), "r"(w) : "memory"); }
DEVI void lds128(uint32_t a, uint32_t& x, uint32_t& y, uint32_t& z, uint32_t& w) { asm volatile("ld.shared.v4.b32 {%0,%1,%2,%3},[%4];" : "=r"(x), "=r"(y), "=r"(z), "=r"(w) : "r"(a) : "memory"); }
DEVI void ldsm4(uint32_t& r0, uint32_t& r1, uint32_t& r2, uint32_t& r3, uint32_t addr) {
  asm volatile("ldmatrix.sync.aligned.m8n8.x4.shared.b16 {%0,%1,%2,%3}, [%4];" : "=r"(r0), "=r"(r1), "=r"(r2), "=r"(r3) : "r"(addr) : "memory");
}
DEVI void ldsm4t(uint32_t& r0, uint32_t& r1, uint32_t& r2, uint32_t& r3, uint32_t addr) {
  asm volatile("ldmatrix.sync.aligned.m8n8.x4.trans.shared.b16 {%0,%1,%2,%3}, [%4];" : "=r"(r0), "=r"(r1), "=r"(r2), "=r"(r3) : "r"(addr) : "memory");
}
DEVI void stsm4(uint32_t addr, uint32_t r0, uint32_t r1, uint32_t r2, uint32_t r3) {
  asm volatile("stmatrix.sync.aligned.m8n8.x4.shared.b16 [%0], {%1,%2,%3,%4};" ::"r"(addr), "r"(r0), "r"(r1), "r"(r2), "r"(r3) : "memory");
}
DEVI void stsm4t(uint32_t addr, uint32_t r0, uint32_t r1, uint32_t r2, uint32_t r3) {
  asm volatile("stmatrix.sync.aligned.m8n8.x4.trans.shared.b16 [%0], {%1,%2,%3,%4};" ::"r"(addr), "r"(r0), "r"(r1), "r"(r2), "r"(r3) : "memory");
}
DEVI uint32_t movm(uint32_t a) { uint32_t r; asm volatile("movmatrix.sync.aligned.m8n8.trans.b16 %0, %1;" : "=r"(r) : "r"(a)); return r; }
DEVI uint32_t pack_bf16(float lo, float hi) { uint32_t r; asm("cvt.rn.bf16x2.f32 %0, %1, %2;" : "=r"(r) : "f"(hi), "f"(lo)); return r; }
DEVI uint32_t hmul2(uint32_t a, uint32_t b) { uint32_t r; asm("mul.rn.bf16x2 %0,%1,%2;" : "=r"(r) : "r"(a), "r"(b)); return r; }
DEVI uint32_t hadd2(uint32_t a, uint32_t b) { uint32_t r; asm("add.rn.bf16x2 %0,%1,%2;" : "=r"(r) : "r"(a), "r"(b)); return r; }
DEVI float bf_lo(uint32_t a) { return __uint_as_float(prmt(a, 0, 0x1044)); }
DEVI float bf_hi(uint32_t a) { return __uint_as_float(a & 0xFFFF0000u); }
DEVI void mma16(float (&c)[4], uint32_t a0, uint32_t a1, uint32_t a2, uint32_t a3, uint32_t b0, uint32_t b1) {
  asm("mma.sync.aligned.m16n8k16.row.col.f32.bf16.bf16.f32 {%0,%1,%2,%3},{%4,%5,%6,%7},{%8,%9},{%0,%1,%2,%3};"
      : "+f"(c[0]), "+f"(c[1]), "+f"(c[2]), "+f"(c[3]) : "r"(a0), "r"(a1), "r"(a2), "r"(a3), "r"(b0), "r"(b1));
}
DEVI void mma8(float (&c)[4], uint32_t a0, uint32_t a1, uint32_t b0) {
  asm("mma.sync.aligned.m16n8k8.row.col.f32.bf16.bf16.f32 {%0,%1,%2,%3},{%4,%5},{%6},{%0,%1,%2,%3};"
      : "+f"(c[0]), "+f"(c[1]), "+f"(c[2]), "+f"(c[3]) : "r"(a0), "r"(a1), "r"(b0));
}
DEVI float ex2(float x) { float r; asm("ex2.approx.ftz.f32 %0, %1;" : "=f"(r) : "f"(x)); return r; }

DEVI uint32_t clk() { uint32_t c; asm volatile("mov.u32 %0, %%clock;" : "=r"(c)); return c; }
DEVI void wait_until(uint32_t t0, int dt) { while ((int)(clk() - t0) < dt) __nanosleep(40); }
DEVI void spin_until(uint32_t t0, int dt) { while ((int)(clk() - t0) < dt) {} }
DEVI uint32_t hfma2(uint32_t a, uint32_t b, uint32_t c) { uint32_t r; asm("fma.rn.bf16x2 %0,%1,%2,%3;" : "=r"(r) : "r"(a), "r"(b), "r"(c)); return r; }
DEVI void bar_sync_p(int on, int id, int n) { asm volatile("{\n.reg .pred p;\nsetp.ne.b32 p, %0, 0;\n@p bar.sync %1, %2;\n}" ::"r"(on), "r"(id), "r"(n) : "memory"); }
DEVI void bar_arrive_p(int on, int id, int n) { asm volatile("{\n.reg .pred p;\nsetp.ne.b32 p, %0, 0;\n@p bar.arrive %1, %2;\n}" ::"r"(on), "r"(id), "r"(n) : "memory"); }
DEVI void mbar_arrive_p(int on, uint32_t bar) { asm volatile("{\n.reg .pred p;\nsetp.ne.b32 p, %1, 0;\n@p mbarrier.arrive.shared::cta.b64 _, [%0];\n}" ::"r"(bar), "r"(on) : "memory"); }
DEVI void mbar_arrive2_p(int on, uint32_t bar, uint32_t rbar) {
  asm volatile("{\n.reg .pred p;\nsetp.ne.b32 p, %2, 0;\n@p mbarrier.arrive.shared::cta.b64 _, [%0];\n@p mbarrier.arrive.shared::cluster.b64 _, [%1];\n}" ::"r"(bar), "r"(rbar), "r"(on) : "memory");
}
DEVI uint32_t mapa(uint32_t a, uint32_t cta) { uint32_t r; asm("mapa.shared::cluster.u32 %0, %1, %2;" : "=r"(r) : "r"(a), "r"(cta)); return r; }
DEVI void st_async128(uint32_t a, uint32_t x, uint32_t y, uint32_t z, uint32_t w, uint32_t bar) {
  asm volatile("st.async.weak.shared::cluster.mbarrier::complete_tx::bytes.v4.b32 [%0], {%1,%2,%3,%4}, [%5];" ::"r"(a), "r"(x), "r"(y), "r"(z), "r"(w), "r"(bar) : "memory");
}

template<int OFF, int TB, int S> __device__ __forceinline__ void wgmma_rs_n192(float (&d)[S], uint32_t a0, uint32_t a1, uint32_t a2, uint32_t a3, uint64_t db, int sd) {
  asm volatile("{\n.reg .pred p;\nsetp.ne.b32 p, %101, 0;\n"
    "wgmma.mma_async.sync.aligned.m64n192k16.f32.bf16.bf16 {%0, %1, %2, %3, %4, %5, %6, %7, %8, %9, %10, %11, %12, %13, %14, %15, %16, %17, %18, %19, %20, %21, %22, %23, %24, %25, %26, %27, %28, %29, %30, %31, %32, %33, %34, %35, %36, %37, %38, %39, %40, %41, %42, %43, %44, %45, %46, %47, %48, %49, %50, %51, %52, %53, %54, %55, %56, %57, %58, %59, %60, %61, %62, %63, %64, %65, %66, %67, %68, %69, %70, %71, %72, %73, %74, %75, %76, %77, %78, %79, %80, %81, %82, %83, %84, %85, %86, %87, %88, %89, %90, %91, %92, %93, %94, %95}, {%96, %97, %98, %99}, %100, p, 1, 1, %102;\n}\n"
    : "+f"(d[OFF+0]), "+f"(d[OFF+1]), "+f"(d[OFF+2]), "+f"(d[OFF+3]), "+f"(d[OFF+4]), "+f"(d[OFF+5]), "+f"(d[OFF+6]), "+f"(d[OFF+7]), "+f"(d[OFF+8]), "+f"(d[OFF+9]), "+f"(d[OFF+10]), "+f"(d[OFF+11]), "+f"(d[OFF+12]), "+f"(d[OFF+13]), "+f"(d[OFF+14]), "+f"(d[OFF+15]), "+f"(d[OFF+16]), "+f"(d[OFF+17]), "+f"(d[OFF+18]), "+f"(d[OFF+19]), "+f"(d[OFF+20]), "+f"(d[OFF+21]), "+f"(d[OFF+22]), "+f"(d[OFF+23]), "+f"(d[OFF+24]), "+f"(d[OFF+25]), "+f"(d[OFF+26]), "+f"(d[OFF+27]), "+f"(d[OFF+28]), "+f"(d[OFF+29]), "+f"(d[OFF+30]), "+f"(d[OFF+31]), "+f"(d[OFF+32]), "+f"(d[OFF+33]), "+f"(d[OFF+34]), "+f"(d[OFF+35]), "+f"(d[OFF+36]), "+f"(d[OFF+37]), "+f"(d[OFF+38]), "+f"(d[OFF+39]), "+f"(d[OFF+40]), "+f"(d[OFF+41]), "+f"(d[OFF+42]), "+f"(d[OFF+43]), "+f"(d[OFF+44]), "+f"(d[OFF+45]), "+f"(d[OFF+46]), "+f"(d[OFF+47]), "+f"(d[OFF+48]), "+f"(d[OFF+49]), "+f"(d[OFF+50]), "+f"(d[OFF+51]), "+f"(d[OFF+52]), "+f"(d[OFF+53]), "+f"(d[OFF+54]), "+f"(d[OFF+55]), "+f"(d[OFF+56]), "+f"(d[OFF+57]), "+f"(d[OFF+58]), "+f"(d[OFF+59]), "+f"(d[OFF+60]), "+f"(d[OFF+61]), "+f"(d[OFF+62]), "+f"(d[OFF+63]), "+f"(d[OFF+64]), "+f"(d[OFF+65]), "+f"(d[OFF+66]), "+f"(d[OFF+67]), "+f"(d[OFF+68]), "+f"(d[OFF+69]), "+f"(d[OFF+70]), "+f"(d[OFF+71]), "+f"(d[OFF+72]), "+f"(d[OFF+73]), "+f"(d[OFF+74]), "+f"(d[OFF+75]), "+f"(d[OFF+76]), "+f"(d[OFF+77]), "+f"(d[OFF+78]), "+f"(d[OFF+79]), "+f"(d[OFF+80]), "+f"(d[OFF+81]), "+f"(d[OFF+82]), "+f"(d[OFF+83]), "+f"(d[OFF+84]), "+f"(d[OFF+85]), "+f"(d[OFF+86]), "+f"(d[OFF+87]), "+f"(d[OFF+88]), "+f"(d[OFF+89]), "+f"(d[OFF+90]), "+f"(d[OFF+91]), "+f"(d[OFF+92]), "+f"(d[OFF+93]), "+f"(d[OFF+94]), "+f"(d[OFF+95]) : "r"(a0), "r"(a1), "r"(a2), "r"(a3), "l"(db), "r"(sd), "n"(TB));
}
template<int OFF, int TB, int S> __device__ __forceinline__ void wgmma_rs_n48(float (&d)[S], uint32_t a0, uint32_t a1, uint32_t a2, uint32_t a3, uint64_t db, int sd) {
  asm volatile("{\n.reg .pred p;\nsetp.ne.b32 p, %29, 0;\n"
    "wgmma.mma_async.sync.aligned.m64n48k16.f32.bf16.bf16 {%0, %1, %2, %3, %4, %5, %6, %7, %8, %9, %10, %11, %12, %13, %14, %15, %16, %17, %18, %19, %20, %21, %22, %23}, {%24, %25, %26, %27}, %28, p, 1, 1, %30;\n}\n"
    : "+f"(d[OFF+0]), "+f"(d[OFF+1]), "+f"(d[OFF+2]), "+f"(d[OFF+3]), "+f"(d[OFF+4]), "+f"(d[OFF+5]), "+f"(d[OFF+6]), "+f"(d[OFF+7]), "+f"(d[OFF+8]), "+f"(d[OFF+9]), "+f"(d[OFF+10]), "+f"(d[OFF+11]), "+f"(d[OFF+12]), "+f"(d[OFF+13]), "+f"(d[OFF+14]), "+f"(d[OFF+15]), "+f"(d[OFF+16]), "+f"(d[OFF+17]), "+f"(d[OFF+18]), "+f"(d[OFF+19]), "+f"(d[OFF+20]), "+f"(d[OFF+21]), "+f"(d[OFF+22]), "+f"(d[OFF+23]) : "r"(a0), "r"(a1), "r"(a2), "r"(a3), "l"(db), "r"(sd), "n"(TB));
}
template<int OFF, int TB, int S> __device__ __forceinline__ void wgmma_rs_n16(float (&d)[S], uint32_t a0, uint32_t a1, uint32_t a2, uint32_t a3, uint64_t db, int sd) {
  asm volatile("{\n.reg .pred p;\nsetp.ne.b32 p, %13, 0;\n"
    "wgmma.mma_async.sync.aligned.m64n16k16.f32.bf16.bf16 {%0, %1, %2, %3, %4, %5, %6, %7}, {%8, %9, %10, %11}, %12, p, 1, 1, %14;\n}\n"
    : "+f"(d[OFF+0]), "+f"(d[OFF+1]), "+f"(d[OFF+2]), "+f"(d[OFF+3]), "+f"(d[OFF+4]), "+f"(d[OFF+5]), "+f"(d[OFF+6]), "+f"(d[OFF+7]) : "r"(a0), "r"(a1), "r"(a2), "r"(a3), "l"(db), "r"(sd), "n"(TB));
}
template<int OFF, int TA, int TB, int S> __device__ __forceinline__ void wgmma_ss_n160(float (&d)[S], uint64_t da, uint64_t db, int sd) {
  asm volatile("{\n.reg .pred p;\nsetp.ne.b32 p, %82, 0;\n"
    "wgmma.mma_async.sync.aligned.m64n160k16.f32.bf16.bf16 {%0, %1, %2, %3, %4, %5, %6, %7, %8, %9, %10, %11, %12, %13, %14, %15, %16, %17, %18, %19, %20, %21, %22, %23, %24, %25, %26, %27, %28, %29, %30, %31, %32, %33, %34, %35, %36, %37, %38, %39, %40, %41, %42, %43, %44, %45, %46, %47, %48, %49, %50, %51, %52, %53, %54, %55, %56, %57, %58, %59, %60, %61, %62, %63, %64, %65, %66, %67, %68, %69, %70, %71, %72, %73, %74, %75, %76, %77, %78, %79}, %80, %81, p, 1, 1, %83, %84;\n}\n"
    : "+f"(d[OFF+0]), "+f"(d[OFF+1]), "+f"(d[OFF+2]), "+f"(d[OFF+3]), "+f"(d[OFF+4]), "+f"(d[OFF+5]), "+f"(d[OFF+6]), "+f"(d[OFF+7]), "+f"(d[OFF+8]), "+f"(d[OFF+9]), "+f"(d[OFF+10]), "+f"(d[OFF+11]), "+f"(d[OFF+12]), "+f"(d[OFF+13]), "+f"(d[OFF+14]), "+f"(d[OFF+15]), "+f"(d[OFF+16]), "+f"(d[OFF+17]), "+f"(d[OFF+18]), "+f"(d[OFF+19]), "+f"(d[OFF+20]), "+f"(d[OFF+21]), "+f"(d[OFF+22]), "+f"(d[OFF+23]), "+f"(d[OFF+24]), "+f"(d[OFF+25]), "+f"(d[OFF+26]), "+f"(d[OFF+27]), "+f"(d[OFF+28]), "+f"(d[OFF+29]), "+f"(d[OFF+30]), "+f"(d[OFF+31]), "+f"(d[OFF+32]), "+f"(d[OFF+33]), "+f"(d[OFF+34]), "+f"(d[OFF+35]), "+f"(d[OFF+36]), "+f"(d[OFF+37]), "+f"(d[OFF+38]), "+f"(d[OFF+39]), "+f"(d[OFF+40]), "+f"(d[OFF+41]), "+f"(d[OFF+42]), "+f"(d[OFF+43]), "+f"(d[OFF+44]), "+f"(d[OFF+45]), "+f"(d[OFF+46]), "+f"(d[OFF+47]), "+f"(d[OFF+48]), "+f"(d[OFF+49]), "+f"(d[OFF+50]), "+f"(d[OFF+51]), "+f"(d[OFF+52]), "+f"(d[OFF+53]), "+f"(d[OFF+54]), "+f"(d[OFF+55]), "+f"(d[OFF+56]), "+f"(d[OFF+57]), "+f"(d[OFF+58]), "+f"(d[OFF+59]), "+f"(d[OFF+60]), "+f"(d[OFF+61]), "+f"(d[OFF+62]), "+f"(d[OFF+63]), "+f"(d[OFF+64]), "+f"(d[OFF+65]), "+f"(d[OFF+66]), "+f"(d[OFF+67]), "+f"(d[OFF+68]), "+f"(d[OFF+69]), "+f"(d[OFF+70]), "+f"(d[OFF+71]), "+f"(d[OFF+72]), "+f"(d[OFF+73]), "+f"(d[OFF+74]), "+f"(d[OFF+75]), "+f"(d[OFF+76]), "+f"(d[OFF+77]), "+f"(d[OFF+78]), "+f"(d[OFF+79]) : "l"(da), "l"(db), "r"(sd), "n"(TA), "n"(TB));
}
template<int OFF, int TA, int TB, int S> __device__ __forceinline__ void wgmma_ss_n192(float (&d)[S], uint64_t da, uint64_t db, int sd) {
  asm volatile("{\n.reg .pred p;\nsetp.ne.b32 p, %98, 0;\n"
    "wgmma.mma_async.sync.aligned.m64n192k16.f32.bf16.bf16 {%0, %1, %2, %3, %4, %5, %6, %7, %8, %9, %10, %11, %12, %13, %14, %15, %16, %17, %18, %19, %20, %21, %22, %23, %24, %25, %26, %27, %28, %29, %30, %31, %32, %33, %34, %35, %36, %37, %38, %39, %40, %41, %42, %43, %44, %45, %46, %47, %48, %49, %50, %51, %52, %53, %54, %55, %56, %57, %58, %59, %60, %61, %62, %63, %64, %65, %66, %67, %68, %69, %70, %71, %72, %73, %74, %75, %76, %77, %78, %79, %80, %81, %82, %83, %84, %85, %86, %87, %88, %89, %90, %91, %92, %93, %94, %95}, %96, %97, p, 1, 1, %99, %100;\n}\n"
    : "+f"(d[OFF+0]), "+f"(d[OFF+1]), "+f"(d[OFF+2]), "+f"(d[OFF+3]), "+f"(d[OFF+4]), "+f"(d[OFF+5]), "+f"(d[OFF+6]), "+f"(d[OFF+7]), "+f"(d[OFF+8]), "+f"(d[OFF+9]), "+f"(d[OFF+10]), "+f"(d[OFF+11]), "+f"(d[OFF+12]), "+f"(d[OFF+13]), "+f"(d[OFF+14]), "+f"(d[OFF+15]), "+f"(d[OFF+16]), "+f"(d[OFF+17]), "+f"(d[OFF+18]), "+f"(d[OFF+19]), "+f"(d[OFF+20]), "+f"(d[OFF+21]), "+f"(d[OFF+22]), "+f"(d[OFF+23]), "+f"(d[OFF+24]), "+f"(d[OFF+25]), "+f"(d[OFF+26]), "+f"(d[OFF+27]), "+f"(d[OFF+28]), "+f"(d[OFF+29]), "+f"(d[OFF+30]), "+f"(d[OFF+31]), "+f"(d[OFF+32]), "+f"(d[OFF+33]), "+f"(d[OFF+34]), "+f"(d[OFF+35]), "+f"(d[OFF+36]), "+f"(d[OFF+37]), "+f"(d[OFF+38]), "+f"(d[OFF+39]), "+f"(d[OFF+40]), "+f"(d[OFF+41]), "+f"(d[OFF+42]), "+f"(d[OFF+43]), "+f"(d[OFF+44]), "+f"(d[OFF+45]), "+f"(d[OFF+46]), "+f"(d[OFF+47]), "+f"(d[OFF+48]), "+f"(d[OFF+49]), "+f"(d[OFF+50]), "+f"(d[OFF+51]), "+f"(d[OFF+52]), "+f"(d[OFF+53]), "+f"(d[OFF+54]), "+f"(d[OFF+55]), "+f"(d[OFF+56]), "+f"(d[OFF+57]), "+f"(d[OFF+58]), "+f"(d[OFF+59]), "+f"(d[OFF+60]), "+f"(d[OFF+61]), "+f"(d[OFF+62]), "+f"(d[OFF+63]), "+f"(d[OFF+64]), "+f"(d[OFF+65]), "+f"(d[OFF+66]), "+f"(d[OFF+67]), "+f"(d[OFF+68]), "+f"(d[OFF+69]), "+f"(d[OFF+70]), "+f"(d[OFF+71]), "+f"(d[OFF+72]), "+f"(d[OFF+73]), "+f"(d[OFF+74]), "+f"(d[OFF+75]), "+f"(d[OFF+76]), "+f"(d[OFF+77]), "+f"(d[OFF+78]), "+f"(d[OFF+79]), "+f"(d[OFF+80]), "+f"(d[OFF+81]), "+f"(d[OFF+82]), "+f"(d[OFF+83]), "+f"(d[OFF+84]), "+f"(d[OFF+85]), "+f"(d[OFF+86]), "+f"(d[OFF+87]), "+f"(d[OFF+88]), "+f"(d[OFF+89]), "+f"(d[OFF+90]), "+f"(d[OFF+91]), "+f"(d[OFF+92]), "+f"(d[OFF+93]), "+f"(d[OFF+94]), "+f"(d[OFF+95]) : "l"(da), "l"(db), "r"(sd), "n"(TA), "n"(TB));
}
template<int OFF, int TA, int TB, int S> __device__ __forceinline__ void wgmma_ss_n48(float (&d)[S], uint64_t da, uint64_t db, int sd) {
  asm volatile("{\n.reg .pred p;\nsetp.ne.b32 p, %26, 0;\n"
    "wgmma.mma_async.sync.aligned.m64n48k16.f32.bf16.bf16 {%0, %1, %2, %3, %4, %5, %6, %7, %8, %9, %10, %11, %12, %13, %14, %15, %16, %17, %18, %19, %20, %21, %22, %23}, %24, %25, p, 1, 1, %27, %28;\n}\n"
    : "+f"(d[OFF+0]), "+f"(d[OFF+1]), "+f"(d[OFF+2]), "+f"(d[OFF+3]), "+f"(d[OFF+4]), "+f"(d[OFF+5]), "+f"(d[OFF+6]), "+f"(d[OFF+7]), "+f"(d[OFF+8]), "+f"(d[OFF+9]), "+f"(d[OFF+10]), "+f"(d[OFF+11]), "+f"(d[OFF+12]), "+f"(d[OFF+13]), "+f"(d[OFF+14]), "+f"(d[OFF+15]), "+f"(d[OFF+16]), "+f"(d[OFF+17]), "+f"(d[OFF+18]), "+f"(d[OFF+19]), "+f"(d[OFF+20]), "+f"(d[OFF+21]), "+f"(d[OFF+22]), "+f"(d[OFF+23]) : "l"(da), "l"(db), "r"(sd), "n"(TA), "n"(TB));
}

__device__ __align__(1024) uint16_t g_kvT[2 * 640 * 2048];
__device__ __align__(1024) uint16_t g_y2T[640 * 2048];
__device__ __align__(1024) uint16_t g_o[2048 * 640];
__device__ __align__(1024) uint16_t g_gate[2080];
__device__ __align__(1024) uint4 g_halo[128 * 10 * 32];
__device__ __align__(1024) unsigned g_cnt[46 * 32];
__device__ __align__(1024) unsigned g_launch[132];
#define CNT_KV(i) (g_cnt + 32 * (i))
#define CNT_O(i) (g_cnt + 32 * (10 + (i)))
#define CNT_Y(i) (g_cnt + 32 * (26 + (i)))
#define PT(i) do {} while (0)
#define PTP(on, i) do {} while (0)

constexpr uint32_t SB = 1024;
constexpr uint32_t STG = 23552, WST = 15360;
DEVI constexpr uint32_t o_px(int ks) { return (((ks >> 1) + 1) & 3) * 2 * STG; }
DEVI constexpr uint32_t o_pw(int ks) { return o_px(ks) + 16384 + (ks & 1) * WST; }
constexpr uint32_t O_HALO = 0, O_OST = STG;
constexpr uint32_t P3S = 28672;
constexpr uint32_t HC = 8320, UC = 4624, UZ = 528;
constexpr uint32_t O_H0 = 5 * P3S, O_U2 = O_H0 + 3 * HC, O_H3 = O_U2 + UC, O_U0 = O_H3 + 2 * HC;
DEVI constexpr uint32_t o_h(int c) { return O_H0 + c * HC + (c > 2 ? UC : 0); }
DEVI constexpr uint32_t o_u(int c) { return c == 2 ? O_U2 : O_U0 + (c > 2 ? c - 1 : c) * UC; }
constexpr uint32_t O_Y = 208896;
DEVI constexpr uint32_t o_x(int c) { return c < 2 ? O_Y + c * 5120 : O_U0 + (c & 1) * UC; }
constexpr uint32_t O_HIN = O_Y + 16384;
DEVI constexpr uint32_t o_kst(int hw) { return hw == 1 ? (O_U0 + 511) & ~511u : hw == 2 ? (O_U0 + 2 * UC + 511) & ~511u : O_Y + (hw & 1) * 8192; }
constexpr uint32_t O_BT = 4 * P3S;
constexpr uint32_t O_GT = O_Y + 20480, O_GW = O_GT + 320;
constexpr uint32_t O_BAR = 231040;
constexpr uint32_t B_FULL = O_BAR, B_EMPTY = O_BAR + 8 * 8, B_P3F = O_BAR + 8 * 16, B_P3R = O_BAR + 8 * 22, B_G = O_BAR + 8 * 23, B_U = O_BAR + 8 * 24,
                   B_KVD = O_BAR + 8 * 29, B_Y = O_BAR + 8 * 34, B_EP = O_BAR + 8 * 36, B_LAST = O_BAR + 8 * 37, B_DONE = O_BAR + 8 * 39,
                   B_P1E = O_BAR + 8 * 40, B_HX = O_BAR + 8 * 41  , B_P3E = O_BAR + 8 * 52, B_HX0 = O_BAR + 8 * 57;
constexpr uint32_t B_S13 = B_EMPTY + 8 * 5, B_S15 = B_EMPTY + 8 * 7, B_S19 = B_EMPTY + 8 * 3;
constexpr uint32_t O_GP = O_BAR + 512, O_EPOCH = O_GW + 1280;
constexpr uint32_t SMEM_BYTES = 232448;
static_assert(O_U0 + 4 * UC <= O_Y && O_EPOCH + 4 <= O_BAR && O_U0 >= 8 * STG, "smem map");
enum { NB_LEAD = 1, NB_HELP = 2, NB_HALO = 3, NB_ATT = 4, NB_G = 5, NB_TOK = 6, NB_RFULL = 8, NB_RFREE = 10 };

struct Maps { CUtensorMap x_par, w_main, w_tail, o_st, kv_st, wo, o_ld, y_ld; };

template <int M> DEVI void conv_step(float (&acc)[128], uint32_t a0, uint32_t a1, uint32_t a2, uint32_t a3, uint32_t dl) {
  auto D = [&](int off) { return ((uint64_t)8 << 32) | (uint64_t)(uint32_t)(dl + off - 16 * M); };
  if constexpr (M == 0) wgmma_rs_n16<0, 0>(acc, a0, a1, a2, a3, D(0), 0);
  if constexpr (M <= 3) wgmma_rs_n48<8, 0>(acc, a0, a1, a2, a3, D(16), M == 0 ? 0 : 1);
  if constexpr (M <= 6) wgmma_rs_n48<32, 0>(acc, a0, a1, a2, a3, D(64), M == 0 ? 0 : 1);
  if constexpr (M <= 9) wgmma_rs_n48<56, 0>(acc, a0, a1, a2, a3, D(112), M == 0 ? 0 : 1);
  if constexpr (M <= 12) wgmma_rs_n48<80, 0>(acc, a0, a1, a2, a3, D(160), M == 0 ? 0 : 1);
  wgmma_rs_n48<104, 0>(acc, a0, a1, a2, a3, D(208), M == 0 ? 0 : 1);
}
template <int P> DEVI void load_pair(uint32_t (&a)[8], uint32_t ab) {
#pragma unroll
  for (int i = 0; i < 2; i++) {
    const int m = i ? 15 - P : P;
    a[4 * i + 0] = lds32(ab - 4 * (64 * m));
    a[4 * i + 1] = lds32(ab - 4 * (64 * m + 32));
    a[4 * i + 2] = lds32(ab - 4 * (64 * m - 4));
    a[4 * i + 3] = lds32(ab - 4 * (64 * m + 28));
  }
}
template <int P> DEVI void mma_pair(float (&acc)[128], uint32_t (&a)[8], uint32_t db) {
  wg_fence();
  conv_step<P>(acc, a[0], a[1], a[2], a[3], db);
  conv_step<15 - P>(acc, a[4], a[5], a[6], a[7], db);
  wg_commit();
}

DEVI void conv_reduce(uint32_t sb, int c, int ht, int chan) {
  const uint32_t a0 = sb + o_h(c) + ht * 16, a2 = sb + o_u(c) + ht * 16, a3 = sb + o_x(c) + ht * 16;
  uint4* yp = (uint4*)(g_y2T + (size_t)chan * 2048) + ht;
#pragma unroll
  for (int i = 0; i < 2; i++) {
    uint4 p, q, r, s;
    lds128(a0 + i * 2048, p.x, p.y, p.z, p.w); lds128(a0 + 4160 + i * 2048, q.x, q.y, q.z, q.w);
    lds128(a2 + i * 2048, r.x, r.y, r.z, r.w); lds128(a3 + i * 2048, s.x, s.y, s.z, s.w);
    yp[i * 128] = make_uint4(hadd2(hadd2(p.x, q.x), hadd2(r.x, s.x)), hadd2(hadd2(p.y, q.y), hadd2(r.y, s.y)),
                             hadd2(hadd2(p.z, q.z), hadd2(r.z, s.z)), hadd2(hadd2(p.w, q.w), hadd2(r.w, s.w)));
  }
}

template <int I> DEVI void ld_rows(uint32_t (&kk)[32], uint32_t (&vv)[32], const char* kp, const char* vp) {
  if constexpr (I < 32) { kk[I] = ldg_v<I * 1280>(kp); vv[I] = ldg_v<I * 1280>(vp); ld_rows<I + 1>(kk, vv, kp, vp); }
}
DEVI void kv_task(const CUtensorMap* map, const uint16_t* kin, const uint16_t* vin, uint4 sk, int kb, int tk, uint32_t st, int lane) {
  const char* kp = (const char*)kin + tk * (32 * 1280) + kb * 128 + lane * 4;
  const char* vp = (const char*)vin + tk * (32 * 1280) + kb * 128 + lane * 4;
  uint32_t km = 0, k0 = 0, k1 = 0, k2 = 0, op = 0, kk[32], vv[32];
  if (tk > 0) { km = ldg_v<-4 * 1280>(kp); k0 = ldg_v<-3 * 1280>(kp); k1 = ldg_v<-2 * 1280>(kp); k2 = ldg_v<-1280>(kp); op = ldg_v<-1280>(vp); }
  ld_rows<0>(kk, vv, kp, vp);
  const uint32_t zz = vv[31] & (uint32_t)(threadIdx.y);
  const uint32_t w0 = prmt(sk.x, sk.z, 0x5410) | zz, w1 = prmt(sk.x, sk.z, 0x7632), w2 = prmt(sk.y, sk.w, 0x5410), w3 = prmt(sk.y, sk.w, 0x7632) | zz;
  const int odd = (lane >> 2) & 1;
  const uint32_t sel0 = odd ? 0x7632 : 0x5410, sel1 = odd ? 0x5410 : 0x7632;
  op = hmul2(hfma2(k2, w0, hfma2(k1, w1, hfma2(k0, w2, hmul2(km, w3)))), op);
#pragma unroll
  for (int ch = 0; ch < 4; ch++) {
    uint32_t o[8];
#pragma unroll
    for (int i = 0; i < 8; i++) {
      const uint32_t k3 = kk[8 * ch + i];
      o[i] = hmul2(hfma2(k3, w0, hfma2(k2, w1, hfma2(k1, w2, hmul2(k0, w3)))), vv[8 * ch + i]);
      k0 = k1; k1 = k2; k2 = k3;
    }
    const uint32_t oa = st + (2 * lane) * 64 + (((3 - ch) ^ (lane & 3)) << 4), o0 = oa + odd * 64, o1 = oa + 64 - odd * 64;
    sts128v(o0, prmt(o[6], o[5], sel0), prmt(o[4], o[3], sel0), prmt(o[2], o[1], sel0), prmt(o[0], op, sel0));
    sts128v(o1, prmt(o[6], o[5], sel1), prmt(o[4], o[3], sel1), prmt(o[2], o[1], sel1), prmt(o[0], op, sel1));
    sts128v(o0 + 4096, prmt(o[7], o[6], sel0), prmt(o[5], o[4], sel0), prmt(o[3], o[2], sel0), prmt(o[1], o[0], sel0));
    sts128v(o1 + 4096, prmt(o[7], o[6], sel1), prmt(o[5], o[4], sel1), prmt(o[3], o[2], sel1), prmt(o[1], o[0], sel1));
    op = o[7];
  }
  fence_async_smem();
  __syncwarp();
  if (elect_one()) {
    tma3_store(map, 0, kb * 64, 63 - tk, st); tma3_store(map, 0, 640 + kb * 64, 63 - tk, st + 4096);
    bulk_commit(); bulk_wait_all();
    flag_add(CNT_KV(kb), 1);
  }
  __syncwarp();
}

template <int ODD, int PART> DEVI void pack_qkv(const float (&acc)[120], uint32_t (&Q)[10][2], uint32_t (&K)[10][2], uint32_t (&V)[10][2]) {
#pragma unroll
  for (int f = 0; f < 10; f++) {
    const bool tail = ODD ? (f < 2) : (f >= 8);
    const int fm = ODD ? f - 2 : f, ft = ODD ? f : f - 8;
    const int nq = tail ? 24 + ft : fm, nk = tail ? 26 + ft : 8 + fm, nv = tail ? 28 + ft : 16 + fm;
    if (PART == 0) {
      V[f][1] = pack_bf16(acc[4 * nv + 2], acc[4 * nv + 3]);
      K[f][1] = pack_bf16(acc[4 * nk + 2], acc[4 * nk + 3]);
    } else {
      Q[f][0] = pack_bf16(acc[4 * nq], acc[4 * nq + 1]); Q[f][1] = pack_bf16(acc[4 * nq + 2], acc[4 * nq + 3]);
      K[f][0] = pack_bf16(acc[4 * nk], acc[4 * nk + 1]); V[f][0] = pack_bf16(acc[4 * nv], acc[4 * nv + 1]);
    }
  }
}
template <int R> DEVI void softmax8(float (&l)[R][2], uint32_t (&P)[R]) {
  const float C = 0.22360679774997896f * 1.4426950408889634f;
  float m[R], s[R];
#pragma unroll
  for (int j = 0; j < R; j++) m[j] = fmaxf(l[j][0], l[j][1]);
#pragma unroll
  for (int j = 0; j < R; j++) m[j] = fmaxf(m[j], __shfl_xor_sync(~0u, m[j], 1));
#pragma unroll
  for (int j = 0; j < R; j++) m[j] = fmaxf(m[j], __shfl_xor_sync(~0u, m[j], 2));
#pragma unroll
  for (int j = 0; j < R; j++) { const float mc = m[j] * C; l[j][0] = ex2(fmaf(l[j][0], C, -mc)); l[j][1] = ex2(fmaf(l[j][1], C, -mc)); s[j] = l[j][0] + l[j][1]; }
#pragma unroll
  for (int j = 0; j < R; j++) s[j] += __shfl_xor_sync(~0u, s[j], 1);
#pragma unroll
  for (int j = 0; j < R; j++) s[j] += __shfl_xor_sync(~0u, s[j], 2);
#pragma unroll
  for (int j = 0; j < R; j++) {
    float r; asm("rcp.approx.ftz.f32 %0, %1;" : "=f"(r) : "f"(s[j]));
    P[j] = pack_bf16(l[j][0] * r, l[j][1] * r);
  }
}

DEVI int pair_of(int c) {
  const int lo = 32 + 8 * c, hi = c - 4 + ((max(c - 29, 0) * 37) >> 8);
  int p; asm("{\n.reg .pred q;\nsetp.lt.s32 q, %1, 4;\nselp.b32 %0, %2, %3, q;\n}" : "=r"(p) : "r"(c), "r"(lo), "r"(hi));
  return p;
}
DEVI uint32_t make_ctx() {
  int b; asm volatile("mov.u32 %0, %%ctaid.x;" : "=r"(b));
  b += clk() & threadIdx.y;
  const int p = pair_of(b >> 1);
  const int j = b < 128 ? 8 * (p & 7) + (p >> 3) : 64, cp = (j * 79) >> 10;
  return ((2 * p + (b & 1)) & 255) | (j - 13 * cp) << 8 | (2 * cp + (b & 1)) << 12 | (b >> 7) << 16;
}
#define CTX() asm volatile("" : "+r"(ctx)); CTXU()
#define CTXU() int tid; asm volatile("mov.u32 %0, %%tid.x;" : "=r"(tid)); \
  const int lane = tid & 31, vb = ctx & 255, hg = (ctx >> 4) & 7, rt = ctx & 15, par = (ctx >> 3) & 1, mt = ctx & 7, rank = ctx & 1, \
  tb = (ctx >> 8) & 15, cb = (ctx >> 12) & 15; const bool main_cta = ctx < 65536; \
  (void)tid; (void)lane; (void)vb; (void)hg; (void)rt; (void)par; (void)mt; (void)rank; (void)tb; (void)cb; (void)main_cta
#define CTXW() CTX(); const int wg = warp >> 2, w = warp & 3, g = lane >> 2, t = lane & 3; const bool lead = (tid & 127) == 0; \
  (void)wg; (void)w; (void)g; (void)t; (void)lead

__global__ void __cluster_dims__(2, 1, 1) __launch_bounds__(512, 1)
fused_kernel(const uint16_t* __restrict__ xq, const uint16_t* __restrict__ wqkv, const uint16_t* __restrict__ gate_w, const __grid_constant__ Maps M, const uint16_t* __restrict__ shift_k, const uint16_t* __restrict__ ssm_k, const uint16_t* __restrict__ ssm_D,
             const uint16_t* __restrict__ kin, const uint16_t* __restrict__ vin, uint16_t* __restrict__ outp) {
  extern __shared__ __align__(1024) uint8_t smem_raw[];
  const uint32_t sb = smem_u32(smem_raw);
  const uint32_t t0 = clk();
  auto get_epoch = [&]() { mbar_wait(sb + B_EP, 0); return lds32(sb + O_EPOCH); };

  auto p1_load_x = [&](int ks, int p, int rank) {
    tma3(sb + o_px(ks), &M.x_par, ks * 32, (p >> 2) & 1, (p & 3) * 256 + rank * 128, sb + B_FULL + 8 * (ks & 7));
  };
  auto p1_load_w = [&](int ks, int p, int rank) {
    const uint32_t st = sb + o_pw(ks), fb = sb + B_FULL + 8 * (ks & 7);
    tma3_mc(st + rank * 6144, &M.w_main, (p >> 3) * 80 + 2 * (p & 8), ks * 32 + rank * 16, 0, fb);
    tma3_mc(st + 12288 + rank * 1536, &M.w_tail, (p >> 3) * 80 + 8 * (~p & 8), ks * 32 + rank * 16, 0, fb);
  };
  auto cta_pair = [&]() { return pair_of(blockIdx.x >> 1); };

  const uint16_t* pfp = nullptr;
  if (threadIdx.x < 32) {
    const unsigned b = blockIdx.x, l = threadIdx.x;
    pfp = l < 16 ? xq + (16 * b + l) * 640 : wqkv + (15 * b + l - 16) * 64;
    if ((l | b >> 7 << 5) < 31) pf_l2(pfp);
  }
  const int warp = __shfl_sync(~0u, threadIdx.x >> 5, 0);
  if ((warp & 14) == 8) {
    if (elect_one()) {
#pragma unroll
      for (int s = 0; s < 8; s++) mbar_init(sb + O_BAR - 512 + 64 * warp + 8 * s, 5 * warp - 39);
      asm volatile("fence.mbarrier_init.release.cluster;" ::: "memory");
    }
    __syncwarp();
  }
  asm volatile("barrier.cluster.arrive.relaxed.aligned;" ::: "memory");
  if (warp == 8 && blockIdx.x < 128) {
    const int p = cta_pair(), rank = blockIdx.x & 1;
    if (elect_one()) { mbar_expect_tx(sb + B_FULL, 16384 + WST); p1_load_x(0, p, rank); }
    __syncwarp();
    asm volatile("barrier.cluster.wait.aligned;" ::: "memory");
    if (elect_one()) { p1_load_w(0, p, rank); PT(100); }
    __syncwarp();
  } else if (warp != 15) {
    asm volatile("barrier.cluster.wait.aligned;" ::: "memory");
    spin_until(t0, HOLD);
  }
  auto init_rest = [&]() {
    if (warp >= 11 && elect_one()) {
#pragma unroll
      for (int s = 0; s < 12; s++) mbar_init(sb + O_BAR + 128 - 11 * 96 + 96 * warp + 8 * s, warp == 14 ? 2 : 1);
      asm volatile("fence.mbarrier_init.release.cluster;" ::: "memory");
    }
    __syncwarp();
    bar_sync(0, blockIdx.x < 128 ? 224 : 512);
  };
  uint32_t ctx = 0;

  if (warp < 8) {
    if (PF2 && warp == 0) {
#pragma unroll 1
      for (int i = 1; i <= NPF; i++) {
        spin_until(t0, PF2 + (i - 1) * PFD);
        if ((threadIdx.x | blockIdx.x >> 7 << 5) < 31) pf_l2(pfp + (threadIdx.x < 16 ? 64 : 64 * 1920) * i);
        __syncwarp();
      }
    }
    reg_inc<RC>();
    ctx = make_ctx();
    if (blockIdx.x >= 128) bar_sync(0, 512);
    else {
      {
        uint32_t Q[10][2], K[10][2], V[10][2];
        {
          {
            float acc[120];
            unsigned epoch;
            {
              CTXW();
              const uint32_t aa = sb + (warp * 16 + (lane & 15)) * 128 + (((lane >> 4) ^ (lane & 7)) << 4);
              const uint32_t rsb = mapa(sb, (blockIdx.x & 1) ^ 1);
              uint32_t a0[8], a1[8], a2[8];
              auto load_a = [&](uint32_t (&r)[8], int ks) {
                mbar_wait(sb + B_FULL + 8 * (ks & 7), (ks >> 3) & 1);
                PTP(lead && (wg || !(ks & 3)), wg ? 60 + ks : 80 + (ks >> 2));
                if (SSMASK >> ks & 1) return;
                ldsm4(r[0], r[1], r[2], r[3], (aa ^ ((ks & 1) * 64)) + o_px(ks)); ldsm4(r[4], r[5], r[6], r[7], (aa ^ ((ks & 1) * 64 + 32)) + o_px(ks));
              };
              auto stage = [&](uint32_t (&r)[8], uint32_t (&nx)[8], int ks, int u) {
                const uint32_t dl = o_pw(ks) >> 4;
                const uint64_t db = mkdesc(SB, 2048, 1024, 1), dt = mkdesc(SB + 12288, 512, 256, 3);
                auto D = [&](uint64_t d) { return (d & ~0xFFFFFFFFull) | (uint32_t)((uint32_t)d + dl); };
                if (LEAD && u == (20 - LEAD) % 3) bar_sync_p(wg == 0 && ks == 20 - LEAD, NB_LEAD, 256);
                wg_fence();
                const uint64_t da = mkdesc(SB + o_px(ks) + (ks & 1) * 64, 16, 1024, 1) + wg * 512;
                if (SSMASK >> ks & 1) { wgmma_ss_n192<0, 0, 1>(acc, da, D(db), ks); wgmma_ss_n48<96, 0, 1>(acc, da, D(dt), ks); }
                else { wgmma_rs_n192<0, 1>(acc, r[0], r[1], r[2], r[3], D(db), ks); wgmma_rs_n48<96, 1>(acc, r[0], r[1], r[2], r[3], D(dt), ks); }
                wg_commit();
                if (LEAD && u == 1) bar_arrive_p(wg && ks == 19, NB_LEAD, 256);
                if (ks < 19) load_a(nx, ks + 1);
                wg_fence();
                if (SSMASK >> ks & 1) { wgmma_ss_n192<0, 0, 1>(acc, da + 2, D(db + 384), 1); wgmma_ss_n48<96, 0, 1>(acc, da + 2, D(dt + 96), 1); }
                else { wgmma_rs_n192<0, 1>(acc, r[4], r[5], r[6], r[7], D(db + 384), 1); wgmma_rs_n48<96, 1>(acc, r[4], r[5], r[6], r[7], D(dt + 96), 1); }
                wg_commit();
                wg_wait<2>();
                mbar_arrive2_p(lead && (u || ks), sb + B_EMPTY + 8 * ((ks - 1) & 7), rsb + B_EMPTY + 8 * ((ks - 1) & 7));
              };
              if (lead) PT(1 + wg);
              load_a(a0, 0);
              constexpr int p1u = P1U;
#pragma unroll p1u
              for (int ks = 0; ks < 21; ks += 3) {
                stage(a0, a1, ks, 0);
                stage(a1, a2, ks + 1, 1);
                if (ks == 18) break;
                stage(a2, a0, ks + 2, 2);
              }
              epoch = get_epoch();
              mbar_wait(sb + B_S15, 1);
              wg_wait<0>();
              fence_regs(acc);
              mbar_arrive_p(tid == 0, sb + B_P1E);
              mbar_arrive2_p(lead, sb + B_S19, rsb + B_S19);
              PTP(lead, 50 + wg);
            }
            CTXW();
            if (hg & 1) pack_qkv<1, 0>(acc, Q, K, V); else pack_qkv<0, 0>(acc, Q, K, V);
#pragma unroll
            for (int f = 0; f < 10; f++) V[f][1] = movm(V[f][1]);
            const uint32_t ho = sb + O_HALO + warp * 2560 + lane * 16;
            if (warp == 7) {
              if (!rank) {
                const uint32_t ra = mapa(sb + O_HIN + lane * 16, 1), rb = mapa(sb + B_HX0, 1);
#pragma unroll
                for (int i = 0; i < 2; i++) {
                  st_async128(ra + i * 512, K[5 * i][1], K[5 * i + 1][1], K[5 * i + 3][1], K[5 * i + 4][1], rb);
                  st_async128(ra + 1024 + i * 512, V[5 * i][1], V[5 * i + 1][1], V[5 * i + 3][1], V[5 * i + 4][1], rb);
                }
                st_async128(ra + 2048, K[2][1], K[7][1], V[2][1], V[7][1], rb);
              } else if (mt < 7) {
                const uint64_t tag = (uint64_t)epoch << 32;
                uint4* hp = g_halo + (size_t)vb * 320 + lane;
                auto put = [&](int i, uint32_t x, uint32_t y) { asm volatile("st.relaxed.gpu.global.v2.b64 [%0], {%1, %2};" ::"l"(hp + 32 * i), "l"(tag | x), "l"(tag | y) : "memory"); };
                put(0, K[0][1], K[1][1]); put(1, K[3][1], K[4][1]); put(2, K[5][1], K[6][1]); put(3, K[8][1], K[9][1]); put(4, K[2][1], K[7][1]);
                put(5, V[0][1], V[1][1]); put(6, V[3][1], V[4][1]); put(7, V[5][1], V[6][1]); put(8, V[8][1], V[9][1]); put(9, V[2][1], V[7][1]);
              }
            } else {
#pragma unroll
              for (int i = 0; i < 2; i++) {
                sts128(ho + i * 512, K[5 * i][1], K[5 * i + 1][1], K[5 * i + 3][1], K[5 * i + 4][1]);
                sts128(ho + 1024 + i * 512, V[5 * i][1], V[5 * i + 1][1], V[5 * i + 3][1], V[5 * i + 4][1]);
              }
              sts128(ho + 2048, K[2][1], K[7][1], V[2][1], V[7][1]);
              __syncwarp();
              if (lane == 0) mbar_arrive(sb + B_HX + 8 + 8 * warp);
            }
            if (hg & 1) pack_qkv<1, 1>(acc, Q, K, V); else pack_qkv<0, 1>(acc, Q, K, V);
#pragma unroll
            for (int f = 0; f < 10; f++) V[f][0] = movm(V[f][0]);
            if (lead) PT(52 + wg);
            if (wg) mbar_wait(sb + B_P1E, 0);
          }
          CTXW();
          const bool gt0 = 2 * t > g, gt1 = 2 * t + 1 > g;
          const uint32_t pmask = (gt0 ? 0xFFFFu : 0u) | (gt1 ? 0xFFFF0000u : 0u);
          uint32_t Qh[4][2];
          float lg[8][2];
#pragma unroll
          for (int j = 0; j < 4; j++) {
            const int fa = (j >> 1) * 5 + (j & 1) * 3, fh = (j >> 1) * 5 + 2;
            const bool mine = (j & 1) ? (t >= 2) : (t < 2);
            Qh[j][0] = mine ? Q[fh][0] : 0u; Qh[j][1] = mine ? Q[fh][1] : 0u;
            float c1[4] = {0.f, 0.f, 0.f, 0.f}, c2[4] = {0.f, 0.f, 0.f, 0.f};
            mma16(c1, Q[fa][0], Q[fa][1], Q[fa + 1][0], Q[fa + 1][1], K[fa][0], K[fa + 1][0]);
            mma16(c2, Q[fa][0], Q[fa][1], Q[fa + 1][0], Q[fa + 1][1], K[fa][1], K[fa + 1][1]);
            mma8(c1, Qh[j][0], Qh[j][1], K[fh][0]);
            mma8(c2, Qh[j][0], Qh[j][1], K[fh][1]);
            lg[j][0] = c1[0]; lg[j][1] = c1[1];
            lg[4 + j][0] = gt0 ? c1[2] : c2[2]; lg[4 + j][1] = gt1 ? c1[3] : c2[3];
          }
          if (lead) PT(54 + wg);
          mbar_wait(sb + (warp ? B_HX + 8 * warp : B_HX0), 0);
          if (lead) PT(56 + wg);
          const uint32_t ha = sb + (warp ? O_HALO + (warp - 1) * 2560 : O_HIN) + lane * 16;
          uint32_t Kh[10], Vh[10];
#pragma unroll
          for (int i = 0; i < 2; i++) lds128(ha + i * 512, Kh[5 * i], Kh[5 * i + 1], Kh[5 * i + 3], Kh[5 * i + 4]);
          lds128(ha + 2048, Kh[2], Kh[7], Vh[2], Vh[7]);
#pragma unroll
          for (int i = 0; i < 2; i++) lds128(ha + 1024 + i * 512, Vh[5 * i], Vh[5 * i + 1], Vh[5 * i + 3], Vh[5 * i + 4]);
          const bool have_halo = warp > 0 || mt > 0;
#pragma unroll
          for (int j = 0; j < 4; j++) {
            const int fa = (j >> 1) * 5 + (j & 1) * 3, fh = (j >> 1) * 5 + 2;
            float c0[4] = {0.f, 0.f, 0.f, 0.f};
            mma16(c0, Q[fa][0], Q[fa][1], Q[fa + 1][0], Q[fa + 1][1], Kh[fa], Kh[fa + 1]);
            mma8(c0, Qh[j][0], Qh[j][1], Kh[fh]);
            if (!have_halo) c0[0] = c0[1] = -INFINITY;
            lg[j][0] = gt0 ? c0[0] : lg[j][0]; lg[j][1] = gt1 ? c0[1] : lg[j][1];
          }
          uint32_t Pv[8], O[10][2];
          softmax8<8>(lg, Pv);
#pragma unroll
          for (int j = 0; j < 4; j++) {
            const int fa = (j >> 1) * 5 + (j & 1) * 3, fh = (j >> 1) * 5 + 2;
            const uint32_t a0 = Pv[j] & pmask, a2 = Pv[j] & ~pmask, a3 = Pv[4 + j] & pmask, a5 = Pv[4 + j] & ~pmask;
#pragma unroll
            for (int q = 0; q < 3; q++) {
              const int f = q < 2 ? fa + q : fh;
              float o[4] = {0.f, 0.f, 0.f, 0.f};
              mma8(o, a0, 0u, Vh[f]);
              mma16(o, a2, a3, 0u, a5, V[f][0], V[f][1]);
              const uint32_t o0 = pack_bf16(o[0], o[1]), o1 = pack_bf16(o[2], o[3]);
              if (q < 2 || !(j & 1)) { O[f][0] = o0; O[f][1] = o1; }
              else { O[f][0] = t >= 2 ? o0 : O[f][0]; O[f][1] = t >= 2 ? o1 : O[f][1]; }
            }
          }
          const uint32_t oa = sb + O_OST + (warp * 16 + (lane & 15)) * 160 + (lane >> 4) * 16;
#pragma unroll
          for (int i = 0; i < 5; i++) stsm4(oa + i * 32, O[2 * i][0], O[2 * i][1], O[2 * i + 1][0], O[2 * i + 1][1]);
        }
      }
      {
        CTXW();
        bar_arrive_p(wg == 0, NB_HALO, 256);
        fence_async_smem();
        bar_arrive(NB_ATT, 288);
        if (lead) PT(58 + wg);
        const uint32_t abase = sb + (g & 1) * 4160 + 4 * (1023 - 4 - 8 * w - (g >> 1) + t);
        float acc[128];
        uint32_t a0[8], a1[8], a2[8], a3[8];
#pragma unroll 1
        for (int c = wg ^ 1; c < 5; c += 2) {
          const uint32_t ab = abase + o_h(c);
          const uint32_t db = __shfl_sync(~0u, ((SB + o_u(c) + UZ - 16) >> 4) | 0x10000u, 0);
          mbar_wait(sb + B_U + 8 * c, 0);
          load_pair<0>(a0, ab); load_pair<1>(a1, ab); load_pair<2>(a2, ab); load_pair<3>(a3, ab);
          if (lead) PT(85 + c);
          bar_sync(c ? NB_TOK + wg : NB_HALO, 256);
          fence_regs(acc);
          if (lead) PT(90 + c);
          mma_pair<0>(acc, a0, db);
          mma_pair<1>(acc, a1, db); wg_wait<1>();  load_pair<4>(a0, ab);
          mma_pair<2>(acc, a2, db); wg_wait<1>();  load_pair<5>(a1, ab);
          mma_pair<3>(acc, a3, db); wg_wait<1>();  load_pair<6>(a2, ab);
          mma_pair<4>(acc, a0, db); wg_wait<1>();  load_pair<7>(a3, ab);
          mma_pair<5>(acc, a1, db);
          mma_pair<6>(acc, a2, db);
          bar_arrive(NB_TOK + (wg ^ 1), 256);
          mma_pair<7>(acc, a3, db);
          wg_wait<0>();
          fence_regs(acc);
          if (lead) PT(95 + c);
          bar_sync(NB_RFREE + wg, 256);
          const uint32_t pb = sb + (w < 2 ? o_h(c) + w * 4160 : w == 2 ? o_u(c) : o_x(c)) + lane * 16;
          if (lane < 2 * w) sts128(pb, 0, 0, 0, 0);
#pragma unroll
          for (int q = 0; q < 8; q++) {
            uint32_t p[4];
#pragma unroll
            for (int i = 0; i < 4; i++) {
              const int nu = 4 * q + i;
              float v0 = acc[4 * nu], v1 = acc[4 * nu + 1];
              if (nu > 0) { v0 += acc[4 * nu - 2]; v1 += acc[4 * nu - 1]; }
              p[i] = pack_bf16(v0, v1);
            }
            stsm4t(pb + w * 32 + q * 512, p[0], p[1], p[2], p[3]);
          }
          bar_arrive(NB_RFULL + wg, 256);
          if (lead) PT(140 + c);
        }
      }
    }
    if (warp < 4) {
      CTXW();
      const uint32_t rsb = mapa(sb, (blockIdx.x & 1) ^ 1);
      const uint32_t ba = sb + O_BT + ((lane >> 4) * 8 + (lane & 7)) * 128 + (((2 * w + ((lane >> 3) & 1)) ^ ((lane & 1) << 2 | (lane >> 1 & 3))) << 4);
      mbar_wait(sb + B_P3F, 0);
      if (lead) PT(145);
      if (blockIdx.x < 128) bar_sync(NB_TOK, 256);
      float acc[80];
#pragma unroll 1
      for (int ks = 0; ks < 10; ks++) {
        PTP(lead, 146 + ks);
        const uint32_t dl = (ks < 6 ? ks : ks - 6) * (P3S >> 4);
        const uint64_t da = mkdesc(SB, 1024, 1024, 1), db = mkdesc(SB + 8192, 16, 1024, 1);
        auto D = [&](uint64_t d) { return (d & ~0xFFFFFFFFull) | (uint32_t)((uint32_t)d + dl); };
        wg_fence();
#pragma unroll
        for (int j = 0; j < 4; j++) wgmma_ss_n160<0, 1, 0>(acc, D(da + j * 128), D(db + j * 2), j ? 1 : ks);
        wg_commit();
        wg_wait<1>();
        mbar_arrive2_p(lead && ks >= 1 && ks <= 4, sb + B_P3E + 8 * (ks - 1), rsb + B_P3E + 8 * (ks - 1));
        mbar_wait(sb + B_P3F + 8 * (ks < 5 ? ks + 1 : ks - 5), ks >= 5 && ks < 9);
      }
      wg_wait<0>();
      fence_regs(acc);
      if (lead) PT(156);
#pragma unroll
      for (int i = 0; i < 10; i++) {
        stsm4t(ba + i * 2048, pack_bf16(acc[8 * i], acc[8 * i + 1]), pack_bf16(acc[8 * i + 2], acc[8 * i + 3]),
               pack_bf16(acc[8 * i + 4], acc[8 * i + 5]), pack_bf16(acc[8 * i + 6], acc[8 * i + 7]));
        if (i & 1) bar_arrive(1 + (i >> 1), 256);
      }
      if (lead) PT(157);
    }
  } else if (warp < 12) {
    reg_dec<RH>();
    const int hw = warp - 8;
    init_rest();
    ctx = __shfl_sync(~0u, make_ctx(), 0);
    if (ctx < 65536) {
      CTXU();
#pragma unroll 1
      for (int c = hw; c < 5; c += 4) {
        const int kb = 2 * c + (vb >> 6);
        const uint4 sk = __ldg((const uint4*)(shift_k + (size_t)(kb * 64 + 2 * lane) * 4));
        wait_until(t0, KT0 + c * KTD + ((((vb * KPH) & 63) * KTD) >> 6));
        if (lane == 0) PT(20 + c);
        kv_task(&M.kv_st, kin, vin, sk, kb, vb & 63, sb + o_kst(hw), lane);
        if (lane == 0) PT(30 + c);
      }
      if (lane == 0) mbar_arrive(sb + B_KVD + 8 * hw);
    }
    CTXU();
    const int g = lane >> 2, t = lane & 3, row = 8 * hw + g;
    const uint32_t go = (tb * 160 + row) * 80 + cb * 8 + t;
    uint4 T[10];
    auto load_q = [&]() {
#pragma unroll
      for (int i = 0; i < 10; i++) {
        T[i] = make_uint4(0, 0, 0, 0);
        if (i < 8 || tb < 12) asm volatile("ld.volatile.global.v4.b32 {%0,%1,%2,%3}, [%4];" : "=r"(T[i].x), "=r"(T[i].y), "=r"(T[i].z), "=r"(T[i].w) : "l"((const uint4*)xq + go + (i >> 1) * 2560 + (i & 1) * 4));
      }
    };
    if (main_cta) {
      bar_arrive(NB_RFREE, 256);
      bar_arrive(NB_RFREE + 1, 256);
      const int yrow = (vb & 0x61) | (vb & 6) << 2 | (vb >> 2 & 6);
#pragma unroll 1
      for (int c = 0; c < 5; c++) {
        const int wg = (c & 1) ^ 1;
        bar_sync(NB_RFULL + wg, 256);
        conv_reduce(sb, c, tid - 256, 128 * c + yrow);
        __syncwarp();
        if (lane == 0) flag_add(CNT_Y(4 * c + (vb >> 5)), 1);
        if (tid == 256) PT(41 + c);
        if (c < 3) bar_arrive(NB_RFREE + wg, 256);
        if (c == 2) {
          bar_sync(NB_HELP, 128);
          if (tid == 256) { mbar_arrive(sb + B_P3E + 32); mbar_arrive_remote(sb + B_P3E + 32, rank ^ 1); }
        }
      }
    }
    load_q();
    uint32_t G[5];
    mbar_wait(sb + B_G, 0);
#pragma unroll
    for (int q = 0; q < 5; q++) { uint16_t v; asm volatile("ld.shared.u16 %0, [%1];" : "=h"(v) : "r"(sb + O_GT + (32 * q + row) * 2)); G[q] = prmt(v, 0, 0x1010); }
#pragma unroll
    for (int i = 0; i < 10; i++) { const uint32_t c = G[i >> 1]; T[i] = make_uint4(hmul2(T[i].x, c), hmul2(T[i].y, c), hmul2(T[i].z, c), hmul2(T[i].w, c)); }
#pragma unroll
    for (int h = 0; h < 2; h++) {
      mbar_wait(sb + B_Y + 8 * h, 0);
      if (tid == 256) PT(46);
#pragma unroll
      for (int q = 0; q < 5; q++) {
        uint32_t y0, y1, y2, y3;
        ldsm4t(y0, y1, y2, y3, sb + O_Y + h * 10240 + q * 2048 + lane * 64 + ((hw ^ ((lane >> 1) & 3)) << 4));
        uint4& r = T[2 * q + h];
        r = make_uint4(hmul2(r.x, y0), hmul2(r.y, y1), hmul2(r.z, y2), hmul2(r.w, y3));
      }
    }
    const uint32_t so = sb + O_BT + row * 128 + ((t ^ ((g & 1) << 2 | g >> 1)) << 4);
    if (tid == 256) PT(47);
#pragma unroll
    for (int q = 0; q < 5; q++) {
      const uint32_t c = hfma2(G[q], 0xBF80BF80u, 0x3F803F80u);
      bar_sync(1 + q, 256);
      if (q == 4) mbar_arrive_p(tid == 256, sb + B_DONE);
#pragma unroll
      for (int h = 0; h < 2; h++) {
        uint4 u;
        lds128((so ^ (h * 64)) + q * 4096, u.x, u.y, u.z, u.w);
        const uint4& r = T[2 * q + h];
        if (q < 4 || tb < 12) ((uint4*)outp)[go + q * 2560 + h * 4] = make_uint4(hfma2(u.x, c, r.x), hfma2(u.y, c, r.y), hfma2(u.z, c, r.z), hfma2(u.w, c, r.w));
      }
    }
  } else {
    reg_dec<RP>();
    if (warp == 15) {
      const int p = cta_pair(), rank = blockIdx.x & 1;
      asm volatile("barrier.cluster.wait.aligned;" ::: "memory");
      if (blockIdx.x >= 128) bar_sync(0, 512);
      else {
#pragma unroll 1
        for (int ks = 1;; ks += 2) {
          mbar_wait(sb + B_EMPTY + 8 * (ks & 7), ((ks >> 3) & 1) ^ 1);
          spin_until(t0, PT1 + (ks - 1) * PTD);
          if (elect_one()) { mbar_expect_tx(sb + B_FULL + 8 * (ks & 7), WST); p1_load_w(ks, p, rank); PT(100 + ks); }
          if (ks == HT && elect_one()) mbar_arrive(sb + B_LAST);
          if (ks == 19) break;
          const int kn = ks + 1;
          mbar_wait(sb + B_EMPTY + 8 * (kn & 7), ((kn >> 3) & 1) ^ 1);
          spin_until(t0, PT1 + ks * PTD - PTE);
          if (elect_one()) { mbar_expect_tx(sb + B_FULL + 8 * (kn & 7), 16384 + WST); p1_load_x(kn, p, rank); p1_load_w(kn, p, rank); PT(100 + kn); }
        }
        mbar_wait(sb + B_S19, 0);
      }
    } else init_rest();
    ctx = __shfl_sync(~0u, make_ctx(), 0);
    CTXU();
    if (warp == 12) {
        unsigned epoch = 0;
      if (lane == 0) {
        if ((sb & 0xFFFFFF) != SB) __trap();
        epoch = *(volatile unsigned*)(g_launch + blockIdx.x) + 1;
        *(volatile unsigned*)(g_launch + blockIdx.x) = epoch;
        sts32(sb + O_EPOCH, epoch);
        mbar_arrive(sb + B_EP);
#pragma unroll 1
        for (int i = 3; i < 8; i++) asm volatile("prefetch.tensormap [%0];" ::"l"(&M.x_par + i) : "memory");
      }
      __syncwarp();
      if (main_cta) {
        uint4 h0 = make_uint4(0, 0, 0, 0);
        if (lane < 5) {
          h0 = __ldg((const uint4*)(ssm_k + (size_t)(128 * lane + vb) * 2048));
          h0.x = prmt(pack_bf16(bf_lo(h0.x) + bf_lo(__ldg(ssm_D + 128 * lane + vb)), 0.f), h0.x, 0x7610);
        }
        epoch = __shfl_sync(~0u, epoch, 0);
        mbar_wait(sb + B_LAST, 0);
        mbar_wait(sb + B_S13, 1);
#pragma unroll 1
        for (int c = 0; c < 5; c++) {
          if (c == 0 || c == 3) mbar_wait(sb + B_KVD + (c ? 16 : 8), 0);
          sts128(sb + o_u(c) + lane * 16, 0, 0, 0, 0);
          if (lane < 3) sts128(sb + (lane < 2 ? o_h(c) + lane * 4160 + 4096 : o_u(c) + 512), 0, 0, 0, 0);
          if (lane == c) sts128(sb + o_u(c) + UZ, h0.x, h0.y, h0.z, h0.w);
          fence_async_smem();
          __syncwarp();
          if (elect_one()) {
            mbar_expect_tx(sb + B_U + 8 * c, 3 * 4096 - 16);
            bulk_load(sb + o_u(c) + UZ + 16, ssm_k + (size_t)(128 * c + vb) * 2048 + 8, 4080, sb + B_U + 8 * c);
          }
          flag_wait(CNT_KV(2 * c + (vb >> 6)), 64 * epoch);
          __syncwarp();
          if (elect_one()) {
            bulk_load(sb + o_h(c), g_kvT + (size_t)(128 * c + vb) * 2048, 4096, sb + B_U + 8 * c);
            bulk_load(sb + o_h(c) + 4160, g_kvT + (size_t)(640 + 128 * c + vb) * 2048, 4096, sb + B_U + 8 * c);
            PT(10 + c);
          }
        }
      }
    } else if (warp != 15) {
        const int r = warp - 13;
      if (main_cta) {
        if (rank) {
#pragma unroll
          for (int f = 0; f < 5; f++)
            asm volatile("st.relaxed.gpu.global.v2.b64 [%0], {%1, %1};" ::"l"(g_halo + (size_t)vb * 320 + r * 160 + lane + 32 * f), "l"(0ull) : "memory");
          if (lane == 0) mbar_expect_tx(sb + B_HX0, 1280);
        }
        const int t = lane & 3, grow = hg * 16 + (lane & 15);
        const uint32_t ga = sb + grow * 128 + (((4 * r + (lane >> 4)) ^ (lane & 7)) << 4);
        const uint32_t gp = sb + O_GW + 64 * r + 4 * t;
        float s0 = 0.f, s1 = 0.f;
        {
          const int o = (lane >> 3) * 128 + 64 * r + (lane & 7) * 8;
          uint2 wv[3];
#pragma unroll
          for (int i = 0; i < 3; i++) if (i < 2 || lane < 16) wv[i] = __ldg((const uint2*)((const char*)gate_w + o + i * 512));
#pragma unroll
          for (int i = 0; i < 3; i++) if (i < 2 || lane < 16) asm volatile("st.shared.v2.b32 [%0], {%1,%2};" ::"r"(sb + O_GW + o + i * 512), "r"(wv[i].x), "r"(wv[i].y) : "memory");
          __syncwarp();
        }
#pragma unroll 1
        for (int ks = 0; ks < 20; ks += 2) {
          uint32_t x[8], gw[4];
#pragma unroll
          for (int i = 0; i < 4; i++) gw[i] = lds32(gp + ks * 64 + i * 16);
          mbar_wait_wd(sb + B_FULL + 8 * (ks & 7), (ks >> 3) & 1, t0);
          if (r == 0 && lane == 0) PT(120 + ks);
          ldsm4(x[0], x[1], x[2], x[3], ga + o_px(ks)); ldsm4(x[4], x[5], x[6], x[7], (ga ^ 32) + o_px(ks));
#pragma unroll
          for (int i = 0; i < 8; i++) x[i] = hmul2(x[i], gw[i >> 1]);
          if (lane < 2) mbar_arrive(sb + B_EMPTY + 8 * (ks & 7) + 8 * lane + (x[0] & x[7] & threadIdx.y));
#pragma unroll
          for (int i = 0; i < 8; i += 4) {
            s0 += (bf_lo(x[i]) + bf_hi(x[i])) + (bf_lo(x[i + 2]) + bf_hi(x[i + 2]));
            s1 += (bf_lo(x[i + 1]) + bf_hi(x[i + 1])) + (bf_lo(x[i + 3]) + bf_hi(x[i + 3]));
          }
        }
        s0 += __shfl_xor_sync(~0u, s0, 1); s1 += __shfl_xor_sync(~0u, s1, 1);
        s0 += __shfl_xor_sync(~0u, s0, 2); s1 += __shfl_xor_sync(~0u, s1, 2);
        if (t < 2) sts32(sb + O_GP + r * 64 + (8 * t + (lane >> 2)) * 4, __float_as_uint(t ? s1 : s0));
        if (r == 0) bar_arrive(NB_G, 64);
        if (!rank) {
          const uint32_t ha = sb + O_HIN + lane * 16 + r * 1024, hb = sb + O_HIN + lane * 16 + 2048 + r * 8;
          uint32_t d[10];
          if (mt > 0) {
            const uint4* hp = g_halo + (size_t)(vb - 1) * 320 + r * 160 + lane;
            mbar_wait_wd(sb + B_HX + 56, 0, t0);
            const unsigned epoch = lds32(sb + O_EPOCH);
            for (;;) {
              uint64_t u[10];
#pragma unroll
              for (int f = 0; f < 5; f++) asm volatile("ld.relaxed.gpu.global.v2.b64 {%0, %1}, [%2];" : "=l"(u[2 * f]), "=l"(u[2 * f + 1]) : "l"(hp + 32 * f) : "memory");
              uint32_t bad = 0;
#pragma unroll
              for (int f = 0; f < 10; f++) { d[f] = (uint32_t)u[f]; bad |= (uint32_t)(u[f] >> 32) ^ epoch; }
              if (__all_sync(~0u, bad == 0)) break;
              if (clk() - t0 > 0x70000000u) __trap();
            }
          } else {
#pragma unroll
            for (int f = 0; f < 10; f++) d[f] = 0u;
          }
          sts128(ha, d[0], d[1], d[2], d[3]); sts128(ha + 512, d[4], d[5], d[6], d[7]);
          sts32(hb, d[8]); sts32(hb + 4, d[9]);
          __syncwarp();
          if (lane == 0) { mbar_arrive(sb + B_HX0); PT(15 + r); }
        }
        if (r == 1) {
          bar_sync(NB_G, 64);
          if (lane < 16) {
            const uint32_t pa = sb + O_GP + lane * 4;
            const float z = __uint_as_float(lds32(pa)) + __uint_as_float(lds32(pa + 64));
            g_gate[2 * (mt * 128 + hg * 16 + lane) + par] = (uint16_t)pack_bf16(__fdividef(1.f, 1.f + __expf(-bf_lo(pack_bf16(z, 0.f)))), 0.f);
          }
          __syncwarp();
          if (lane == 0) flag_add(CNT_O(rt), 1);
        }
      }
      if (elect_one()) {
        mbar_wait_wd(sb + B_EP, 0, t0);
        const unsigned epoch = lds32(sb + O_EPOCH);
        if (main_cta) mbar_wait_wd(sb + B_P3E + 32, 0, t0);
        unsigned v;
        do {
          asm volatile("ld.relaxed.gpu.global.u32 %0, [%1];" : "=r"(v) : "l"(CNT_Y(2 * cb + r)) : "memory");
          if (clk() - t0 > 0x70000000u) __trap();
        } while ((int)(v - 128 * epoch) < 0);
        mbar_expect_tx(sb + B_Y + 8 * r, 10240);
        tma3(sb + O_Y + r * 10240, &M.y_ld, 0, cb * 64 + 32 * r, tb * 5, sb + B_Y + 8 * r);
        PT(17 + r);
        mbar_wait_wd(sb + B_DONE, 0, t0);
      }
    } else {
      const unsigned epoch = get_epoch();
      if (main_cta) bar_sync(NB_ATT, 288);
      if (elect_one()) {
        if (main_cta) {
          tma3_store(&M.o_st, hg * 80, par, mt * 128, sb + O_OST);
          bulk_commit(); bulk_wait_all();
          flag_add(CNT_O(rt), 1);
        }
        PT(3);
      }
      __syncwarp();
      if (lane < 4) flag_wait(CNT_O(8 * (lane & 1) + min(7, (80 * tb + 79 * (lane >> 1)) >> 7)), 16 * epoch);
      __syncwarp();
      if (elect_one()) {
        PT(4);
        mbar_arrive_remote(sb + B_P3R, rank ^ 1);
        mbar_expect_tx(sb + B_G, 320);
        bulk_load(sb + O_GT, g_gate + tb * 160, 320, sb + B_G);
      }
      mbar_wait(sb + B_P3R, 0);
#pragma unroll 1
      for (int ks = 0; ks < 10; ks++) {
        const int q = ks < 6 ? ks : ks - 6;
        if (ks > 5 || (ks == 5 && main_cta)) mbar_wait(sb + B_P3E + 8 * (ks == 5 ? 4 : q), 0);
        if (elect_one()) {
          PTP(ks >= 5, ks);
          mbar_expect_tx(sb + B_P3F + 8 * q, P3S);
          tma2(sb + q * P3S, &M.wo, cb * 64, ks * 64, sb + B_P3F + 8 * q);
          tma2_mc(sb + q * P3S + 8192 + rank * 10240, &M.o_ld, ks * 64, tb * 160 + rank * 80, sb + B_P3F + 8 * q);
        }
      }
    }
  }
}

typedef CUresult (*PFN_enc)(CUtensorMap*, CUtensorMapDataType, cuuint32_t, void*, const cuuint64_t*, const cuuint64_t*, const cuuint32_t*,
                            const cuuint32_t*, CUtensorMapInterleave, CUtensorMapSwizzle, CUtensorMapL2promotion, CUtensorMapFloatOOBfill);
static void enc(PFN_enc f, CUtensorMap* m, const void* base, int rank, const cuuint64_t* dims, const cuuint64_t* strides, const cuuint32_t* box,
                CUtensorMapSwizzle sw) {
  const cuuint32_t es[5] = {1, 1, 1, 1, 1};
  f(m, CU_TENSOR_MAP_DATA_TYPE_BFLOAT16, rank, (void*)base, dims, strides, box, es, CU_TENSOR_MAP_INTERLEAVE_NONE, sw,
    CU_TENSOR_MAP_L2_PROMOTION_NONE, CU_TENSOR_MAP_FLOAT_OOB_FILL_NONE);
}

extern "C" void kernel_launch(void* const* d_in, const int* in_sizes, int n_in, void* d_out, int out_size) {
  (void)in_sizes; (void)n_in; (void)out_size;
  static PFN_enc f = nullptr;
  static void *kvT, *y2T, *o;
  if (!f) {
    void* p = nullptr;
    cudaDriverEntryPointQueryResult q;
    cudaGetDriverEntryPoint("cuTensorMapEncodeTiled", &p, cudaEnableDefault, &q);
    f = (PFN_enc)p;
    cudaGetSymbolAddress(&kvT, g_kvT); cudaGetSymbolAddress(&y2T, g_y2T); cudaGetSymbolAddress(&o, g_o);
    cudaFuncSetAttribute(fused_kernel, cudaFuncAttributeMaxDynamicSharedMemorySize, SMEM_BYTES);
  }
  Maps M;
  const CUtensorMapSwizzle S0 = CU_TENSOR_MAP_SWIZZLE_NONE, S32 = CU_TENSOR_MAP_SWIZZLE_32B, S64 = CU_TENSOR_MAP_SWIZZLE_64B, S128 = CU_TENSOR_MAP_SWIZZLE_128B;
  const cuuint64_t dpar[3] = {640, 2, 1024}, spar[2] = {1280, 2560};
  const cuuint64_t dw[3] = {640, 640, 3}, sw[2] = {3840, 1280};
  const cuuint64_t dnat[2] = {640, 2048}, snat[1] = {1280};
  const cuuint64_t dT[3] = {32, 640, 64}, dT2[3] = {32, 1280, 64}, sT[2] = {4096, 64};
  const cuuint64_t dwo[2] = {640, 640};
  { const cuuint32_t bx[3] = {64, 1, 128}; enc(f, &M.x_par, d_in[0], 3, dpar, spar, bx, S128); }
  { const cuuint32_t bx[3] = {64, 16, 3}; enc(f, &M.w_main, d_in[7], 3, dw, sw, bx, S128); }
  { const cuuint32_t bx[3] = {16, 16, 3}; enc(f, &M.w_tail, d_in[7], 3, dw, sw, bx, S32); }
  { const cuuint32_t bx[3] = {80, 1, 128}; enc(f, &M.o_st, o, 3, dpar, spar, bx, S0); }
  { const cuuint32_t bx[3] = {32, 64, 1}; enc(f, &M.kv_st, kvT, 3, dT2, sT, bx, S64); }
  { const cuuint32_t bx[3] = {32, 32, 5}; enc(f, &M.y_ld, y2T, 3, dT, sT, bx, S64); }
  { const cuuint32_t bx[2] = {64, 64}; enc(f, &M.wo, d_in[8], 2, dwo, snat, bx, S128); }
  { const cuuint32_t bx[2] = {64, 80}; enc(f, &M.o_ld, o, 2, dnat, snat, bx, S128); }
  fused_kernel<<<130, 512, SMEM_BYTES, cudaStreamPerThread>>>((const uint16_t*)d_in[0], (const uint16_t*)d_in[7], (const uint16_t*)d_in[9], M, (const uint16_t*)d_in[3], (const uint16_t*)d_in[4], (const uint16_t*)d_in[5],
                                                              (const uint16_t*)d_in[1], (const uint16_t*)d_in[2], (uint16_t*)d_out);
}
```

```cpp
#include <cuda_runtime.h>
#include <cuda_bf16.h>
#include <cuda.h>
#include <stdint.h>

#define DEVI __device__ __forceinline__
#define PT1 550
#define PTD 460
#define PTE 200
#define PF2 0
#define NPF 1
#define PFD 0
#define SSMASK 0
static_assert((SSMASK & 0xAAA) == 0, "an x tile is refilled as soon as its even stage is released");
#define HT 19
#define KPH 37
#define CV 0
#define TOKP 6
#define NPRE 0
#define P3GO 0
#define QC 0
#define KT0 1500
#define KTD 1300
#define RC 192
#define RH 96
#define RP 32
#define HOLD 750
#define P1U 7
#define LEAD 3

DEVI uint32_t smem_u32(const void* p) { return (uint32_t)__cvta_generic_to_shared(p); }
DEVI void wg_fence() { asm volatile("wgmma.fence.sync.aligned;" ::: "memory"); }
DEVI void wg_commit() { asm volatile("wgmma.commit_group.sync.aligned;" ::: "memory"); }
template <int N> DEVI void wg_wait() { asm volatile("wgmma.wait_group.sync.aligned %0;" ::"n"(N) : "memory"); }
template <int S> DEVI void fence_regs(float (&d)[S]) {
#pragma unroll
  for (int i = 0; i < S; i++) asm volatile("" : "+f"(d[i])::"memory");
}
DEVI uint64_t mkdesc(uint32_t addr, uint32_t lbo, uint32_t sbo, int swz) {
  return (uint64_t)((addr & 0x3FFFF) >> 4) | ((uint64_t)(lbo >> 4) << 16) | ((uint64_t)(sbo >> 4) << 32) | ((uint64_t)swz << 62);
}
DEVI void mbar_init(uint32_t bar, uint32_t cnt) { asm volatile("mbarrier.init.shared::cta.b64 [%0], %1;" ::"r"(bar), "r"(cnt) : "memory"); }
DEVI void mbar_expect_tx(uint32_t bar, uint32_t bytes) { asm volatile("mbarrier.arrive.expect_tx.shared::cta.b64 _, [%0], %1;" ::"r"(bar), "r"(bytes) : "memory"); }
DEVI void mbar_arrive(uint32_t bar) { asm volatile("mbarrier.arrive.shared::cta.b64 _, [%0];" ::"r"(bar) : "memory"); }
DEVI void mbar_wait(uint32_t bar, uint32_t parity) {
  asm volatile("{\n.reg .pred p;\nLAB_WAIT:\nmbarrier.try_wait.parity.shared::cta.b64 p, [%0], %1;\n@!p bra LAB_WAIT;\n}" ::"r"(bar), "r"(parity) : "memory");
}
DEVI void mbar_wait_wd(uint32_t bar, uint32_t parity, uint32_t t0) {
  asm volatile("{\n.reg .pred p;\n.reg .u32 c;\nLAB_WAIT:\nmbarrier.try_wait.parity.shared::cta.b64 p, [%0], %1;\n@p bra DONE;\nmov.u32 c, %%clock;\nsub.u32 c, c, %2;\nsetp.lt.u32 p, c, 0x70000000;\n@p bra LAB_WAIT;\ntrap;\nDONE:\n}" ::"r"(bar), "r"(parity), "r"(t0) : "memory");
}
DEVI void flag_wait(const unsigned* p, unsigned target) {
  asm volatile("{\n.reg .pred p;\n.reg .s32 v;\nLAB_WAIT:\nld.relaxed.gpu.global.u32 v, [%0];\nsub.s32 v, v, %1;\nsetp.lt.s32 p, v, 0;\n@p bra LAB_WAIT;\n}" ::"l"(p), "r"(target) : "memory");
}
DEVI void flag_add(unsigned* p, unsigned v) { asm volatile("red.relaxed.gpu.global.add.u32 [%0], %1;" ::"l"(p), "r"(v) : "memory"); }
DEVI void fence_async_smem() { asm volatile("fence.proxy.async.shared::cta;" ::: "memory"); }
DEVI bool elect_one() { uint32_t p; asm volatile("{\n.reg .pred P;\nelect.sync _|P, 0xffffffff;\nselp.u32 %0, 1, 0, P;\n}" : "=r"(p)); return p; }
DEVI void bar_sync(int id, int n) { asm volatile("bar.sync %0, %1;" ::"r"(id), "r"(n) : "memory"); }
DEVI void bar_arrive(int id, int n) { asm volatile("bar.arrive %0, %1;" ::"r"(id), "r"(n) : "memory"); }
DEVI void tma2(uint32_t dst, const CUtensorMap* m, int c0, int c1, uint32_t bar) {
  asm volatile("cp.async.bulk.tensor.2d.shared::cluster.global.mbarrier::complete_tx::bytes [%0], [%1, {%3, %4}], [%2];" ::"r"(dst), "l"(m), "r"(bar), "r"(c0), "r"(c1) : "memory");
}
DEVI void tma3(uint32_t dst, const CUtensorMap* m, int c0, int c1, int c2, uint32_t bar) {
  asm volatile("cp.async.bulk.tensor.3d.shared::cluster.global.mbarrier::complete_tx::bytes [%0], [%1, {%3, %4, %5}], [%2];" ::"r"(dst), "l"(m), "r"(bar), "r"(c0), "r"(c1), "r"(c2) : "memory");
}
DEVI void tma3_mc(uint32_t dst, const CUtensorMap* m, int c0, int c1, int c2, uint32_t bar) {
  asm volatile("cp.async.bulk.tensor.3d.shared::cluster.global.mbarrier::complete_tx::bytes.multicast::cluster [%0], [%1, {%3, %4, %5}], [%2], %6;" ::"r"(dst), "l"(m), "r"(bar), "r"(c0), "r"(c1), "r"(c2), "h"((uint16_t)3) : "memory");
}
DEVI void tma2_mc(uint32_t dst, const CUtensorMap* m, int c0, int c1, uint32_t bar) {
  asm volatile("cp.async.bulk.tensor.2d.shared::cluster.global.mbarrier::complete_tx::bytes.multicast::cluster [%0], [%1, {%3, %4}], [%2], %5;" ::"r"(dst), "l"(m), "r"(bar), "r"(c0), "r"(c1), "h"((uint16_t)3) : "memory");
}
DEVI void mbar_arrive_remote(uint32_t bar, uint32_t cta) {
  asm volatile("{\n.reg .b32 ra;\nmapa.shared::cluster.u32 ra, %0, %1;\nmbarrier.arrive.shared::cluster.b64 _, [ra];\n}" ::"r"(bar), "r"(cta) : "memory");
}
DEVI void tma3_store(const CUtensorMap* m, int c0, int c1, int c2, uint32_t src) {
  asm volatile("cp.async.bulk.tensor.3d.global.shared::cta.bulk_group [%0, {%2, %3, %4}], [%1];" ::"l"(m), "r"(src), "r"(c0), "r"(c1), "r"(c2) : "memory");
}
DEVI void bulk_load(uint32_t dst, const void* src, uint32_t bytes, uint32_t bar) {
  asm volatile("cp.async.bulk.shared::cluster.global.mbarrier::complete_tx::bytes [%0], [%1], %2, [%3];" ::"r"(dst), "l"(src), "r"(bytes), "r"(bar) : "memory");
}
DEVI void bulk_store(void* dst, uint32_t src, uint32_t bytes) {
  asm volatile("cp.async.bulk.global.shared::cta.bulk_group [%0], [%1], %2;" ::"l"(dst), "r"(src), "r"(bytes) : "memory");
}
DEVI void pf_l2(const void* p) { asm volatile("prefetch.global.L2 [%0];" ::"l"(p)); }
template <int OFF> DEVI uint32_t ldg_v(const void* p) { uint32_t v; asm volatile("ld.volatile.global.b32 %0, [%1 + %2];" : "=r"(v) : "l"(p), "n"(OFF)); return v; }
DEVI void bulk_commit() { asm volatile("cp.async.bulk.commit_group;" ::: "memory"); }
DEVI void bulk_wait_all() { asm volatile("cp.async.bulk.wait_group 0;" ::: "memory"); }
DEVI void bulk_wait_read() { asm volatile("cp.async.bulk.wait_group.read 0;" ::: "memory"); }
template <int R> DEVI void reg_inc() { asm volatile("setmaxnreg.inc.sync.aligned.u32 %0;" ::"n"(R)); }
template <int R> DEVI void reg_dec() { asm volatile("setmaxnreg.dec.sync.aligned.u32 %0;" ::"n"(R)); }
DEVI uint32_t prmt(uint32_t a, uint32_t b, uint32_t s) { uint32_t r; asm("prmt.b32 %0,%1,%2,%3;" : "=r"(r) : "r"(a), "r"(b), "r"(s)); return r; }
DEVI uint32_t lds32(uint32_t a) { uint32_t r; asm volatile("ld.shared.b32 %0,[%1];" : "=r"(r) : "r"(a)); return r; }
DEVI void sts32(uint32_t a, uint32_t x) { asm volatile("st.shared.b32 [%0],%1;" ::"r"(a), "r"(x) : "memory"); }
DEVI void sts128(uint32_t a, uint32_t x, uint32_t y, uint32_t z, uint32_t w) { asm volatile("st.shared.v4.b32 [%0],{%1,%2,%3,%4};" ::"r"(a), "r"(x), "r"(y), "r"(z), "r"(w) : "memory"); }
DEVI void sts128v(uint32_t a, uint32_t x, uint32_t y, uint32_t z, uint32_t w) { asm volatile("st.volatile.shared.v4.b32 [%0],{%1,%2,%3,%4};" ::"r"(a), "r"(x), "r"(y), "r"(z), "r"(w) : "memory"); }
DEVI void lds128(uint32_t a, uint32_t& x, uint32_t& y, uint32_t& z, uint32_t& w) { asm volatile("ld.shared.v4.b32 {%0,%1,%2,%3},[%4];" : "=r"(x), "=r"(y), "=r"(z), "=r"(w) : "r"(a) : "memory"); }
DEVI void ldsm4(uint32_t& r0, uint32_t& r1, uint32_t& r2, uint32_t& r3, uint32_t addr) {
  asm volatile("ldmatrix.sync.aligned.m8n8.x4.shared.b16 {%0,%1,%2,%3}, [%4];" : "=r"(r0), "=r"(r1), "=r"(r2), "=r"(r3) : "r"(addr) : "memory");
}
DEVI void ldsm4t(uint32_t& r0, uint32_t& r1, uint32_t& r2, uint32_t& r3, uint32_t addr) {
  asm volatile("ldmatrix.sync.aligned.m8n8.x4.trans.shared.b16 {%0,%1,%2,%3}, [%4];" : "=r"(r0), "=r"(r1), "=r"(r2), "=r"(r3) : "r"(addr) : "memory");
}
DEVI void stsm4(uint32_t addr, uint32_t r0, uint32_t r1, uint32_t r2, uint32_t r3) {
  asm volatile("stmatrix.sync.aligned.m8n8.x4.shared.b16 [%0], {%1,%2,%3,%4};" ::"r"(addr), "r"(r0), "r"(r1), "r"(r2), "r"(r3) : "memory");
}
DEVI void stsm4t(uint32_t addr, uint32_t r0, uint32_t r1, uint32_t r2, uint32_t r3) {
  asm volatile("stmatrix.sync.aligned.m8n8.x4.trans.shared.b16 [%0], {%1,%2,%3,%4};" ::"r"(addr), "r"(r0), "r"(r1), "r"(r2), "r"(r3) : "memory");
}
DEVI uint32_t movm(uint32_t a) { uint32_t r; asm volatile("movmatrix.sync.aligned.m8n8.trans.b16 %0, %1;" : "=r"(r) : "r"(a)); return r; }
DEVI uint32_t pack_bf16(float lo, float hi) { uint32_t r; asm("cvt.rn.bf16x2.f32 %0, %1, %2;" : "=r"(r) : "f"(hi), "f"(lo)); return r; }
DEVI uint32_t hmul2(uint32_t a, uint32_t b) { uint32_t r; asm("mul.rn.bf16x2 %0,%1,%2;" : "=r"(r) : "r"(a), "r"(b)); return r; }
DEVI uint32_t hadd2(uint32_t a, uint32_t b) { uint32_t r; asm("add.rn.bf16x2 %0,%1,%2;" : "=r"(r) : "r"(a), "r"(b)); return r; }
DEVI float bf_lo(uint32_t a) { return __uint_as_float(prmt(a, 0, 0x1044)); }
DEVI float bf_hi(uint32_t a) { return __uint_as_float(a & 0xFFFF0000u); }
DEVI void mma16(float (&c)[4], uint32_t a0, uint32_t a1, uint32_t a2, uint32_t a3, uint32_t b0, uint32_t b1) {
  asm("mma.sync.aligned.m16n8k16.row.col.f32.bf16.bf16.f32 {%0,%1,%2,%3},{%4,%5,%6,%7},{%8,%9},{%0,%1,%2,%3};"
      : "+f"(c[0]), "+f"(c[1]), "+f"(c[2]), "+f"(c[3]) : "r"(a0), "r"(a1), "r"(a2), "r"(a3), "r"(b0), "r"(b1));
}
DEVI void mma8(float (&c)[4], uint32_t a0, uint32_t a1, uint32_t b0) {
  asm("mma.sync.aligned.m16n8k8.row.col.f32.bf16.bf16.f32 {%0,%1,%2,%3},{%4,%5},{%6},{%0,%1,%2,%3};"
      : "+f"(c[0]), "+f"(c[1]), "+f"(c[2]), "+f"(c[3]) : "r"(a0), "r"(a1), "r"(b0));
}
DEVI float ex2(float x) { float r; asm("ex2.approx.ftz.f32 %0, %1;" : "=f"(r) : "f"(x)); return r; }

DEVI uint32_t clk() { uint32_t c; asm volatile("mov.u32 %0, %%clock;" : "=r"(c)); return c; }
DEVI void wait_until(uint32_t t0, int dt) { while ((int)(clk() - t0) < dt) __nanosleep(40); }
DEVI void spin_until(uint32_t t0, int dt) { while ((int)(clk() - t0) < dt) {} }
DEVI uint32_t hfma2(uint32_t a, uint32_t b, uint32_t c) { uint32_t r; asm("fma.rn.bf16x2 %0,%1,%2,%3;" : "=r"(r) : "r"(a), "r"(b), "r"(c)); return r; }
DEVI void bar_sync_p(int on, int id, int n) { asm volatile("{\n.reg .pred p;\nsetp.ne.b32 p, %0, 0;\n@p bar.sync %1, %2;\n}" ::"r"(on), "r"(id), "r"(n) : "memory"); }
DEVI void bar_arrive_p(int on, int id, int n) { asm volatile("{\n.reg .pred p;\nsetp.ne.b32 p, %0, 0;\n@p bar.arrive %1, %2;\n}" ::"r"(on), "r"(id), "r"(n) : "memory"); }
DEVI void mbar_arrive_p(int on, uint32_t bar) { asm volatile("{\n.reg .pred p;\nsetp.ne.b32 p, %1, 0;\n@p mbarrier.arrive.shared::cta.b64 _, [%0];\n}" ::"r"(bar), "r"(on) : "memory"); }
DEVI void mbar_arrive2_p(int on, uint32_t bar, uint32_t rbar) {
  asm volatile("{\n.reg .pred p;\nsetp.ne.b32 p, %2, 0;\n@p mbarrier.arrive.shared::cta.b64 _, [%0];\n@p mbarrier.arrive.shared::cluster.b64 _, [%1];\n}" ::"r"(bar), "r"(rbar), "r"(on) : "memory");
}
DEVI uint32_t mapa(uint32_t a, uint32_t cta) { uint32_t r; asm("mapa.shared::cluster.u32 %0, %1, %2;" : "=r"(r) : "r"(a), "r"(cta)); return r; }
DEVI void st_async128(uint32_t a, uint32_t x, uint32_t y, uint32_t z, uint32_t w, uint32_t bar) {
  asm volatile("st.async.weak.shared::cluster.mbarrier::complete_tx::bytes.v4.b32 [%0], {%1,%2,%3,%4}, [%5];" ::"r"(a), "r"(x), "r"(y), "r"(z), "r"(w), "r"(bar) : "memory");
}

template<int OFF, int TB, int S> __device__ __forceinline__ void wgmma_rs_n192(float (&d)[S], uint32_t a0, uint32_t a1, uint32_t a2, uint32_t a3, uint64_t db, int sd) {
  asm volatile("{\n.reg .pred p;\nsetp.ne.b32 p, %101, 0;\n"
    "wgmma.mma_async.sync.aligned.m64n192k16.f32.bf16.bf16 {%0, %1, %2, %3, %4, %5, %6, %7, %8, %9, %10, %11, %12, %13, %14, %15, %16, %17, %18, %19, %20, %21, %22, %23, %24, %25, %26, %27, %28, %29, %30, %31, %32, %33, %34, %35, %36, %37, %38, %39, %40, %41, %42, %43, %44, %45, %46, %47, %48, %49, %50, %51, %52, %53, %54, %55, %56, %57, %58, %59, %60, %61, %62, %63, %64, %65, %66, %67, %68, %69, %70, %71, %72, %73, %74, %75, %76, %77, %78, %79, %80, %81, %82, %83, %84, %85, %86, %87, %88, %89, %90, %91, %92, %93, %94, %95}, {%96, %97, %98, %99}, %100, p, 1, 1, %102;\n}\n"
    : "+f"(d[OFF+0]), "+f"(d[OFF+1]), "+f"(d[OFF+2]), "+f"(d[OFF+3]), "+f"(d[OFF+4]), "+f"(d[OFF+5]), "+f"(d[OFF+6]), "+f"(d[OFF+7]), "+f"(d[OFF+8]), "+f"(d[OFF+9]), "+f"(d[OFF+10]), "+f"(d[OFF+11]), "+f"(d[OFF+12]), "+f"(d[OFF+13]), "+f"(d[OFF+14]), "+f"(d[OFF+15]), "+f"(d[OFF+16]), "+f"(d[OFF+17]), "+f"(d[OFF+18]), "+f"(d[OFF+19]), "+f"(d[OFF+20]), "+f"(d[OFF+21]), "+f"(d[OFF+22]), "+f"(d[OFF+23]), "+f"(d[OFF+24]), "+f"(d[OFF+25]), "+f"(d[OFF+26]), "+f"(d[OFF+27]), "+f"(d[OFF+28]), "+f"(d[OFF+29]), "+f"(d[OFF+30]), "+f"(d[OFF+31]), "+f"(d[OFF+32]), "+f"(d[OFF+33]), "+f"(d[OFF+34]), "+f"(d[OFF+35]), "+f"(d[OFF+36]), "+f"(d[OFF+37]), "+f"(d[OFF+38]), "+f"(d[OFF+39]), "+f"(d[OFF+40]), "+f"(d[OFF+41]), "+f"(d[OFF+42]), "+f"(d[OFF+43]), "+f"(d[OFF+44]), "+f"(d[OFF+45]), "+f"(d[OFF+46]), "+f"(d[OFF+47]), "+f"(d[OFF+48]), "+f"(d[OFF+49]), "+f"(d[OFF+50]), "+f"(d[OFF+51]), "+f"(d[OFF+52]), "+f"(d[OFF+53]), "+f"(d[OFF+54]), "+f"(d[OFF+55]), "+f"(d[OFF+56]), "+f"(d[OFF+57]), "+f"(d[OFF+58]), "+f"(d[OFF+59]), "+f"(d[OFF+60]), "+f"(d[OFF+61]), "+f"(d[OFF+62]), "+f"(d[OFF+63]), "+f"(d[OFF+64]), "+f"(d[OFF+65]), "+f"(d[OFF+66]), "+f"(d[OFF+67]), "+f"(d[OFF+68]), "+f"(d[OFF+69]), "+f"(d[OFF+70]), "+f"(d[OFF+71]), "+f"(d[OFF+72]), "+f"(d[OFF+73]), "+f"(d[OFF+74]), "+f"(d[OFF+75]), "+f"(d[OFF+76]), "+f"(d[OFF+77]), "+f"(d[OFF+78]), "+f"(d[OFF+79]), "+f"(d[OFF+80]), "+f"(d[OFF+81]), "+f"(d[OFF+82]), "+f"(d[OFF+83]), "+f"(d[OFF+84]), "+f"(d[OFF+85]), "+f"(d[OFF+86]), "+f"(d[OFF+87]), "+f"(d[OFF+88]), "+f"(d[OFF+89]), "+f"(d[OFF+90]), "+f"(d[OFF+91]), "+f"(d[OFF+92]), "+f"(d[OFF+93]), "+f"(d[OFF+94]), "+f"(d[OFF+95]) : "r"(a0), "r"(a1), "r"(a2), "r"(a3), "l"(db), "r"(sd), "n"(TB));
}
template<int OFF, int TB, int S> __device__ __forceinline__ void wgmma_rs_n48(float (&d)[S], uint32_t a0, uint32_t a1, uint32_t a2, uint32_t a3, uint64_t db, int sd) {
  asm volatile("{\n.reg .pred p;\nsetp.ne.b32 p, %29, 0;\n"
    "wgmma.mma_async.sync.aligned.m64n48k16.f32.bf16.bf16 {%0, %1, %2, %3, %4, %5, %6, %7, %8, %9, %10, %11, %12, %13, %14, %15, %16, %17, %18, %19, %20, %21, %22, %23}, {%24, %25, %26, %27}, %28, p, 1, 1, %30;\n}\n"
    : "+f"(d[OFF+0]), "+f"(d[OFF+1]), "+f"(d[OFF+2]), "+f"(d[OFF+3]), "+f"(d[OFF+4]), "+f"(d[OFF+5]), "+f"(d[OFF+6]), "+f"(d[OFF+7]), "+f"(d[OFF+8]), "+f"(d[OFF+9]), "+f"(d[OFF+10]), "+f"(d[OFF+11]), "+f"(d[OFF+12]), "+f"(d[OFF+13]), "+f"(d[OFF+14]), "+f"(d[OFF+15]), "+f"(d[OFF+16]), "+f"(d[OFF+17]), "+f"(d[OFF+18]), "+f"(d[OFF+19]), "+f"(d[OFF+20]), "+f"(d[OFF+21]), "+f"(d[OFF+22]), "+f"(d[OFF+23]) : "r"(a0), "r"(a1), "r"(a2), "r"(a3), "l"(db), "r"(sd), "n"(TB));
}
template<int OFF, int TB, int S> __device__ __forceinline__ void wgmma_rs_n16(float (&d)[S], uint32_t a0, uint32_t a1, uint32_t a2, uint32_t a3, uint64_t db, int sd) {
  asm volatile("{\n.reg .pred p;\nsetp.ne.b32 p, %13, 0;\n"
    "wgmma.mma_async.sync.aligned.m64n16k16.f32.bf16.bf16 {%0, %1, %2, %3, %4, %5, %6, %7}, {%8, %9, %10, %11}, %12, p, 1, 1, %14;\n}\n"
    : "+f"(d[OFF+0]), "+f"(d[OFF+1]), "+f"(d[OFF+2]), "+f"(d[OFF+3]), "+f"(d[OFF+4]), "+f"(d[OFF+5]), "+f"(d[OFF+6]), "+f"(d[OFF+7]) : "r"(a0), "r"(a1), "r"(a2), "r"(a3), "l"(db), "r"(sd), "n"(TB));
}
template<int OFF, int TA, int TB, int S> __device__ __forceinline__ void wgmma_ss_n160(float (&d)[S], uint64_t da, uint64_t db, int sd) {
  asm volatile("{\n.reg .pred p;\nsetp.ne.b32 p, %82, 0;\n"
    "wgmma.mma_async.sync.aligned.m64n160k16.f32.bf16.bf16 {%0, %1, %2, %3, %4, %5, %6, %7, %8, %9, %10, %11, %12, %13, %14, %15, %16, %17, %18, %19, %20, %21, %22, %23, %24, %25, %26, %27, %28, %29, %30, %31, %32, %33, %34, %35, %36, %37, %38, %39, %40, %41, %42, %43, %44, %45, %46, %47, %48, %49, %50, %51, %52, %53, %54, %55, %56, %57, %58, %59, %60, %61, %62, %63, %64, %65, %66, %67, %68, %69, %70, %71, %72, %73, %74, %75, %76, %77, %78, %79}, %80, %81, p, 1, 1, %83, %84;\n}\n"
    : "+f"(d[OFF+0]), "+f"(d[OFF+1]), "+f"(d[OFF+2]), "+f"(d[OFF+3]), "+f"(d[OFF+4]), "+f"(d[OFF+5]), "+f"(d[OFF+6]), "+f"(d[OFF+7]), "+f"(d[OFF+8]), "+f"(d[OFF+9]), "+f"(d[OFF+10]), "+f"(d[OFF+11]), "+f"(d[OFF+12]), "+f"(d[OFF+13]), "+f"(d[OFF+14]), "+f"(d[OFF+15]), "+f"(d[OFF+16]), "+f"(d[OFF+17]), "+f"(d[OFF+18]), "+f"(d[OFF+19]), "+f"(d[OFF+20]), "+f"(d[OFF+21]), "+f"(d[OFF+22]), "+f"(d[OFF+23]), "+f"(d[OFF+24]), "+f"(d[OFF+25]), "+f"(d[OFF+26]), "+f"(d[OFF+27]), "+f"(d[OFF+28]), "+f"(d[OFF+29]), "+f"(d[OFF+30]), "+f"(d[OFF+31]), "+f"(d[OFF+32]), "+f"(d[OFF+33]), "+f"(d[OFF+34]), "+f"(d[OFF+35]), "+f"(d[OFF+36]), "+f"(d[OFF+37]), "+f"(d[OFF+38]), "+f"(d[OFF+39]), "+f"(d[OFF+40]), "+f"(d[OFF+41]), "+f"(d[OFF+42]), "+f"(d[OFF+43]), "+f"(d[OFF+44]), "+f"(d[OFF+45]), "+f"(d[OFF+46]), "+f"(d[OFF+47]), "+f"(d[OFF+48]), "+f"(d[OFF+49]), "+f"(d[OFF+50]), "+f"(d[OFF+51]), "+f"(d[OFF+52]), "+f"(d[OFF+53]), "+f"(d[OFF+54]), "+f"(d[OFF+55]), "+f"(d[OFF+56]), "+f"(d[OFF+57]), "+f"(d[OFF+58]), "+f"(d[OFF+59]), "+f"(d[OFF+60]), "+f"(d[OFF+61]), "+f"(d[OFF+62]), "+f"(d[OFF+63]), "+f"(d[OFF+64]), "+f"(d[OFF+65]), "+f"(d[OFF+66]), "+f"(d[OFF+67]), "+f"(d[OFF+68]), "+f"(d[OFF+69]), "+f"(d[OFF+70]), "+f"(d[OFF+71]), "+f"(d[OFF+72]), "+f"(d[OFF+73]), "+f"(d[OFF+74]), "+f"(d[OFF+75]), "+f"(d[OFF+76]), "+f"(d[OFF+77]), "+f"(d[OFF+78]), "+f"(d[OFF+79]) : "l"(da), "l"(db), "r"(sd), "n"(TA), "n"(TB));
}
template<int OFF, int TA, int TB, int S> __device__ __forceinline__ void wgmma_ss_n192(float (&d)[S], uint64_t da, uint64_t db, int sd) {
  asm volatile("{\n.reg .pred p;\nsetp.ne.b32 p, %98, 0;\n"
    "wgmma.mma_async.sync.aligned.m64n192k16.f32.bf16.bf16 {%0, %1, %2, %3, %4, %5, %6, %7, %8, %9, %10, %11, %12, %13, %14, %15, %16, %17, %18, %19, %20, %21, %22, %23, %24, %25, %26, %27, %28, %29, %30, %31, %32, %33, %34, %35, %36, %37, %38, %39, %40, %41, %42, %43, %44, %45, %46, %47, %48, %49, %50, %51, %52, %53, %54, %55, %56, %57, %58, %59, %60, %61, %62, %63, %64, %65, %66, %67, %68, %69, %70, %71, %72, %73, %74, %75, %76, %77, %78, %79, %80, %81, %82, %83, %84, %85, %86, %87, %88, %89, %90, %91, %92, %93, %94, %95}, %96, %97, p, 1, 1, %99, %100;\n}\n"
    : "+f"(d[OFF+0]), "+f"(d[OFF+1]), "+f"(d[OFF+2]), "+f"(d[OFF+3]), "+f"(d[OFF+4]), "+f"(d[OFF+5]), "+f"(d[OFF+6]), "+f"(d[OFF+7]), "+f"(d[OFF+8]), "+f"(d[OFF+9]), "+f"(d[OFF+10]), "+f"(d[OFF+11]), "+f"(d[OFF+12]), "+f"(d[OFF+13]), "+f"(d[OFF+14]), "+f"(d[OFF+15]), "+f"(d[OFF+16]), "+f"(d[OFF+17]), "+f"(d[OFF+18]), "+f"(d[OFF+19]), "+f"(d[OFF+20]), "+f"(d[OFF+21]), "+f"(d[OFF+22]), "+f"(d[OFF+23]), "+f"(d[OFF+24]), "+f"(d[OFF+25]), "+f"(d[OFF+26]), "+f"(d[OFF+27]), "+f"(d[OFF+28]), "+f"(d[OFF+29]), "+f"(d[OFF+30]), "+f"(d[OFF+31]), "+f"(d[OFF+32]), "+f"(d[OFF+33]), "+f"(d[OFF+34]), "+f"(d[OFF+35]), "+f"(d[OFF+36]), "+f"(d[OFF+37]), "+f"(d[OFF+38]), "+f"(d[OFF+39]), "+f"(d[OFF+40]), "+f"(d[OFF+41]), "+f"(d[OFF+42]), "+f"(d[OFF+43]), "+f"(d[OFF+44]), "+f"(d[OFF+45]), "+f"(d[OFF+46]), "+f"(d[OFF+47]), "+f"(d[OFF+48]), "+f"(d[OFF+49]), "+f"(d[OFF+50]), "+f"(d[OFF+51]), "+f"(d[OFF+52]), "+f"(d[OFF+53]), "+f"(d[OFF+54]), "+f"(d[OFF+55]), "+f"(d[OFF+56]), "+f"(d[OFF+57]), "+f"(d[OFF+58]), "+f"(d[OFF+59]), "+f"(d[OFF+60]), "+f"(d[OFF+61]), "+f"(d[OFF+62]), "+f"(d[OFF+63]), "+f"(d[OFF+64]), "+f"(d[OFF+65]), "+f"(d[OFF+66]), "+f"(d[OFF+67]), "+f"(d[OFF+68]), "+f"(d[OFF+69]), "+f"(d[OFF+70]), "+f"(d[OFF+71]), "+f"(d[OFF+72]), "+f"(d[OFF+73]), "+f"(d[OFF+74]), "+f"(d[OFF+75]), "+f"(d[OFF+76]), "+f"(d[OFF+77]), "+f"(d[OFF+78]), "+f"(d[OFF+79]), "+f"(d[OFF+80]), "+f"(d[OFF+81]), "+f"(d[OFF+82]), "+f"(d[OFF+83]), "+f"(d[OFF+84]), "+f"(d[OFF+85]), "+f"(d[OFF+86]), "+f"(d[OFF+87]), "+f"(d[OFF+88]), "+f"(d[OFF+89]), "+f"(d[OFF+90]), "+f"(d[OFF+91]), "+f"(d[OFF+92]), "+f"(d[OFF+93]), "+f"(d[OFF+94]), "+f"(d[OFF+95]) : "l"(da), "l"(db), "r"(sd), "n"(TA), "n"(TB));
}
template<int OFF, int TA, int TB, int S> __device__ __forceinline__ void wgmma_ss_n48(float (&d)[S], uint64_t da, uint64_t db, int sd) {
  asm volatile("{\n.reg .pred p;\nsetp.ne.b32 p, %26, 0;\n"
    "wgmma.mma_async.sync.aligned.m64n48k16.f32.bf16.bf16 {%0, %1, %2, %3, %4, %5, %6, %7, %8, %9, %10, %11, %12, %13, %14, %15, %16, %17, %18, %19, %20, %21, %22, %23}, %24, %25, p, 1, 1, %27, %28;\n}\n"
    : "+f"(d[OFF+0]), "+f"(d[OFF+1]), "+f"(d[OFF+2]), "+f"(d[OFF+3]), "+f"(d[OFF+4]), "+f"(d[OFF+5]), "+f"(d[OFF+6]), "+f"(d[OFF+7]), "+f"(d[OFF+8]), "+f"(d[OFF+9]), "+f"(d[OFF+10]), "+f"(d[OFF+11]), "+f"(d[OFF+12]), "+f"(d[OFF+13]), "+f"(d[OFF+14]), "+f"(d[OFF+15]), "+f"(d[OFF+16]), "+f"(d[OFF+17]), "+f"(d[OFF+18]), "+f"(d[OFF+19]), "+f"(d[OFF+20]), "+f"(d[OFF+21]), "+f"(d[OFF+22]), "+f"(d[OFF+23]) : "l"(da), "l"(db), "r"(sd), "n"(TA), "n"(TB));
}

__device__ __align__(1024) uint16_t g_kvT[2 * 640 * 2048];
__device__ __align__(1024) uint16_t g_y2T[640 * 2048];
__device__ __align__(1024) uint16_t g_o[2048 * 640];
__device__ __align__(1024) uint16_t g_gate[2080];
__device__ __align__(1024) uint4 g_halo[128 * 10 * 32];
__device__ __align__(1024) unsigned g_cnt[46 * 32];
__device__ __align__(1024) unsigned g_launch[132];
#define CNT_KV(i) (g_cnt + 32 * (i))
#define CNT_O(i) (g_cnt + 32 * (10 + (i)))
#define CNT_Y(i) (g_cnt + 32 * (26 + (i)))
#define PT(i) do {} while (0)
#define PTP(on, i) do {} while (0)

constexpr uint32_t SB = 1024;
constexpr uint32_t STG = 23552, WST = 15360;
DEVI constexpr uint32_t o_px(int ks) { return (((ks >> 1) + 1) & 3) * 2 * STG; }
DEVI constexpr uint32_t o_pw(int ks) { return o_px(ks) + 16384 + (ks & 1) * WST; }
constexpr uint32_t O_HALO = 0, O_OST = STG;
constexpr uint32_t P3S = 28672;
constexpr uint32_t HC = 8320, UC = 4624, UZ = 528;
constexpr uint32_t O_H0 = 5 * P3S, O_U2 = O_H0 + 3 * HC, O_H3 = O_U2 + UC, O_U0 = O_H3 + 2 * HC;
DEVI constexpr uint32_t o_h(int c) { return O_H0 + c * HC + (c > 2 ? UC : 0); }
DEVI constexpr uint32_t o_u(int c) { return c == 2 ? O_U2 : O_U0 + (c > 2 ? c - 1 : c) * UC; }
constexpr uint32_t O_Y = 208896;
DEVI constexpr uint32_t o_x(int c) { return c < 2 ? O_Y + c * 5120 : O_U0 + (c & 1) * UC; }
constexpr uint32_t O_HIN = O_Y + 16384;
DEVI constexpr uint32_t o_kst(int hw) { return hw == 1 ? (O_U0 + 511) & ~511u : hw == 2 ? (O_U0 + 2 * UC + 511) & ~511u : O_Y + (hw & 1) * 8192; }
constexpr uint32_t O_BT = 4 * P3S;
constexpr uint32_t O_GT = O_Y + 20480, O_GW = O_GT + 320;
constexpr uint32_t O_BAR = 231040;
constexpr uint32_t B_FULL = O_BAR, B_EMPTY = O_BAR + 8 * 8, B_P3F = O_BAR + 8 * 16, B_P3R = O_BAR + 8 * 22, B_G = O_BAR + 8 * 23, B_U = O_BAR + 8 * 24,
                   B_KVD = O_BAR + 8 * 29, B_Y = O_BAR + 8 * 34, B_EP = O_BAR + 8 * 36, B_LAST = O_BAR + 8 * 37, B_DONE = O_BAR + 8 * 39,
                   B_P1E = O_BAR + 8 * 40, B_HX = O_BAR + 8 * 41  , B_P3E = O_BAR + 8 * 52, B_HX0 = O_BAR + 8 * 57;
constexpr uint32_t B_S13 = B_EMPTY + 8 * 5, B_S15 = B_EMPTY + 8 * 7, B_S19 = B_EMPTY + 8 * 3;
constexpr uint32_t O_GP = O_BAR + 512, O_EPOCH = O_GW + 1280;
constexpr uint32_t SMEM_BYTES = 232448;
static_assert(O_U0 + 4 * UC <= O_Y && O_EPOCH + 4 <= O_BAR && O_U0 >= 8 * STG, "smem map");
enum { NB_LEAD = 1, NB_HELP = 2, NB_HALO = 3, NB_ATT = 4, NB_G = 5, NB_TOK = 6, NB_RFULL = 8, NB_RFREE = 10 };

struct Maps { CUtensorMap x_par, w_main, w_tail, o_st, kv_st, wo, o_ld, y_ld; };

template <int M, class F> DEVI void conv_step(float (&acc)[128], uint32_t a0, uint32_t a1, uint32_t a2, uint32_t a3, uint32_t dl, F&& gap) {
  auto D = [&](int off) { return ((uint64_t)8 << 32) | (uint64_t)(uint32_t)(dl + off - 16 * M); };
  if constexpr (M == 0) wgmma_rs_n16<0, 0>(acc, a0, a1, a2, a3, D(0), 0);
  if constexpr (M <= 3) { wgmma_rs_n48<8, 0>(acc, a0, a1, a2, a3, D(16), M == 0 ? 0 : 1); gap(); }
  if constexpr (M <= 6) { wgmma_rs_n48<32, 0>(acc, a0, a1, a2, a3, D(64), M == 0 ? 0 : 1); gap(); }
  if constexpr (M <= 9) { wgmma_rs_n48<56, 0>(acc, a0, a1, a2, a3, D(112), M == 0 ? 0 : 1); gap(); }
  if constexpr (M <= 12) { wgmma_rs_n48<80, 0>(acc, a0, a1, a2, a3, D(160), M == 0 ? 0 : 1); gap(); }
  wgmma_rs_n48<104, 0>(acc, a0, a1, a2, a3, D(208), M == 0 ? 0 : 1); gap();
}
DEVI constexpr int a_off(int P, int i) { return -4 * (64 * ((i & 4) ? 15 - P : P) + (i & 1) * 32 - (i & 2) * 2); }
template <int P> DEVI void load_pair(uint32_t (&a)[8], uint32_t ab) {
#pragma unroll
  for (int i = 0; i < 8; i++) a[i] = lds32(ab + a_off(P, i));
}
template <int P> DEVI void mma_pair(float (&acc)[128], uint32_t (&a)[8], uint32_t db) {
  wg_fence();
  conv_step<P>(acc, a[0], a[1], a[2], a[3], db, []() {});
  conv_step<15 - P>(acc, a[4], a[5], a[6], a[7], db, []() {});
  wg_commit();
}
template <int P, int Q, int W> DEVI void mma_pair_ld(float (&acc)[128], uint32_t (&a)[8], uint32_t db, uint32_t (&nx)[8], uint32_t ab, int on) {
  int n = 0, j = 0;
  auto ld = [&](int cnt) {
#pragma unroll
    for (int r = 0; r < cnt; r++, n++) {
      if (Q >= 4) nx[n] = lds32(ab + a_off(Q, n));
      else asm volatile("{\n.reg .pred p;\nsetp.ne.b32 p, %2, 0;\n@p ld.shared.b32 %0, [%1];\n}" : "+r"(nx[n]) : "r"(ab + a_off(Q, n)), "r"(on));
    }
  };
  auto gap = [&]() {
    if (j == 1) { wg_commit(); wg_wait<W + 1>(); ld(3); wg_fence(); }
    if (j == 3) { wg_commit(); ld(3); wg_fence(); }
    j++;
  };
  wg_fence();
  conv_step<P>(acc, a[0], a[1], a[2], a[3], db, gap);
  conv_step<15 - P>(acc, a[4], a[5], a[6], a[7], db, gap);
  wg_commit();
  ld(2);
}

DEVI void conv_reduce(uint32_t sb, int c, int ht, int chan) {
  const uint32_t a0 = sb + o_h(c) + ht * 16, a2 = sb + o_u(c) + ht * 16, a3 = sb + o_x(c) + ht * 16;
  uint4* yp = (uint4*)(g_y2T + (size_t)chan * 2048) + ht;
#pragma unroll
  for (int i = 0; i < 2; i++) {
    uint4 p, q, r, s;
    lds128(a0 + i * 2048, p.x, p.y, p.z, p.w); lds128(a0 + 4160 + i * 2048, q.x, q.y, q.z, q.w);
    lds128(a2 + i * 2048, r.x, r.y, r.z, r.w); lds128(a3 + i * 2048, s.x, s.y, s.z, s.w);
    yp[i * 128] = make_uint4(hadd2(hadd2(p.x, q.x), hadd2(r.x, s.x)), hadd2(hadd2(p.y, q.y), hadd2(r.y, s.y)),
                             hadd2(hadd2(p.z, q.z), hadd2(r.z, s.z)), hadd2(hadd2(p.w, q.w), hadd2(r.w, s.w)));
  }
}

template <int I> DEVI void ld_rows(uint32_t (&kk)[32], uint32_t (&vv)[32], const char* kp, const char* vp) {
  if constexpr (I < 32) { kk[I] = ldg_v<I * 1280>(kp); vv[I] = ldg_v<I * 1280>(vp); ld_rows<I + 1>(kk, vv, kp, vp); }
}
DEVI void kv_task(const CUtensorMap* map, const uint16_t* kin, const uint16_t* vin, uint4 sk, int kb, int tk, uint32_t st, int lane) {
  const char* kp = (const char*)kin + tk * (32 * 1280) + kb * 128 + lane * 4;
  const char* vp = (const char*)vin + tk * (32 * 1280) + kb * 128 + lane * 4;
  uint32_t km = 0, k0 = 0, k1 = 0, k2 = 0, op = 0, kk[32], vv[32];
  if (tk > 0) { km = ldg_v<-4 * 1280>(kp); k0 = ldg_v<-3 * 1280>(kp); k1 = ldg_v<-2 * 1280>(kp); k2 = ldg_v<-1280>(kp); op = ldg_v<-1280>(vp); }
  ld_rows<0>(kk, vv, kp, vp);
  const uint32_t zz = vv[31] & (uint32_t)(threadIdx.y);
  const uint32_t w0 = prmt(sk.x, sk.z, 0x5410) | zz, w1 = prmt(sk.x, sk.z, 0x7632), w2 = prmt(sk.y, sk.w, 0x5410), w3 = prmt(sk.y, sk.w, 0x7632) | zz;
  const int odd = (lane >> 2) & 1;
  const uint32_t sel0 = odd ? 0x7632 : 0x5410, sel1 = odd ? 0x5410 : 0x7632;
  op = hmul2(hfma2(k2, w0, hfma2(k1, w1, hfma2(k0, w2, hmul2(km, w3)))), op);
#pragma unroll
  for (int ch = 0; ch < 4; ch++) {
    uint32_t o[8];
#pragma unroll
    for (int i = 0; i < 8; i++) {
      const uint32_t k3 = kk[8 * ch + i];
      o[i] = hmul2(hfma2(k3, w0, hfma2(k2, w1, hfma2(k1, w2, hmul2(k0, w3)))), vv[8 * ch + i]);
      k0 = k1; k1 = k2; k2 = k3;
    }
    const uint32_t oa = st + (2 * lane) * 64 + (((3 - ch) ^ (lane & 3)) << 4), o0 = oa + odd * 64, o1 = oa + 64 - odd * 64;
    sts128v(o0, prmt(o[6], o[5], sel0), prmt(o[4], o[3], sel0), prmt(o[2], o[1], sel0), prmt(o[0], op, sel0));
    sts128v(o1, prmt(o[6], o[5], sel1), prmt(o[4], o[3], sel1), prmt(o[2], o[1], sel1), prmt(o[0], op, sel1));
    sts128v(o0 + 4096, prmt(o[7], o[6], sel0), prmt(o[5], o[4], sel0), prmt(o[3], o[2], sel0), prmt(o[1], o[0], sel0));
    sts128v(o1 + 4096, prmt(o[7], o[6], sel1), prmt(o[5], o[4], sel1), prmt(o[3], o[2], sel1), prmt(o[1], o[0], sel1));
    op = o[7];
  }
  fence_async_smem();
  __syncwarp();
  if (elect_one()) {
    tma3_store(map, 0, kb * 64, 63 - tk, st); tma3_store(map, 0, 640 + kb * 64, 63 - tk, st + 4096);
    bulk_commit(); bulk_wait_all();
    flag_add(CNT_KV(kb), 1);
  }
  __syncwarp();
}

template <int ODD, int PART> DEVI void pack_qkv(const float (&acc)[120], uint32_t (&Q)[10][2], uint32_t (&K)[10][2], uint32_t (&V)[10][2]) {
#pragma unroll
  for (int f = 0; f < 10; f++) {
    const bool tail = ODD ? (f < 2) : (f >= 8);
    const int fm = ODD ? f - 2 : f, ft = ODD ? f : f - 8;
    const int nq = tail ? 24 + ft : fm, nk = tail ? 26 + ft : 8 + fm, nv = tail ? 28 + ft : 16 + fm;
    if (PART == 0) {
      V[f][1] = pack_bf16(acc[4 * nv + 2], acc[4 * nv + 3]);
      K[f][1] = pack_bf16(acc[4 * nk + 2], acc[4 * nk + 3]);
    } else {
      Q[f][0] = pack_bf16(acc[4 * nq], acc[4 * nq + 1]); Q[f][1] = pack_bf16(acc[4 * nq + 2], acc[4 * nq + 3]);
      K[f][0] = pack_bf16(acc[4 * nk], acc[4 * nk + 1]); V[f][0] = pack_bf16(acc[4 * nv], acc[4 * nv + 1]);
    }
  }
}
template <int R> DEVI void softmax8(float (&l)[R][2], uint32_t (&P)[R]) {
  const float C = 0.22360679774997896f * 1.4426950408889634f;
  float m[R], s[R];
#pragma unroll
  for (int j = 0; j < R; j++) m[j] = fmaxf(l[j][0], l[j][1]);
#pragma unroll
  for (int j = 0; j < R; j++) m[j] = fmaxf(m[j], __shfl_xor_sync(~0u, m[j], 1));
#pragma unroll
  for (int j = 0; j < R; j++) m[j] = fmaxf(m[j], __shfl_xor_sync(~0u, m[j], 2));
#pragma unroll
  for (int j = 0; j < R; j++) { const float mc = m[j] * C; l[j][0] = ex2(fmaf(l[j][0], C, -mc)); l[j][1] = ex2(fmaf(l[j][1], C, -mc)); s[j] = l[j][0] + l[j][1]; }
#pragma unroll
  for (int j = 0; j < R; j++) s[j] += __shfl_xor_sync(~0u, s[j], 1);
#pragma unroll
  for (int j = 0; j < R; j++) s[j] += __shfl_xor_sync(~0u, s[j], 2);
#pragma unroll
  for (int j = 0; j < R; j++) {
    float r; asm("rcp.approx.ftz.f32 %0, %1;" : "=f"(r) : "f"(s[j]));
    P[j] = pack_bf16(l[j][0] * r, l[j][1] * r);
  }
}

DEVI int pair_of(int c) {
  const int lo = 32 + 8 * c, hi = c - 4 + ((max(c - 29, 0) * 37) >> 8);
  int p; asm("{\n.reg .pred q;\nsetp.lt.s32 q, %1, 4;\nselp.b32 %0, %2, %3, q;\n}" : "=r"(p) : "r"(c), "r"(lo), "r"(hi));
  return p;
}
DEVI uint32_t make_ctx() {
  int b; asm volatile("mov.u32 %0, %%ctaid.x;" : "=r"(b));
  b += clk() & threadIdx.y;
  const int p = pair_of(b >> 1);
  const int j = b < 128 ? 8 * (p & 7) + (p >> 3) : 64, cp = (j * 79) >> 10;
  return ((2 * p + (b & 1)) & 255) | (j - 13 * cp) << 8 | (2 * cp + (b & 1)) << 12 | (b >> 7) << 16;
}
#define CTX() asm volatile("" : "+r"(ctx)); CTXU()
#define CTXU() int tid; asm volatile("mov.u32 %0, %%tid.x;" : "=r"(tid)); \
  const int lane = tid & 31, vb = ctx & 255, hg = (ctx >> 4) & 7, rt = ctx & 15, par = (ctx >> 3) & 1, mt = ctx & 7, rank = ctx & 1, \
  tb = (ctx >> 8) & 15, cb = (ctx >> 12) & 15; const bool main_cta = ctx < 65536; \
  (void)tid; (void)lane; (void)vb; (void)hg; (void)rt; (void)par; (void)mt; (void)rank; (void)tb; (void)cb; (void)main_cta
#define CTXW() CTX(); const int wg = warp >> 2, w = warp & 3, g = lane >> 2, t = lane & 3; const bool lead = (tid & 127) == 0; \
  (void)wg; (void)w; (void)g; (void)t; (void)lead

__global__ void __cluster_dims__(2, 1, 1) __launch_bounds__(512, 1)
fused_kernel(const uint16_t* __restrict__ xq, const uint16_t* __restrict__ wqkv, const uint16_t* __restrict__ gate_w, const __grid_constant__ Maps M, const uint16_t* __restrict__ shift_k, const uint16_t* __restrict__ ssm_k, const uint16_t* __restrict__ ssm_D,
             const uint16_t* __restrict__ kin, const uint16_t* __restrict__ vin, uint16_t* __restrict__ outp) {
  extern __shared__ __align__(1024) uint8_t smem_raw[];
  const uint32_t sb = smem_u32(smem_raw);
  const uint32_t t0 = clk();
  auto get_epoch = [&]() { mbar_wait(sb + B_EP, 0); return lds32(sb + O_EPOCH); };

  auto p1_load_x = [&](int ks, int p, int rank) {
    tma3(sb + o_px(ks), &M.x_par, ks * 32, (p >> 2) & 1, (p & 3) * 256 + rank * 128, sb + B_FULL + 8 * (ks & 7));
  };
  auto p1_load_w = [&](int ks, int p, int rank) {
    const uint32_t st = sb + o_pw(ks), fb = sb + B_FULL + 8 * (ks & 7);
    tma3_mc(st + rank * 6144, &M.w_main, (p >> 3) * 80 + 2 * (p & 8), ks * 32 + rank * 16, 0, fb);
    tma3_mc(st + 12288 + rank * 1536, &M.w_tail, (p >> 3) * 80 + 8 * (~p & 8), ks * 32 + rank * 16, 0, fb);
  };
  auto cta_pair = [&]() { return pair_of(blockIdx.x >> 1); };

  const uint16_t* pfp = nullptr;
  if (threadIdx.x < 32) {
    const unsigned b = blockIdx.x, l = threadIdx.x;
    pfp = l < 16 ? xq + (16 * b + l) * 640 : wqkv + (15 * b + l - 16) * 64;
    if ((l | b >> 7 << 5) < 31) pf_l2(pfp);
  }
  const int warp = __shfl_sync(~0u, threadIdx.x >> 5, 0);
  if ((warp & 14) == 8) {
    if (elect_one()) {
#pragma unroll
      for (int s = 0; s < 8; s++) mbar_init(sb + O_BAR - 512 + 64 * warp + 8 * s, 5 * warp - 39);
      asm volatile("fence.mbarrier_init.release.cluster;" ::: "memory");
    }
    __syncwarp();
  }
  asm volatile("barrier.cluster.arrive.relaxed.aligned;" ::: "memory");
  if (warp == 8 && blockIdx.x < 128) {
    const int p = cta_pair(), rank = blockIdx.x & 1;
    if (elect_one()) { mbar_expect_tx(sb + B_FULL, 16384 + WST); p1_load_x(0, p, rank); }
    __syncwarp();
    asm volatile("barrier.cluster.wait.aligned;" ::: "memory");
    if (elect_one()) { p1_load_w(0, p, rank); PT(100); }
    __syncwarp();
  } else if (warp != 15) {
    asm volatile("barrier.cluster.wait.aligned;" ::: "memory");
    spin_until(t0, HOLD);
  }
  auto init_rest = [&]() {
    if (warp >= 11 && elect_one()) {
#pragma unroll
      for (int s = 0; s < 12; s++) mbar_init(sb + O_BAR + 128 - 11 * 96 + 96 * warp + 8 * s, warp == 14 ? 2 : 1);
      asm volatile("fence.mbarrier_init.release.cluster;" ::: "memory");
    }
    __syncwarp();
    bar_sync(0, blockIdx.x < 128 ? 224 : 512);
  };
  uint32_t ctx = 0;

  if (warp < 8) {
    if (PF2 && warp == 0) {
#pragma unroll 1
      for (int i = 1; i <= NPF; i++) {
        spin_until(t0, PF2 + (i - 1) * PFD);
        if ((threadIdx.x | blockIdx.x >> 7 << 5) < 31) pf_l2(pfp + (threadIdx.x < 16 ? 64 : 64 * 1920) * i);
        __syncwarp();
      }
    }
    reg_inc<RC>();
    ctx = make_ctx();
    if (blockIdx.x >= 128) bar_sync(0, 512);
    else {
      {
        uint32_t Q[10][2], K[10][2], V[10][2];
        {
          {
            float acc[120];
            unsigned epoch;
            {
              CTXW();
              const uint32_t aa = sb + (warp * 16 + (lane & 15)) * 128 + (((lane >> 4) ^ (lane & 7)) << 4);
              const uint32_t rsb = mapa(sb, (blockIdx.x & 1) ^ 1);
              uint32_t a0[8], a1[8], a2[8];
              auto load_a = [&](uint32_t (&r)[8], int ks) {
                mbar_wait(sb + B_FULL + 8 * (ks & 7), (ks >> 3) & 1);
                PTP(lead && (wg || !(ks & 3)), wg ? 60 + ks : 80 + (ks >> 2));
                if (SSMASK >> ks & 1) return;
                ldsm4(r[0], r[1], r[2], r[3], (aa ^ ((ks & 1) * 64)) + o_px(ks)); ldsm4(r[4], r[5], r[6], r[7], (aa ^ ((ks & 1) * 64 + 32)) + o_px(ks));
              };
              auto stage = [&](uint32_t (&r)[8], uint32_t (&nx)[8], int ks, int u) {
                const uint32_t dl = o_pw(ks) >> 4;
                const uint64_t db = mkdesc(SB, 2048, 1024, 1), dt = mkdesc(SB + 12288, 512, 256, 3);
                auto D = [&](uint64_t d) { return (d & ~0xFFFFFFFFull) | (uint32_t)((uint32_t)d + dl); };
                if (LEAD && u == (20 - LEAD) % 3) bar_sync_p(wg == 0 && ks == 20 - LEAD, NB_LEAD, 256);
                wg_fence();
                const uint64_t da = mkdesc(SB + o_px(ks) + (ks & 1) * 64, 16, 1024, 1) + wg * 512;
                if (SSMASK >> ks & 1) { wgmma_ss_n192<0, 0, 1>(acc, da, D(db), ks); wgmma_ss_n48<96, 0, 1>(acc, da, D(dt), ks); }
                else { wgmma_rs_n192<0, 1>(acc, r[0], r[1], r[2], r[3], D(db), ks); wgmma_rs_n48<96, 1>(acc, r[0], r[1], r[2], r[3], D(dt), ks); }
                wg_commit();
                if (LEAD && u == 1) bar_arrive_p(wg && ks == 19, NB_LEAD, 256);
                if (ks < 19) load_a(nx, ks + 1);
                wg_fence();
                if (SSMASK >> ks & 1) { wgmma_ss_n192<0, 0, 1>(acc, da + 2, D(db + 384), 1); wgmma_ss_n48<96, 0, 1>(acc, da + 2, D(dt + 96), 1); }
                else { wgmma_rs_n192<0, 1>(acc, r[4], r[5], r[6], r[7], D(db + 384), 1); wgmma_rs_n48<96, 1>(acc, r[4], r[5], r[6], r[7], D(dt + 96), 1); }
                wg_commit();
                wg_wait<2>();
                mbar_arrive2_p(lead && (u || ks), sb + B_EMPTY + 8 * ((ks - 1) & 7), rsb + B_EMPTY + 8 * ((ks - 1) & 7));
              };
              if (lead) PT(1 + wg);
              load_a(a0, 0);
              constexpr int p1u = P1U;
#pragma unroll p1u
              for (int ks = 0; ks < 21; ks += 3) {
                stage(a0, a1, ks, 0);
                stage(a1, a2, ks + 1, 1);
                if (ks == 18) break;
                stage(a2, a0, ks + 2, 2);
              }
              epoch = get_epoch();
              mbar_wait(sb + B_S15, 1);
              wg_wait<0>();
              fence_regs(acc);
              mbar_arrive_p(tid == 0, sb + B_P1E);
              mbar_arrive2_p(lead, sb + B_S19, rsb + B_S19);
              PTP(lead, 50 + wg);
            }
            CTXW();
            if (hg & 1) pack_qkv<1, 0>(acc, Q, K, V); else pack_qkv<0, 0>(acc, Q, K, V);
#pragma unroll
            for (int f = 0; f < 10; f++) V[f][1] = movm(V[f][1]);
            const uint32_t ho = sb + O_HALO + warp * 2560 + lane * 16;
            if (warp == 7) {
              if (!rank) {
                const uint32_t ra = mapa(sb + O_HIN + lane * 16, 1), rb = mapa(sb + B_HX0, 1);
#pragma unroll
                for (int i = 0; i < 2; i++) {
                  st_async128(ra + i * 512, K[5 * i][1], K[5 * i + 1][1], K[5 * i + 3][1], K[5 * i + 4][1], rb);
                  st_async128(ra + 1024 + i * 512, V[5 * i][1], V[5 * i + 1][1], V[5 * i + 3][1], V[5 * i + 4][1], rb);
                }
                st_async128(ra + 2048, K[2][1], K[7][1], V[2][1], V[7][1], rb);
              } else if (mt < 7) {
                const uint64_t tag = (uint64_t)epoch << 32;
                uint4* hp = g_halo + (size_t)vb * 320 + lane;
                auto put = [&](int i, uint32_t x, uint32_t y) { asm volatile("st.relaxed.gpu.global.v2.b64 [%0], {%1, %2};" ::"l"(hp + 32 * i), "l"(tag | x), "l"(tag | y) : "memory"); };
                put(0, K[0][1], K[1][1]); put(1, K[3][1], K[4][1]); put(2, K[5][1], K[6][1]); put(3, K[8][1], K[9][1]); put(4, K[2][1], K[7][1]);
                put(5, V[0][1], V[1][1]); put(6, V[3][1], V[4][1]); put(7, V[5][1], V[6][1]); put(8, V[8][1], V[9][1]); put(9, V[2][1], V[7][1]);
              }
            } else {
#pragma unroll
              for (int i = 0; i < 2; i++) {
                sts128(ho + i * 512, K[5 * i][1], K[5 * i + 1][1], K[5 * i + 3][1], K[5 * i + 4][1]);
                sts128(ho + 1024 + i * 512, V[5 * i][1], V[5 * i + 1][1], V[5 * i + 3][1], V[5 * i + 4][1]);
              }
              sts128(ho + 2048, K[2][1], K[7][1], V[2][1], V[7][1]);
              __syncwarp();
              if (lane == 0) mbar_arrive(sb + B_HX + 8 + 8 * warp);
            }
            if (hg & 1) pack_qkv<1, 1>(acc, Q, K, V); else pack_qkv<0, 1>(acc, Q, K, V);
#pragma unroll
            for (int f = 0; f < 10; f++) V[f][0] = movm(V[f][0]);
            if (lead) PT(52 + wg);
            if (wg) mbar_wait(sb + B_P1E, 0);
          }
          CTXW();
          const bool gt0 = 2 * t > g, gt1 = 2 * t + 1 > g;
          const uint32_t pmask = (gt0 ? 0xFFFFu : 0u) | (gt1 ? 0xFFFF0000u : 0u);
          uint32_t Qh[4][2];
          float lg[8][2];
#pragma unroll
          for (int j = 0; j < 4; j++) {
            const int fa = (j >> 1) * 5 + (j & 1) * 3, fh = (j >> 1) * 5 + 2;
            const bool mine = (j & 1) ? (t >= 2) : (t < 2);
            Qh[j][0] = mine ? Q[fh][0] : 0u; Qh[j][1] = mine ? Q[fh][1] : 0u;
            float c1[4] = {0.f, 0.f, 0.f, 0.f}, c2[4] = {0.f, 0.f, 0.f, 0.f};
            mma16(c1, Q[fa][0], Q[fa][1], Q[fa + 1][0], Q[fa + 1][1], K[fa][0], K[fa + 1][0]);
            mma16(c2, Q[fa][0], Q[fa][1], Q[fa + 1][0], Q[fa + 1][1], K[fa][1], K[fa + 1][1]);
            mma8(c1, Qh[j][0], Qh[j][1], K[fh][0]);
            mma8(c2, Qh[j][0], Qh[j][1], K[fh][1]);
            lg[j][0] = c1[0]; lg[j][1] = c1[1];
            lg[4 + j][0] = gt0 ? c1[2] : c2[2]; lg[4 + j][1] = gt1 ? c1[3] : c2[3];
          }
          if (lead) PT(54 + wg);
          mbar_wait(sb + (warp ? B_HX + 8 * warp : B_HX0), 0);
          if (lead) PT(56 + wg);
          const uint32_t ha = sb + (warp ? O_HALO + (warp - 1) * 2560 : O_HIN) + lane * 16;
          uint32_t Kh[10], Vh[10];
#pragma unroll
          for (int i = 0; i < 2; i++) lds128(ha + i * 512, Kh[5 * i], Kh[5 * i + 1], Kh[5 * i + 3], Kh[5 * i + 4]);
          lds128(ha + 2048, Kh[2], Kh[7], Vh[2], Vh[7]);
#pragma unroll
          for (int i = 0; i < 2; i++) lds128(ha + 1024 + i * 512, Vh[5 * i], Vh[5 * i + 1], Vh[5 * i + 3], Vh[5 * i + 4]);
          const bool have_halo = warp > 0 || mt > 0;
#pragma unroll
          for (int j = 0; j < 4; j++) {
            const int fa = (j >> 1) * 5 + (j & 1) * 3, fh = (j >> 1) * 5 + 2;
            float c0[4] = {0.f, 0.f, 0.f, 0.f};
            mma16(c0, Q[fa][0], Q[fa][1], Q[fa + 1][0], Q[fa + 1][1], Kh[fa], Kh[fa + 1]);
            mma8(c0, Qh[j][0], Qh[j][1], Kh[fh]);
            if (!have_halo) c0[0] = c0[1] = -INFINITY;
            lg[j][0] = gt0 ? c0[0] : lg[j][0]; lg[j][1] = gt1 ? c0[1] : lg[j][1];
          }
          uint32_t Pv[8], O[10][2];
          softmax8<8>(lg, Pv);
#pragma unroll
          for (int j = 0; j < 4; j++) {
            const int fa = (j >> 1) * 5 + (j & 1) * 3, fh = (j >> 1) * 5 + 2;
            const uint32_t a0 = Pv[j] & pmask, a2 = Pv[j] & ~pmask, a3 = Pv[4 + j] & pmask, a5 = Pv[4 + j] & ~pmask;
#pragma unroll
            for (int q = 0; q < 3; q++) {
              const int f = q < 2 ? fa + q : fh;
              float o[4] = {0.f, 0.f, 0.f, 0.f};
              mma8(o, a0, 0u, Vh[f]);
              mma16(o, a2, a3, 0u, a5, V[f][0], V[f][1]);
              const uint32_t o0 = pack_bf16(o[0], o[1]), o1 = pack_bf16(o[2], o[3]);
              if (q < 2 || !(j & 1)) { O[f][0] = o0; O[f][1] = o1; }
              else { O[f][0] = t >= 2 ? o0 : O[f][0]; O[f][1] = t >= 2 ? o1 : O[f][1]; }
            }
          }
          const uint32_t oa = sb + O_OST + (warp * 16 + (lane & 15)) * 160 + (lane >> 4) * 16;
#pragma unroll
          for (int i = 0; i < 5; i++) stsm4(oa + i * 32, O[2 * i][0], O[2 * i][1], O[2 * i + 1][0], O[2 * i + 1][1]);
        }
      }
      {
        CTXW();
        bar_arrive_p(wg == 0, NB_HALO, 256);
        fence_async_smem();
        bar_arrive(NB_ATT, 288);
        if (lead) PT(58 + wg);
        const uint32_t abase = sb + (g & 1) * 4160 + 4 * (1023 - 4 - 8 * w - (g >> 1) + t);
        float acc[128];
        uint32_t a0[8], a1[8], a2[8], a3[8];
#pragma unroll 1
        for (int c = wg ^ 1; c < 5; c += 2) {
          const uint32_t ab = abase + o_h(c);
          const uint32_t db = __shfl_sync(~0u, ((SB + o_u(c) + UZ - 16) >> 4) | 0x10000u, 0);
          mbar_wait(sb + B_U + 8 * c, 0);
          load_pair<0>(a0, ab); load_pair<1>(a1, ab);
          load_pair<2>(a2, ab); load_pair<3>(a3, ab);
          if (lead) PT(85 + c);
          bar_sync(c ? NB_TOK + wg : NB_HALO, 256);
          fence_regs(acc);
          auto tok = [&](int p) { if (p == TOKP) bar_arrive_p(P3GO == 0 || c < 4, NB_TOK + (wg ^ 1), 256); };
          const uint32_t an = abase + o_h(c + 2);
          auto nxt = [&](auto P, uint32_t (&a)[8]) {
#pragma unroll
            for (int i = 0; i < 8; i++)
              asm volatile("{\n.reg .pred p;\nsetp.ne.b32 p, %2, 0;\n@p ld.shared.b32 %0, [%1];\n}" : "+r"(a[i]) : "r"(an + a_off(P, i)), "r"((int)(c < 3)));
          };
          mma_pair<0>(acc, a0, db);
          mma_pair<1>(acc, a1, db); wg_wait<1>();  load_pair<4>(a0, ab);
          if (lead) PT(90 + c);
          mma_pair<2>(acc, a2, db); wg_wait<1>();  load_pair<5>(a1, ab);
          mma_pair<3>(acc, a3, db); tok(3); wg_wait<1>();  load_pair<6>(a2, ab);
          mma_pair<4>(acc, a0, db); tok(4); wg_wait<1>();  load_pair<7>(a3, ab);
          mma_pair<5>(acc, a1, db); tok(5);
          mma_pair<6>(acc, a2, db); tok(6);
          mma_pair<7>(acc, a3, db);
          wg_wait<0>();
          fence_regs(acc);
          if (lead) PT(95 + c);
          bar_sync(NB_RFREE + wg, 256);
          const uint32_t pb = sb + (w < 2 ? o_h(c) + w * 4160 : w == 2 ? o_u(c) : o_x(c)) + lane * 16;
          if (lane < 2 * w) sts128(pb, 0, 0, 0, 0);
#pragma unroll
          for (int q = 0; q < 8; q++) {
            uint32_t p[4];
#pragma unroll
            for (int i = 0; i < 4; i++) {
              const int nu = 4 * q + i;
              float v0 = acc[4 * nu], v1 = acc[4 * nu + 1];
              p[i] = pack_bf16(v0, v1);
              if (nu > 0) p[i] = hadd2(p[i], pack_bf16(acc[4 * nu - 2], acc[4 * nu - 1]));
            }
            stsm4t(pb + w * 32 + q * 512, p[0], p[1], p[2], p[3]);
          }
          bar_arrive(NB_RFULL + wg, 256);
          if (P3GO == 1 && c == 4) bar_arrive(NB_TOK, 256);
          if (lead) PT(140 + c);
        }
      }
    }
    if (warp < 4) {
      CTXW();
      const uint32_t rsb = mapa(sb, (blockIdx.x & 1) ^ 1);
      const uint32_t ba = sb + O_BT + ((lane >> 4) * 8 + (lane & 7)) * 128 + (((2 * w + ((lane >> 3) & 1)) ^ ((lane & 1) << 2 | (lane >> 1 & 3))) << 4);
      mbar_wait(sb + B_P3F, 0);
      if (lead) PT(145);
      float acc[80];
#pragma unroll 1
      for (int ks = 0; ks < 10; ks++) {
        if (ks == NPRE) {
          if (NPRE) { wg_wait<0>(); mbar_arrive2_p(lead, sb + B_P3E + 8 * (NPRE - 1), rsb + B_P3E + 8 * (NPRE - 1)); }
          if (blockIdx.x < 128) bar_sync(NB_TOK, 256);
        }
        PTP(lead, 146 + ks);
        const uint32_t dl = (ks < 6 ? ks : ks - 6) * (P3S >> 4);
        const uint64_t da = mkdesc(SB, 1024, 1024, 1), db = mkdesc(SB + 8192, 16, 1024, 1);
        auto D = [&](uint64_t d) { return (d & ~0xFFFFFFFFull) | (uint32_t)((uint32_t)d + dl); };
        wg_fence();
#pragma unroll
        for (int j = 0; j < 4; j++) wgmma_ss_n160<0, 1, 0>(acc, D(da + j * 128), D(db + j * 2), j ? 1 : ks);
        wg_commit();
        wg_wait<1>();
        mbar_arrive2_p(lead && ks >= 1 && ks <= 4 && ks != NPRE, sb + B_P3E + 8 * (ks - 1), rsb + B_P3E + 8 * (ks - 1));
        mbar_wait(sb + B_P3F + 8 * (ks < 5 ? ks + 1 : ks - 5), ks >= 5 && ks < 9);
      }
      wg_wait<0>();
      fence_regs(acc);
      if (lead) PT(156);
#pragma unroll
      for (int i = 0; i < 10; i++) {
        stsm4t(ba + i * 2048, pack_bf16(acc[8 * i], acc[8 * i + 1]), pack_bf16(acc[8 * i + 2], acc[8 * i + 3]),
               pack_bf16(acc[8 * i + 4], acc[8 * i + 5]), pack_bf16(acc[8 * i + 6], acc[8 * i + 7]));
        if (i & 1) bar_arrive(1 + (i >> 1), 256);
      }
      if (lead) PT(157);
    }
  } else if (warp < 12) {
    reg_dec<RH>();
    const int hw = warp - 8;
    init_rest();
    ctx = __shfl_sync(~0u, make_ctx(), 0);
    if (ctx < 65536) {
      CTXU();
#pragma unroll 1
      for (int c = hw; c < 5; c += 4) {
        const int kb = 2 * c + (vb >> 6);
        const uint4 sk = __ldg((const uint4*)(shift_k + (size_t)(kb * 64 + 2 * lane) * 4));
        wait_until(t0, KT0 + c * KTD + ((((vb * KPH) & 63) * KTD) >> 6));
        if (lane == 0) PT(20 + c);
        kv_task(&M.kv_st, kin, vin, sk, kb, vb & 63, sb + o_kst(hw), lane);
        if (lane == 0) PT(30 + c);
      }
      if (lane == 0) mbar_arrive(sb + B_KVD + 8 * hw);
    }
    CTXU();
    const int g = lane >> 2, t = lane & 3, row = 8 * hw + g;
    const uint32_t go = (tb * 160 + row) * 80 + cb * 8 + t;
    uint4 T[10];
    auto load_q = [&]() {
#pragma unroll
      for (int i = 0; i < 10; i++) {
        T[i] = make_uint4(0, 0, 0, 0);
        if (i < 8 || tb < 12) asm volatile("ld.volatile.global.v4.b32 {%0,%1,%2,%3}, [%4];" : "=r"(T[i].x), "=r"(T[i].y), "=r"(T[i].z), "=r"(T[i].w) : "l"((const uint4*)xq + go + (i >> 1) * 2560 + (i & 1) * 4));
      }
    };
    if (main_cta) {
      bar_arrive(NB_RFREE, 256);
      bar_arrive(NB_RFREE + 1, 256);
      const int yrow = (vb & 0x61) | (vb & 6) << 2 | (vb >> 2 & 6);
      auto red = [&](int c) {
        const int wg = (c & 1) ^ 1;
        bar_sync(NB_RFULL + wg, 256);
        conv_reduce(sb, c, tid - 256, 128 * c + yrow);
        if (P3GO == 2 && c == 4) bar_arrive(NB_TOK, 256);
        __syncwarp();
        if (lane == 0) flag_add(CNT_Y(4 * c + (vb >> 5)), 1);
        if (tid == 256) PT(41 + c);
        if (c < 3) bar_arrive(NB_RFREE + wg, 256);
        if (c == 2) {
          bar_sync(NB_HELP, 128);
          if (tid == 256) { mbar_arrive(sb + B_P3E + 32); mbar_arrive_remote(sb + B_P3E + 32, rank ^ 1); }
        }
      };
#pragma unroll 1
      for (int c = 0; c < QC; c++) red(c);
      load_q();
#pragma unroll 1
      for (int c = QC; c < 5; c++) red(c);
    } else load_q();
    uint32_t G[5];
    mbar_wait(sb + B_G, 0);
#pragma unroll
    for (int q = 0; q < 5; q++) { uint16_t v; asm volatile("ld.shared.u16 %0, [%1];" : "=h"(v) : "r"(sb + O_GT + (32 * q + row) * 2)); G[q] = prmt(v, 0, 0x1010); }
#pragma unroll
    for (int i = 0; i < 10; i++) { const uint32_t c = G[i >> 1]; T[i] = make_uint4(hmul2(T[i].x, c), hmul2(T[i].y, c), hmul2(T[i].z, c), hmul2(T[i].w, c)); }
#pragma unroll
    for (int h = 0; h < 2; h++) {
      mbar_wait(sb + B_Y + 8 * h, 0);
      if (tid == 256) PT(46);
#pragma unroll
      for (int q = 0; q < 5; q++) {
        uint32_t y0, y1, y2, y3;
        ldsm4t(y0, y1, y2, y3, sb + O_Y + h * 10240 + q * 2048 + lane * 64 + ((hw ^ ((lane >> 1) & 3)) << 4));
        uint4& r = T[2 * q + h];
        r = make_uint4(hmul2(r.x, y0), hmul2(r.y, y1), hmul2(r.z, y2), hmul2(r.w, y3));
      }
    }
    const uint32_t so = sb + O_BT + row * 128 + ((t ^ ((g & 1) << 2 | g >> 1)) << 4);
    if (tid == 256) PT(47);
#pragma unroll
    for (int q = 0; q < 5; q++) {
      const uint32_t c = hfma2(G[q], 0xBF80BF80u, 0x3F803F80u);
      bar_sync(1 + q, 256);
      if (q == 4) mbar_arrive_p(tid == 256, sb + B_DONE);
#pragma unroll
      for (int h = 0; h < 2; h++) {
        uint4 u;
        lds128((so ^ (h * 64)) + q * 4096, u.x, u.y, u.z, u.w);
        const uint4& r = T[2 * q + h];
        if (q < 4 || tb < 12) ((uint4*)outp)[go + q * 2560 + h * 4] = make_uint4(hfma2(u.x, c, r.x), hfma2(u.y, c, r.y), hfma2(u.z, c, r.z), hfma2(u.w, c, r.w));
      }
    }
  } else {
    reg_dec<RP>();
    if (warp == 15) {
      const int p = cta_pair(), rank = blockIdx.x & 1;
      asm volatile("barrier.cluster.wait.aligned;" ::: "memory");
      if (blockIdx.x >= 128) bar_sync(0, 512);
      else {
#pragma unroll 1
        for (int ks = 1;; ks += 2) {
          mbar_wait(sb + B_EMPTY + 8 * (ks & 7), ((ks >> 3) & 1) ^ 1);
          spin_until(t0, PT1 + (ks - 1) * PTD);
          if (elect_one()) { mbar_expect_tx(sb + B_FULL + 8 * (ks & 7), WST); p1_load_w(ks, p, rank); PT(100 + ks); }
          if (ks == HT && elect_one()) mbar_arrive(sb + B_LAST);
          if (ks == 19) break;
          const int kn = ks + 1;
          mbar_wait(sb + B_EMPTY + 8 * (kn & 7), ((kn >> 3) & 1) ^ 1);
          spin_until(t0, PT1 + ks * PTD - PTE);
          if (elect_one()) { mbar_expect_tx(sb + B_FULL + 8 * (kn & 7), 16384 + WST); p1_load_x(kn, p, rank); p1_load_w(kn, p, rank); PT(100 + kn); }
        }
        mbar_wait(sb + B_S19, 0);
      }
    } else init_rest();
    ctx = __shfl_sync(~0u, make_ctx(), 0);
    CTXU();
    if (warp == 12) {
        unsigned epoch = 0;
      if (lane == 0) {
        if ((sb & 0xFFFFFF) != SB) __trap();
        epoch = *(volatile unsigned*)(g_launch + blockIdx.x) + 1;
        *(volatile unsigned*)(g_launch + blockIdx.x) = epoch;
        sts32(sb + O_EPOCH, epoch);
        mbar_arrive(sb + B_EP);
#pragma unroll 1
        for (int i = 3; i < 8; i++) asm volatile("prefetch.tensormap [%0];" ::"l"(&M.x_par + i) : "memory");
      }
      __syncwarp();
      if (main_cta) {
        uint4 h0 = make_uint4(0, 0, 0, 0);
        if (lane < 5) {
          h0 = __ldg((const uint4*)(ssm_k + (size_t)(128 * lane + vb) * 2048));
          h0.x = prmt(pack_bf16(bf_lo(h0.x) + bf_lo(__ldg(ssm_D + 128 * lane + vb)), 0.f), h0.x, 0x7610);
        }
        epoch = __shfl_sync(~0u, epoch, 0);
        mbar_wait(sb + B_LAST, 0);
        mbar_wait(sb + B_S13, 1);
#pragma unroll 1
        for (int c = 0; c < 5; c++) {
          if (c == 0 || c == 3) mbar_wait(sb + B_KVD + (c ? 16 : 8), 0);
          sts128(sb + o_u(c) + lane * 16, 0, 0, 0, 0);
          if (lane < 3) sts128(sb + (lane < 2 ? o_h(c) + lane * 4160 + 4096 : o_u(c) + 512), 0, 0, 0, 0);
          if (lane == c) sts128(sb + o_u(c) + UZ, h0.x, h0.y, h0.z, h0.w);
          fence_async_smem();
          __syncwarp();
          if (elect_one()) {
            mbar_expect_tx(sb + B_U + 8 * c, 3 * 4096 - 16);
            bulk_load(sb + o_u(c) + UZ + 16, ssm_k + (size_t)(128 * c + vb) * 2048 + 8, 4080, sb + B_U + 8 * c);
          }
          flag_wait(CNT_KV(2 * c + (vb >> 6)), 64 * epoch);
          __syncwarp();
          if (elect_one()) {
            bulk_load(sb + o_h(c), g_kvT + (size_t)(128 * c + vb) * 2048, 4096, sb + B_U + 8 * c);
            bulk_load(sb + o_h(c) + 4160, g_kvT + (size_t)(640 + 128 * c + vb) * 2048, 4096, sb + B_U + 8 * c);
            PT(10 + c);
          }
        }
      }
    } else if (warp != 15) {
        const int r = warp - 13;
      if (main_cta) {
        if (rank) {
#pragma unroll
          for (int f = 0; f < 5; f++)
            asm volatile("st.relaxed.gpu.global.v2.b64 [%0], {%1, %1};" ::"l"(g_halo + (size_t)vb * 320 + r * 160 + lane + 32 * f), "l"(0ull) : "memory");
          if (lane == 0) mbar_expect_tx(sb + B_HX0, 1280);
        }
        const int t = lane & 3, grow = hg * 16 + (lane & 15);
        const uint32_t ga = sb + grow * 128 + (((4 * r + (lane >> 4)) ^ (lane & 7)) << 4);
        const uint32_t gp = sb + O_GW + 64 * r + 4 * t;
        float s0 = 0.f, s1 = 0.f;
        {
          const int o = (lane >> 3) * 128 + 64 * r + (lane & 7) * 8;
          uint2 wv[3];
#pragma unroll
          for (int i = 0; i < 3; i++) if (i < 2 || lane < 16) wv[i] = __ldg((const uint2*)((const char*)gate_w + o + i * 512));
#pragma unroll
          for (int i = 0; i < 3; i++) if (i < 2 || lane < 16) asm volatile("st.shared.v2.b32 [%0], {%1,%2};" ::"r"(sb + O_GW + o + i * 512), "r"(wv[i].x), "r"(wv[i].y) : "memory");
          __syncwarp();
        }
#pragma unroll 1
        for (int ks = 0; ks < 20; ks += 2) {
          uint32_t x[8], gw[4];
#pragma unroll
          for (int i = 0; i < 4; i++) gw[i] = lds32(gp + ks * 64 + i * 16);
          mbar_wait_wd(sb + B_FULL + 8 * (ks & 7), (ks >> 3) & 1, t0);
          if (r == 0 && lane == 0) PT(120 + ks);
          ldsm4(x[0], x[1], x[2], x[3], ga + o_px(ks)); ldsm4(x[4], x[5], x[6], x[7], (ga ^ 32) + o_px(ks));
#pragma unroll
          for (int i = 0; i < 8; i++) x[i] = hmul2(x[i], gw[i >> 1]);
          if (lane < 2) mbar_arrive(sb + B_EMPTY + 8 * (ks & 7) + 8 * lane + (x[0] & x[7] & threadIdx.y));
#pragma unroll
          for (int i = 0; i < 8; i += 4) {
            s0 += (bf_lo(x[i]) + bf_hi(x[i])) + (bf_lo(x[i + 2]) + bf_hi(x[i + 2]));
            s1 += (bf_lo(x[i + 1]) + bf_hi(x[i + 1])) + (bf_lo(x[i + 3]) + bf_hi(x[i + 3]));
          }
        }
        s0 += __shfl_xor_sync(~0u, s0, 1); s1 += __shfl_xor_sync(~0u, s1, 1);
        s0 += __shfl_xor_sync(~0u, s0, 2); s1 += __shfl_xor_sync(~0u, s1, 2);
        if (t < 2) sts32(sb + O_GP + r * 64 + (8 * t + (lane >> 2)) * 4, __float_as_uint(t ? s1 : s0));
        if (r == 0) bar_arrive(NB_G, 64);
        if (!rank) {
          const uint32_t ha = sb + O_HIN + lane * 16 + r * 1024, hb = sb + O_HIN + lane * 16 + 2048 + r * 8;
          uint32_t d[10];
          if (mt > 0) {
            const uint4* hp = g_halo + (size_t)(vb - 1) * 320 + r * 160 + lane;
            mbar_wait_wd(sb + B_HX + 56, 0, t0);
            const unsigned epoch = lds32(sb + O_EPOCH);
            for (;;) {
              uint64_t u[10];
#pragma unroll
              for (int f = 0; f < 5; f++) asm volatile("ld.relaxed.gpu.global.v2.b64 {%0, %1}, [%2];" : "=l"(u[2 * f]), "=l"(u[2 * f + 1]) : "l"(hp + 32 * f) : "memory");
              uint32_t bad = 0;
#pragma unroll
              for (int f = 0; f < 10; f++) { d[f] = (uint32_t)u[f]; bad |= (uint32_t)(u[f] >> 32) ^ epoch; }
              if (__all_sync(~0u, bad == 0)) break;
              if (clk() - t0 > 0x70000000u) __trap();
            }
          } else {
#pragma unroll
            for (int f = 0; f < 10; f++) d[f] = 0u;
          }
          sts128(ha, d[0], d[1], d[2], d[3]); sts128(ha + 512, d[4], d[5], d[6], d[7]);
          sts32(hb, d[8]); sts32(hb + 4, d[9]);
          __syncwarp();
          if (lane == 0) { mbar_arrive(sb + B_HX0); PT(15 + r); }
        }
        if (r == 1) {
          bar_sync(NB_G, 64);
          if (lane < 16) {
            const uint32_t pa = sb + O_GP + lane * 4;
            const float z = __uint_as_float(lds32(pa)) + __uint_as_float(lds32(pa + 64));
            g_gate[2 * (mt * 128 + hg * 16 + lane) + par] = (uint16_t)pack_bf16(__fdividef(1.f, 1.f + __expf(-bf_lo(pack_bf16(z, 0.f)))), 0.f);
          }
          __syncwarp();
          if (lane == 0) flag_add(CNT_O(rt), 1);
        }
      }
      if (elect_one()) {
        mbar_wait_wd(sb + B_EP, 0, t0);
        const unsigned epoch = lds32(sb + O_EPOCH);
        if (main_cta) mbar_wait_wd(sb + B_P3E + 32, 0, t0);
        unsigned v;
        do {
          asm volatile("ld.relaxed.gpu.global.u32 %0, [%1];" : "=r"(v) : "l"(CNT_Y(2 * cb + r)) : "memory");
          if (clk() - t0 > 0x70000000u) __trap();
        } while ((int)(v - 128 * epoch) < 0);
        mbar_expect_tx(sb + B_Y + 8 * r, 10240);
        tma3(sb + O_Y + r * 10240, &M.y_ld, 0, cb * 64 + 32 * r, tb * 5, sb + B_Y + 8 * r);
        PT(17 + r);
        mbar_wait_wd(sb + B_DONE, 0, t0);
      }
    } else {
      const unsigned epoch = get_epoch();
      if (main_cta) bar_sync(NB_ATT, 288);
      if (elect_one()) {
        if (main_cta) {
          tma3_store(&M.o_st, hg * 80, par, mt * 128, sb + O_OST);
          bulk_commit(); bulk_wait_all();
          flag_add(CNT_O(rt), 1);
        }
        PT(3);
      }
      __syncwarp();
      if (lane < 4) flag_wait(CNT_O(8 * (lane & 1) + min(7, (80 * tb + 79 * (lane >> 1)) >> 7)), 16 * epoch);
      __syncwarp();
      if (elect_one()) {
        PT(4);
        mbar_arrive_remote(sb + B_P3R, rank ^ 1);
        mbar_expect_tx(sb + B_G, 320);
        bulk_load(sb + O_GT, g_gate + tb * 160, 320, sb + B_G);
      }
      mbar_wait(sb + B_P3R, 0);
#pragma unroll 1
      for (int ks = 0; ks < 10; ks++) {
        const int q = ks < 6 ? ks : ks - 6;
        if (ks > 5 || (ks == 5 && main_cta)) mbar_wait(sb + B_P3E + 8 * (ks == 5 ? 4 : q), 0);
        if (elect_one()) {
          PTP(ks >= 5, ks);
          mbar_expect_tx(sb + B_P3F + 8 * q, P3S);
          tma2(sb + q * P3S, &M.wo, cb * 64, ks * 64, sb + B_P3F + 8 * q);
          tma2_mc(sb + q * P3S + 8192 + rank * 10240, &M.o_ld, ks * 64, tb * 160 + rank * 80, sb + B_P3F + 8 * q);
        }
      }
    }
  }
}

typedef CUresult (*PFN_enc)(CUtensorMap*, CUtensorMapDataType, cuuint32_t, void*, const cuuint64_t*, const cuuint64_t*, const cuuint32_t*,
                            const cuuint32_t*, CUtensorMapInterleave, CUtensorMapSwizzle, CUtensorMapL2promotion, CUtensorMapFloatOOBfill);
static void enc(PFN_enc f, CUtensorMap* m, const void* base, int rank, const cuuint64_t* dims, const cuuint64_t* strides, const cuuint32_t* box,
                CUtensorMapSwizzle sw) {
  const cuuint32_t es[5] = {1, 1, 1, 1, 1};
  f(m, CU_TENSOR_MAP_DATA_TYPE_BFLOAT16, rank, (void*)base, dims, strides, box, es, CU_TENSOR_MAP_INTERLEAVE_NONE, sw,
    CU_TENSOR_MAP_L2_PROMOTION_NONE, CU_TENSOR_MAP_FLOAT_OOB_FILL_NONE);
}

extern "C" void kernel_launch(void* const* d_in, const int* in_sizes, int n_in, void* d_out, int out_size) {
  (void)in_sizes; (void)n_in; (void)out_size;
  static PFN_enc f = nullptr;
  static void *kvT, *y2T, *o;
  if (!f) {
    void* p = nullptr;
    cudaDriverEntryPointQueryResult q;
    cudaGetDriverEntryPoint("cuTensorMapEncodeTiled", &p, cudaEnableDefault, &q);
    f = (PFN_enc)p;
    cudaGetSymbolAddress(&kvT, g_kvT); cudaGetSymbolAddress(&y2T, g_y2T); cudaGetSymbolAddress(&o, g_o);
    cudaFuncSetAttribute(fused_kernel, cudaFuncAttributeMaxDynamicSharedMemorySize, SMEM_BYTES);
  }
  Maps M;
  const CUtensorMapSwizzle S0 = CU_TENSOR_MAP_SWIZZLE_NONE, S32 = CU_TENSOR_MAP_SWIZZLE_32B, S64 = CU_TENSOR_MAP_SWIZZLE_64B, S128 = CU_TENSOR_MAP_SWIZZLE_128B;
  const cuuint64_t dpar[3] = {640, 2, 1024}, spar[2] = {1280, 2560};
  const cuuint64_t dw[3] = {640, 640, 3}, sw[2] = {3840, 1280};
  const cuuint64_t dnat[2] = {640, 2048}, snat[1] = {1280};
  const cuuint64_t dT[3] = {32, 640, 64}, dT2[3] = {32, 1280, 64}, sT[2] = {4096, 64};
  const cuuint64_t dwo[2] = {640, 640};
  { const cuuint32_t bx[3] = {64, 1, 128}; enc(f, &M.x_par, d_in[0], 3, dpar, spar, bx, S128); }
  { const cuuint32_t bx[3] = {64, 16, 3}; enc(f, &M.w_main, d_in[7], 3, dw, sw, bx, S128); }
  { const cuuint32_t bx[3] = {16, 16, 3}; enc(f, &M.w_tail, d_in[7], 3, dw, sw, bx, S32); }
  { const cuuint32_t bx[3] = {80, 1, 128}; enc(f, &M.o_st, o, 3, dpar, spar, bx, S0); }
  { const cuuint32_t bx[3] = {32, 64, 1}; enc(f, &M.kv_st, kvT, 3, dT2, sT, bx, S64); }
  { const cuuint32_t bx[3] = {32, 32, 5}; enc(f, &M.y_ld, y2T, 3, dT, sT, bx, S64); }
  { const cuuint32_t bx[2] = {64, 64}; enc(f, &M.wo, d_in[8], 2, dwo, snat, bx, S128); }
  { const cuuint32_t bx[2] = {64, 80}; enc(f, &M.o_ld, o, 2, dnat, snat, bx, S128); }
  fused_kernel<<<130, 512, SMEM_BYTES, cudaStreamPerThread>>>((const uint16_t*)d_in[0], (const uint16_t*)d_in[7], (const uint16_t*)d_in[9], M, (const uint16_t*)d_in[3], (const uint16_t*)d_in[4], (const uint16_t*)d_in[5],
                                                              (const uint16_t*)d_in[1], (const uint16_t*)d_in[2], (uint16_t*)d_out);
}
```

```cpp
#include <cuda_runtime.h>
#include <cuda_bf16.h>
#include <cuda.h>
#include <stdint.h>

#define DEVI __device__ __forceinline__
#define PT1 550
#define PTD 460
#define PTE 200
#define PF2 0
#define NPF 1
#define PFD 0
#define SSMASK 0
static_assert((SSMASK & 0xAAA) == 0, "an x tile is refilled as soon as its even stage is released");
#define HT 19
#define KPH 37
#define CV 0
#define TOKP 6
#define NPRE 0
#define P3GO 0
#define QC 0
#define HALVES 0
#define HDL 0
#define KT0 1500
#define KTD 1100
#define RC 192
#define RH 96
#define RP 32
#define HOLD 750
#define P1U 7
#define LEAD 3

DEVI uint32_t smem_u32(const void* p) { return (uint32_t)__cvta_generic_to_shared(p); }
DEVI void wg_fence() { asm volatile("wgmma.fence.sync.aligned;" ::: "memory"); }
DEVI void wg_commit() { asm volatile("wgmma.commit_group.sync.aligned;" ::: "memory"); }
template <int N> DEVI void wg_wait() { asm volatile("wgmma.wait_group.sync.aligned %0;" ::"n"(N) : "memory"); }
template <int S> DEVI void fence_regs(float (&d)[S]) {
#pragma unroll
  for (int i = 0; i < S; i++) asm volatile("" : "+f"(d[i])::"memory");
}
DEVI uint64_t mkdesc(uint32_t addr, uint32_t lbo, uint32_t sbo, int swz) {
  return (uint64_t)((addr & 0x3FFFF) >> 4) | ((uint64_t)(lbo >> 4) << 16) | ((uint64_t)(sbo >> 4) << 32) | ((uint64_t)swz << 62);
}
DEVI void mbar_init(uint32_t bar, uint32_t cnt) { asm volatile("mbarrier.init.shared::cta.b64 [%0], %1;" ::"r"(bar), "r"(cnt) : "memory"); }
DEVI void mbar_expect_tx(uint32_t bar, uint32_t bytes) { asm volatile("mbarrier.arrive.expect_tx.shared::cta.b64 _, [%0], %1;" ::"r"(bar), "r"(bytes) : "memory"); }
DEVI void mbar_arrive(uint32_t bar) { asm volatile("mbarrier.arrive.shared::cta.b64 _, [%0];" ::"r"(bar) : "memory"); }
DEVI void mbar_wait(uint32_t bar, uint32_t parity) {
  asm volatile("{\n.reg .pred p;\nLAB_WAIT:\nmbarrier.try_wait.parity.shared::cta.b64 p, [%0], %1;\n@!p bra LAB_WAIT;\n}" ::"r"(bar), "r"(parity) : "memory");
}
DEVI void mbar_wait_wd(uint32_t bar, uint32_t parity, uint32_t t0) {
  asm volatile("{\n.reg .pred p;\n.reg .u32 c;\nLAB_WAIT:\nmbarrier.try_wait.parity.shared::cta.b64 p, [%0], %1;\n@p bra DONE;\nmov.u32 c, %%clock;\nsub.u32 c, c, %2;\nsetp.lt.u32 p, c, 0x70000000;\n@p bra LAB_WAIT;\ntrap;\nDONE:\n}" ::"r"(bar), "r"(parity), "r"(t0) : "memory");
}
DEVI void flag_wait(const unsigned* p, unsigned target) {
  asm volatile("{\n.reg .pred p;\n.reg .s32 v;\nLAB_WAIT:\nld.relaxed.gpu.global.u32 v, [%0];\nsub.s32 v, v, %1;\nsetp.lt.s32 p, v, 0;\n@p bra LAB_WAIT;\n}" ::"l"(p), "r"(target) : "memory");
}
DEVI void flag_add(unsigned* p, unsigned v) { asm volatile("red.relaxed.gpu.global.add.u32 [%0], %1;" ::"l"(p), "r"(v) : "memory"); }
DEVI void fence_async_smem() { asm volatile("fence.proxy.async.shared::cta;" ::: "memory"); }
DEVI bool elect_one() { uint32_t p; asm volatile("{\n.reg .pred P;\nelect.sync _|P, 0xffffffff;\nselp.u32 %0, 1, 0, P;\n}" : "=r"(p)); return p; }
DEVI void bar_sync(int id, int n) { asm volatile("bar.sync %0, %1;" ::"r"(id), "r"(n) : "memory"); }
DEVI void bar_arrive(int id, int n) { asm volatile("bar.arrive %0, %1;" ::"r"(id), "r"(n) : "memory"); }
DEVI void tma2(uint32_t dst, const CUtensorMap* m, int c0, int c1, uint32_t bar) {
  asm volatile("cp.async.bulk.tensor.2d.shared::cluster.global.mbarrier::complete_tx::bytes [%0], [%1, {%3, %4}], [%2];" ::"r"(dst), "l"(m), "r"(bar), "r"(c0), "r"(c1) : "memory");
}
DEVI void tma3(uint32_t dst, const CUtensorMap* m, int c0, int c1, int c2, uint32_t bar) {
  asm volatile("cp.async.bulk.tensor.3d.shared::cluster.global.mbarrier::complete_tx::bytes [%0], [%1, {%3, %4, %5}], [%2];" ::"r"(dst), "l"(m), "r"(bar), "r"(c0), "r"(c1), "r"(c2) : "memory");
}
DEVI void tma3_mc(uint32_t dst, const CUtensorMap* m, int c0, int c1, int c2, uint32_t bar) {
  asm volatile("cp.async.bulk.tensor.3d.shared::cluster.global.mbarrier::complete_tx::bytes.multicast::cluster [%0], [%1, {%3, %4, %5}], [%2], %6;" ::"r"(dst), "l"(m), "r"(bar), "r"(c0), "r"(c1), "r"(c2), "h"((uint16_t)3) : "memory");
}
DEVI void tma2_mc(uint32_t dst, const CUtensorMap* m, int c0, int c1, uint32_t bar) {
  asm volatile("cp.async.bulk.tensor.2d.shared::cluster.global.mbarrier::complete_tx::bytes.multicast::cluster [%0], [%1, {%3, %4}], [%2], %5;" ::"r"(dst), "l"(m), "r"(bar), "r"(c0), "r"(c1), "h"((uint16_t)3) : "memory");
}
DEVI void mbar_arrive_remote(uint32_t bar, uint32_t cta) {
  asm volatile("{\n.reg .b32 ra;\nmapa.shared::cluster.u32 ra, %0, %1;\nmbarrier.arrive.shared::cluster.b64 _, [ra];\n}" ::"r"(bar), "r"(cta) : "memory");
}
DEVI void tma3_store(const CUtensorMap* m, int c0, int c1, int c2, uint32_t src) {
  asm volatile("cp.async.bulk.tensor.3d.global.shared::cta.bulk_group [%0, {%2, %3, %4}], [%1];" ::"l"(m), "r"(src), "r"(c0), "r"(c1), "r"(c2) : "memory");
}
DEVI void bulk_load(uint32_t dst, const void* src, uint32_t bytes, uint32_t bar) {
  asm volatile("cp.async.bulk.shared::cluster.global.mbarrier::complete_tx::bytes [%0], [%1], %2, [%3];" ::"r"(dst), "l"(src), "r"(bytes), "r"(bar) : "memory");
}
DEVI void bulk_store(void* dst, uint32_t src, uint32_t bytes) {
  asm volatile("cp.async.bulk.global.shared::cta.bulk_group [%0], [%1], %2;" ::"l"(dst), "r"(src), "r"(bytes) : "memory");
}
DEVI void pf_l2(const void* p) { asm volatile("prefetch.global.L2 [%0];" ::"l"(p)); }
template <int OFF> DEVI uint32_t ldg_v(const void* p) { uint32_t v; asm volatile("ld.volatile.global.b32 %0, [%1 + %2];" : "=r"(v) : "l"(p), "n"(OFF)); return v; }
DEVI void bulk_commit() { asm volatile("cp.async.bulk.commit_group;" ::: "memory"); }
DEVI void bulk_wait_all() { asm volatile("cp.async.bulk.wait_group 0;" ::: "memory"); }
DEVI void bulk_wait_read() { asm volatile("cp.async.bulk.wait_group.read 0;" ::: "memory"); }
template <int R> DEVI void reg_inc() { asm volatile("setmaxnreg.inc.sync.aligned.u32 %0;" ::"n"(R)); }
template <int R> DEVI void reg_dec() { asm volatile("setmaxnreg.dec.sync.aligned.u32 %0;" ::"n"(R)); }
DEVI uint32_t prmt(uint32_t a, uint32_t b, uint32_t s) { uint32_t r; asm("prmt.b32 %0,%1,%2,%3;" : "=r"(r) : "r"(a), "r"(b), "r"(s)); return r; }
DEVI uint32_t lds32(uint32_t a) { uint32_t r; asm volatile("ld.shared.b32 %0,[%1];" : "=r"(r) : "r"(a)); return r; }
DEVI void sts32(uint32_t a, uint32_t x) { asm volatile("st.shared.b32 [%0],%1;" ::"r"(a), "r"(x) : "memory"); }
DEVI void sts128(uint32_t a, uint32_t x, uint32_t y, uint32_t z, uint32_t w) { asm volatile("st.shared.v4.b32 [%0],{%1,%2,%3,%4};" ::"r"(a), "r"(x), "r"(y), "r"(z), "r"(w) : "memory"); }
DEVI void sts128v(uint32_t a, uint32_t x, uint32_t y, uint32_t z, uint32_t w) { asm volatile("st.volatile.shared.v4.b32 [%0],{%1,%2,%3,%4};" ::"r"(a), "r"(x), "r"(y), "r"(z), "r"(w) : "memory"); }
DEVI void lds128(uint32_t a, uint32_t& x, uint32_t& y, uint32_t& z, uint32_t& w) { asm volatile("ld.shared.v4.b32 {%0,%1,%2,%3},[%4];" : "=r"(x), "=r"(y), "=r"(z), "=r"(w) : "r"(a) : "memory"); }
DEVI void ldsm4(uint32_t& r0, uint32_t& r1, uint32_t& r2, uint32_t& r3, uint32_t addr) {
  asm volatile("ldmatrix.sync.aligned.m8n8.x4.shared.b16 {%0,%1,%2,%3}, [%4];" : "=r"(r0), "=r"(r1), "=r"(r2), "=r"(r3) : "r"(addr) : "memory");
}
DEVI void ldsm4t(uint32_t& r0, uint32_t& r1, uint32_t& r2, uint32_t& r3, uint32_t addr) {
  asm volatile("ldmatrix.sync.aligned.m8n8.x4.trans.shared.b16 {%0,%1,%2,%3}, [%4];" : "=r"(r0), "=r"(r1), "=r"(r2), "=r"(r3) : "r"(addr) : "memory");
}
DEVI void stsm4(uint32_t addr, uint32_t r0, uint32_t r1, uint32_t r2, uint32_t r3) {
  asm volatile("stmatrix.sync.aligned.m8n8.x4.shared.b16 [%0], {%1,%2,%3,%4};" ::"r"(addr), "r"(r0), "r"(r1), "r"(r2), "r"(r3) : "memory");
}
DEVI void stsm4t(uint32_t addr, uint32_t r0, uint32_t r1, uint32_t r2, uint32_t r3) {
  asm volatile("stmatrix.sync.aligned.m8n8.x4.trans.shared.b16 [%0], {%1,%2,%3,%4};" ::"r"(addr), "r"(r0), "r"(r1), "r"(r2), "r"(r3) : "memory");
}
DEVI uint32_t movm(uint32_t a) { uint32_t r; asm volatile("movmatrix.sync.aligned.m8n8.trans.b16 %0, %1;" : "=r"(r) : "r"(a)); return r; }
DEVI uint32_t pack_bf16(float lo, float hi) { uint32_t r; asm("cvt.rn.bf16x2.f32 %0, %1, %2;" : "=r"(r) : "f"(hi), "f"(lo)); return r; }
DEVI uint32_t hmul2(uint32_t a, uint32_t b) { uint32_t r; asm("mul.rn.bf16x2 %0,%1,%2;" : "=r"(r) : "r"(a), "r"(b)); return r; }
DEVI uint32_t hadd2(uint32_t a, uint32_t b) { uint32_t r; asm("add.rn.bf16x2 %0,%1,%2;" : "=r"(r) : "r"(a), "r"(b)); return r; }
DEVI float bf_lo(uint32_t a) { return __uint_as_float(prmt(a, 0, 0x1044)); }
DEVI float bf_hi(uint32_t a) { return __uint_as_float(a & 0xFFFF0000u); }
DEVI void mma16(float (&c)[4], uint32_t a0, uint32_t a1, uint32_t a2, uint32_t a3, uint32_t b0, uint32_t b1) {
  asm("mma.sync.aligned.m16n8k16.row.col.f32.bf16.bf16.f32 {%0,%1,%2,%3},{%4,%5,%6,%7},{%8,%9},{%0,%1,%2,%3};"
      : "+f"(c[0]), "+f"(c[1]), "+f"(c[2]), "+f"(c[3]) : "r"(a0), "r"(a1), "r"(a2), "r"(a3), "r"(b0), "r"(b1));
}
DEVI void mma8(float (&c)[4], uint32_t a0, uint32_t a1, uint32_t b0) {
  asm("mma.sync.aligned.m16n8k8.row.col.f32.bf16.bf16.f32 {%0,%1,%2,%3},{%4,%5},{%6},{%0,%1,%2,%3};"
      : "+f"(c[0]), "+f"(c[1]), "+f"(c[2]), "+f"(c[3]) : "r"(a0), "r"(a1), "r"(b0));
}
DEVI float ex2(float x) { float r; asm("ex2.approx.ftz.f32 %0, %1;" : "=f"(r) : "f"(x)); return r; }

DEVI uint32_t clk() { uint32_t c; asm volatile("mov.u32 %0, %%clock;" : "=r"(c)); return c; }
DEVI void wait_until(uint32_t t0, int dt) { while ((int)(clk() - t0) < dt) __nanosleep(40); }
DEVI void spin_until(uint32_t t0, int dt) { while ((int)(clk() - t0) < dt) {} }
DEVI uint32_t hfma2(uint32_t a, uint32_t b, uint32_t c) { uint32_t r; asm("fma.rn.bf16x2 %0,%1,%2,%3;" : "=r"(r) : "r"(a), "r"(b), "r"(c)); return r; }
DEVI void bar_sync_p(int on, int id, int n) { asm volatile("{\n.reg .pred p;\nsetp.ne.b32 p, %0, 0;\n@p bar.sync %1, %2;\n}" ::"r"(on), "r"(id), "r"(n) : "memory"); }
DEVI void bar_arrive_p(int on, int id, int n) { asm volatile("{\n.reg .pred p;\nsetp.ne.b32 p, %0, 0;\n@p bar.arrive %1, %2;\n}" ::"r"(on), "r"(id), "r"(n) : "memory"); }
DEVI void mbar_arrive_p(int on, uint32_t bar) { asm volatile("{\n.reg .pred p;\nsetp.ne.b32 p, %1, 0;\n@p mbarrier.arrive.shared::cta.b64 _, [%0];\n}" ::"r"(bar), "r"(on) : "memory"); }
DEVI void mbar_arrive2_p(int on, uint32_t bar, uint32_t rbar) {
  asm volatile("{\n.reg .pred p;\nsetp.ne.b32 p, %2, 0;\n@p mbarrier.arrive.shared::cta.b64 _, [%0];\n@p mbarrier.arrive.shared::cluster.b64 _, [%1];\n}" ::"r"(bar), "r"(rbar), "r"(on) : "memory");
}
DEVI void st_relaxed(uint4* p, uint32_t x, uint32_t y, uint32_t z, uint32_t w) {
  asm volatile("st.relaxed.gpu.global.v4.b32 [%0], {%1,%2,%3,%4};" ::"l"(p), "r"(x), "r"(y), "r"(z), "r"(w) : "memory");
}
DEVI uint32_t mapa(uint32_t a, uint32_t cta) { uint32_t r; asm("mapa.shared::cluster.u32 %0, %1, %2;" : "=r"(r) : "r"(a), "r"(cta)); return r; }
DEVI void st_async128(uint32_t a, uint32_t x, uint32_t y, uint32_t z, uint32_t w, uint32_t bar) {
  asm volatile("st.async.weak.shared::cluster.mbarrier::complete_tx::bytes.v4.b32 [%0], {%1,%2,%3,%4}, [%5];" ::"r"(a), "r"(x), "r"(y), "r"(z), "r"(w), "r"(bar) : "memory");
}

template<int OFF, int TB, int S> __device__ __forceinline__ void wgmma_rs_n192(float (&d)[S], uint32_t a0, uint32_t a1, uint32_t a2, uint32_t a3, uint64_t db, int sd) {
  asm volatile("{\n.reg .pred p;\nsetp.ne.b32 p, %101, 0;\n"
    "wgmma.mma_async.sync.aligned.m64n192k16.f32.bf16.bf16 {%0, %1, %2, %3, %4, %5, %6, %7, %8, %9, %10, %11, %12, %13, %14, %15, %16, %17, %18, %19, %20, %21, %22, %23, %24, %25, %26, %27, %28, %29, %30, %31, %32, %33, %34, %35, %36, %37, %38, %39, %40, %41, %42, %43, %44, %45, %46, %47, %48, %49, %50, %51, %52, %53, %54, %55, %56, %57, %58, %59, %60, %61, %62, %63, %64, %65, %66, %67, %68, %69, %70, %71, %72, %73, %74, %75, %76, %77, %78, %79, %80, %81, %82, %83, %84, %85, %86, %87, %88, %89, %90, %91, %92, %93, %94, %95}, {%96, %97, %98, %99}, %100, p, 1, 1, %102;\n}\n"
    : "+f"(d[OFF+0]), "+f"(d[OFF+1]), "+f"(d[OFF+2]), "+f"(d[OFF+3]), "+f"(d[OFF+4]), "+f"(d[OFF+5]), "+f"(d[OFF+6]), "+f"(d[OFF+7]), "+f"(d[OFF+8]), "+f"(d[OFF+9]), "+f"(d[OFF+10]), "+f"(d[OFF+11]), "+f"(d[OFF+12]), "+f"(d[OFF+13]), "+f"(d[OFF+14]), "+f"(d[OFF+15]), "+f"(d[OFF+16]), "+f"(d[OFF+17]), "+f"(d[OFF+18]), "+f"(d[OFF+19]), "+f"(d[OFF+20]), "+f"(d[OFF+21]), "+f"(d[OFF+22]), "+f"(d[OFF+23]), "+f"(d[OFF+24]), "+f"(d[OFF+25]), "+f"(d[OFF+26]), "+f"(d[OFF+27]), "+f"(d[OFF+28]), "+f"(d[OFF+29]), "+f"(d[OFF+30]), "+f"(d[OFF+31]), "+f"(d[OFF+32]), "+f"(d[OFF+33]), "+f"(d[OFF+34]), "+f"(d[OFF+35]), "+f"(d[OFF+36]), "+f"(d[OFF+37]), "+f"(d[OFF+38]), "+f"(d[OFF+39]), "+f"(d[OFF+40]), "+f"(d[OFF+41]), "+f"(d[OFF+42]), "+f"(d[OFF+43]), "+f"(d[OFF+44]), "+f"(d[OFF+45]), "+f"(d[OFF+46]), "+f"(d[OFF+47]), "+f"(d[OFF+48]), "+f"(d[OFF+49]), "+f"(d[OFF+50]), "+f"(d[OFF+51]), "+f"(d[OFF+52]), "+f"(d[OFF+53]), "+f"(d[OFF+54]), "+f"(d[OFF+55]), "+f"(d[OFF+56]), "+f"(d[OFF+57]), "+f"(d[OFF+58]), "+f"(d[OFF+59]), "+f"(d[OFF+60]), "+f"(d[OFF+61]), "+f"(d[OFF+62]), "+f"(d[OFF+63]), "+f"(d[OFF+64]), "+f"(d[OFF+65]), "+f"(d[OFF+66]), "+f"(d[OFF+67]), "+f"(d[OFF+68]), "+f"(d[OFF+69]), "+f"(d[OFF+70]), "+f"(d[OFF+71]), "+f"(d[OFF+72]), "+f"(d[OFF+73]), "+f"(d[OFF+74]), "+f"(d[OFF+75]), "+f"(d[OFF+76]), "+f"(d[OFF+77]), "+f"(d[OFF+78]), "+f"(d[OFF+79]), "+f"(d[OFF+80]), "+f"(d[OFF+81]), "+f"(d[OFF+82]), "+f"(d[OFF+83]), "+f"(d[OFF+84]), "+f"(d[OFF+85]), "+f"(d[OFF+86]), "+f"(d[OFF+87]), "+f"(d[OFF+88]), "+f"(d[OFF+89]), "+f"(d[OFF+90]), "+f"(d[OFF+91]), "+f"(d[OFF+92]), "+f"(d[OFF+93]), "+f"(d[OFF+94]), "+f"(d[OFF+95]) : "r"(a0), "r"(a1), "r"(a2), "r"(a3), "l"(db), "r"(sd), "n"(TB));
}
template<int OFF, int TB, int S> __device__ __forceinline__ void wgmma_rs_n48(float (&d)[S], uint32_t a0, uint32_t a1, uint32_t a2, uint32_t a3, uint64_t db, int sd) {
  asm volatile("{\n.reg .pred p;\nsetp.ne.b32 p, %29, 0;\n"
    "wgmma.mma_async.sync.aligned.m64n48k16.f32.bf16.bf16 {%0, %1, %2, %3, %4, %5, %6, %7, %8, %9, %10, %11, %12, %13, %14, %15, %16, %17, %18, %19, %20, %21, %22, %23}, {%24, %25, %26, %27}, %28, p, 1, 1, %30;\n}\n"
    : "+f"(d[OFF+0]), "+f"(d[OFF+1]), "+f"(d[OFF+2]), "+f"(d[OFF+3]), "+f"(d[OFF+4]), "+f"(d[OFF+5]), "+f"(d[OFF+6]), "+f"(d[OFF+7]), "+f"(d[OFF+8]), "+f"(d[OFF+9]), "+f"(d[OFF+10]), "+f"(d[OFF+11]), "+f"(d[OFF+12]), "+f"(d[OFF+13]), "+f"(d[OFF+14]), "+f"(d[OFF+15]), "+f"(d[OFF+16]), "+f"(d[OFF+17]), "+f"(d[OFF+18]), "+f"(d[OFF+19]), "+f"(d[OFF+20]), "+f"(d[OFF+21]), "+f"(d[OFF+22]), "+f"(d[OFF+23]) : "r"(a0), "r"(a1), "r"(a2), "r"(a3), "l"(db), "r"(sd), "n"(TB));
}
template<int OFF, int TB, int S> __device__ __forceinline__ void wgmma_rs_n16(float (&d)[S], uint32_t a0, uint32_t a1, uint32_t a2, uint32_t a3, uint64_t db, int sd) {
  asm volatile("{\n.reg .pred p;\nsetp.ne.b32 p, %13, 0;\n"
    "wgmma.mma_async.sync.aligned.m64n16k16.f32.bf16.bf16 {%0, %1, %2, %3, %4, %5, %6, %7}, {%8, %9, %10, %11}, %12, p, 1, 1, %14;\n}\n"
    : "+f"(d[OFF+0]), "+f"(d[OFF+1]), "+f"(d[OFF+2]), "+f"(d[OFF+3]), "+f"(d[OFF+4]), "+f"(d[OFF+5]), "+f"(d[OFF+6]), "+f"(d[OFF+7]) : "r"(a0), "r"(a1), "r"(a2), "r"(a3), "l"(db), "r"(sd), "n"(TB));
}
template<int OFF, int TA, int TB, int S> __device__ __forceinline__ void wgmma_ss_n160(float (&d)[S], uint64_t da, uint64_t db, int sd) {
  asm volatile("{\n.reg .pred p;\nsetp.ne.b32 p, %82, 0;\n"
    "wgmma.mma_async.sync.aligned.m64n160k16.f32.bf16.bf16 {%0, %1, %2, %3, %4, %5, %6, %7, %8, %9, %10, %11, %12, %13, %14, %15, %16, %17, %18, %19, %20, %21, %22, %23, %24, %25, %26, %27, %28, %29, %30, %31, %32, %33, %34, %35, %36, %37, %38, %39, %40, %41, %42, %43, %44, %45, %46, %47, %48, %49, %50, %51, %52, %53, %54, %55, %56, %57, %58, %59, %60, %61, %62, %63, %64, %65, %66, %67, %68, %69, %70, %71, %72, %73, %74, %75, %76, %77, %78, %79}, %80, %81, p, 1, 1, %83, %84;\n}\n"
    : "+f"(d[OFF+0]), "+f"(d[OFF+1]), "+f"(d[OFF+2]), "+f"(d[OFF+3]), "+f"(d[OFF+4]), "+f"(d[OFF+5]), "+f"(d[OFF+6]), "+f"(d[OFF+7]), "+f"(d[OFF+8]), "+f"(d[OFF+9]), "+f"(d[OFF+10]), "+f"(d[OFF+11]), "+f"(d[OFF+12]), "+f"(d[OFF+13]), "+f"(d[OFF+14]), "+f"(d[OFF+15]), "+f"(d[OFF+16]), "+f"(d[OFF+17]), "+f"(d[OFF+18]), "+f"(d[OFF+19]), "+f"(d[OFF+20]), "+f"(d[OFF+21]), "+f"(d[OFF+22]), "+f"(d[OFF+23]), "+f"(d[OFF+24]), "+f"(d[OFF+25]), "+f"(d[OFF+26]), "+f"(d[OFF+27]), "+f"(d[OFF+28]), "+f"(d[OFF+29]), "+f"(d[OFF+30]), "+f"(d[OFF+31]), "+f"(d[OFF+32]), "+f"(d[OFF+33]), "+f"(d[OFF+34]), "+f"(d[OFF+35]), "+f"(d[OFF+36]), "+f"(d[OFF+37]), "+f"(d[OFF+38]), "+f"(d[OFF+39]), "+f"(d[OFF+40]), "+f"(d[OFF+41]), "+f"(d[OFF+42]), "+f"(d[OFF+43]), "+f"(d[OFF+44]), "+f"(d[OFF+45]), "+f"(d[OFF+46]), "+f"(d[OFF+47]), "+f"(d[OFF+48]), "+f"(d[OFF+49]), "+f"(d[OFF+50]), "+f"(d[OFF+51]), "+f"(d[OFF+52]), "+f"(d[OFF+53]), "+f"(d[OFF+54]), "+f"(d[OFF+55]), "+f"(d[OFF+56]), "+f"(d[OFF+57]), "+f"(d[OFF+58]), "+f"(d[OFF+59]), "+f"(d[OFF+60]), "+f"(d[OFF+61]), "+f"(d[OFF+62]), "+f"(d[OFF+63]), "+f"(d[OFF+64]), "+f"(d[OFF+65]), "+f"(d[OFF+66]), "+f"(d[OFF+67]), "+f"(d[OFF+68]), "+f"(d[OFF+69]), "+f"(d[OFF+70]), "+f"(d[OFF+71]), "+f"(d[OFF+72]), "+f"(d[OFF+73]), "+f"(d[OFF+74]), "+f"(d[OFF+75]), "+f"(d[OFF+76]), "+f"(d[OFF+77]), "+f"(d[OFF+78]), "+f"(d[OFF+79]) : "l"(da), "l"(db), "r"(sd), "n"(TA), "n"(TB));
}
template<int OFF, int TA, int TB, int S> __device__ __forceinline__ void wgmma_ss_n192(float (&d)[S], uint64_t da, uint64_t db, int sd) {
  asm volatile("{\n.reg .pred p;\nsetp.ne.b32 p, %98, 0;\n"
    "wgmma.mma_async.sync.aligned.m64n192k16.f32.bf16.bf16 {%0, %1, %2, %3, %4, %5, %6, %7, %8, %9, %10, %11, %12, %13, %14, %15, %16, %17, %18, %19, %20, %21, %22, %23, %24, %25, %26, %27, %28, %29, %30, %31, %32, %33, %34, %35, %36, %37, %38, %39, %40, %41, %42, %43, %44, %45, %46, %47, %48, %49, %50, %51, %52, %53, %54, %55, %56, %57, %58, %59, %60, %61, %62, %63, %64, %65, %66, %67, %68, %69, %70, %71, %72, %73, %74, %75, %76, %77, %78, %79, %80, %81, %82, %83, %84, %85, %86, %87, %88, %89, %90, %91, %92, %93, %94, %95}, %96, %97, p, 1, 1, %99, %100;\n}\n"
    : "+f"(d[OFF+0]), "+f"(d[OFF+1]), "+f"(d[OFF+2]), "+f"(d[OFF+3]), "+f"(d[OFF+4]), "+f"(d[OFF+5]), "+f"(d[OFF+6]), "+f"(d[OFF+7]), "+f"(d[OFF+8]), "+f"(d[OFF+9]), "+f"(d[OFF+10]), "+f"(d[OFF+11]), "+f"(d[OFF+12]), "+f"(d[OFF+13]), "+f"(d[OFF+14]), "+f"(d[OFF+15]), "+f"(d[OFF+16]), "+f"(d[OFF+17]), "+f"(d[OFF+18]), "+f"(d[OFF+19]), "+f"(d[OFF+20]), "+f"(d[OFF+21]), "+f"(d[OFF+22]), "+f"(d[OFF+23]), "+f"(d[OFF+24]), "+f"(d[OFF+25]), "+f"(d[OFF+26]), "+f"(d[OFF+27]), "+f"(d[OFF+28]), "+f"(d[OFF+29]), "+f"(d[OFF+30]), "+f"(d[OFF+31]), "+f"(d[OFF+32]), "+f"(d[OFF+33]), "+f"(d[OFF+34]), "+f"(d[OFF+35]), "+f"(d[OFF+36]), "+f"(d[OFF+37]), "+f"(d[OFF+38]), "+f"(d[OFF+39]), "+f"(d[OFF+40]), "+f"(d[OFF+41]), "+f"(d[OFF+42]), "+f"(d[OFF+43]), "+f"(d[OFF+44]), "+f"(d[OFF+45]), "+f"(d[OFF+46]), "+f"(d[OFF+47]), "+f"(d[OFF+48]), "+f"(d[OFF+49]), "+f"(d[OFF+50]), "+f"(d[OFF+51]), "+f"(d[OFF+52]), "+f"(d[OFF+53]), "+f"(d[OFF+54]), "+f"(d[OFF+55]), "+f"(d[OFF+56]), "+f"(d[OFF+57]), "+f"(d[OFF+58]), "+f"(d[OFF+59]), "+f"(d[OFF+60]), "+f"(d[OFF+61]), "+f"(d[OFF+62]), "+f"(d[OFF+63]), "+f"(d[OFF+64]), "+f"(d[OFF+65]), "+f"(d[OFF+66]), "+f"(d[OFF+67]), "+f"(d[OFF+68]), "+f"(d[OFF+69]), "+f"(d[OFF+70]), "+f"(d[OFF+71]), "+f"(d[OFF+72]), "+f"(d[OFF+73]), "+f"(d[OFF+74]), "+f"(d[OFF+75]), "+f"(d[OFF+76]), "+f"(d[OFF+77]), "+f"(d[OFF+78]), "+f"(d[OFF+79]), "+f"(d[OFF+80]), "+f"(d[OFF+81]), "+f"(d[OFF+82]), "+f"(d[OFF+83]), "+f"(d[OFF+84]), "+f"(d[OFF+85]), "+f"(d[OFF+86]), "+f"(d[OFF+87]), "+f"(d[OFF+88]), "+f"(d[OFF+89]), "+f"(d[OFF+90]), "+f"(d[OFF+91]), "+f"(d[OFF+92]), "+f"(d[OFF+93]), "+f"(d[OFF+94]), "+f"(d[OFF+95]) : "l"(da), "l"(db), "r"(sd), "n"(TA), "n"(TB));
}
template<int OFF, int TA, int TB, int S> __device__ __forceinline__ void wgmma_ss_n48(float (&d)[S], uint64_t da, uint64_t db, int sd) {
  asm volatile("{\n.reg .pred p;\nsetp.ne.b32 p, %26, 0;\n"
    "wgmma.mma_async.sync.aligned.m64n48k16.f32.bf16.bf16 {%0, %1, %2, %3, %4, %5, %6, %7, %8, %9, %10, %11, %12, %13, %14, %15, %16, %17, %18, %19, %20, %21, %22, %23}, %24, %25, p, 1, 1, %27, %28;\n}\n"
    : "+f"(d[OFF+0]), "+f"(d[OFF+1]), "+f"(d[OFF+2]), "+f"(d[OFF+3]), "+f"(d[OFF+4]), "+f"(d[OFF+5]), "+f"(d[OFF+6]), "+f"(d[OFF+7]), "+f"(d[OFF+8]), "+f"(d[OFF+9]), "+f"(d[OFF+10]), "+f"(d[OFF+11]), "+f"(d[OFF+12]), "+f"(d[OFF+13]), "+f"(d[OFF+14]), "+f"(d[OFF+15]), "+f"(d[OFF+16]), "+f"(d[OFF+17]), "+f"(d[OFF+18]), "+f"(d[OFF+19]), "+f"(d[OFF+20]), "+f"(d[OFF+21]), "+f"(d[OFF+22]), "+f"(d[OFF+23]) : "l"(da), "l"(db), "r"(sd), "n"(TA), "n"(TB));
}

__device__ __align__(1024) uint16_t g_kvT[2 * 640 * 2048];
__device__ __align__(1024) uint16_t g_y2T[640 * 2048];
__device__ __align__(1024) uint16_t g_o[2048 * 640];
__device__ __align__(1024) uint16_t g_gate[2080];
__device__ __align__(1024) uint4 g_halo[128 * 5 * 32];
__device__ __align__(1024) unsigned g_cnt[46 * 32];
__device__ __align__(1024) unsigned g_launch[132];
#define CNT_KV(i) (g_cnt + 32 * (i))
#define CNT_O(i) (g_cnt + 32 * (10 + (i)))
#define CNT_Y(i) (g_cnt + 32 * (26 + (i)))
#define PTL(i) do {} while (0)
#define PTPL(on, i) do {} while (0)
#define PT(i) do {} while (0)
#define PTP(on, i) do {} while (0)

constexpr uint32_t SB = 1024;
constexpr uint32_t STG = 23552, WST = 15360;
DEVI constexpr uint32_t o_px(int ks) { return (((ks >> 1) + 1) & 3) * 2 * STG; }
DEVI constexpr uint32_t o_pw(int ks) { return o_px(ks) + 16384 + (ks & 1) * WST; }
constexpr uint32_t O_HALO = 0, O_OST = STG;
constexpr uint32_t P3S = 28672;
constexpr uint32_t HC = 8320, UC = 4624, UZ = 528;
constexpr uint32_t O_H0 = 5 * P3S, O_U2 = O_H0 + 3 * HC, O_H3 = O_U2 + UC, O_U0 = O_H3 + 2 * HC;
DEVI constexpr uint32_t o_h(int c) { return O_H0 + c * HC + (c > 2 ? UC : 0); }
DEVI constexpr uint32_t o_u(int c) { return c == 2 ? O_U2 : O_U0 + (c > 2 ? c - 1 : c) * UC; }
constexpr uint32_t O_Y = 208896;
DEVI constexpr uint32_t o_x(int c) { return c < 2 ? O_Y + c * 5120 : O_U0 + (c & 1) * UC; }
constexpr uint32_t O_HIN = O_Y + 16384;
DEVI constexpr uint32_t o_kst(int hw) { return hw == 1 ? (O_U0 + 511) & ~511u : hw == 2 ? (O_U0 + 2 * UC + 511) & ~511u : O_Y + (hw & 1) * 8192; }
DEVI constexpr uint32_t o_p3(int ks) { return (ks < 6 ? ks : ks - 6) * P3S; }
constexpr uint32_t O_BT = 4 * P3S;
constexpr uint32_t O_GT = O_Y + 20480, O_GW = O_GT + 320;
constexpr uint32_t O_BAR = 231040;
constexpr uint32_t B_FULL = O_BAR, B_EMPTY = O_BAR + 8 * 8, B_P3F = O_BAR + 8 * 16, B_P3R = O_BAR + 8 * 26, B_G = O_BAR + 8 * 27, B_U = O_BAR + 8 * 28,
                   B_KVD = O_BAR + 8 * 33, B_Y = O_BAR + 8 * 37, B_EP = O_BAR + 8 * 39, B_LAST = O_BAR + 8 * 40, B_DONE = O_BAR + 8 * 41,
                   B_P1E = O_BAR + 8 * 43, B_HX = O_BAR + 8 * 43  , B_P3E = O_BAR + 8 * 52, B_HX0 = O_BAR + 8 * 57;
constexpr uint32_t B_S13 = B_EMPTY + 8 * 5, B_S15 = B_EMPTY + 8 * 7, B_S19 = B_EMPTY + 8 * 3;
constexpr uint32_t O_GP = O_BAR + 512, O_EPOCH = O_GW + 1280;
constexpr uint32_t SMEM_BYTES = 232448;
static_assert(O_U0 + 4 * UC <= O_Y && O_EPOCH + 4 <= O_BAR && O_U0 >= 8 * STG, "smem map");
enum { NB_LEAD = 1, NB_HELP = 2, NB_HALO = 3, NB_ATT = 4, NB_G = 5, NB_TOK = 6, NB_RFULL = 8, NB_RFREE = 10 };

struct Maps { CUtensorMap x_par, w_main, w_tail, o_st, kv_st, wo, o_ld, y_ld; };

template <int M, class F> DEVI void conv_step(float (&acc)[128], uint32_t a0, uint32_t a1, uint32_t a2, uint32_t a3, uint32_t dl, F&& gap) {
  auto D = [&](int off) { return ((uint64_t)8 << 32) | (uint64_t)(uint32_t)(dl + off - 16 * M); };
  if constexpr (M == 0) wgmma_rs_n16<0, 0>(acc, a0, a1, a2, a3, D(0), 0);
  if constexpr (M <= 3) { wgmma_rs_n48<8, 0>(acc, a0, a1, a2, a3, D(16), M == 0 ? 0 : 1); gap(); }
  if constexpr (M <= 6) { wgmma_rs_n48<32, 0>(acc, a0, a1, a2, a3, D(64), M == 0 ? 0 : 1); gap(); }
  if constexpr (M <= 9) { wgmma_rs_n48<56, 0>(acc, a0, a1, a2, a3, D(112), M == 0 ? 0 : 1); gap(); }
  if constexpr (M <= 12) { wgmma_rs_n48<80, 0>(acc, a0, a1, a2, a3, D(160), M == 0 ? 0 : 1); gap(); }
  wgmma_rs_n48<104, 0>(acc, a0, a1, a2, a3, D(208), M == 0 ? 0 : 1); gap();
}
DEVI constexpr int a_off(int P, int i) { return -4 * (64 * ((i & 4) ? 15 - P : P) + (i & 1) * 32 - (i & 2) * 2); }
template <int P> DEVI void load_pair(uint32_t (&a)[8], uint32_t ab) {
#pragma unroll
  for (int i = 0; i < 8; i++) a[i] = lds32(ab + a_off(P, i));
}
template <int P> DEVI void mma_pair(float (&acc)[128], uint32_t (&a)[8], uint32_t db) {
  wg_fence();
  conv_step<P>(acc, a[0], a[1], a[2], a[3], db, []() {});
  conv_step<15 - P>(acc, a[4], a[5], a[6], a[7], db, []() {});
  wg_commit();
}
template <int P, int Q, int W> DEVI void mma_pair_ld(float (&acc)[128], uint32_t (&a)[8], uint32_t db, uint32_t (&nx)[8], uint32_t ab, int on) {
  int n = 0, j = 0;
  auto ld = [&](int cnt) {
#pragma unroll
    for (int r = 0; r < cnt; r++, n++) {
      if (Q >= 4) nx[n] = lds32(ab + a_off(Q, n));
      else asm volatile("{\n.reg .pred p;\nsetp.ne.b32 p, %2, 0;\n@p ld.shared.b32 %0, [%1];\n}" : "+r"(nx[n]) : "r"(ab + a_off(Q, n)), "r"(on));
    }
  };
  auto gap = [&]() {
    if (j == 1) { wg_commit(); wg_wait<W + 1>(); ld(3); wg_fence(); }
    if (j == 3) { wg_commit(); ld(3); wg_fence(); }
    j++;
  };
  wg_fence();
  conv_step<P>(acc, a[0], a[1], a[2], a[3], db, gap);
  conv_step<15 - P>(acc, a[4], a[5], a[6], a[7], db, gap);
  wg_commit();
  ld(2);
}

DEVI void conv_reduce(uint32_t sb, int c, int ht, int chan, int bar) {
  const uint32_t a0 = sb + o_h(c) + ht * 16, a2 = sb + o_u(c) + ht * 16, a3 = sb + o_x(c) + ht * 16;
  uint4* yp = (uint4*)(g_y2T + (size_t)chan * 2048) + ht;
#pragma unroll
  for (int i = 0; i < 2; i++) {
    uint4 p, q, r, s;
    if (HALVES || !i) bar_sync(bar + (HALVES ? 4 - 4 * i : 0), 256);
    lds128(a0 + i * 2048, p.x, p.y, p.z, p.w); lds128(a0 + 4160 + i * 2048, q.x, q.y, q.z, q.w);
    lds128(a2 + i * 2048, r.x, r.y, r.z, r.w); lds128(a3 + i * 2048, s.x, s.y, s.z, s.w);
    yp[i * 128] = make_uint4(hadd2(hadd2(p.x, q.x), hadd2(r.x, s.x)), hadd2(hadd2(p.y, q.y), hadd2(r.y, s.y)),
                             hadd2(hadd2(p.z, q.z), hadd2(r.z, s.z)), hadd2(hadd2(p.w, q.w), hadd2(r.w, s.w)));
  }
}

template <int I> DEVI void ld_rows(uint32_t (&kk)[32], uint32_t (&vv)[32], const char* kp, const char* vp) {
  if constexpr (I < 32) { kk[I] = ldg_v<I * 1280>(kp); vv[I] = ldg_v<I * 1280>(vp); ld_rows<I + 1>(kk, vv, kp, vp); }
}
DEVI void kv_task(const CUtensorMap* map, const uint16_t* kin, const uint16_t* vin, uint4 sk, int kb, int tk, uint32_t st, int lane) {
  const char* kp = (const char*)kin + tk * (32 * 1280) + kb * 128 + lane * 4;
  const char* vp = (const char*)vin + tk * (32 * 1280) + kb * 128 + lane * 4;
  uint32_t km = 0, k0 = 0, k1 = 0, k2 = 0, op = 0, kk[32], vv[32];
  if (tk > 0) { km = ldg_v<-4 * 1280>(kp); k0 = ldg_v<-3 * 1280>(kp); k1 = ldg_v<-2 * 1280>(kp); k2 = ldg_v<-1280>(kp); op = ldg_v<-1280>(vp); }
  ld_rows<0>(kk, vv, kp, vp);
  const uint32_t zz = vv[31] & (uint32_t)(threadIdx.y);
  const uint32_t w0 = prmt(sk.x, sk.z, 0x5410) | zz, w1 = prmt(sk.x, sk.z, 0x7632), w2 = prmt(sk.y, sk.w, 0x5410), w3 = prmt(sk.y, sk.w, 0x7632) | zz;
  const int odd = (lane >> 2) & 1;
  const uint32_t sel0 = odd ? 0x7632 : 0x5410, sel1 = odd ? 0x5410 : 0x7632;
  op = hmul2(hfma2(k2, w0, hfma2(k1, w1, hfma2(k0, w2, hmul2(km, w3)))), op);
#pragma unroll
  for (int ch = 0; ch < 4; ch++) {
    uint32_t o[8];
#pragma unroll
    for (int i = 0; i < 8; i++) {
      const uint32_t k3 = kk[8 * ch + i];
      o[i] = hmul2(hfma2(k3, w0, hfma2(k2, w1, hfma2(k1, w2, hmul2(k0, w3)))), vv[8 * ch + i]);
      k0 = k1; k1 = k2; k2 = k3;
    }
    const uint32_t oa = st + (2 * lane) * 64 + (((3 - ch) ^ (lane & 3)) << 4), o0 = oa + odd * 64, o1 = oa + 64 - odd * 64;
    sts128v(o0, prmt(o[6], o[5], sel0), prmt(o[4], o[3], sel0), prmt(o[2], o[1], sel0), prmt(o[0], op, sel0));
    sts128v(o1, prmt(o[6], o[5], sel1), prmt(o[4], o[3], sel1), prmt(o[2], o[1], sel1), prmt(o[0], op, sel1));
    sts128v(o0 + 4096, prmt(o[7], o[6], sel0), prmt(o[5], o[4], sel0), prmt(o[3], o[2], sel0), prmt(o[1], o[0], sel0));
    sts128v(o1 + 4096, prmt(o[7], o[6], sel1), prmt(o[5], o[4], sel1), prmt(o[3], o[2], sel1), prmt(o[1], o[0], sel1));
    op = o[7];
  }
  fence_async_smem();
  __syncwarp();
  if (elect_one()) {
    tma3_store(map, 0, kb * 64, 63 - tk, st); tma3_store(map, 0, 640 + kb * 64, 63 - tk, st + 4096);
    bulk_commit(); bulk_wait_all();
    flag_add(CNT_KV(kb), 1);
  }
  __syncwarp();
}

template <int ODD, int PART> DEVI void pack_qkv(const float (&acc)[120], uint32_t (&Q)[10][2], uint32_t (&K)[10][2], uint32_t (&V)[10][2]) {
#pragma unroll
  for (int f = 0; f < 10; f++) {
    const bool tail = ODD ? (f < 2) : (f >= 8);
    const int fm = ODD ? f - 2 : f, ft = ODD ? f : f - 8;
    const int nq = tail ? 24 + ft : fm, nk = tail ? 26 + ft : 8 + fm, nv = tail ? 28 + ft : 16 + fm;
    if (PART == 0) {
      V[f][1] = pack_bf16(acc[4 * nv + 2], acc[4 * nv + 3]);
      K[f][1] = pack_bf16(acc[4 * nk + 2], acc[4 * nk + 3]);
    } else {
      Q[f][0] = pack_bf16(acc[4 * nq], acc[4 * nq + 1]); Q[f][1] = pack_bf16(acc[4 * nq + 2], acc[4 * nq + 3]);
      K[f][0] = pack_bf16(acc[4 * nk], acc[4 * nk + 1]); V[f][0] = pack_bf16(acc[4 * nv], acc[4 * nv + 1]);
    }
  }
}
DEVI void softmax8(float (&l)[8][2], uint32_t (&P)[8]) {
  const float C = 0.22360679774997896f * 1.4426950408889634f;
  float m[8];
#pragma unroll
  for (int j = 0; j < 8; j++) m[j] = fmaxf(l[j][0], l[j][1]);
#pragma unroll
  for (int j = 0; j < 8; j++) m[j] = fmaxf(m[j], __shfl_xor_sync(~0u, m[j], 1));
#pragma unroll
  for (int j = 0; j < 8; j++) m[j] = fmaxf(m[j], __shfl_xor_sync(~0u, m[j], 2));
#pragma unroll
  for (int j = 0; j < 8; j++) { const float mc = m[j] * C; l[j][0] = ex2(fmaf(l[j][0], C, -mc)); l[j][1] = ex2(fmaf(l[j][1], C, -mc)); }
#pragma unroll
  for (int j = 0; j < 4; j++) {
    float s[4] = {0.f, 0.f, 0.f, 0.f}, r0, r1;
    mma8(s, pack_bf16(l[j][0], l[j][1]), pack_bf16(l[4 + j][0], l[4 + j][1]), 0x3F803F80u);
    asm("rcp.approx.ftz.f32 %0, %1;" : "=f"(r0) : "f"(s[0]));
    asm("rcp.approx.ftz.f32 %0, %1;" : "=f"(r1) : "f"(s[2]));
    P[j] = pack_bf16(l[j][0] * r0, l[j][1] * r0); P[4 + j] = pack_bf16(l[4 + j][0] * r1, l[4 + j][1] * r1);
  }
}

DEVI int pair_of(int c) {
  const int lo = 32 + 8 * c, hi = c - 4 + ((max(c - 29, 0) * 37) >> 8);
  int p; asm("{\n.reg .pred q;\nsetp.lt.s32 q, %1, 4;\nselp.b32 %0, %2, %3, q;\n}" : "=r"(p) : "r"(c), "r"(lo), "r"(hi));
  return p;
}
DEVI uint32_t make_ctx() {
  int b; asm volatile("mov.u32 %0, %%ctaid.x;" : "=r"(b));
  b += clk() & threadIdx.y;
  const int p = pair_of(b >> 1);
  const int j = b < 128 ? 8 * (p & 7) + (p >> 3) : 64, cp = (j * 79) >> 10;
  return ((2 * p + (b & 1)) & 255) | (j - 13 * cp) << 8 | (2 * cp + (b & 1)) << 12 | (b >> 7) << 16;
}
#define CTX() asm volatile("" : "+r"(ctx)); CTXU()
#define CTXU() int tid; asm volatile("mov.u32 %0, %%tid.x;" : "=r"(tid)); \
  const int lane = tid & 31, vb = ctx & 255, hg = (ctx >> 4) & 7, rt = ctx & 15, par = (ctx >> 3) & 1, mt = ctx & 7, rank = ctx & 1, \
  tb = (ctx >> 8) & 15, cb = (ctx >> 12) & 15; const bool main_cta = ctx < 65536; \
  (void)tid; (void)lane; (void)vb; (void)hg; (void)rt; (void)par; (void)mt; (void)rank; (void)tb; (void)cb; (void)main_cta
#define CTXW() CTX(); const int wg = warp >> 2, w = warp & 3, g = lane >> 2, t = lane & 3; const bool lead = (tid & 127) == 0; \
  (void)wg; (void)w; (void)g; (void)t; (void)lead

__global__ void __cluster_dims__(2, 1, 1) __launch_bounds__(512, 1)
fused_kernel(const uint16_t* __restrict__ xq, const uint16_t* __restrict__ wqkv, const uint16_t* __restrict__ gate_w, const __grid_constant__ Maps M, const uint16_t* __restrict__ shift_k, const uint16_t* __restrict__ ssm_k, const uint16_t* __restrict__ ssm_D,
             const uint16_t* __restrict__ kin, const uint16_t* __restrict__ vin, uint16_t* __restrict__ outp) {
  extern __shared__ __align__(1024) uint8_t smem_raw[];
  const uint32_t sb = smem_u32(smem_raw);
  const uint32_t t0 = clk();
  auto get_epoch = [&]() { mbar_wait(sb + B_EP, 0); return lds32(sb + O_EPOCH); };

  auto p1_load_x = [&](int ks, int p, int rank) {
    tma3(sb + o_px(ks), &M.x_par, ks * 32, (p >> 2) & 1, (p & 3) * 256 + rank * 128, sb + B_FULL + 8 * (ks & 7));
  };
  auto p1_load_w = [&](int ks, int p, int rank) {
    const uint32_t st = sb + o_pw(ks), fb = sb + B_FULL + 8 * (ks & 7);
    tma3_mc(st + rank * 6144, &M.w_main, (p >> 3) * 80 + 2 * (p & 8), ks * 32 + rank * 16, 0, fb);
    tma3_mc(st + 12288 + rank * 1536, &M.w_tail, (p >> 3) * 80 + 8 * (~p & 8), ks * 32 + rank * 16, 0, fb);
  };
  auto cta_pair = [&]() { return pair_of(blockIdx.x >> 1); };

  const uint16_t* pfp = nullptr;
  if (threadIdx.x < 32) {
    const unsigned b = blockIdx.x, l = threadIdx.x;
    pfp = l < 16 ? xq + (16 * b + l) * 640 : wqkv + (15 * b + l - 16) * 64;
    if ((l | b >> 7 << 5) < 31) pf_l2(pfp);
  }
  const int warp = __shfl_sync(~0u, threadIdx.x >> 5, 0);
  if ((warp & 14) == 8) {
    if (elect_one()) {
#pragma unroll
      for (int s = 0; s < 8; s++) mbar_init(sb + O_BAR - 512 + 64 * warp + 8 * s, 5 * warp - 39);
      asm volatile("fence.mbarrier_init.release.cluster;" ::: "memory");
    }
    __syncwarp();
  }
  asm volatile("barrier.cluster.arrive.relaxed.aligned;" ::: "memory");
  if (warp == 8 && blockIdx.x < 128) {
    const int p = cta_pair(), rank = blockIdx.x & 1;
    if (elect_one()) { mbar_expect_tx(sb + B_FULL, 16384 + WST); p1_load_x(0, p, rank); }
    __syncwarp();
    asm volatile("barrier.cluster.wait.aligned;" ::: "memory");
    if (elect_one()) { p1_load_w(0, p, rank); PT(100); }
    __syncwarp();
  } else if (warp != 15) {
    asm volatile("barrier.cluster.wait.aligned;" ::: "memory");
    spin_until(t0, HOLD);
  }
  auto init_rest = [&]() {
    if (warp >= 11 && elect_one()) {
#pragma unroll
      for (int s = 0; s < 12; s++) mbar_init(sb + O_BAR + 128 - 11 * 96 + 96 * warp + 8 * s, warp == 14 ? 2 : 1);
      asm volatile("fence.mbarrier_init.release.cluster;" ::: "memory");
    }
    __syncwarp();
    bar_sync(0, blockIdx.x < 128 ? 224 : 512);
  };
  uint32_t ctx = 0;

  if (warp < 8) {
    if (PF2 && warp == 0) {
#pragma unroll 1
      for (int i = 1; i <= NPF; i++) {
        spin_until(t0, PF2 + (i - 1) * PFD);
        if ((threadIdx.x | blockIdx.x >> 7 << 5) < 31) pf_l2(pfp + (threadIdx.x < 16 ? 64 : 64 * 1920) * i);
        __syncwarp();
      }
    }
    reg_inc<RC>();
    ctx = make_ctx();
    if (blockIdx.x >= 128) bar_sync(0, 512);
    else {
      {
        uint32_t Q[10][2], K[10][2], V[10][2];
        {
          {
            float acc[120];
            {
              CTXW();
              const uint32_t aa = sb + (warp * 16 + (lane & 15)) * 128 + (((lane >> 4) ^ (lane & 7)) << 4);
              const uint32_t rsb = mapa(sb, (blockIdx.x & 1) ^ 1);
              uint32_t a0[8], a1[8], a2[8];
              auto load_a = [&](uint32_t (&r)[8], int ks) {
                mbar_wait(sb + B_FULL + 8 * (ks & 7), (ks >> 3) & 1);
                PTP(lead && (wg || !(ks & 3)), wg ? 60 + ks : 80 + (ks >> 2));
                if (SSMASK >> ks & 1) return;
                ldsm4(r[0], r[1], r[2], r[3], (aa ^ ((ks & 1) * 64)) + o_px(ks)); ldsm4(r[4], r[5], r[6], r[7], (aa ^ ((ks & 1) * 64 + 32)) + o_px(ks));
              };
              auto stage = [&](uint32_t (&r)[8], uint32_t (&nx)[8], int ks, int u) {
                const uint32_t dl = o_pw(ks) >> 4;
                const uint64_t db = mkdesc(SB, 2048, 1024, 1), dt = mkdesc(SB + 12288, 512, 256, 3);
                auto D = [&](uint64_t d) { return (d & ~0xFFFFFFFFull) | (uint32_t)((uint32_t)d + dl); };
                if (LEAD && u == (20 - LEAD) % 3) bar_sync_p(wg == 0 && ks == 20 - LEAD, NB_LEAD, 256);
                wg_fence();
                const uint64_t da = mkdesc(SB + o_px(ks) + (ks & 1) * 64, 16, 1024, 1) + wg * 512;
                if (SSMASK >> ks & 1) { wgmma_ss_n192<0, 0, 1>(acc, da, D(db), ks); wgmma_ss_n48<96, 0, 1>(acc, da, D(dt), ks); }
                else { wgmma_rs_n192<0, 1>(acc, r[0], r[1], r[2], r[3], D(db), ks); wgmma_rs_n48<96, 1>(acc, r[0], r[1], r[2], r[3], D(dt), ks); }
                wg_commit();
                if (LEAD && u == 1) bar_arrive_p(wg && ks == 19, NB_LEAD, 256);
                if (ks < 19) load_a(nx, ks + 1);
                wg_fence();
                if (SSMASK >> ks & 1) { wgmma_ss_n192<0, 0, 1>(acc, da + 2, D(db + 384), 1); wgmma_ss_n48<96, 0, 1>(acc, da + 2, D(dt + 96), 1); }
                else { wgmma_rs_n192<0, 1>(acc, r[4], r[5], r[6], r[7], D(db + 384), 1); wgmma_rs_n48<96, 1>(acc, r[4], r[5], r[6], r[7], D(dt + 96), 1); }
                wg_commit();
                wg_wait<2>();
                mbar_arrive2_p(lead && (u || ks), sb + B_EMPTY + 8 * ((ks - 1) & 7), rsb + B_EMPTY + 8 * ((ks - 1) & 7));
              };
              if (lead) PT(1 + wg);
              load_a(a0, 0);
              constexpr int p1u = P1U;
#pragma unroll p1u
              for (int ks = 0; ks < 21; ks += 3) {
                stage(a0, a1, ks, 0);
                stage(a1, a2, ks + 1, 1);
                if (ks == 18) break;
                stage(a2, a0, ks + 2, 2);
              }
              mbar_wait(sb + B_S15, 1);
              wg_wait<1>();
              mbar_arrive_p(tid == 0, sb + B_P1E);
              wg_wait<0>();
              fence_regs(acc);
              mbar_arrive2_p(lead, sb + B_S19, rsb + B_S19);
              PTPL(lead, 50 + wg);
            }
            CTXW();
            if (hg & 1) pack_qkv<1, 0>(acc, Q, K, V); else pack_qkv<0, 0>(acc, Q, K, V);
            if (warp == 7 && rank) {
              uint4* hp = g_halo + vb * 160 + lane;
              st_relaxed(hp, K[0][1], K[1][1], K[3][1], K[4][1]); st_relaxed(hp + 32, K[5][1], K[6][1], K[8][1], K[9][1]);
              st_relaxed(hp + 64, K[2][1], K[7][1], V[0][1], V[1][1]);
              st_relaxed(hp + 96, V[2][1], V[3][1], V[4][1], V[5][1]); st_relaxed(hp + 128, V[6][1], V[7][1], V[8][1], V[9][1]);
              PTPL(lane == 0, 25);
            }
            const uint32_t ho = sb + O_HALO + warp * 2560 + lane * 16;
            stsm4(ho, K[0][1], K[1][1], K[3][1], K[4][1]); stsm4(ho + 512, K[5][1], K[6][1], K[8][1], K[9][1]);
            stsm4(ho + 1024, K[2][1], K[7][1], V[0][1], V[1][1]);
            stsm4(ho + 1536, V[2][1], V[3][1], V[4][1], V[5][1]); stsm4(ho + 2048, V[6][1], V[7][1], V[8][1], V[9][1]);
            if (warp == 7) {
              if (!rank) {
                fence_async_smem();
                __syncwarp();
                if (elect_one())
                  asm volatile("cp.async.bulk.shared::cluster.shared::cta.mbarrier::complete_tx::bytes [%0], [%1], 2560, [%2];"
                               ::"r"(mapa(sb + O_HIN, 1)), "r"(sb + O_HALO + 7 * 2560), "r"(mapa(sb + B_HX0, 1)) : "memory");
              }
              __syncwarp();
            } else {
              __syncwarp();
              if (lane == 0) mbar_arrive(sb + B_HX + 8 + 8 * warp);
            }
            if (hg & 1) pack_qkv<1, 1>(acc, Q, K, V); else pack_qkv<0, 1>(acc, Q, K, V);
#pragma unroll
            for (int f = 0; f < 10; f++) V[f][0] = movm(V[f][0]);
            if (lead) PT(52 + wg);
            if (wg) mbar_wait(sb + B_P1E, 0);
          }
          CTXW();
          const bool gt0 = 2 * t > g, gt1 = 2 * t + 1 > g;
          const uint32_t pmask = (gt0 ? 0xFFFFu : 0u) | (gt1 ? 0xFFFF0000u : 0u);
          uint32_t Qh[4][2];
          float lg[8][2];
#pragma unroll
          for (int j = 0; j < 4; j++) {
            const int fa = (j >> 1) * 5 + (j & 1) * 3, fh = (j >> 1) * 5 + 2;
            const bool mine = (j & 1) ? (t >= 2) : (t < 2);
            Qh[j][0] = mine ? Q[fh][0] : 0u; Qh[j][1] = mine ? Q[fh][1] : 0u;
            float c1[4] = {0.f, 0.f, 0.f, 0.f}, c2[4] = {0.f, 0.f, 0.f, 0.f};
            mma16(c1, Q[fa][0], Q[fa][1], Q[fa + 1][0], Q[fa + 1][1], K[fa][0], K[fa + 1][0]);
            mma16(c2, Q[fa][0], Q[fa][1], Q[fa + 1][0], Q[fa + 1][1], K[fa][1], K[fa + 1][1]);
            mma8(c1, Qh[j][0], Qh[j][1], K[fh][0]);
            mma8(c2, Qh[j][0], Qh[j][1], K[fh][1]);
            lg[j][0] = c1[0]; lg[j][1] = c1[1];
            lg[4 + j][0] = gt0 ? c1[2] : c2[2]; lg[4 + j][1] = gt1 ? c1[3] : c2[3];
          }
          if (lead) PT(54 + wg);
          mbar_wait(sb + (warp ? B_HX + 8 * warp : B_HX0), 0);
          if (lead) PT(56 + wg);
          const uint32_t hs = warp ? O_HALO + (warp - 1) * 2560 : O_HIN, ha = sb + hs + lane * 16;
          const uint32_t va = sb + ((lane & 8) ? O_HALO + warp * 2560 : hs) + 1280 + (lane >> 4) * 128 + (lane & 7) * 16;
          uint32_t Kh[10], Vh[10];
          ldsm4(Kh[0], Kh[1], Kh[3], Kh[4], ha); ldsm4(Kh[5], Kh[6], Kh[8], Kh[9], ha + 512);
          asm volatile("ldmatrix.sync.aligned.m8n8.x2.shared.b16 {%0,%1}, [%2];" : "=r"(Kh[2]), "=r"(Kh[7]) : "r"(ha + 1024) : "memory");
#pragma unroll
          for (int i = 0; i < 5; i++) ldsm4t(Vh[2 * i], V[2 * i][1], Vh[2 * i + 1], V[2 * i + 1][1], va + i * 256);
          const bool have_halo = warp > 0 || mt > 0;
#pragma unroll
          for (int j = 0; j < 4; j++) {
            const int fa = (j >> 1) * 5 + (j & 1) * 3, fh = (j >> 1) * 5 + 2;
            float c0[4] = {0.f, 0.f, 0.f, 0.f};
            mma16(c0, Q[fa][0], Q[fa][1], Q[fa + 1][0], Q[fa + 1][1], Kh[fa], Kh[fa + 1]);
            mma8(c0, Qh[j][0], Qh[j][1], Kh[fh]);
            if (!have_halo) c0[0] = c0[1] = -INFINITY;
            lg[j][0] = gt0 ? c0[0] : lg[j][0]; lg[j][1] = gt1 ? c0[1] : lg[j][1];
          }
          uint32_t Pv[8], O[10][2];
          softmax8(lg, Pv);
#pragma unroll
          for (int j = 0; j < 4; j++) {
            const int fa = (j >> 1) * 5 + (j & 1) * 3, fh = (j >> 1) * 5 + 2;
            const uint32_t a0 = Pv[j] & pmask, a2 = Pv[j] & ~pmask, a3 = Pv[4 + j] & pmask, a5 = Pv[4 + j] & ~pmask;
#pragma unroll
            for (int q = 0; q < 3; q++) {
              const int f = q < 2 ? fa + q : fh;
              float o[4] = {0.f, 0.f, 0.f, 0.f};
              mma8(o, a2, a3, V[f][0]);
              mma16(o, a0, 0u, 0u, a5, Vh[f], V[f][1]);
              const uint32_t o0 = pack_bf16(o[0], o[1]), o1 = pack_bf16(o[2], o[3]);
              if (q < 2 || !(j & 1)) { O[f][0] = o0; O[f][1] = o1; }
              else { O[f][0] = t >= 2 ? o0 : O[f][0]; O[f][1] = t >= 2 ? o1 : O[f][1]; }
            }
          }
          {
            uint32_t z = threadIdx.y;
#pragma unroll
            for (int f = 0; f < 10; f++) z &= O[f][0];
            bar_arrive_p(wg == 0, NB_HALO + z, 256);
          }
          const uint32_t oa = sb + O_OST + (warp * 16 + (lane & 15)) * 160 + (lane >> 4) * 16;
#pragma unroll
          for (int i = 0; i < 5; i++) stsm4(oa + i * 32, O[2 * i][0], O[2 * i][1], O[2 * i + 1][0], O[2 * i + 1][1]);
        }
      }
      {
        CTXW();
        fence_async_smem();
        bar_arrive(NB_ATT, 288);
        if (lead) PT(58 + wg);
        const uint32_t abase = sb + (g & 1) * 4160 + 4 * (1023 - 4 - 8 * w - (g >> 1) + t);
        float acc[128];
        uint32_t a0[8], a1[8], a2[8], a3[8];
#pragma unroll 1
        for (int c = wg ^ 1; c < 5; c += 2) {
          const uint32_t ab = abase + o_h(c);
          const uint32_t db = __shfl_sync(~0u, ((SB + o_u(c) + UZ - 16) >> 4) | 0x10000u, 0);
          mbar_wait(sb + B_U + 8 * c, 0);
          load_pair<0>(a0, ab); load_pair<1>(a1, ab);
          load_pair<2>(a2, ab); load_pair<3>(a3, ab);
          if (lead) PT(85 + c);
          bar_sync(c ? NB_TOK + wg : NB_HALO, 256);
          fence_regs(acc);
          auto tok = [&](int p) { if (p == TOKP) bar_arrive_p(P3GO == 0 || c < 4, NB_TOK + (wg ^ 1), 256); };
          const uint32_t an = abase + o_h(c + 2);
          auto nxt = [&](auto P, uint32_t (&a)[8]) {
#pragma unroll
            for (int i = 0; i < 8; i++)
              asm volatile("{\n.reg .pred p;\nsetp.ne.b32 p, %2, 0;\n@p ld.shared.b32 %0, [%1];\n}" : "+r"(a[i]) : "r"(an + a_off(P, i)), "r"((int)(c < 3)));
          };
          mma_pair<0>(acc, a0, db);
          mma_pair<1>(acc, a1, db); wg_wait<1>();  load_pair<4>(a0, ab);
          if (lead) PT(90 + c);
          mma_pair<2>(acc, a2, db); wg_wait<1>();  load_pair<5>(a1, ab);
          mma_pair<3>(acc, a3, db); tok(3); wg_wait<1>();  load_pair<6>(a2, ab);
          mma_pair<4>(acc, a0, db); tok(4); wg_wait<1>();  load_pair<7>(a3, ab);
          mma_pair<5>(acc, a1, db); tok(5);
          mma_pair<6>(acc, a2, db); tok(6);
          mma_pair<7>(acc, a3, db);
          if (P3GO == 5) wg_wait<1>();
          if (P3GO == 3 || P3GO == 5) bar_arrive_p(c == 4, NB_TOK, 256);
          wg_wait<0>();
          if (P3GO == 4) bar_arrive_p(c == 4, NB_TOK, 256);
          fence_regs(acc);
          PTPL(lead, 95 + c);
          bar_sync(NB_RFREE + wg, 256);
          const uint32_t pb = sb + (w < 2 ? o_h(c) + w * 4160 : w == 2 ? o_u(c) : o_x(c)) + lane * 16;
          if (lane < 2 * w) sts128(pb, 0, 0, 0, 0);
#pragma unroll
          for (int q = 0; q < 8; q++) {
            uint32_t p[4];
#pragma unroll
            for (int i = 0; i < 4; i++) {
              const int nu = 4 * q + i;
              float v0 = acc[4 * nu], v1 = acc[4 * nu + 1];
              p[i] = pack_bf16(v0, v1);
              if (nu > 0) p[i] = hadd2(p[i], pack_bf16(acc[4 * nu - 2], acc[4 * nu - 1]));
            }
            stsm4t(pb + w * 32 + q * 512, p[0], p[1], p[2], p[3]);
            if (HALVES && q == 3) bar_arrive(NB_RFULL + 4 + wg, 256);
          }
          bar_arrive(NB_RFULL + wg, 256);
          if (P3GO == 1 && c == 4) bar_arrive(NB_TOK, 256);
          if (lead) PT(140 + c);
        }
      }
    }
    if (warp < 4) {
      CTXW();
      const uint32_t rsb = mapa(sb, (blockIdx.x & 1) ^ 1);
      const uint32_t ba = sb + O_BT + ((lane >> 4) * 8 + (lane & 7)) * 128 + (((2 * w + ((lane >> 3) & 1)) ^ ((lane & 1) << 2 | (lane >> 1 & 3))) << 4);
      mbar_wait(sb + B_P3F, 0);
      if (lead) PT(145);
      float acc[80];
#pragma unroll
      for (int ks = 0; ks < 10; ks++) {
        if (ks == NPRE) {
          if (NPRE) { wg_wait<0>(); mbar_arrive2_p(lead, sb + B_P3E + 8 * NPRE, rsb + B_P3E + 8 * NPRE); }
          bar_sync_p(blockIdx.x < 128, NB_TOK, 256);
        }
        PTP(lead, 146 + ks);
        const uint64_t da = mkdesc(SB + o_p3(ks), 1024, 1024, 1), db = mkdesc(SB + o_p3(ks) + 8192, 16, 1024, 1);
        wg_fence();
#pragma unroll
        for (int j = 0; j < 4; j++) wgmma_ss_n160<0, 1, 0>(acc, da + j * 128, db + j * 2, j | ks);
        wg_commit();
        if (ks < 9) mbar_wait(sb + B_P3F + 8 * (ks + 1), 0);
        if (ks >= 1 && ks <= 4 && ks != NPRE) { wg_wait<1>(); mbar_arrive2_p(lead, sb + B_P3E + 8 * ks, rsb + B_P3E + 8 * ks); }
      }
      wg_wait<0>();
      fence_regs(acc);
      PTPL(lead, 156);
#pragma unroll
      for (int i = 0; i < 10; i++) {
        stsm4t(ba + i * 2048, pack_bf16(acc[8 * i], acc[8 * i + 1]), pack_bf16(acc[8 * i + 2], acc[8 * i + 3]),
               pack_bf16(acc[8 * i + 4], acc[8 * i + 5]), pack_bf16(acc[8 * i + 6], acc[8 * i + 7]));
        if (i & 1) bar_arrive(1 + (i >> 1), 256);
      }
      if (lead) PT(157);
    }
  } else if (warp < 12) {
    reg_dec<RH>();
    const int hw = warp - 8;
    init_rest();
    ctx = __shfl_sync(~0u, make_ctx(), 0);
    if (ctx < 65536) {
      CTXU();
      if (hw == 0 && rank) {
#pragma unroll
        for (int f = 0; f < 5; f++) st_relaxed(g_halo + vb * 160 + lane + 32 * f, ~0u, ~0u, ~0u, ~0u);
      }
#pragma unroll 1
      for (int c = hw; c < 5; c += 4) {
        const int kb = 2 * c + (vb >> 6);
        const uint4 sk = __ldg((const uint4*)(shift_k + (size_t)(kb * 64 + 2 * lane) * 4));
        wait_until(t0, KT0 + c * KTD + ((((vb * KPH) & 63) * KTD) >> 6));
        if (lane == 0) PT(20 + c);
        kv_task(&M.kv_st, kin, vin, sk, kb, vb & 63, sb + o_kst(hw), lane);
        if (lane == 0) PT(30 + c);
      }
      if (lane == 0) mbar_arrive(sb + B_KVD + 8 * hw);
    }
    CTXU();
    const int g = lane >> 2, t = lane & 3, row = 8 * hw + g;
    const uint32_t go = (tb * 160 + row) * 80 + cb * 8 + t;
    uint4 T[10];
    auto load_q = [&]() {
#pragma unroll
      for (int i = 0; i < 10; i++) {
        T[i] = make_uint4(0, 0, 0, 0);
        if (i < 8 || tb < 12) asm volatile("ld.volatile.global.v4.b32 {%0,%1,%2,%3}, [%4];" : "=r"(T[i].x), "=r"(T[i].y), "=r"(T[i].z), "=r"(T[i].w) : "l"((const uint4*)xq + go + (i >> 1) * 2560 + (i & 1) * 4));
      }
    };
    if (main_cta) {
      bar_arrive(NB_RFREE, 256);
      bar_arrive(NB_RFREE + 1, 256);
      const int yrow = (vb & 0x61) | (vb & 6) << 2 | (vb >> 2 & 6);
      auto red = [&](int c) {
        const int wg = (c & 1) ^ 1;
        conv_reduce(sb, c, tid - 256, 128 * c + yrow, NB_RFULL + wg);
        if (P3GO == 2 && c == 4) bar_arrive(NB_TOK, 256);
        __syncwarp();
        if (lane == 0) flag_add(CNT_Y(4 * c + (vb >> 5)), 1);
        if (tid == 256) PTL(41 + c);
        if (c < 3) bar_arrive(NB_RFREE + wg, 256);
        if (c == 2) {
          bar_sync(NB_HELP, 128);
          if (tid == 256) { mbar_arrive(sb + B_P3E); mbar_arrive_remote(sb + B_P3E, rank ^ 1); }
        }
      };
#pragma unroll 1
      for (int c = 0; c < QC; c++) red(c);
      load_q();
#pragma unroll 1
      for (int c = QC; c < 5; c++) red(c);
    } else load_q();
    uint32_t G[5];
    mbar_wait(sb + B_G, 0);
#pragma unroll
    for (int q = 0; q < 5; q++) { uint16_t v; asm volatile("ld.shared.u16 %0, [%1];" : "=h"(v) : "r"(sb + O_GT + (32 * q + row) * 2)); G[q] = prmt(v, 0, 0x1010); }
#pragma unroll
    for (int i = 0; i < 10; i++) { const uint32_t c = G[i >> 1]; T[i] = make_uint4(hmul2(T[i].x, c), hmul2(T[i].y, c), hmul2(T[i].z, c), hmul2(T[i].w, c)); }
#pragma unroll
    for (int h = 0; h < 2; h++) {
      mbar_wait(sb + B_Y + 8 * h, 0);
      if (tid == 256) PT(46);
#pragma unroll
      for (int q = 0; q < 5; q++) {
        uint32_t y0, y1, y2, y3;
        ldsm4t(y0, y1, y2, y3, sb + O_Y + h * 10240 + q * 2048 + lane * 64 + ((hw ^ ((lane >> 1) & 3)) << 4));
        uint4& r = T[2 * q + h];
        r = make_uint4(hmul2(r.x, y0), hmul2(r.y, y1), hmul2(r.z, y2), hmul2(r.w, y3));
      }
    }
    const uint32_t so = sb + O_BT + row * 128 + ((t ^ ((g & 1) << 2 | g >> 1)) << 4);
    if (tid == 256) PTL(47);
#pragma unroll
    for (int q = 0; q < 5; q++) {
      const uint32_t c = hfma2(G[q], 0xBF80BF80u, 0x3F803F80u);
      bar_sync(1 + q, 256);
      if (q == 4) mbar_arrive_p(tid == 256, sb + B_DONE);
#pragma unroll
      for (int h = 0; h < 2; h++) {
        uint4 u;
        lds128((so ^ (h * 64)) + q * 4096, u.x, u.y, u.z, u.w);
        const uint4& r = T[2 * q + h];
        if (q < 4 || tb < 12) ((uint4*)outp)[go + q * 2560 + h * 4] = make_uint4(hfma2(u.x, c, r.x), hfma2(u.y, c, r.y), hfma2(u.z, c, r.z), hfma2(u.w, c, r.w));
      }
    }
  } else {
    reg_dec<RP>();
    if (warp == 15) {
      const int p = cta_pair(), rank = blockIdx.x & 1;
      asm volatile("barrier.cluster.wait.aligned;" ::: "memory");
      if (blockIdx.x >= 128) bar_sync(0, 512);
      else {
#pragma unroll 1
        for (int ks = 1;; ks += 2) {
          mbar_wait(sb + B_EMPTY + 8 * (ks & 7), ((ks >> 3) & 1) ^ 1);
          spin_until(t0, PT1 + (ks - 1) * PTD);
          if (elect_one()) { mbar_expect_tx(sb + B_FULL + 8 * (ks & 7), WST); p1_load_w(ks, p, rank); PT(100 + ks); }
          if (ks == HT && elect_one()) mbar_arrive(sb + B_LAST);
          if (ks == 19) break;
          const int kn = ks + 1;
          mbar_wait(sb + B_EMPTY + 8 * (kn & 7), ((kn >> 3) & 1) ^ 1);
          spin_until(t0, PT1 + ks * PTD - PTE);
          if (elect_one()) { mbar_expect_tx(sb + B_FULL + 8 * (kn & 7), 16384 + WST); p1_load_x(kn, p, rank); p1_load_w(kn, p, rank); PT(100 + kn); }
        }
        mbar_wait(sb + B_S19, 0);
      }
    } else init_rest();
    ctx = __shfl_sync(~0u, make_ctx(), 0);
    CTXU();
    if (warp == 12) {
        unsigned epoch = 0;
      if (lane == 0) {
        if ((sb & 0xFFFFFF) != SB) __trap();
        epoch = *(volatile unsigned*)(g_launch + blockIdx.x) + 1;
        *(volatile unsigned*)(g_launch + blockIdx.x) = epoch;
        sts32(sb + O_EPOCH, epoch);
        mbar_arrive(sb + B_EP);
#pragma unroll 1
        for (int i = 3; i < 8; i++) asm volatile("prefetch.tensormap [%0];" ::"l"(&M.x_par + i) : "memory");
      }
      __syncwarp();
      if (main_cta) {
        uint4 h0 = make_uint4(0, 0, 0, 0);
        if (lane < 5) {
          h0 = __ldg((const uint4*)(ssm_k + (size_t)(128 * lane + vb) * 2048));
          h0.x = prmt(pack_bf16(bf_lo(h0.x) + bf_lo(__ldg(ssm_D + 128 * lane + vb)), 0.f), h0.x, 0x7610);
        }
        epoch = __shfl_sync(~0u, epoch, 0);
        mbar_wait(sb + B_LAST, 0);
        mbar_wait(sb + B_S13, 1);
#pragma unroll 1
        for (int c = 0; c < 5; c++) {
          if (c == 0 || c == 3) mbar_wait(sb + B_KVD + (c ? 16 : 8), 0);
          sts128(sb + o_u(c) + lane * 16, 0, 0, 0, 0);
          if (lane < 3) sts128(sb + (lane < 2 ? o_h(c) + lane * 4160 + 4096 : o_u(c) + 512), 0, 0, 0, 0);
          if (lane == c) sts128(sb + o_u(c) + UZ, h0.x, h0.y, h0.z, h0.w);
          fence_async_smem();
          __syncwarp();
          if (elect_one()) {
            mbar_expect_tx(sb + B_U + 8 * c, 3 * 4096 - 16);
            bulk_load(sb + o_u(c) + UZ + 16, ssm_k + (size_t)(128 * c + vb) * 2048 + 8, 4080, sb + B_U + 8 * c);
          }
          flag_wait(CNT_KV(2 * c + (vb >> 6)), 64 * epoch);
          __syncwarp();
          if (elect_one()) {
            bulk_load(sb + o_h(c), g_kvT + (size_t)(128 * c + vb) * 2048, 4096, sb + B_U + 8 * c);
            bulk_load(sb + o_h(c) + 4160, g_kvT + (size_t)(640 + 128 * c + vb) * 2048, 4096, sb + B_U + 8 * c);
            PT(10 + c);
          }
        }
      }
    } else if (warp != 15) {
        const int r = warp - 13;
      if (main_cta) {
        if (rank && lane == 0) mbar_expect_tx(sb + B_HX0, 1280);
        const int t = lane & 3, grow = hg * 16 + (lane & 15);
        const uint32_t ga = sb + grow * 128 + (((4 * r + (lane >> 4)) ^ (lane & 7)) << 4);
        const uint32_t gp = sb + O_GW + 64 * r + 4 * t;
        float s0 = 0.f, s1 = 0.f;
        {
          const int o = (lane >> 3) * 128 + 64 * r + (lane & 7) * 8;
          uint2 wv[3];
#pragma unroll
          for (int i = 0; i < 3; i++) if (i < 2 || lane < 16) wv[i] = __ldg((const uint2*)((const char*)gate_w + o + i * 512));
#pragma unroll
          for (int i = 0; i < 3; i++) if (i < 2 || lane < 16) asm volatile("st.shared.v2.b32 [%0], {%1,%2};" ::"r"(sb + O_GW + o + i * 512), "r"(wv[i].x), "r"(wv[i].y) : "memory");
          __syncwarp();
        }
#pragma unroll 1
        for (int ks = 0; ks < 20; ks += 2) {
          uint32_t x[8], gw[4];
#pragma unroll
          for (int i = 0; i < 4; i++) gw[i] = lds32(gp + ks * 64 + i * 16);
          mbar_wait_wd(sb + B_FULL + 8 * (ks & 7), (ks >> 3) & 1, t0);
          if (r == 0 && lane == 0) PT(120 + ks);
          ldsm4(x[0], x[1], x[2], x[3], ga + o_px(ks)); ldsm4(x[4], x[5], x[6], x[7], (ga ^ 32) + o_px(ks));
#pragma unroll
          for (int i = 0; i < 8; i++) x[i] = hmul2(x[i], gw[i >> 1]);
          if (lane < 2) mbar_arrive(sb + B_EMPTY + 8 * (ks & 7) + 8 * lane + (x[0] & x[7] & threadIdx.y));
#pragma unroll
          for (int i = 0; i < 8; i += 4) {
            s0 += (bf_lo(x[i]) + bf_hi(x[i])) + (bf_lo(x[i + 2]) + bf_hi(x[i + 2]));
            s1 += (bf_lo(x[i + 1]) + bf_hi(x[i + 1])) + (bf_lo(x[i + 3]) + bf_hi(x[i + 3]));
          }
        }
        s0 += __shfl_xor_sync(~0u, s0, 1); s1 += __shfl_xor_sync(~0u, s1, 1);
        s0 += __shfl_xor_sync(~0u, s0, 2); s1 += __shfl_xor_sync(~0u, s1, 2);
        if (t < 2) sts32(sb + O_GP + r * 64 + (8 * t + (lane >> 2)) * 4, __float_as_uint(t ? s1 : s0));
        if (r == 0) bar_arrive(NB_G, 64);
        if (!rank) {
          uint4 d[3];
          if (mt > 0) {
            const uint4* hp = g_halo + (vb - 1) * 160 + r * 64 + lane;
            mbar_wait_wd(sb + B_EP, 0, t0);
            const unsigned target = 64 * lds32(sb + O_EPOCH);
            unsigned v;
            do {
              asm volatile("ld.relaxed.gpu.global.u32 %0, [%1];" : "=r"(v) : "l"(CNT_KV(vb >> 6)) : "memory");
              if (clk() - t0 > 0x70000000u) __trap();
            } while ((int)(v - target) < 0);
            mbar_wait_wd(sb + B_HX + 56, 0, t0);
            if (HDL) { const uint32_t t1 = clk(); spin_until(t1, HDL); }
            PTPL(lane == 0 && r == 1, 26);
            for (;;) {
              bool ok = true;
#pragma unroll
              for (int f = 0; f < 3; f++) {
                asm volatile("ld.relaxed.gpu.global.v4.b32 {%0,%1,%2,%3}, [%4];" : "=r"(d[f].x), "=r"(d[f].y), "=r"(d[f].z), "=r"(d[f].w) : "l"(hp + 32 * f) : "memory");
              }
#pragma unroll
              for (int f = 0; f < 3; f++) ok = ok && max(max(d[f].x, d[f].y), max(d[f].z, d[f].w)) != ~0u;
              if (__all_sync(~0u, ok)) break;
              PTPL(lane == 0 && r == 1, 27);
              if (clk() - t0 > 0x70000000u) __trap();
            }
          } else {
#pragma unroll
            for (int f = 0; f < 3; f++) d[f] = make_uint4(0, 0, 0, 0);
          }
#pragma unroll
          for (int f = 0; f < 3; f++) stsm4(sb + O_HIN + r * 1024 + f * 512 + lane * 16, d[f].x, d[f].y, d[f].z, d[f].w);
          __syncwarp();
          if (lane == 0) { mbar_arrive(sb + B_HX0); PTL(15 + r); }
        }
        if (r == 1) {
          bar_sync(NB_G, 64);
          if (lane < 16) {
            const uint32_t pa = sb + O_GP + lane * 4;
            const float z = __uint_as_float(lds32(pa)) + __uint_as_float(lds32(pa + 64));
            g_gate[2 * (mt * 128 + hg * 16 + lane) + par] = (uint16_t)pack_bf16(__fdividef(1.f, 1.f + __expf(-bf_lo(pack_bf16(z, 0.f)))), 0.f);
          }
          __syncwarp();
          if (lane == 0) flag_add(CNT_O(rt), 1);
        }
      }
      if (elect_one()) {
        mbar_wait_wd(sb + B_EP, 0, t0);
        const unsigned epoch = lds32(sb + O_EPOCH);
        if (main_cta) mbar_wait_wd(sb + B_P3E, 0, t0);
        unsigned v;
        do {
          asm volatile("ld.relaxed.gpu.global.u32 %0, [%1];" : "=r"(v) : "l"(CNT_Y(2 * cb + r)) : "memory");
          if (clk() - t0 > 0x70000000u) __trap();
        } while ((int)(v - 128 * epoch) < 0);
        mbar_expect_tx(sb + B_Y + 8 * r, 10240);
        tma3(sb + O_Y + r * 10240, &M.y_ld, 0, cb * 64 + 32 * r, tb * 5, sb + B_Y + 8 * r);
        PTL(17 + r);
        mbar_wait_wd(sb + B_DONE, 0, t0);
      }
    } else {
      const unsigned epoch = get_epoch();
      if (main_cta) bar_sync(NB_ATT, 288);
      if (elect_one()) {
        if (main_cta) {
          tma3_store(&M.o_st, hg * 80, par, mt * 128, sb + O_OST);
          bulk_commit(); bulk_wait_all();
          flag_add(CNT_O(rt), 1);
        }
        PT(3);
      }
      __syncwarp();
      if (lane < 4) flag_wait(CNT_O(8 * (lane & 1) + min(7, (80 * tb + 79 * (lane >> 1)) >> 7)), 16 * epoch);
      __syncwarp();
      if (elect_one()) {
        PT(4);
        mbar_arrive_remote(sb + B_P3R, rank ^ 1);
        mbar_expect_tx(sb + B_G, 320);
        bulk_load(sb + O_GT, g_gate + tb * 160, 320, sb + B_G);
      }
      mbar_wait(sb + B_P3R, 0);
#pragma unroll 1
      for (int ks = 0; ks < 10; ks++) {
        if (ks > 5 || (ks == 5 && main_cta)) mbar_wait(sb + B_P3E + 8 * (ks - 5), 0);
        if (elect_one()) {
          PTP(ks >= 5, ks);
          tma2_mc(sb + o_p3(ks) + 8192 + rank * 10240, &M.o_ld, ks * 64, tb * 160 + rank * 80, sb + B_P3F + 8 * ks);
          tma2(sb + o_p3(ks), &M.wo, cb * 64, ks * 64, sb + B_P3F + 8 * ks);
          mbar_expect_tx(sb + B_P3F + 8 * ks, P3S);
        }
      }
    }
  }
}

typedef CUresult (*PFN_enc)(CUtensorMap*, CUtensorMapDataType, cuuint32_t, void*, const cuuint64_t*, const cuuint64_t*, const cuuint32_t*,
                            const cuuint32_t*, CUtensorMapInterleave, CUtensorMapSwizzle, CUtensorMapL2promotion, CUtensorMapFloatOOBfill);
static void enc(PFN_enc f, CUtensorMap* m, const void* base, int rank, const cuuint64_t* dims, const cuuint64_t* strides, const cuuint32_t* box,
                CUtensorMapSwizzle sw) {
  const cuuint32_t es[5] = {1, 1, 1, 1, 1};
  f(m, CU_TENSOR_MAP_DATA_TYPE_BFLOAT16, rank, (void*)base, dims, strides, box, es, CU_TENSOR_MAP_INTERLEAVE_NONE, sw,
    CU_TENSOR_MAP_L2_PROMOTION_NONE, CU_TENSOR_MAP_FLOAT_OOB_FILL_NONE);
}

extern "C" void kernel_launch(void* const* d_in, const int* in_sizes, int n_in, void* d_out, int out_size) {
  (void)in_sizes; (void)n_in; (void)out_size;
  static PFN_enc f = nullptr;
  static void *kvT, *y2T, *o;
  if (!f) {
    void* p = nullptr;
    cudaDriverEntryPointQueryResult q;
    cudaGetDriverEntryPoint("cuTensorMapEncodeTiled", &p, cudaEnableDefault, &q);
    f = (PFN_enc)p;
    cudaGetSymbolAddress(&kvT, g_kvT); cudaGetSymbolAddress(&y2T, g_y2T); cudaGetSymbolAddress(&o, g_o);
    cudaFuncSetAttribute(fused_kernel, cudaFuncAttributeMaxDynamicSharedMemorySize, SMEM_BYTES);
  }
  Maps M;
  const CUtensorMapSwizzle S0 = CU_TENSOR_MAP_SWIZZLE_NONE, S32 = CU_TENSOR_MAP_SWIZZLE_32B, S64 = CU_TENSOR_MAP_SWIZZLE_64B, S128 = CU_TENSOR_MAP_SWIZZLE_128B;
  const cuuint64_t dpar[3] = {640, 2, 1024}, spar[2] = {1280, 2560};
  const cuuint64_t dw[3] = {640, 640, 3}, sw[2] = {3840, 1280};
  const cuuint64_t dnat[2] = {640, 2048}, snat[1] = {1280};
  const cuuint64_t dT[3] = {32, 640, 64}, dT2[3] = {32, 1280, 64}, sT[2] = {4096, 64};
  const cuuint64_t dwo[2] = {640, 640};
  { const cuuint32_t bx[3] = {64, 1, 128}; enc(f, &M.x_par, d_in[0], 3, dpar, spar, bx, S128); }
  { const cuuint32_t bx[3] = {64, 16, 3}; enc(f, &M.w_main, d_in[7], 3, dw, sw, bx, S128); }
  { const cuuint32_t bx[3] = {16, 16, 3}; enc(f, &M.w_tail, d_in[7], 3, dw, sw, bx, S32); }
  { const cuuint32_t bx[3] = {80, 1, 128}; enc(f, &M.o_st, o, 3, dpar, spar, bx, S0); }
  { const cuuint32_t bx[3] = {32, 64, 1}; enc(f, &M.kv_st, kvT, 3, dT2, sT, bx, S64); }
  { const cuuint32_t bx[3] = {32, 32, 5}; enc(f, &M.y_ld, y2T, 3, dT, sT, bx, S64); }
  { const cuuint32_t bx[2] = {64, 64}; enc(f, &M.wo, d_in[8], 2, dwo, snat, bx, S128); }
  { const cuuint32_t bx[2] = {64, 80}; enc(f, &M.o_ld, o, 2, dnat, snat, bx, S128); }
  fused_kernel<<<130, 512, SMEM_BYTES, cudaStreamPerThread>>>((const uint16_t*)d_in[0], (const uint16_t*)d_in[7], (const uint16_t*)d_in[9], M, (const uint16_t*)d_in[3], (const uint16_t*)d_in[4], (const uint16_t*)d_in[5],
                                                              (const uint16_t*)d_in[1], (const uint16_t*)d_in[2], (uint16_t*)d_out);
}
```

```cpp
#include <cuda_runtime.h>
#include <cuda_bf16.h>
#include <cuda.h>
#include <stdint.h>

#define DEVI __device__ __forceinline__
#define PT1 100
#define PTD 460
#define PTE 200
#define PF2 0
#define NPF 1
#define PFD 0
#define SSMASK 0
static_assert((SSMASK & 0xAAA) == 0, "an x tile is refilled as soon as its even stage is released");
#define HT 19
#define KPH 37
#define CV 0
#define TOKP 6
#define NPRE 0
#define P3GO 0
#define QC 0
#define HALVES 0
#define HDL 0
#define KT0 1500
#define KTD 1100
#define RC 192
#define RH 96
#define RP 32
#define HOLD 750
#define P1U 7
#define LEAD 3

DEVI uint32_t smem_u32(const void* p) { return (uint32_t)__cvta_generic_to_shared(p); }
DEVI void wg_fence() { asm volatile("wgmma.fence.sync.aligned;" ::: "memory"); }
DEVI void wg_commit() { asm volatile("wgmma.commit_group.sync.aligned;" ::: "memory"); }
template <int N> DEVI void wg_wait() { asm volatile("wgmma.wait_group.sync.aligned %0;" ::"n"(N) : "memory"); }
template <int S> DEVI void fence_regs(float (&d)[S]) {
#pragma unroll
  for (int i = 0; i < S; i++) asm volatile("" : "+f"(d[i])::"memory");
}
DEVI uint64_t mkdesc(uint32_t addr, uint32_t lbo, uint32_t sbo, int swz) {
  return (uint64_t)((addr & 0x3FFFF) >> 4) | ((uint64_t)(lbo >> 4) << 16) | ((uint64_t)(sbo >> 4) << 32) | ((uint64_t)swz << 62);
}
DEVI void mbar_init(uint32_t bar, uint32_t cnt) { asm volatile("mbarrier.init.shared::cta.b64 [%0], %1;" ::"r"(bar), "r"(cnt) : "memory"); }
DEVI void mbar_expect_tx(uint32_t bar, uint32_t bytes) { asm volatile("mbarrier.arrive.expect_tx.shared::cta.b64 _, [%0], %1;" ::"r"(bar), "r"(bytes) : "memory"); }
DEVI void mbar_arrive(uint32_t bar) { asm volatile("mbarrier.arrive.shared::cta.b64 _, [%0];" ::"r"(bar) : "memory"); }
DEVI void mbar_wait(uint32_t bar, uint32_t parity) {
  asm volatile("{\n.reg .pred p;\nLAB_WAIT:\nmbarrier.try_wait.parity.shared::cta.b64 p, [%0], %1;\n@!p bra LAB_WAIT;\n}" ::"r"(bar), "r"(parity) : "memory");
}
DEVI void mbar_wait_wd(uint32_t bar, uint32_t parity, uint32_t t0) {
  asm volatile("{\n.reg .pred p;\n.reg .u32 c;\nLAB_WAIT:\nmbarrier.try_wait.parity.shared::cta.b64 p, [%0], %1;\n@p bra DONE;\nmov.u32 c, %%clock;\nsub.u32 c, c, %2;\nsetp.lt.u32 p, c, 0x70000000;\n@p bra LAB_WAIT;\ntrap;\nDONE:\n}" ::"r"(bar), "r"(parity), "r"(t0) : "memory");
}
DEVI void flag_wait(const unsigned* p, unsigned target) {
  asm volatile("{\n.reg .pred p;\n.reg .s32 v;\nLAB_WAIT:\nld.relaxed.gpu.global.u32 v, [%0];\nsub.s32 v, v, %1;\nsetp.lt.s32 p, v, 0;\n@p bra LAB_WAIT;\n}" ::"l"(p), "r"(target) : "memory");
}
DEVI void flag_add(unsigned* p, unsigned v) { asm volatile("red.relaxed.gpu.global.add.u32 [%0], %1;" ::"l"(p), "r"(v) : "memory"); }
DEVI void fence_async_smem() { asm volatile("fence.proxy.async.shared::cta;" ::: "memory"); }
DEVI bool elect_one() { uint32_t p; asm volatile("{\n.reg .pred P;\nelect.sync _|P, 0xffffffff;\nselp.u32 %0, 1, 0, P;\n}" : "=r"(p)); return p; }
DEVI void bar_sync(int id, int n) { asm volatile("bar.sync %0, %1;" ::"r"(id), "r"(n) : "memory"); }
DEVI void bar_arrive(int id, int n) { asm volatile("bar.arrive %0, %1;" ::"r"(id), "r"(n) : "memory"); }
DEVI void tma2(uint32_t dst, const CUtensorMap* m, int c0, int c1, uint32_t bar) {
  asm volatile("cp.async.bulk.tensor.2d.shared::cluster.global.mbarrier::complete_tx::bytes [%0], [%1, {%3, %4}], [%2];" ::"r"(dst), "l"(m), "r"(bar), "r"(c0), "r"(c1) : "memory");
}
DEVI void tma3(uint32_t dst, const CUtensorMap* m, int c0, int c1, int c2, uint32_t bar) {
  asm volatile("cp.async.bulk.tensor.3d.shared::cluster.global.mbarrier::complete_tx::bytes [%0], [%1, {%3, %4, %5}], [%2];" ::"r"(dst), "l"(m), "r"(bar), "r"(c0), "r"(c1), "r"(c2) : "memory");
}
DEVI void tma3_mc(uint32_t dst, const CUtensorMap* m, int c0, int c1, int c2, uint32_t bar) {
  asm volatile("cp.async.bulk.tensor.3d.shared::cluster.global.mbarrier::complete_tx::bytes.multicast::cluster [%0], [%1, {%3, %4, %5}], [%2], %6;" ::"r"(dst), "l"(m), "r"(bar), "r"(c0), "r"(c1), "r"(c2), "h"((uint16_t)3) : "memory");
}
DEVI void tma2_mc(uint32_t dst, const CUtensorMap* m, int c0, int c1, uint32_t bar) {
  asm volatile("cp.async.bulk.tensor.2d.shared::cluster.global.mbarrier::complete_tx::bytes.multicast::cluster [%0], [%1, {%3, %4}], [%2], %5;" ::"r"(dst), "l"(m), "r"(bar), "r"(c0), "r"(c1), "h"((uint16_t)3) : "memory");
}
DEVI void mbar_arrive_remote(uint32_t bar, uint32_t cta) {
  asm volatile("{\n.reg .b32 ra;\nmapa.shared::cluster.u32 ra, %0, %1;\nmbarrier.arrive.shared::cluster.b64 _, [ra];\n}" ::"r"(bar), "r"(cta) : "memory");
}
DEVI void tma3_store(const CUtensorMap* m, int c0, int c1, int c2, uint32_t src) {
  asm volatile("cp.async.bulk.tensor.3d.global.shared::cta.bulk_group [%0, {%2, %3, %4}], [%1];" ::"l"(m), "r"(src), "r"(c0), "r"(c1), "r"(c2) : "memory");
}
DEVI void bulk_load(uint32_t dst, const void* src, uint32_t bytes, uint32_t bar) {
  asm volatile("cp.async.bulk.shared::cluster.global.mbarrier::complete_tx::bytes [%0], [%1], %2, [%3];" ::"r"(dst), "l"(src), "r"(bytes), "r"(bar) : "memory");
}
DEVI void bulk_store(void* dst, uint32_t src, uint32_t bytes) {
  asm volatile("cp.async.bulk.global.shared::cta.bulk_group [%0], [%1], %2;" ::"l"(dst), "r"(src), "r"(bytes) : "memory");
}
DEVI void pf_l2(const void* p) { asm volatile("prefetch.global.L2 [%0];" ::"l"(p)); }
template <int OFF> DEVI uint32_t ldg_v(const void* p) { uint32_t v; asm volatile("ld.volatile.global.b32 %0, [%1 + %2];" : "=r"(v) : "l"(p), "n"(OFF)); return v; }
DEVI void bulk_commit() { asm volatile("cp.async.bulk.commit_group;" ::: "memory"); }
DEVI void bulk_wait_all() { asm volatile("cp.async.bulk.wait_group 0;" ::: "memory"); }
DEVI void bulk_wait_read() { asm volatile("cp.async.bulk.wait_group.read 0;" ::: "memory"); }
template <int R> DEVI void reg_inc() { asm volatile("setmaxnreg.inc.sync.aligned.u32 %0;" ::"n"(R)); }
template <int R> DEVI void reg_dec() { asm volatile("setmaxnreg.dec.sync.aligned.u32 %0;" ::"n"(R)); }
DEVI uint32_t prmt(uint32_t a, uint32_t b, uint32_t s) { uint32_t r; asm("prmt.b32 %0,%1,%2,%3;" : "=r"(r) : "r"(a), "r"(b), "r"(s)); return r; }
DEVI uint32_t lds32(uint32_t a) { uint32_t r; asm volatile("ld.shared.b32 %0,[%1];" : "=r"(r) : "r"(a)); return r; }
DEVI void sts32(uint32_t a, uint32_t x) { asm volatile("st.shared.b32 [%0],%1;" ::"r"(a), "r"(x) : "memory"); }
DEVI void sts128(uint32_t a, uint32_t x, uint32_t y, uint32_t z, uint32_t w) { asm volatile("st.shared.v4.b32 [%0],{%1,%2,%3,%4};" ::"r"(a), "r"(x), "r"(y), "r"(z), "r"(w) : "memory"); }
DEVI void sts128v(uint32_t a, uint32_t x, uint32_t y, uint32_t z, uint32_t w) { asm volatile("st.volatile.shared.v4.b32 [%0],{%1,%2,%3,%4};" ::"r"(a), "r"(x), "r"(y), "r"(z), "r"(w) : "memory"); }
DEVI void lds128(uint32_t a, uint32_t& x, uint32_t& y, uint32_t& z, uint32_t& w) { asm volatile("ld.shared.v4.b32 {%0,%1,%2,%3},[%4];" : "=r"(x), "=r"(y), "=r"(z), "=r"(w) : "r"(a) : "memory"); }
DEVI void ldsm4(uint32_t& r0, uint32_t& r1, uint32_t& r2, uint32_t& r3, uint32_t addr) {
  asm volatile("ldmatrix.sync.aligned.m8n8.x4.shared.b16 {%0,%1,%2,%3}, [%4];" : "=r"(r0), "=r"(r1), "=r"(r2), "=r"(r3) : "r"(addr) : "memory");
}
DEVI void ldsm4t(uint32_t& r0, uint32_t& r1, uint32_t& r2, uint32_t& r3, uint32_t addr) {
  asm volatile("ldmatrix.sync.aligned.m8n8.x4.trans.shared.b16 {%0,%1,%2,%3}, [%4];" : "=r"(r0), "=r"(r1), "=r"(r2), "=r"(r3) : "r"(addr) : "memory");
}
DEVI void stsm4(uint32_t addr, uint32_t r0, uint32_t r1, uint32_t r2, uint32_t r3) {
  asm volatile("stmatrix.sync.aligned.m8n8.x4.shared.b16 [%0], {%1,%2,%3,%4};" ::"r"(addr), "r"(r0), "r"(r1), "r"(r2), "r"(r3) : "memory");
}
DEVI void stsm4t(uint32_t addr, uint32_t r0, uint32_t r1, uint32_t r2, uint32_t r3) {
  asm volatile("stmatrix.sync.aligned.m8n8.x4.trans.shared.b16 [%0], {%1,%2,%3,%4};" ::"r"(addr), "r"(r0), "r"(r1), "r"(r2), "r"(r3) : "memory");
}
DEVI uint32_t movm(uint32_t a) { uint32_t r; asm volatile("movmatrix.sync.aligned.m8n8.trans.b16 %0, %1;" : "=r"(r) : "r"(a)); return r; }
DEVI uint32_t pack_bf16(float lo, float hi) { uint32_t r; asm("cvt.rn.bf16x2.f32 %0, %1, %2;" : "=r"(r) : "f"(hi), "f"(lo)); return r; }
DEVI uint32_t hmul2(uint32_t a, uint32_t b) { uint32_t r; asm("mul.rn.bf16x2 %0,%1,%2;" : "=r"(r) : "r"(a), "r"(b)); return r; }
DEVI uint32_t hadd2(uint32_t a, uint32_t b) { uint32_t r; asm("add.rn.bf16x2 %0,%1,%2;" : "=r"(r) : "r"(a), "r"(b)); return r; }
DEVI float bf_lo(uint32_t a) { return __uint_as_float(prmt(a, 0, 0x1044)); }
DEVI float bf_hi(uint32_t a) { return __uint_as_float(a & 0xFFFF0000u); }
DEVI void mma16(float (&c)[4], uint32_t a0, uint32_t a1, uint32_t a2, uint32_t a3, uint32_t b0, uint32_t b1) {
  asm("mma.sync.aligned.m16n8k16.row.col.f32.bf16.bf16.f32 {%0,%1,%2,%3},{%4,%5,%6,%7},{%8,%9},{%0,%1,%2,%3};"
      : "+f"(c[0]), "+f"(c[1]), "+f"(c[2]), "+f"(c[3]) : "r"(a0), "r"(a1), "r"(a2), "r"(a3), "r"(b0), "r"(b1));
}
DEVI void mma8(float (&c)[4], uint32_t a0, uint32_t a1, uint32_t b0) {
  asm("mma.sync.aligned.m16n8k8.row.col.f32.bf16.bf16.f32 {%0,%1,%2,%3},{%4,%5},{%6},{%0,%1,%2,%3};"
      : "+f"(c[0]), "+f"(c[1]), "+f"(c[2]), "+f"(c[3]) : "r"(a0), "r"(a1), "r"(b0));
}
DEVI float ex2(float x) { float r; asm("ex2.approx.ftz.f32 %0, %1;" : "=f"(r) : "f"(x)); return r; }

DEVI uint32_t clk() { uint32_t c; asm volatile("mov.u32 %0, %%clock;" : "=r"(c)); return c; }
DEVI void wait_until(uint32_t t0, int dt) { while ((int)(clk() - t0) < dt) __nanosleep(40); }
DEVI void spin_until(uint32_t t0, int dt) { while ((int)(clk() - t0) < dt) {} }
DEVI uint32_t hfma2(uint32_t a, uint32_t b, uint32_t c) { uint32_t r; asm("fma.rn.bf16x2 %0,%1,%2,%3;" : "=r"(r) : "r"(a), "r"(b), "r"(c)); return r; }
DEVI void bar_sync_p(int on, int id, int n) { asm volatile("{\n.reg .pred p;\nsetp.ne.b32 p, %0, 0;\n@p bar.sync %1, %2;\n}" ::"r"(on), "r"(id), "r"(n) : "memory"); }
DEVI void bar_arrive_p(int on, int id, int n) { asm volatile("{\n.reg .pred p;\nsetp.ne.b32 p, %0, 0;\n@p bar.arrive %1, %2;\n}" ::"r"(on), "r"(id), "r"(n) : "memory"); }
DEVI void mbar_arrive_p(int on, uint32_t bar) { asm volatile("{\n.reg .pred p;\nsetp.ne.b32 p, %1, 0;\n@p mbarrier.arrive.shared::cta.b64 _, [%0];\n}" ::"r"(bar), "r"(on) : "memory"); }
DEVI void mbar_arrive2_p(int on, uint32_t bar, uint32_t rbar) {
  asm volatile("{\n.reg .pred p;\nsetp.ne.b32 p, %2, 0;\n@p mbarrier.arrive.shared::cta.b64 _, [%0];\n@p mbarrier.arrive.shared::cluster.b64 _, [%1];\n}" ::"r"(bar), "r"(rbar), "r"(on) : "memory");
}
DEVI void st_relaxed(uint4* p, uint32_t x, uint32_t y, uint32_t z, uint32_t w) {
  asm volatile("st.relaxed.gpu.global.v4.b32 [%0], {%1,%2,%3,%4};" ::"l"(p), "r"(x), "r"(y), "r"(z), "r"(w) : "memory");
}
DEVI uint32_t mapa(uint32_t a, uint32_t cta) { uint32_t r; asm("mapa.shared::cluster.u32 %0, %1, %2;" : "=r"(r) : "r"(a), "r"(cta)); return r; }
DEVI void st_async128(uint32_t a, uint32_t x, uint32_t y, uint32_t z, uint32_t w, uint32_t bar) {
  asm volatile("st.async.weak.shared::cluster.mbarrier::complete_tx::bytes.v4.b32 [%0], {%1,%2,%3,%4}, [%5];" ::"r"(a), "r"(x), "r"(y), "r"(z), "r"(w), "r"(bar) : "memory");
}

template<int OFF, int TB, int S> __device__ __forceinline__ void wgmma_rs_n192(float (&d)[S], uint32_t a0, uint32_t a1, uint32_t a2, uint32_t a3, uint64_t db, int sd) {
  asm volatile("{\n.reg .pred p;\nsetp.ne.b32 p, %101, 0;\n"
    "wgmma.mma_async.sync.aligned.m64n192k16.f32.bf16.bf16 {%0, %1, %2, %3, %4, %5, %6, %7, %8, %9, %10, %11, %12, %13, %14, %15, %16, %17, %18, %19, %20, %21, %22, %23, %24, %25, %26, %27, %28, %29, %30, %31, %32, %33, %34, %35, %36, %37, %38, %39, %40, %41, %42, %43, %44, %45, %46, %47, %48, %49, %50, %51, %52, %53, %54, %55, %56, %57, %58, %59, %60, %61, %62, %63, %64, %65, %66, %67, %68, %69, %70, %71, %72, %73, %74, %75, %76, %77, %78, %79, %80, %81, %82, %83, %84, %85, %86, %87, %88, %89, %90, %91, %92, %93, %94, %95}, {%96, %97, %98, %99}, %100, p, 1, 1, %102;\n}\n"
    : "+f"(d[OFF+0]), "+f"(d[OFF+1]), "+f"(d[OFF+2]), "+f"(d[OFF+3]), "+f"(d[OFF+4]), "+f"(d[OFF+5]), "+f"(d[OFF+6]), "+f"(d[OFF+7]), "+f"(d[OFF+8]), "+f"(d[OFF+9]), "+f"(d[OFF+10]), "+f"(d[OFF+11]), "+f"(d[OFF+12]), "+f"(d[OFF+13]), "+f"(d[OFF+14]), "+f"(d[OFF+15]), "+f"(d[OFF+16]), "+f"(d[OFF+17]), "+f"(d[OFF+18]), "+f"(d[OFF+19]), "+f"(d[OFF+20]), "+f"(d[OFF+21]), "+f"(d[OFF+22]), "+f"(d[OFF+23]), "+f"(d[OFF+24]), "+f"(d[OFF+25]), "+f"(d[OFF+26]), "+f"(d[OFF+27]), "+f"(d[OFF+28]), "+f"(d[OFF+29]), "+f"(d[OFF+30]), "+f"(d[OFF+31]), "+f"(d[OFF+32]), "+f"(d[OFF+33]), "+f"(d[OFF+34]), "+f"(d[OFF+35]), "+f"(d[OFF+36]), "+f"(d[OFF+37]), "+f"(d[OFF+38]), "+f"(d[OFF+39]), "+f"(d[OFF+40]), "+f"(d[OFF+41]), "+f"(d[OFF+42]), "+f"(d[OFF+43]), "+f"(d[OFF+44]), "+f"(d[OFF+45]), "+f"(d[OFF+46]), "+f"(d[OFF+47]), "+f"(d[OFF+48]), "+f"(d[OFF+49]), "+f"(d[OFF+50]), "+f"(d[OFF+51]), "+f"(d[OFF+52]), "+f"(d[OFF+53]), "+f"(d[OFF+54]), "+f"(d[OFF+55]), "+f"(d[OFF+56]), "+f"(d[OFF+57]), "+f"(d[OFF+58]), "+f"(d[OFF+59]), "+f"(d[OFF+60]), "+f"(d[OFF+61]), "+f"(d[OFF+62]), "+f"(d[OFF+63]), "+f"(d[OFF+64]), "+f"(d[OFF+65]), "+f"(d[OFF+66]), "+f"(d[OFF+67]), "+f"(d[OFF+68]), "+f"(d[OFF+69]), "+f"(d[OFF+70]), "+f"(d[OFF+71]), "+f"(d[OFF+72]), "+f"(d[OFF+73]), "+f"(d[OFF+74]), "+f"(d[OFF+75]), "+f"(d[OFF+76]), "+f"(d[OFF+77]), "+f"(d[OFF+78]), "+f"(d[OFF+79]), "+f"(d[OFF+80]), "+f"(d[OFF+81]), "+f"(d[OFF+82]), "+f"(d[OFF+83]), "+f"(d[OFF+84]), "+f"(d[OFF+85]), "+f"(d[OFF+86]), "+f"(d[OFF+87]), "+f"(d[OFF+88]), "+f"(d[OFF+89]), "+f"(d[OFF+90]), "+f"(d[OFF+91]), "+f"(d[OFF+92]), "+f"(d[OFF+93]), "+f"(d[OFF+94]), "+f"(d[OFF+95]) : "r"(a0), "r"(a1), "r"(a2), "r"(a3), "l"(db), "r"(sd), "n"(TB));
}
template<int OFF, int TB, int S> __device__ __forceinline__ void wgmma_rs_n48(float (&d)[S], uint32_t a0, uint32_t a1, uint32_t a2, uint32_t a3, uint64_t db, int sd) {
  asm volatile("{\n.reg .pred p;\nsetp.ne.b32 p, %29, 0;\n"
    "wgmma.mma_async.sync.aligned.m64n48k16.f32.bf16.bf16 {%0, %1, %2, %3, %4, %5, %6, %7, %8, %9, %10, %11, %12, %13, %14, %15, %16, %17, %18, %19, %20, %21, %22, %23}, {%24, %25, %26, %27}, %28, p, 1, 1, %30;\n}\n"
    : "+f"(d[OFF+0]), "+f"(d[OFF+1]), "+f"(d[OFF+2]), "+f"(d[OFF+3]), "+f"(d[OFF+4]), "+f"(d[OFF+5]), "+f"(d[OFF+6]), "+f"(d[OFF+7]), "+f"(d[OFF+8]), "+f"(d[OFF+9]), "+f"(d[OFF+10]), "+f"(d[OFF+11]), "+f"(d[OFF+12]), "+f"(d[OFF+13]), "+f"(d[OFF+14]), "+f"(d[OFF+15]), "+f"(d[OFF+16]), "+f"(d[OFF+17]), "+f"(d[OFF+18]), "+f"(d[OFF+19]), "+f"(d[OFF+20]), "+f"(d[OFF+21]), "+f"(d[OFF+22]), "+f"(d[OFF+23]) : "r"(a0), "r"(a1), "r"(a2), "r"(a3), "l"(db), "r"(sd), "n"(TB));
}
template<int OFF, int TB, int S> __device__ __forceinline__ void wgmma_rs_n16(float (&d)[S], uint32_t a0, uint32_t a1, uint32_t a2, uint32_t a3, uint64_t db, int sd) {
  asm volatile("{\n.reg .pred p;\nsetp.ne.b32 p, %13, 0;\n"
    "wgmma.mma_async.sync.aligned.m64n16k16.f32.bf16.bf16 {%0, %1, %2, %3, %4, %5, %6, %7}, {%8, %9, %10, %11}, %12, p, 1, 1, %14;\n}\n"
    : "+f"(d[OFF+0]), "+f"(d[OFF+1]), "+f"(d[OFF+2]), "+f"(d[OFF+3]), "+f"(d[OFF+4]), "+f"(d[OFF+5]), "+f"(d[OFF+6]), "+f"(d[OFF+7]) : "r"(a0), "r"(a1), "r"(a2), "r"(a3), "l"(db), "r"(sd), "n"(TB));
}
template<int OFF, int TA, int TB, int S> __device__ __forceinline__ void wgmma_ss_n160(float (&d)[S], uint64_t da, uint64_t db, int sd) {
  asm volatile("{\n.reg .pred p;\nsetp.ne.b32 p, %82, 0;\n"
    "wgmma.mma_async.sync.aligned.m64n160k16.f32.bf16.bf16 {%0, %1, %2, %3, %4, %5, %6, %7, %8, %9, %10, %11, %12, %13, %14, %15, %16, %17, %18, %19, %20, %21, %22, %23, %24, %25, %26, %27, %28, %29, %30, %31, %32, %33, %34, %35, %36, %37, %38, %39, %40, %41, %42, %43, %44, %45, %46, %47, %48, %49, %50, %51, %52, %53, %54, %55, %56, %57, %58, %59, %60, %61, %62, %63, %64, %65, %66, %67, %68, %69, %70, %71, %72, %73, %74, %75, %76, %77, %78, %79}, %80, %81, p, 1, 1, %83, %84;\n}\n"
    : "+f"(d[OFF+0]), "+f"(d[OFF+1]), "+f"(d[OFF+2]), "+f"(d[OFF+3]), "+f"(d[OFF+4]), "+f"(d[OFF+5]), "+f"(d[OFF+6]), "+f"(d[OFF+7]), "+f"(d[OFF+8]), "+f"(d[OFF+9]), "+f"(d[OFF+10]), "+f"(d[OFF+11]), "+f"(d[OFF+12]), "+f"(d[OFF+13]), "+f"(d[OFF+14]), "+f"(d[OFF+15]), "+f"(d[OFF+16]), "+f"(d[OFF+17]), "+f"(d[OFF+18]), "+f"(d[OFF+19]), "+f"(d[OFF+20]), "+f"(d[OFF+21]), "+f"(d[OFF+22]), "+f"(d[OFF+23]), "+f"(d[OFF+24]), "+f"(d[OFF+25]), "+f"(d[OFF+26]), "+f"(d[OFF+27]), "+f"(d[OFF+28]), "+f"(d[OFF+29]), "+f"(d[OFF+30]), "+f"(d[OFF+31]), "+f"(d[OFF+32]), "+f"(d[OFF+33]), "+f"(d[OFF+34]), "+f"(d[OFF+35]), "+f"(d[OFF+36]), "+f"(d[OFF+37]), "+f"(d[OFF+38]), "+f"(d[OFF+39]), "+f"(d[OFF+40]), "+f"(d[OFF+41]), "+f"(d[OFF+42]), "+f"(d[OFF+43]), "+f"(d[OFF+44]), "+f"(d[OFF+45]), "+f"(d[OFF+46]), "+f"(d[OFF+47]), "+f"(d[OFF+48]), "+f"(d[OFF+49]), "+f"(d[OFF+50]), "+f"(d[OFF+51]), "+f"(d[OFF+52]), "+f"(d[OFF+53]), "+f"(d[OFF+54]), "+f"(d[OFF+55]), "+f"(d[OFF+56]), "+f"(d[OFF+57]), "+f"(d[OFF+58]), "+f"(d[OFF+59]), "+f"(d[OFF+60]), "+f"(d[OFF+61]), "+f"(d[OFF+62]), "+f"(d[OFF+63]), "+f"(d[OFF+64]), "+f"(d[OFF+65]), "+f"(d[OFF+66]), "+f"(d[OFF+67]), "+f"(d[OFF+68]), "+f"(d[OFF+69]), "+f"(d[OFF+70]), "+f"(d[OFF+71]), "+f"(d[OFF+72]), "+f"(d[OFF+73]), "+f"(d[OFF+74]), "+f"(d[OFF+75]), "+f"(d[OFF+76]), "+f"(d[OFF+77]), "+f"(d[OFF+78]), "+f"(d[OFF+79]) : "l"(da), "l"(db), "r"(sd), "n"(TA), "n"(TB));
}
template<int OFF, int TA, int TB, int S> __device__ __forceinline__ void wgmma_ss_n192(float (&d)[S], uint64_t da, uint64_t db, int sd) {
  asm volatile("{\n.reg .pred p;\nsetp.ne.b32 p, %98, 0;\n"
    "wgmma.mma_async.sync.aligned.m64n192k16.f32.bf16.bf16 {%0, %1, %2, %3, %4, %5, %6, %7, %8, %9, %10, %11, %12, %13, %14, %15, %16, %17, %18, %19, %20, %21, %22, %23, %24, %25, %26, %27, %28, %29, %30, %31, %32, %33, %34, %35, %36, %37, %38, %39, %40, %41, %42, %43, %44, %45, %46, %47, %48, %49, %50, %51, %52, %53, %54, %55, %56, %57, %58, %59, %60, %61, %62, %63, %64, %65, %66, %67, %68, %69, %70, %71, %72, %73, %74, %75, %76, %77, %78, %79, %80, %81, %82, %83, %84, %85, %86, %87, %88, %89, %90, %91, %92, %93, %94, %95}, %96, %97, p, 1, 1, %99, %100;\n}\n"
    : "+f"(d[OFF+0]), "+f"(d[OFF+1]), "+f"(d[OFF+2]), "+f"(d[OFF+3]), "+f"(d[OFF+4]), "+f"(d[OFF+5]), "+f"(d[OFF+6]), "+f"(d[OFF+7]), "+f"(d[OFF+8]), "+f"(d[OFF+9]), "+f"(d[OFF+10]), "+f"(d[OFF+11]), "+f"(d[OFF+12]), "+f"(d[OFF+13]), "+f"(d[OFF+14]), "+f"(d[OFF+15]), "+f"(d[OFF+16]), "+f"(d[OFF+17]), "+f"(d[OFF+18]), "+f"(d[OFF+19]), "+f"(d[OFF+20]), "+f"(d[OFF+21]), "+f"(d[OFF+22]), "+f"(d[OFF+23]), "+f"(d[OFF+24]), "+f"(d[OFF+25]), "+f"(d[OFF+26]), "+f"(d[OFF+27]), "+f"(d[OFF+28]), "+f"(d[OFF+29]), "+f"(d[OFF+30]), "+f"(d[OFF+31]), "+f"(d[OFF+32]), "+f"(d[OFF+33]), "+f"(d[OFF+34]), "+f"(d[OFF+35]), "+f"(d[OFF+36]), "+f"(d[OFF+37]), "+f"(d[OFF+38]), "+f"(d[OFF+39]), "+f"(d[OFF+40]), "+f"(d[OFF+41]), "+f"(d[OFF+42]), "+f"(d[OFF+43]), "+f"(d[OFF+44]), "+f"(d[OFF+45]), "+f"(d[OFF+46]), "+f"(d[OFF+47]), "+f"(d[OFF+48]), "+f"(d[OFF+49]), "+f"(d[OFF+50]), "+f"(d[OFF+51]), "+f"(d[OFF+52]), "+f"(d[OFF+53]), "+f"(d[OFF+54]), "+f"(d[OFF+55]), "+f"(d[OFF+56]), "+f"(d[OFF+57]), "+f"(d[OFF+58]), "+f"(d[OFF+59]), "+f"(d[OFF+60]), "+f"(d[OFF+61]), "+f"(d[OFF+62]), "+f"(d[OFF+63]), "+f"(d[OFF+64]), "+f"(d[OFF+65]), "+f"(d[OFF+66]), "+f"(d[OFF+67]), "+f"(d[OFF+68]), "+f"(d[OFF+69]), "+f"(d[OFF+70]), "+f"(d[OFF+71]), "+f"(d[OFF+72]), "+f"(d[OFF+73]), "+f"(d[OFF+74]), "+f"(d[OFF+75]), "+f"(d[OFF+76]), "+f"(d[OFF+77]), "+f"(d[OFF+78]), "+f"(d[OFF+79]), "+f"(d[OFF+80]), "+f"(d[OFF+81]), "+f"(d[OFF+82]), "+f"(d[OFF+83]), "+f"(d[OFF+84]), "+f"(d[OFF+85]), "+f"(d[OFF+86]), "+f"(d[OFF+87]), "+f"(d[OFF+88]), "+f"(d[OFF+89]), "+f"(d[OFF+90]), "+f"(d[OFF+91]), "+f"(d[OFF+92]), "+f"(d[OFF+93]), "+f"(d[OFF+94]), "+f"(d[OFF+95]) : "l"(da), "l"(db), "r"(sd), "n"(TA), "n"(TB));
}
template<int OFF, int TA, int TB, int S> __device__ __forceinline__ void wgmma_ss_n48(float (&d)[S], uint64_t da, uint64_t db, int sd) {
  asm volatile("{\n.reg .pred p;\nsetp.ne.b32 p, %26, 0;\n"
    "wgmma.mma_async.sync.aligned.m64n48k16.f32.bf16.bf16 {%0, %1, %2, %3, %4, %5, %6, %7, %8, %9, %10, %11, %12, %13, %14, %15, %16, %17, %18, %19, %20, %21, %22, %23}, %24, %25, p, 1, 1, %27, %28;\n}\n"
    : "+f"(d[OFF+0]), "+f"(d[OFF+1]), "+f"(d[OFF+2]), "+f"(d[OFF+3]), "+f"(d[OFF+4]), "+f"(d[OFF+5]), "+f"(d[OFF+6]), "+f"(d[OFF+7]), "+f"(d[OFF+8]), "+f"(d[OFF+9]), "+f"(d[OFF+10]), "+f"(d[OFF+11]), "+f"(d[OFF+12]), "+f"(d[OFF+13]), "+f"(d[OFF+14]), "+f"(d[OFF+15]), "+f"(d[OFF+16]), "+f"(d[OFF+17]), "+f"(d[OFF+18]), "+f"(d[OFF+19]), "+f"(d[OFF+20]), "+f"(d[OFF+21]), "+f"(d[OFF+22]), "+f"(d[OFF+23]) : "l"(da), "l"(db), "r"(sd), "n"(TA), "n"(TB));
}

__device__ __align__(1024) uint16_t g_kvT[2 * 640 * 2048];
__device__ __align__(1024) uint16_t g_y2T[640 * 2048];
__device__ __align__(1024) uint16_t g_o[2048 * 640];
__device__ __align__(1024) uint16_t g_gate[2080];
__device__ __align__(1024) uint4 g_halo[128 * 5 * 32];
__device__ __align__(1024) unsigned g_cnt[46 * 32];
__device__ __align__(1024) unsigned g_launch[132];
#define CNT_KV(i) (g_cnt + 32 * (i))
#define CNT_O(i) (g_cnt + 32 * (10 + (i)))
#define CNT_Y(i) (g_cnt + 32 * (26 + (i)))
#define PTL(i) do {} while (0)
#define PTPL(on, i) do {} while (0)
#define PT(i) do {} while (0)
#define PTP(on, i) do {} while (0)

constexpr uint32_t SB = 1024;
constexpr uint32_t STG = 23552, WST = 15360;
DEVI constexpr uint32_t o_px(int ks) { return (((ks >> 1) + 1) & 3) * 2 * STG; }
DEVI constexpr uint32_t o_pw(int ks) { return o_px(ks) + 16384 + (ks & 1) * WST; }
constexpr uint32_t O_HALO = 0, O_OST = STG;
constexpr uint32_t P3S = 28672;
constexpr uint32_t HC = 8320, UC = 4624, UZ = 528;
constexpr uint32_t O_H0 = 5 * P3S, O_U2 = O_H0 + 3 * HC, O_H3 = O_U2 + UC, O_U0 = O_H3 + 2 * HC;
DEVI constexpr uint32_t o_h(int c) { return O_H0 + c * HC + (c > 2 ? UC : 0); }
DEVI constexpr uint32_t o_u(int c) { return c == 2 ? O_U2 : O_U0 + (c > 2 ? c - 1 : c) * UC; }
constexpr uint32_t O_Y = 208896;
DEVI constexpr uint32_t o_x(int c) { return c < 2 ? O_Y + c * 5120 : O_U0 + (c & 1) * UC; }
constexpr uint32_t O_HIN = O_Y + 16384;
DEVI constexpr uint32_t o_kst(int hw) { return hw == 1 ? (O_U0 + 511) & ~511u : hw == 2 ? (O_U0 + 2 * UC + 511) & ~511u : O_Y + (hw & 1) * 8192; }
DEVI constexpr uint32_t o_p3(int ks) { return (ks < 6 ? ks : ks - 6) * P3S; }
constexpr uint32_t O_BT = 4 * P3S;
constexpr uint32_t O_GT = O_Y + 20480, O_GW = O_GT + 320;
constexpr uint32_t O_BAR = 231040;
constexpr uint32_t B_FULL = O_BAR, B_EMPTY = O_BAR + 8 * 8, B_P3F = O_BAR + 8 * 16, B_P3R = O_BAR + 8 * 26, B_G = O_BAR + 8 * 27, B_U = O_BAR + 8 * 28,
                   B_KVD = O_BAR + 8 * 33, B_Y = O_BAR + 8 * 37, B_EP = O_BAR + 8 * 39, B_LAST = O_BAR + 8 * 40, B_DONE = O_BAR + 8 * 41,
                   B_P1E = O_BAR + 8 * 43, B_HX = O_BAR + 8 * 43  , B_P3E = O_BAR + 8 * 52, B_HX0 = O_BAR + 8 * 57;
constexpr uint32_t B_S13 = B_EMPTY + 8 * 5, B_S15 = B_EMPTY + 8 * 7, B_S19 = B_EMPTY + 8 * 3;
constexpr uint32_t O_GP = O_BAR + 512, O_EPOCH = O_GW + 1280;
constexpr uint32_t SMEM_BYTES = 232448;
static_assert(O_U0 + 4 * UC <= O_Y && O_EPOCH + 4 <= O_BAR && O_U0 >= 8 * STG, "smem map");
enum { NB_LEAD = 1, NB_HELP = 2, NB_HALO = 3, NB_ATT = 4, NB_G = 5, NB_TOK = 6, NB_RFULL = 8, NB_RFREE = 10 };

struct Maps { CUtensorMap x_par, w_main, w_tail, o_st, kv_st, wo, o_ld, y_ld; };

template <int M, class F> DEVI void conv_step(float (&acc)[128], uint32_t a0, uint32_t a1, uint32_t a2, uint32_t a3, uint32_t dl, F&& gap) {
  auto D = [&](int off) { return ((uint64_t)8 << 32) | (uint64_t)(uint32_t)(dl + off - 16 * M); };
  if constexpr (M == 0) wgmma_rs_n16<0, 0>(acc, a0, a1, a2, a3, D(0), 0);
  if constexpr (M <= 3) { wgmma_rs_n48<8, 0>(acc, a0, a1, a2, a3, D(16), M == 0 ? 0 : 1); gap(); }
  if constexpr (M <= 6) { wgmma_rs_n48<32, 0>(acc, a0, a1, a2, a3, D(64), M == 0 ? 0 : 1); gap(); }
  if constexpr (M <= 9) { wgmma_rs_n48<56, 0>(acc, a0, a1, a2, a3, D(112), M == 0 ? 0 : 1); gap(); }
  if constexpr (M <= 12) { wgmma_rs_n48<80, 0>(acc, a0, a1, a2, a3, D(160), M == 0 ? 0 : 1); gap(); }
  wgmma_rs_n48<104, 0>(acc, a0, a1, a2, a3, D(208), M == 0 ? 0 : 1); gap();
}
DEVI constexpr int a_off(int P, int i) { return -4 * (64 * ((i & 4) ? 15 - P : P) + (i & 1) * 32 - (i & 2) * 2); }
template <int P> DEVI void load_pair(uint32_t (&a)[8], uint32_t ab) {
#pragma unroll
  for (int i = 0; i < 8; i++) a[i] = lds32(ab + a_off(P, i));
}
template <int P> DEVI void mma_pair(float (&acc)[128], uint32_t (&a)[8], uint32_t db) {
  wg_fence();
  conv_step<P>(acc, a[0], a[1], a[2], a[3], db, []() {});
  conv_step<15 - P>(acc, a[4], a[5], a[6], a[7], db, []() {});
  wg_commit();
}
template <int P, int Q, int W> DEVI void mma_pair_ld(float (&acc)[128], uint32_t (&a)[8], uint32_t db, uint32_t (&nx)[8], uint32_t ab, int on) {
  int n = 0, j = 0;
  auto ld = [&](int cnt) {
#pragma unroll
    for (int r = 0; r < cnt; r++, n++) {
      if (Q >= 4) nx[n] = lds32(ab + a_off(Q, n));
      else asm volatile("{\n.reg .pred p;\nsetp.ne.b32 p, %2, 0;\n@p ld.shared.b32 %0, [%1];\n}" : "+r"(nx[n]) : "r"(ab + a_off(Q, n)), "r"(on));
    }
  };
  auto gap = [&]() {
    if (j == 1) { wg_commit(); wg_wait<W + 1>(); ld(3); wg_fence(); }
    if (j == 3) { wg_commit(); ld(3); wg_fence(); }
    j++;
  };
  wg_fence();
  conv_step<P>(acc, a[0], a[1], a[2], a[3], db, gap);
  conv_step<15 - P>(acc, a[4], a[5], a[6], a[7], db, gap);
  wg_commit();
  ld(2);
}

DEVI void conv_reduce(uint32_t sb, int c, int ht, int chan, int bar) {
  const uint32_t a0 = sb + o_h(c) + ht * 16, a2 = sb + o_u(c) + ht * 16, a3 = sb + o_x(c) + ht * 16;
  uint4* yp = (uint4*)(g_y2T + (size_t)chan * 2048) + ht;
#pragma unroll
  for (int i = 0; i < 2; i++) {
    uint4 p, q, r, s;
    if (HALVES || !i) bar_sync(bar + (HALVES ? 4 - 4 * i : 0), 256);
    lds128(a0 + i * 2048, p.x, p.y, p.z, p.w); lds128(a0 + 4160 + i * 2048, q.x, q.y, q.z, q.w);
    lds128(a2 + i * 2048, r.x, r.y, r.z, r.w); lds128(a3 + i * 2048, s.x, s.y, s.z, s.w);
    yp[i * 128] = make_uint4(hadd2(hadd2(p.x, q.x), hadd2(r.x, s.x)), hadd2(hadd2(p.y, q.y), hadd2(r.y, s.y)),
                             hadd2(hadd2(p.z, q.z), hadd2(r.z, s.z)), hadd2(hadd2(p.w, q.w), hadd2(r.w, s.w)));
  }
}

template <int I> DEVI void ld_rows(uint32_t (&kk)[32], uint32_t (&vv)[32], const char* kp, const char* vp) {
  if constexpr (I < 32) { kk[I] = ldg_v<I * 1280>(kp); vv[I] = ldg_v<I * 1280>(vp); ld_rows<I + 1>(kk, vv, kp, vp); }
}
DEVI void kv_task(const CUtensorMap* map, const uint16_t* kin, const uint16_t* vin, uint4 sk, int kb, int tk, uint32_t st, int lane) {
  const char* kp = (const char*)kin + tk * (32 * 1280) + kb * 128 + lane * 4;
  const char* vp = (const char*)vin + tk * (32 * 1280) + kb * 128 + lane * 4;
  uint32_t km = 0, k0 = 0, k1 = 0, k2 = 0, op = 0, kk[32], vv[32];
  if (tk > 0) { km = ldg_v<-4 * 1280>(kp); k0 = ldg_v<-3 * 1280>(kp); k1 = ldg_v<-2 * 1280>(kp); k2 = ldg_v<-1280>(kp); op = ldg_v<-1280>(vp); }
  ld_rows<0>(kk, vv, kp, vp);
  const uint32_t zz = vv[31] & (uint32_t)(threadIdx.y);
  const uint32_t w0 = prmt(sk.x, sk.z, 0x5410) | zz, w1 = prmt(sk.x, sk.z, 0x7632), w2 = prmt(sk.y, sk.w, 0x5410), w3 = prmt(sk.y, sk.w, 0x7632) | zz;
  const int odd = (lane >> 2) & 1;
  const uint32_t sel0 = odd ? 0x7632 : 0x5410, sel1 = odd ? 0x5410 : 0x7632;
  op = hmul2(hfma2(k2, w0, hfma2(k1, w1, hfma2(k0, w2, hmul2(km, w3)))), op);
#pragma unroll
  for (int ch = 0; ch < 4; ch++) {
    uint32_t o[8];
#pragma unroll
    for (int i = 0; i < 8; i++) {
      const uint32_t k3 = kk[8 * ch + i];
      o[i] = hmul2(hfma2(k3, w0, hfma2(k2, w1, hfma2(k1, w2, hmul2(k0, w3)))), vv[8 * ch + i]);
      k0 = k1; k1 = k2; k2 = k3;
    }
    const uint32_t oa = st + (2 * lane) * 64 + (((3 - ch) ^ (lane & 3)) << 4), o0 = oa + odd * 64, o1 = oa + 64 - odd * 64;
    sts128v(o0, prmt(o[6], o[5], sel0), prmt(o[4], o[3], sel0), prmt(o[2], o[1], sel0), prmt(o[0], op, sel0));
    sts128v(o1, prmt(o[6], o[5], sel1), prmt(o[4], o[3], sel1), prmt(o[2], o[1], sel1), prmt(o[0], op, sel1));
    sts128v(o0 + 4096, prmt(o[7], o[6], sel0), prmt(o[5], o[4], sel0), prmt(o[3], o[2], sel0), prmt(o[1], o[0], sel0));
    sts128v(o1 + 4096, prmt(o[7], o[6], sel1), prmt(o[5], o[4], sel1), prmt(o[3], o[2], sel1), prmt(o[1], o[0], sel1));
    op = o[7];
  }
  fence_async_smem();
  __syncwarp();
  if (elect_one()) {
    tma3_store(map, 0, kb * 64, 63 - tk, st); tma3_store(map, 0, 640 + kb * 64, 63 - tk, st + 4096);
    bulk_commit(); bulk_wait_all();
    flag_add(CNT_KV(kb), 1);
  }
  __syncwarp();
}

template <int ODD, int PART> DEVI void pack_qkv(const float (&acc)[120], uint32_t (&Q)[10][2], uint32_t (&K)[10][2], uint32_t (&V)[10][2]) {
#pragma unroll
  for (int f = 0; f < 10; f++) {
    const bool tail = ODD ? (f < 2) : (f >= 8);
    const int fm = ODD ? f - 2 : f, ft = ODD ? f : f - 8;
    const int nq = tail ? 24 + ft : fm, nk = tail ? 26 + ft : 8 + fm, nv = tail ? 28 + ft : 16 + fm;
    if (PART == 0) {
      V[f][1] = pack_bf16(acc[4 * nv + 2], acc[4 * nv + 3]);
      K[f][1] = pack_bf16(acc[4 * nk + 2], acc[4 * nk + 3]);
    } else {
      Q[f][0] = pack_bf16(acc[4 * nq], acc[4 * nq + 1]); Q[f][1] = pack_bf16(acc[4 * nq + 2], acc[4 * nq + 3]);
      K[f][0] = pack_bf16(acc[4 * nk], acc[4 * nk + 1]); V[f][0] = pack_bf16(acc[4 * nv], acc[4 * nv + 1]);
    }
  }
}
DEVI void softmax8(float (&l)[8][2], uint32_t (&P)[8]) {
  const float C = 0.22360679774997896f * 1.4426950408889634f;
  float m[8];
#pragma unroll
  for (int j = 0; j < 8; j++) m[j] = fmaxf(l[j][0], l[j][1]);
#pragma unroll
  for (int j = 0; j < 8; j++) m[j] = fmaxf(m[j], __shfl_xor_sync(~0u, m[j], 1));
#pragma unroll
  for (int j = 0; j < 8; j++) m[j] = fmaxf(m[j], __shfl_xor_sync(~0u, m[j], 2));
#pragma unroll
  for (int j = 0; j < 8; j++) { const float mc = m[j] * C; l[j][0] = ex2(fmaf(l[j][0], C, -mc)); l[j][1] = ex2(fmaf(l[j][1], C, -mc)); }
#pragma unroll
  for (int j = 0; j < 4; j++) {
    float s[4] = {0.f, 0.f, 0.f, 0.f}, r0, r1;
    mma8(s, pack_bf16(l[j][0], l[j][1]), pack_bf16(l[4 + j][0], l[4 + j][1]), 0x3F803F80u);
    asm("rcp.approx.ftz.f32 %0, %1;" : "=f"(r0) : "f"(s[0]));
    asm("rcp.approx.ftz.f32 %0, %1;" : "=f"(r1) : "f"(s[2]));
    P[j] = pack_bf16(l[j][0] * r0, l[j][1] * r0); P[4 + j] = pack_bf16(l[4 + j][0] * r1, l[4 + j][1] * r1);
  }
}

DEVI int pair_of(int c) {
  const int lo = 32 + 8 * c, hi = c - 4 + ((max(c - 29, 0) * 37) >> 8);
  int p; asm("{\n.reg .pred q;\nsetp.lt.s32 q, %1, 4;\nselp.b32 %0, %2, %3, q;\n}" : "=r"(p) : "r"(c), "r"(lo), "r"(hi));
  return p;
}
DEVI uint32_t make_ctx() {
  int b; asm volatile("mov.u32 %0, %%ctaid.x;" : "=r"(b));
  b += clk() & threadIdx.y;
  const int p = pair_of(b >> 1);
  const int j = b < 128 ? 8 * (p & 7) + (p >> 3) : 64, cp = (j * 79) >> 10;
  return ((2 * p + (b & 1)) & 255) | (j - 13 * cp) << 8 | (2 * cp + (b & 1)) << 12 | (b >> 7) << 16;
}
#define CTX() asm volatile("" : "+r"(ctx)); CTXU()
#define CTXU() int tid; asm volatile("mov.u32 %0, %%tid.x;" : "=r"(tid)); \
  const int lane = tid & 31, vb = ctx & 255, hg = (ctx >> 4) & 7, rt = ctx & 15, par = (ctx >> 3) & 1, mt = ctx & 7, rank = ctx & 1, \
  tb = (ctx >> 8) & 15, cb = (ctx >> 12) & 15; const bool main_cta = ctx < 65536; \
  (void)tid; (void)lane; (void)vb; (void)hg; (void)rt; (void)par; (void)mt; (void)rank; (void)tb; (void)cb; (void)main_cta
#define CTXW() CTX(); const int wg = warp >> 2, w = warp & 3, g = lane >> 2, t = lane & 3; const bool lead = (tid & 127) == 0; \
  (void)wg; (void)w; (void)g; (void)t; (void)lead

__global__ void __cluster_dims__(2, 1, 1) __launch_bounds__(512, 1)
fused_kernel(const uint16_t* __restrict__ xq, const uint16_t* __restrict__ wqkv, const uint16_t* __restrict__ gate_w, const __grid_constant__ Maps M, const uint16_t* __restrict__ shift_k, const uint16_t* __restrict__ ssm_k, const uint16_t* __restrict__ ssm_D,
             const uint16_t* __restrict__ kin, const uint16_t* __restrict__ vin, uint16_t* __restrict__ outp) {
  extern __shared__ __align__(1024) uint8_t smem_raw[];
  const uint32_t sb = smem_u32(smem_raw);
  const uint32_t t0 = clk();
  auto get_epoch = [&]() { mbar_wait(sb + B_EP, 0); return lds32(sb + O_EPOCH); };

  auto p1_load_x = [&](int ks, int p, int rank) {
    tma3(sb + o_px(ks), &M.x_par, ks * 32, (p >> 2) & 1, (p & 3) * 256 + rank * 128, sb + B_FULL + 8 * (ks & 7));
  };
  auto p1_load_w = [&](int ks, int p, int rank) {
    const uint32_t st = sb + o_pw(ks), fb = sb + B_FULL + 8 * (ks & 7);
    tma3_mc(st + rank * 6144, &M.w_main, (p >> 3) * 80 + 2 * (p & 8), ks * 32 + rank * 16, 0, fb);
    tma3_mc(st + 12288 + rank * 1536, &M.w_tail, (p >> 3) * 80 + 8 * (~p & 8), ks * 32 + rank * 16, 0, fb);
  };
  auto cta_pair = [&]() { return pair_of(blockIdx.x >> 1); };

  const uint16_t* pfp = nullptr;
  if (threadIdx.x < 32) {
    const unsigned b = blockIdx.x, l = threadIdx.x;
    pfp = l < 16 ? xq + (16 * b + l) * 640 : wqkv + (15 * b + l - 16) * 64;
    if ((l | b >> 7 << 5) < 31) pf_l2(pfp);
  }
  const int warp = __shfl_sync(~0u, threadIdx.x >> 5, 0);
  if ((warp & 14) == 8) {
    if (elect_one()) {
#pragma unroll
      for (int s = 0; s < 8; s++) mbar_init(sb + O_BAR - 512 + 64 * warp + 8 * s, 5 * warp - 39);
      asm volatile("fence.mbarrier_init.release.cluster;" ::: "memory");
    }
    __syncwarp();
  }
  asm volatile("barrier.cluster.arrive.relaxed.aligned;" ::: "memory");
  if (warp == 8 && blockIdx.x < 128) {
    const int p = cta_pair(), rank = blockIdx.x & 1;
    if (elect_one()) { mbar_expect_tx(sb + B_FULL, 16384 + WST); p1_load_x(0, p, rank); }
    __syncwarp();
    asm volatile("barrier.cluster.wait.aligned;" ::: "memory");
    if (elect_one()) { p1_load_w(0, p, rank); PT(100); }
    __syncwarp();
  } else if (warp != 15) {
    asm volatile("barrier.cluster.wait.aligned;" ::: "memory");
    spin_until(t0, HOLD);
  }
  auto init_rest = [&]() {
    if (warp >= 11 && elect_one()) {
#pragma unroll
      for (int s = 0; s < 12; s++) mbar_init(sb + O_BAR + 128 - 11 * 96 + 96 * warp + 8 * s, warp == 14 ? 2 : 1);
      asm volatile("fence.mbarrier_init.release.cluster;" ::: "memory");
    }
    __syncwarp();
    bar_sync(0, blockIdx.x < 128 ? 224 : 512);
  };
  uint32_t ctx = 0;

  if (warp < 8) {
    if (PF2 && warp == 0) {
#pragma unroll 1
      for (int i = 1; i <= NPF; i++) {
        spin_until(t0, PF2 + (i - 1) * PFD);
        if ((threadIdx.x | blockIdx.x >> 7 << 5) < 31) pf_l2(pfp + (threadIdx.x < 16 ? 64 : 64 * 1920) * i);
        __syncwarp();
      }
    }
    reg_inc<RC>();
    ctx = make_ctx();
    if (blockIdx.x >= 128) bar_sync(0, 512);
    else {
      {
        uint32_t Q[10][2], K[10][2], V[10][2];
        {
          {
            float acc[120];
            {
              CTXW();
              const uint32_t aa = sb + (warp * 16 + (lane & 15)) * 128 + (((lane >> 4) ^ (lane & 7)) << 4);
              const uint32_t rsb = mapa(sb, (blockIdx.x & 1) ^ 1);
              uint32_t a0[8], a1[8], a2[8];
              auto load_a = [&](uint32_t (&r)[8], int ks) {
                mbar_wait(sb + B_FULL + 8 * (ks & 7), (ks >> 3) & 1);
                PTP(lead && (wg || !(ks & 3)), wg ? 60 + ks : 80 + (ks >> 2));
                if (SSMASK >> ks & 1) return;
                ldsm4(r[0], r[1], r[2], r[3], (aa ^ ((ks & 1) * 64)) + o_px(ks)); ldsm4(r[4], r[5], r[6], r[7], (aa ^ ((ks & 1) * 64 + 32)) + o_px(ks));
              };
              auto stage = [&](uint32_t (&r)[8], uint32_t (&nx)[8], int ks, int u) {
                const uint32_t dl = o_pw(ks) >> 4;
                const uint64_t db = mkdesc(SB, 2048, 1024, 1), dt = mkdesc(SB + 12288, 512, 256, 3);
                auto D = [&](uint64_t d) { return (d & ~0xFFFFFFFFull) | (uint32_t)((uint32_t)d + dl); };
                if (LEAD && u == (20 - LEAD) % 3) bar_sync_p(wg == 0 && ks == 20 - LEAD, NB_LEAD, 256);
                wg_fence();
                const uint64_t da = mkdesc(SB + o_px(ks) + (ks & 1) * 64, 16, 1024, 1) + wg * 512;
                if (SSMASK >> ks & 1) { wgmma_ss_n192<0, 0, 1>(acc, da, D(db), ks); wgmma_ss_n48<96, 0, 1>(acc, da, D(dt), ks); }
                else { wgmma_rs_n192<0, 1>(acc, r[0], r[1], r[2], r[3], D(db), ks); wgmma_rs_n48<96, 1>(acc, r[0], r[1], r[2], r[3], D(dt), ks); }
                wg_commit();
                if (LEAD && u == 1) bar_arrive_p(wg && ks == 19, NB_LEAD, 256);
                if (ks < 19) load_a(nx, ks + 1);
                wg_fence();
                if (SSMASK >> ks & 1) { wgmma_ss_n192<0, 0, 1>(acc, da + 2, D(db + 384), 1); wgmma_ss_n48<96, 0, 1>(acc, da + 2, D(dt + 96), 1); }
                else { wgmma_rs_n192<0, 1>(acc, r[4], r[5], r[6], r[7], D(db + 384), 1); wgmma_rs_n48<96, 1>(acc, r[4], r[5], r[6], r[7], D(dt + 96), 1); }
                wg_commit();
                wg_wait<2>();
                mbar_arrive2_p(lead && (u || ks), sb + B_EMPTY + 8 * ((ks - 1) & 7), rsb + B_EMPTY + 8 * ((ks - 1) & 7));
              };
              if (lead) PT(1 + wg);
              load_a(a0, 0);
              constexpr int p1u = P1U;
#pragma unroll p1u
              for (int ks = 0; ks < 21; ks += 3) {
                stage(a0, a1, ks, 0);
                stage(a1, a2, ks + 1, 1);
                if (ks == 18) break;
                stage(a2, a0, ks + 2, 2);
              }
              mbar_wait(sb + B_S15, 1);
              wg_wait<1>();
              mbar_arrive_p(tid == 0, sb + B_P1E);
              wg_wait<0>();
              fence_regs(acc);
              mbar_arrive2_p(lead, sb + B_S19, rsb + B_S19);
              PTPL(lead, 50 + wg);
            }
            CTXW();
            if (hg & 1) pack_qkv<1, 0>(acc, Q, K, V); else pack_qkv<0, 0>(acc, Q, K, V);
            if (warp == 7 && rank) {
              uint4* hp = g_halo + vb * 160 + lane;
              st_relaxed(hp, K[0][1], K[1][1], K[3][1], K[4][1]); st_relaxed(hp + 32, K[5][1], K[6][1], K[8][1], K[9][1]);
              st_relaxed(hp + 64, K[2][1], K[7][1], V[0][1], V[1][1]);
              st_relaxed(hp + 96, V[2][1], V[3][1], V[4][1], V[5][1]); st_relaxed(hp + 128, V[6][1], V[7][1], V[8][1], V[9][1]);
              PTPL(lane == 0, 25);
            }
            const uint32_t ho = sb + O_HALO + warp * 2560 + lane * 16;
            stsm4(ho, K[0][1], K[1][1], K[3][1], K[4][1]); stsm4(ho + 512, K[5][1], K[6][1], K[8][1], K[9][1]);
            stsm4(ho + 1024, K[2][1], K[7][1], V[0][1], V[1][1]);
            stsm4(ho + 1536, V[2][1], V[3][1], V[4][1], V[5][1]); stsm4(ho + 2048, V[6][1], V[7][1], V[8][1], V[9][1]);
            if (warp == 7) {
              if (!rank) {
                fence_async_smem();
                __syncwarp();
                if (elect_one())
                  asm volatile("cp.async.bulk.shared::cluster.shared::cta.mbarrier::complete_tx::bytes [%0], [%1], 2560, [%2];"
                               ::"r"(mapa(sb + O_HIN, 1)), "r"(sb + O_HALO + 7 * 2560), "r"(mapa(sb + B_HX0, 1)) : "memory");
              }
              __syncwarp();
            } else {
              __syncwarp();
              if (lane == 0) mbar_arrive(sb + B_HX + 8 + 8 * warp);
            }
            if (hg & 1) pack_qkv<1, 1>(acc, Q, K, V); else pack_qkv<0, 1>(acc, Q, K, V);
#pragma unroll
            for (int f = 0; f < 10; f++) V[f][0] = movm(V[f][0]);
            if (lead) PT(52 + wg);
            if (wg) mbar_wait(sb + B_P1E, 0);
          }
          CTXW();
          const bool gt0 = 2 * t > g, gt1 = 2 * t + 1 > g;
          const uint32_t pmask = (gt0 ? 0xFFFFu : 0u) | (gt1 ? 0xFFFF0000u : 0u);
          uint32_t Qh[4][2];
          float lg[8][2];
#pragma unroll
          for (int j = 0; j < 4; j++) {
            const int fa = (j >> 1) * 5 + (j & 1) * 3, fh = (j >> 1) * 5 + 2;
            const bool mine = (j & 1) ? (t >= 2) : (t < 2);
            Qh[j][0] = mine ? Q[fh][0] : 0u; Qh[j][1] = mine ? Q[fh][1] : 0u;
            float c1[4] = {0.f, 0.f, 0.f, 0.f}, c2[4] = {0.f, 0.f, 0.f, 0.f};
            mma16(c1, Q[fa][0], Q[fa][1], Q[fa + 1][0], Q[fa + 1][1], K[fa][0], K[fa + 1][0]);
            mma16(c2, Q[fa][0], Q[fa][1], Q[fa + 1][0], Q[fa + 1][1], K[fa][1], K[fa + 1][1]);
            mma8(c1, Qh[j][0], Qh[j][1], K[fh][0]);
            mma8(c2, Qh[j][0], Qh[j][1], K[fh][1]);
            lg[j][0] = c1[0]; lg[j][1] = c1[1];
            lg[4 + j][0] = gt0 ? c1[2] : c2[2]; lg[4 + j][1] = gt1 ? c1[3] : c2[3];
          }
          if (lead) PT(54 + wg);
          mbar_wait(sb + (warp ? B_HX + 8 * warp : B_HX0), 0);
          if (lead) PT(56 + wg);
          const uint32_t hs = warp ? O_HALO + (warp - 1) * 2560 : O_HIN, ha = sb + hs + lane * 16;
          const uint32_t va = sb + ((lane & 8) ? O_HALO + warp * 2560 : hs) + 1280 + (lane >> 4) * 128 + (lane & 7) * 16;
          uint32_t Kh[10], Vh[10];
          ldsm4(Kh[0], Kh[1], Kh[3], Kh[4], ha); ldsm4(Kh[5], Kh[6], Kh[8], Kh[9], ha + 512);
          asm volatile("ldmatrix.sync.aligned.m8n8.x2.shared.b16 {%0,%1}, [%2];" : "=r"(Kh[2]), "=r"(Kh[7]) : "r"(ha + 1024) : "memory");
#pragma unroll
          for (int i = 0; i < 5; i++) ldsm4t(Vh[2 * i], V[2 * i][1], Vh[2 * i + 1], V[2 * i + 1][1], va + i * 256);
          const bool have_halo = warp > 0 || mt > 0;
#pragma unroll
          for (int j = 0; j < 4; j++) {
            const int fa = (j >> 1) * 5 + (j & 1) * 3, fh = (j >> 1) * 5 + 2;
            float c0[4] = {0.f, 0.f, 0.f, 0.f};
            mma16(c0, Q[fa][0], Q[fa][1], Q[fa + 1][0], Q[fa + 1][1], Kh[fa], Kh[fa + 1]);
            mma8(c0, Qh[j][0], Qh[j][1], Kh[fh]);
            if (!have_halo) c0[0] = c0[1] = -INFINITY;
            lg[j][0] = gt0 ? c0[0] : lg[j][0]; lg[j][1] = gt1 ? c0[1] : lg[j][1];
          }
          uint32_t Pv[8], O[10][2];
          softmax8(lg, Pv);
#pragma unroll
          for (int j = 0; j < 4; j++) {
            const int fa = (j >> 1) * 5 + (j & 1) * 3, fh = (j >> 1) * 5 + 2;
            const uint32_t a0 = Pv[j] & pmask, a2 = Pv[j] & ~pmask, a3 = Pv[4 + j] & pmask, a5 = Pv[4 + j] & ~pmask;
#pragma unroll
            for (int q = 0; q < 3; q++) {
              const int f = q < 2 ? fa + q : fh;
              float o[4] = {0.f, 0.f, 0.f, 0.f};
              mma8(o, a2, a3, V[f][0]);
              mma16(o, a0, 0u, 0u, a5, Vh[f], V[f][1]);
              const uint32_t o0 = pack_bf16(o[0], o[1]), o1 = pack_bf16(o[2], o[3]);
              if (q < 2 || !(j & 1)) { O[f][0] = o0; O[f][1] = o1; }
              else { O[f][0] = t >= 2 ? o0 : O[f][0]; O[f][1] = t >= 2 ? o1 : O[f][1]; }
            }
          }
          {
            uint32_t z = threadIdx.y;
#pragma unroll
            for (int f = 0; f < 10; f++) z &= O[f][0];
            bar_arrive_p(wg == 0, NB_HALO + z, 256);
          }
          const uint32_t oa = sb + O_OST + (warp * 16 + (lane & 15)) * 160 + (lane >> 4) * 16;
#pragma unroll
          for (int i = 0; i < 5; i++) stsm4(oa + i * 32, O[2 * i][0], O[2 * i][1], O[2 * i + 1][0], O[2 * i + 1][1]);
        }
      }
      {
        CTXW();
        fence_async_smem();
        bar_arrive(NB_ATT, 288);
        if (lead) PT(58 + wg);
        const uint32_t abase = sb + (g & 1) * 4160 + 4 * (1023 - 4 - 8 * w - (g >> 1) + t);
        float acc[128];
        uint32_t a0[8], a1[8], a2[8], a3[8];
#pragma unroll 1
        for (int c = wg ^ 1; c < 5; c += 2) {
          const uint32_t ab = abase + o_h(c);
          const uint32_t db = __shfl_sync(~0u, ((SB + o_u(c) + UZ - 16) >> 4) | 0x10000u, 0);
          mbar_wait(sb + B_U + 8 * c, 0);
          load_pair<0>(a0, ab); load_pair<1>(a1, ab);
          load_pair<2>(a2, ab); load_pair<3>(a3, ab);
          if (lead) PT(85 + c);
          bar_sync(c ? NB_TOK + wg : NB_HALO, 256);
          fence_regs(acc);
          auto tok = [&](int p) { if (p == TOKP) bar_arrive_p(P3GO == 0 || c < 4, NB_TOK + (wg ^ 1), 256); };
          const uint32_t an = abase + o_h(c + 2);
          auto nxt = [&](auto P, uint32_t (&a)[8]) {
#pragma unroll
            for (int i = 0; i < 8; i++)
              asm volatile("{\n.reg .pred p;\nsetp.ne.b32 p, %2, 0;\n@p ld.shared.b32 %0, [%1];\n}" : "+r"(a[i]) : "r"(an + a_off(P, i)), "r"((int)(c < 3)));
          };
          mma_pair<0>(acc, a0, db);
          mma_pair<1>(acc, a1, db); wg_wait<1>();  load_pair<4>(a0, ab);
          if (lead) PT(90 + c);
          mma_pair<2>(acc, a2, db); wg_wait<1>();  load_pair<5>(a1, ab);
          mma_pair<3>(acc, a3, db); tok(3); wg_wait<1>();  load_pair<6>(a2, ab);
          mma_pair<4>(acc, a0, db); tok(4); wg_wait<1>();  load_pair<7>(a3, ab);
          mma_pair<5>(acc, a1, db); tok(5);
          mma_pair<6>(acc, a2, db); tok(6);
          mma_pair<7>(acc, a3, db);
          if (P3GO == 5) wg_wait<1>();
          if (P3GO == 3 || P3GO == 5) bar_arrive_p(c == 4, NB_TOK, 256);
          wg_wait<0>();
          if (P3GO == 4) bar_arrive_p(c == 4, NB_TOK, 256);
          fence_regs(acc);
          PTPL(lead, 95 + c);
          bar_sync(NB_RFREE + wg, 256);
          const uint32_t pb = sb + (w < 2 ? o_h(c) + w * 4160 : w == 2 ? o_u(c) : o_x(c)) + lane * 16;
          if (lane < 2 * w) sts128(pb, 0, 0, 0, 0);
#pragma unroll
          for (int q = 0; q < 8; q++) {
            uint32_t p[4];
#pragma unroll
            for (int i = 0; i < 4; i++) {
              const int nu = 4 * q + i;
              float v0 = acc[4 * nu], v1 = acc[4 * nu + 1];
              p[i] = pack_bf16(v0, v1);
              if (nu > 0) p[i] = hadd2(p[i], pack_bf16(acc[4 * nu - 2], acc[4 * nu - 1]));
            }
            stsm4t(pb + w * 32 + q * 512, p[0], p[1], p[2], p[3]);
            if (HALVES && q == 3) bar_arrive(NB_RFULL + 4 + wg, 256);
          }
          bar_arrive(NB_RFULL + wg, 256);
          if (P3GO == 1 && c == 4) bar_arrive(NB_TOK, 256);
          if (lead) PT(140 + c);
        }
      }
    }
    if (warp < 4) {
      CTXW();
      const uint32_t rsb = mapa(sb, (blockIdx.x & 1) ^ 1);
      const uint32_t ba = sb + O_BT + ((lane >> 4) * 8 + (lane & 7)) * 128 + (((2 * w + ((lane >> 3) & 1)) ^ ((lane & 1) << 2 | (lane >> 1 & 3))) << 4);
      mbar_wait(sb + B_P3F, 0);
      if (lead) PT(145);
      float acc[80];
#pragma unroll
      for (int ks = 0; ks < 10; ks++) {
        if (ks == NPRE) {
          if (NPRE) { wg_wait<0>(); mbar_arrive2_p(lead, sb + B_P3E + 8 * NPRE, rsb + B_P3E + 8 * NPRE); }
          bar_sync_p(blockIdx.x < 128, NB_TOK, 256);
        }
        PTP(lead, 146 + ks);
        const uint64_t da = mkdesc(SB + o_p3(ks), 1024, 1024, 1), db = mkdesc(SB + o_p3(ks) + 8192, 16, 1024, 1);
        wg_fence();
#pragma unroll
        for (int j = 0; j < 4; j++) wgmma_ss_n160<0, 1, 0>(acc, da + j * 128, db + j * 2, j | ks);
        wg_commit();
        if (ks < 9) mbar_wait(sb + B_P3F + 8 * (ks + 1), 0);
        if (ks >= 1 && ks <= 4 && ks != NPRE) { wg_wait<1>(); mbar_arrive2_p(lead, sb + B_P3E + 8 * ks, rsb + B_P3E + 8 * ks); }
      }
      wg_wait<0>();
      fence_regs(acc);
      PTPL(lead, 156);
#pragma unroll
      for (int i = 0; i < 10; i++) {
        stsm4t(ba + i * 2048, pack_bf16(acc[8 * i], acc[8 * i + 1]), pack_bf16(acc[8 * i + 2], acc[8 * i + 3]),
               pack_bf16(acc[8 * i + 4], acc[8 * i + 5]), pack_bf16(acc[8 * i + 6], acc[8 * i + 7]));
        if (i & 1) bar_arrive(1 + (i >> 1), 256);
      }
      if (lead) PT(157);
    }
  } else if (warp < 12) {
    reg_dec<RH>();
    const int hw = warp - 8;
    init_rest();
    ctx = __shfl_sync(~0u, make_ctx(), 0);
    if (ctx < 65536) {
      CTXU();
      if (hw == 0 && rank) {
#pragma unroll
        for (int f = 0; f < 5; f++) st_relaxed(g_halo + vb * 160 + lane + 32 * f, ~0u, ~0u, ~0u, ~0u);
      }
#pragma unroll 1
      for (int c = hw; c < 5; c += 4) {
        const int kb = 2 * c + (vb >> 6);
        const uint4 sk = __ldg((const uint4*)(shift_k + (size_t)(kb * 64 + 2 * lane) * 4));
        wait_until(t0, KT0 + c * KTD + ((((vb * KPH) & 63) * KTD) >> 6));
        if (lane == 0) PT(20 + c);
        kv_task(&M.kv_st, kin, vin, sk, kb, vb & 63, sb + o_kst(hw), lane);
        if (lane == 0) PT(30 + c);
      }
      if (lane == 0) mbar_arrive(sb + B_KVD + 8 * hw);
    }
    CTXU();
    const int g = lane >> 2, t = lane & 3, row = 8 * hw + g;
    const uint32_t go = (tb * 160 + row) * 80 + cb * 8 + t;
    uint4 T[10];
    auto load_q = [&]() {
#pragma unroll
      for (int i = 0; i < 10; i++) {
        T[i] = make_uint4(0, 0, 0, 0);
        if (i < 8 || tb < 12) asm volatile("ld.volatile.global.v4.b32 {%0,%1,%2,%3}, [%4];" : "=r"(T[i].x), "=r"(T[i].y), "=r"(T[i].z), "=r"(T[i].w) : "l"((const uint4*)xq + go + (i >> 1) * 2560 + (i & 1) * 4));
      }
    };
    if (main_cta) {
      bar_arrive(NB_RFREE, 256);
      bar_arrive(NB_RFREE + 1, 256);
      const int yrow = (vb & 0x61) | (vb & 6) << 2 | (vb >> 2 & 6);
      auto red = [&](int c) {
        const int wg = (c & 1) ^ 1;
        conv_reduce(sb, c, tid - 256, 128 * c + yrow, NB_RFULL + wg);
        if (P3GO == 2 && c == 4) bar_arrive(NB_TOK, 256);
        __syncwarp();
        if (lane == 0) flag_add(CNT_Y(4 * c + (vb >> 5)), 1);
        if (tid == 256) PTL(41 + c);
        if (c < 3) bar_arrive(NB_RFREE + wg, 256);
        if (c == 2) {
          bar_sync(NB_HELP, 128);
          if (tid == 256) { mbar_arrive(sb + B_P3E); mbar_arrive_remote(sb + B_P3E, rank ^ 1); }
        }
      };
#pragma unroll 1
      for (int c = 0; c < QC; c++) red(c);
      load_q();
#pragma unroll 1
      for (int c = QC; c < 5; c++) red(c);
    } else load_q();
    uint32_t G[5];
    mbar_wait(sb + B_G, 0);
#pragma unroll
    for (int q = 0; q < 5; q++) { uint16_t v; asm volatile("ld.shared.u16 %0, [%1];" : "=h"(v) : "r"(sb + O_GT + (32 * q + row) * 2)); G[q] = prmt(v, 0, 0x1010); }
#pragma unroll
    for (int i = 0; i < 10; i++) { const uint32_t c = G[i >> 1]; T[i] = make_uint4(hmul2(T[i].x, c), hmul2(T[i].y, c), hmul2(T[i].z, c), hmul2(T[i].w, c)); }
#pragma unroll
    for (int h = 0; h < 2; h++) {
      mbar_wait(sb + B_Y + 8 * h, 0);
      if (tid == 256) PT(46);
#pragma unroll
      for (int q = 0; q < 5; q++) {
        uint32_t y0, y1, y2, y3;
        ldsm4t(y0, y1, y2, y3, sb + O_Y + h * 10240 + q * 2048 + lane * 64 + ((hw ^ ((lane >> 1) & 3)) << 4));
        uint4& r = T[2 * q + h];
        r = make_uint4(hmul2(r.x, y0), hmul2(r.y, y1), hmul2(r.z, y2), hmul2(r.w, y3));
      }
    }
    const uint32_t so = sb + O_BT + row * 128 + ((t ^ ((g & 1) << 2 | g >> 1)) << 4);
    if (tid == 256) PTL(47);
#pragma unroll
    for (int q = 0; q < 5; q++) {
      const uint32_t c = hfma2(G[q], 0xBF80BF80u, 0x3F803F80u);
      bar_sync(1 + q, 256);
      if (q == 4) mbar_arrive_p(tid == 256, sb + B_DONE);
#pragma unroll
      for (int h = 0; h < 2; h++) {
        uint4 u;
        lds128((so ^ (h * 64)) + q * 4096, u.x, u.y, u.z, u.w);
        const uint4& r = T[2 * q + h];
        if (q < 4 || tb < 12) ((uint4*)outp)[go + q * 2560 + h * 4] = make_uint4(hfma2(u.x, c, r.x), hfma2(u.y, c, r.y), hfma2(u.z, c, r.z), hfma2(u.w, c, r.w));
      }
    }
  } else {
    reg_dec<RP>();
    uint4 gwv = make_uint4(0, 0, 0, 0);
    if (warp == 15) {
      const int p = cta_pair(), rank = blockIdx.x & 1;
      asm volatile("barrier.cluster.wait.aligned;" ::: "memory");
      if (blockIdx.x >= 128) bar_sync(0, 512);
      else {
#pragma unroll 1
        for (int ks = 1;; ks += 2) {
          mbar_wait(sb + B_EMPTY + 8 * (ks & 7), ((ks >> 3) & 1) ^ 1);
          spin_until(t0, PT1 + (ks - 1) * PTD);
          if (elect_one()) { mbar_expect_tx(sb + B_FULL + 8 * (ks & 7), WST); p1_load_w(ks, p, rank); PT(100 + ks); }
          if (ks == HT && elect_one()) mbar_arrive(sb + B_LAST);
          if (ks == 19) break;
          const int kn = ks + 1;
          mbar_wait(sb + B_EMPTY + 8 * (kn & 7), ((kn >> 3) & 1) ^ 1);
          spin_until(t0, PT1 + ks * PTD - PTE);
          if (elect_one()) { mbar_expect_tx(sb + B_FULL + 8 * (kn & 7), 16384 + WST); p1_load_x(kn, p, rank); p1_load_w(kn, p, rank); PT(100 + kn); }
        }
        mbar_wait(sb + B_S19, 0);
      }
    } else {
      if (threadIdx.x < 384 + 80) gwv = __ldg((const uint4*)gate_w + threadIdx.x - 384);
      init_rest();
    }
    ctx = __shfl_sync(~0u, make_ctx(), 0);
    CTXU();
    if (warp == 12) {
        unsigned epoch = 0;
      if (lane == 0) epoch = *(volatile unsigned*)(g_launch + blockIdx.x) + 1;
      if (main_cta) { sts128(sb + O_GW + lane * 16, gwv.x, gwv.y, gwv.z, gwv.w); bar_arrive(NB_G, 96); }
      if (lane == 0) {
        if ((sb & 0xFFFFFF) != SB) __trap();
        *(volatile unsigned*)(g_launch + blockIdx.x) = epoch;
        sts32(sb + O_EPOCH, epoch);
        mbar_arrive(sb + B_EP);
#pragma unroll 1
        for (int i = 3; i < 8; i++) asm volatile("prefetch.tensormap [%0];" ::"l"(&M.x_par + i) : "memory");
      }
      __syncwarp();
      if (main_cta) {
        uint4 h0 = make_uint4(0, 0, 0, 0);
        if (lane < 5) {
          h0 = __ldg((const uint4*)(ssm_k + (size_t)(128 * lane + vb) * 2048));
          h0.x = prmt(pack_bf16(bf_lo(h0.x) + bf_lo(__ldg(ssm_D + 128 * lane + vb)), 0.f), h0.x, 0x7610);
        }
        epoch = __shfl_sync(~0u, epoch, 0);
        mbar_wait(sb + B_LAST, 0);
        mbar_wait(sb + B_S13, 1);
#pragma unroll 1
        for (int c = 0; c < 5; c++) {
          if (c == 0 || c == 3) mbar_wait(sb + B_KVD + (c ? 16 : 8), 0);
          sts128(sb + o_u(c) + lane * 16, 0, 0, 0, 0);
          if (lane < 3) sts128(sb + (lane < 2 ? o_h(c) + lane * 4160 + 4096 : o_u(c) + 512), 0, 0, 0, 0);
          if (lane == c) sts128(sb + o_u(c) + UZ, h0.x, h0.y, h0.z, h0.w);
          fence_async_smem();
          __syncwarp();
          if (elect_one()) {
            mbar_expect_tx(sb + B_U + 8 * c, 3 * 4096 - 16);
            bulk_load(sb + o_u(c) + UZ + 16, ssm_k + (size_t)(128 * c + vb) * 2048 + 8, 4080, sb + B_U + 8 * c);
          }
          flag_wait(CNT_KV(2 * c + (vb >> 6)), 64 * epoch);
          __syncwarp();
          if (elect_one()) {
            bulk_load(sb + o_h(c), g_kvT + (size_t)(128 * c + vb) * 2048, 4096, sb + B_U + 8 * c);
            bulk_load(sb + o_h(c) + 4160, g_kvT + (size_t)(640 + 128 * c + vb) * 2048, 4096, sb + B_U + 8 * c);
            PT(10 + c);
          }
        }
      }
    } else if (warp != 15) {
        const int r = warp - 13;
      if (main_cta) {
        if (rank && lane == 0) mbar_expect_tx(sb + B_HX0, 1280);
        const int t = lane & 3, grow = hg * 16 + (lane & 15);
        const uint32_t ga = sb + grow * 128 + (((4 * r + (lane >> 4)) ^ (lane & 7)) << 4);
        const uint32_t gp = sb + O_GW + 64 * r + 4 * t;
        float s0 = 0.f, s1 = 0.f;
        if (tid < 384 + 80) sts128(sb + O_GW + (tid - 384) * 16, gwv.x, gwv.y, gwv.z, gwv.w);
        bar_sync(NB_G, 96);
#pragma unroll 1
        for (int ks = 0; ks < 20; ks += 2) {
          uint32_t x[8], gw[4];
#pragma unroll
          for (int i = 0; i < 4; i++) gw[i] = lds32(gp + ks * 64 + i * 16);
          mbar_wait_wd(sb + B_FULL + 8 * (ks & 7), (ks >> 3) & 1, t0);
          if (r == 0 && lane == 0) PT(120 + ks);
          ldsm4(x[0], x[1], x[2], x[3], ga + o_px(ks)); ldsm4(x[4], x[5], x[6], x[7], (ga ^ 32) + o_px(ks));
#pragma unroll
          for (int i = 0; i < 8; i++) x[i] = hmul2(x[i], gw[i >> 1]);
          if (lane < 2) mbar_arrive(sb + B_EMPTY + 8 * (ks & 7) + 8 * lane + (x[0] & x[7] & threadIdx.y));
#pragma unroll
          for (int i = 0; i < 8; i += 4) {
            s0 += (bf_lo(x[i]) + bf_hi(x[i])) + (bf_lo(x[i + 2]) + bf_hi(x[i + 2]));
            s1 += (bf_lo(x[i + 1]) + bf_hi(x[i + 1])) + (bf_lo(x[i + 3]) + bf_hi(x[i + 3]));
          }
        }
        s0 += __shfl_xor_sync(~0u, s0, 1); s1 += __shfl_xor_sync(~0u, s1, 1);
        s0 += __shfl_xor_sync(~0u, s0, 2); s1 += __shfl_xor_sync(~0u, s1, 2);
        if (t < 2) sts32(sb + O_GP + r * 64 + (8 * t + (lane >> 2)) * 4, __float_as_uint(t ? s1 : s0));
        if (r == 0) bar_arrive(NB_G, 64);
        if (!rank) {
          uint4 d[3];
          if (mt > 0) {
            const uint4* hp = g_halo + (vb - 1) * 160 + r * 64 + lane;
            mbar_wait_wd(sb + B_EP, 0, t0);
            const unsigned target = 64 * lds32(sb + O_EPOCH);
            unsigned v;
            do {
              asm volatile("ld.relaxed.gpu.global.u32 %0, [%1];" : "=r"(v) : "l"(CNT_KV(vb >> 6)) : "memory");
              if (clk() - t0 > 0x70000000u) __trap();
            } while ((int)(v - target) < 0);
            mbar_wait_wd(sb + B_HX + 56, 0, t0);
            if (HDL) { const uint32_t t1 = clk(); spin_until(t1, HDL); }
            PTPL(lane == 0 && r == 1, 26);
            for (;;) {
              bool ok = true;
#pragma unroll
              for (int f = 0; f < 3; f++) {
                asm volatile("ld.relaxed.gpu.global.v4.b32 {%0,%1,%2,%3}, [%4];" : "=r"(d[f].x), "=r"(d[f].y), "=r"(d[f].z), "=r"(d[f].w) : "l"(hp + 32 * f) : "memory");
              }
#pragma unroll
              for (int f = 0; f < 3; f++) ok = ok && max(max(d[f].x, d[f].y), max(d[f].z, d[f].w)) != ~0u;
              if (__all_sync(~0u, ok)) break;
              PTPL(lane == 0 && r == 1, 27);
              if (clk() - t0 > 0x70000000u) __trap();
            }
          } else {
#pragma unroll
            for (int f = 0; f < 3; f++) d[f] = make_uint4(0, 0, 0, 0);
          }
#pragma unroll
          for (int f = 0; f < 3; f++) stsm4(sb + O_HIN + r * 1024 + f * 512 + lane * 16, d[f].x, d[f].y, d[f].z, d[f].w);
          __syncwarp();
          if (lane == 0) { mbar_arrive(sb + B_HX0); PTL(15 + r); }
        }
        if (r == 1) {
          bar_sync(NB_G, 64);
          if (lane < 16) {
            const uint32_t pa = sb + O_GP + lane * 4;
            const float z = __uint_as_float(lds32(pa)) + __uint_as_float(lds32(pa + 64));
            g_gate[2 * (mt * 128 + hg * 16 + lane) + par] = (uint16_t)pack_bf16(__fdividef(1.f, 1.f + __expf(-bf_lo(pack_bf16(z, 0.f)))), 0.f);
          }
          __syncwarp();
          if (lane == 0) flag_add(CNT_O(rt), 1);
        }
      }
      if (elect_one()) {
        mbar_wait_wd(sb + B_EP, 0, t0);
        const unsigned epoch = lds32(sb + O_EPOCH);
        if (main_cta) mbar_wait_wd(sb + B_P3E, 0, t0);
        unsigned v;
        do {
          asm volatile("ld.relaxed.gpu.global.u32 %0, [%1];" : "=r"(v) : "l"(CNT_Y(2 * cb + r)) : "memory");
          if (clk() - t0 > 0x70000000u) __trap();
        } while ((int)(v - 128 * epoch) < 0);
        mbar_expect_tx(sb + B_Y + 8 * r, 10240);
        tma3(sb + O_Y + r * 10240, &M.y_ld, 0, cb * 64 + 32 * r, tb * 5, sb + B_Y + 8 * r);
        PTL(17 + r);
        mbar_wait_wd(sb + B_DONE, 0, t0);
      }
    } else {
      const unsigned epoch = get_epoch();
      if (main_cta) bar_sync(NB_ATT, 288);
      if (elect_one()) {
        if (main_cta) {
          tma3_store(&M.o_st, hg * 80, par, mt * 128, sb + O_OST);
          bulk_commit(); bulk_wait_all();
          flag_add(CNT_O(rt), 1);
        }
        PT(3);
      }
      __syncwarp();
      if (lane < 4) flag_wait(CNT_O(8 * (lane & 1) + min(7, (80 * tb + 79 * (lane >> 1)) >> 7)), 16 * epoch);
      __syncwarp();
      if (elect_one()) {
        PT(4);
        mbar_arrive_remote(sb + B_P3R, rank ^ 1);
        mbar_expect_tx(sb + B_G, 320);
        bulk_load(sb + O_GT, g_gate + tb * 160, 320, sb + B_G);
      }
      mbar_wait(sb + B_P3R, 0);
#pragma unroll 1
      for (int ks = 0; ks < 10; ks++) {
        if (ks > 5 || (ks == 5 && main_cta)) mbar_wait(sb + B_P3E + 8 * (ks - 5), 0);
        if (elect_one()) {
          PTP(ks >= 5, ks);
          tma2_mc(sb + o_p3(ks) + 8192 + rank * 10240, &M.o_ld, ks * 64, tb * 160 + rank * 80, sb + B_P3F + 8 * ks);
          tma2(sb + o_p3(ks), &M.wo, cb * 64, ks * 64, sb + B_P3F + 8 * ks);
          mbar_expect_tx(sb + B_P3F + 8 * ks, P3S);
        }
      }
    }
  }
}

typedef CUresult (*PFN_enc)(CUtensorMap*, CUtensorMapDataType, cuuint32_t, void*, const cuuint64_t*, const cuuint64_t*, const cuuint32_t*,
                            const cuuint32_t*, CUtensorMapInterleave, CUtensorMapSwizzle, CUtensorMapL2promotion, CUtensorMapFloatOOBfill);
static void enc(PFN_enc f, CUtensorMap* m, const void* base, int rank, const cuuint64_t* dims, const cuuint64_t* strides, const cuuint32_t* box,
                CUtensorMapSwizzle sw) {
  const cuuint32_t es[5] = {1, 1, 1, 1, 1};
  f(m, CU_TENSOR_MAP_DATA_TYPE_BFLOAT16, rank, (void*)base, dims, strides, box, es, CU_TENSOR_MAP_INTERLEAVE_NONE, sw,
    CU_TENSOR_MAP_L2_PROMOTION_NONE, CU_TENSOR_MAP_FLOAT_OOB_FILL_NONE);
}

extern "C" void kernel_launch(void* const* d_in, const int* in_sizes, int n_in, void* d_out, int out_size) {
  (void)in_sizes; (void)n_in; (void)out_size;
  static PFN_enc f = nullptr;
  static void *kvT, *y2T, *o;
  if (!f) {
    void* p = nullptr;
    cudaDriverEntryPointQueryResult q;
    cudaGetDriverEntryPoint("cuTensorMapEncodeTiled", &p, cudaEnableDefault, &q);
    f = (PFN_enc)p;
    cudaGetSymbolAddress(&kvT, g_kvT); cudaGetSymbolAddress(&y2T, g_y2T); cudaGetSymbolAddress(&o, g_o);
    cudaFuncSetAttribute(fused_kernel, cudaFuncAttributeMaxDynamicSharedMemorySize, SMEM_BYTES);
  }
  Maps M;
  const CUtensorMapSwizzle S0 = CU_TENSOR_MAP_SWIZZLE_NONE, S32 = CU_TENSOR_MAP_SWIZZLE_32B, S64 = CU_TENSOR_MAP_SWIZZLE_64B, S128 = CU_TENSOR_MAP_SWIZZLE_128B;
  const cuuint64_t dpar[3] = {640, 2, 1024}, spar[2] = {1280, 2560};
  const cuuint64_t dw[3] = {640, 640, 3}, sw[2] = {3840, 1280};
  const cuuint64_t dnat[2] = {640, 2048}, snat[1] = {1280};
  const cuuint64_t dT[3] = {32, 640, 64}, dT2[3] = {32, 1280, 64}, sT[2] = {4096, 64};
  const cuuint64_t dwo[2] = {640, 640};
  { const cuuint32_t bx[3] = {64, 1, 128}; enc(f, &M.x_par, d_in[0], 3, dpar, spar, bx, S128); }
  { const cuuint32_t bx[3] = {64, 16, 3}; enc(f, &M.w_main, d_in[7], 3, dw, sw, bx, S128); }
  { const cuuint32_t bx[3] = {16, 16, 3}; enc(f, &M.w_tail, d_in[7], 3, dw, sw, bx, S32); }
  { const cuuint32_t bx[3] = {80, 1, 128}; enc(f, &M.o_st, o, 3, dpar, spar, bx, S0); }
  { const cuuint32_t bx[3] = {32, 64, 1}; enc(f, &M.kv_st, kvT, 3, dT2, sT, bx, S64); }
  { const cuuint32_t bx[3] = {32, 32, 5}; enc(f, &M.y_ld, y2T, 3, dT, sT, bx, S64); }
  { const cuuint32_t bx[2] = {64, 64}; enc(f, &M.wo, d_in[8], 2, dwo, snat, bx, S128); }
  { const cuuint32_t bx[2] = {64, 80}; enc(f, &M.o_ld, o, 2, dnat, snat, bx, S128); }
  fused_kernel<<<130, 512, SMEM_BYTES, cudaStreamPerThread>>>((const uint16_t*)d_in[0], (const uint16_t*)d_in[7], (const uint16_t*)d_in[9], M, (const uint16_t*)d_in[3], (const uint16_t*)d_in[4], (const uint16_t*)d_in[5],
                                                              (const uint16_t*)d_in[1], (const uint16_t*)d_in[2], (uint16_t*)d_out);
}
```

```cpp
#include <cuda_runtime.h>
#include <cuda_bf16.h>
#include <cuda.h>
#include <stdint.h>

#define DEVI __device__ __forceinline__
#define PT1 100
#define PTD 460
#define PTE 200
#define PF2 0
#define NPF 1
#define PFD 0
#define SSMASK 0
static_assert((SSMASK & 0xAAA) == 0, "an x tile is refilled as soon as its even stage is released");
#define KPH KTD
#define CV 0
#define TOKP 6
#define NPRE 1
#define P3GO 3
#define SPLIT4 1
#define MIXW 1
#define YE 2
#define HDL 0
#define ZD 40
#define BACKOFF 0
#define ZW 1
#define KT0 1500
#define KTD 1000
#define RC 192
#define RH 96
#define RP 32
#define HOLD 750
#define P1U 7
#define LEAD 3

DEVI uint32_t smem_u32(const void* p) { return (uint32_t)__cvta_generic_to_shared(p); }
DEVI void wg_fence() { asm volatile("wgmma.fence.sync.aligned;" ::: "memory"); }
DEVI void wg_commit() { asm volatile("wgmma.commit_group.sync.aligned;" ::: "memory"); }
template <int N> DEVI void wg_wait() { asm volatile("wgmma.wait_group.sync.aligned %0;" ::"n"(N) : "memory"); }
template <int S> DEVI void fence_regs(float (&d)[S]) {
#pragma unroll
  for (int i = 0; i < S; i++) asm volatile("" : "+f"(d[i])::"memory");
}
DEVI uint64_t mkdesc(uint32_t addr, uint32_t lbo, uint32_t sbo, int swz) {
  return (uint64_t)((addr & 0x3FFFF) >> 4) | ((uint64_t)(lbo >> 4) << 16) | ((uint64_t)(sbo >> 4) << 32) | ((uint64_t)swz << 62);
}
DEVI void mbar_init(uint32_t bar, uint32_t cnt) { asm volatile("mbarrier.init.shared::cta.b64 [%0], %1;" ::"r"(bar), "r"(cnt) : "memory"); }
DEVI void mbar_expect_tx(uint32_t bar, uint32_t bytes) { asm volatile("mbarrier.arrive.expect_tx.shared::cta.b64 _, [%0], %1;" ::"r"(bar), "r"(bytes) : "memory"); }
DEVI void mbar_arrive(uint32_t bar) { asm volatile("mbarrier.arrive.shared::cta.b64 _, [%0];" ::"r"(bar) : "memory"); }
DEVI void mbar_wait(uint32_t bar, uint32_t parity) {
  asm volatile("{\n.reg .pred p;\nLAB_WAIT:\nmbarrier.try_wait.parity.shared::cta.b64 p, [%0], %1;\n@!p bra LAB_WAIT;\n}" ::"r"(bar), "r"(parity) : "memory");
}
DEVI void mbar_wait_wd(uint32_t bar, uint32_t parity, uint32_t t0) {
  asm volatile("{\n.reg .pred p;\n.reg .u32 c;\nLAB_WAIT:\nmbarrier.try_wait.parity.shared::cta.b64 p, [%0], %1;\n@p bra DONE;\nmov.u32 c, %%clock;\nsub.u32 c, c, %2;\nsetp.lt.u32 p, c, 0x70000000;\n@p bra LAB_WAIT;\ntrap;\nDONE:\n}" ::"r"(bar), "r"(parity), "r"(t0) : "memory");
}
DEVI void flag_wait(const unsigned* p, unsigned target) {
  asm volatile("{\n.reg .pred p;\n.reg .s32 v;\nLAB_WAIT:\nld.relaxed.gpu.global.u32 v, [%0];\nsub.s32 v, v, %1;\nsetp.lt.s32 p, v, 0;\n@p nanosleep.u32 %2;\n@p bra LAB_WAIT;\n}" ::"l"(p), "r"(target), "n"(BACKOFF) : "memory");
}
DEVI void flag_wait_wd(const unsigned* p, unsigned target, uint32_t t0) {
  asm volatile("{\n.reg .pred p;\n.reg .s32 v;\nLAB_WAIT:\nld.relaxed.gpu.global.u32 v, [%0];\nsub.s32 v, v, %1;\nsetp.ge.s32 p, v, 0;\n@p bra DONE;\nmov.u32 v, %%clock;\nsub.s32 v, v, %2;\nsetp.lt.u32 p, v, 0x70000000;\n@p bra LAB_WAIT;\ntrap;\nDONE:\n}" ::"l"(p), "r"(target), "r"(t0) : "memory");
}
DEVI void flag_add(unsigned* p, unsigned v) { asm volatile("red.relaxed.gpu.global.add.u32 [%0], %1;" ::"l"(p), "r"(v) : "memory"); }
DEVI void flag_release(unsigned* p) { asm volatile("fence.proxy.async;\nred.relaxed.gpu.global.add.u32 [%0], 1;" ::"l"(p) : "memory"); }
DEVI void fence_async_smem() { asm volatile("fence.proxy.async.shared::cta;" ::: "memory"); }
DEVI bool elect_one() { uint32_t p; asm volatile("{\n.reg .pred P;\nelect.sync _|P, 0xffffffff;\nselp.u32 %0, 1, 0, P;\n}" : "=r"(p)); return p; }
DEVI void bar_sync(int id, int n) { asm volatile("bar.sync %0, %1;" ::"r"(id), "r"(n) : "memory"); }
DEVI void bar_arrive(int id, int n) { asm volatile("bar.arrive %0, %1;" ::"r"(id), "r"(n) : "memory"); }
DEVI void tma2(uint32_t dst, const CUtensorMap* m, int c0, int c1, uint32_t bar) {
  asm volatile("cp.async.bulk.tensor.2d.shared::cluster.global.mbarrier::complete_tx::bytes [%0], [%1, {%3, %4}], [%2];" ::"r"(dst), "l"(m), "r"(bar), "r"(c0), "r"(c1) : "memory");
}
DEVI void tma3(uint32_t dst, const CUtensorMap* m, int c0, int c1, int c2, uint32_t bar) {
  asm volatile("cp.async.bulk.tensor.3d.shared::cluster.global.mbarrier::complete_tx::bytes [%0], [%1, {%3, %4, %5}], [%2];" ::"r"(dst), "l"(m), "r"(bar), "r"(c0), "r"(c1), "r"(c2) : "memory");
}
DEVI void tma3_mc(uint32_t dst, const CUtensorMap* m, int c0, int c1, int c2, uint32_t bar) {
  asm volatile("cp.async.bulk.tensor.3d.shared::cluster.global.mbarrier::complete_tx::bytes.multicast::cluster [%0], [%1, {%3, %4, %5}], [%2], %6;" ::"r"(dst), "l"(m), "r"(bar), "r"(c0), "r"(c1), "r"(c2), "h"((uint16_t)3) : "memory");
}
DEVI void tma2_mc(uint32_t dst, const CUtensorMap* m, int c0, int c1, uint32_t bar) {
  asm volatile("cp.async.bulk.tensor.2d.shared::cluster.global.mbarrier::complete_tx::bytes.multicast::cluster [%0], [%1, {%3, %4}], [%2], %5;" ::"r"(dst), "l"(m), "r"(bar), "r"(c0), "r"(c1), "h"((uint16_t)3) : "memory");
}
DEVI void mbar_arrive_remote(uint32_t bar, uint32_t cta) {
  asm volatile("{\n.reg .b32 ra;\nmapa.shared::cluster.u32 ra, %0, %1;\nmbarrier.arrive.shared::cluster.b64 _, [ra];\n}" ::"r"(bar), "r"(cta) : "memory");
}
DEVI void tma3_store(const CUtensorMap* m, int c0, int c1, int c2, uint32_t src) {
  asm volatile("cp.async.bulk.tensor.3d.global.shared::cta.bulk_group [%0, {%2, %3, %4}], [%1];" ::"l"(m), "r"(src), "r"(c0), "r"(c1), "r"(c2) : "memory");
}
DEVI void bulk_load(uint32_t dst, const void* src, uint32_t bytes, uint32_t bar) {
  asm volatile("cp.async.bulk.shared::cluster.global.mbarrier::complete_tx::bytes [%0], [%1], %2, [%3];" ::"r"(dst), "l"(src), "r"(bytes), "r"(bar) : "memory");
}
DEVI void bulk_store(void* dst, uint32_t src, uint32_t bytes) {
  asm volatile("cp.async.bulk.global.shared::cta.bulk_group [%0], [%1], %2;" ::"l"(dst), "r"(src), "r"(bytes) : "memory");
}
DEVI void pf_l2(const void* p) { asm volatile("prefetch.global.L2 [%0];" ::"l"(p)); }
template <int OFF> DEVI uint32_t ldg_v(const void* p) { uint32_t v; asm volatile("ld.volatile.global.b32 %0, [%1 + %2];" : "=r"(v) : "l"(p), "n"(OFF)); return v; }
DEVI void bulk_commit() { asm volatile("cp.async.bulk.commit_group;" ::: "memory"); }
DEVI void bulk_wait_all() { asm volatile("cp.async.bulk.wait_group 0;" ::: "memory"); }
DEVI void bulk_wait_read() { asm volatile("cp.async.bulk.wait_group.read 0;" ::: "memory"); }
template <int R> DEVI void reg_inc() { asm volatile("setmaxnreg.inc.sync.aligned.u32 %0;" ::"n"(R)); }
template <int R> DEVI void reg_dec() { asm volatile("setmaxnreg.dec.sync.aligned.u32 %0;" ::"n"(R)); }
DEVI uint32_t prmt(uint32_t a, uint32_t b, uint32_t s) { uint32_t r; asm("prmt.b32 %0,%1,%2,%3;" : "=r"(r) : "r"(a), "r"(b), "r"(s)); return r; }
DEVI uint32_t lds32(uint32_t a) { uint32_t r; asm volatile("ld.shared.b32 %0,[%1];" : "=r"(r) : "r"(a)); return r; }
DEVI void sts32(uint32_t a, uint32_t x) { asm volatile("st.shared.b32 [%0],%1;" ::"r"(a), "r"(x) : "memory"); }
DEVI void sts128(uint32_t a, uint32_t x, uint32_t y, uint32_t z, uint32_t w) { asm volatile("st.shared.v4.b32 [%0],{%1,%2,%3,%4};" ::"r"(a), "r"(x), "r"(y), "r"(z), "r"(w) : "memory"); }
DEVI void sts128v(uint32_t a, uint32_t x, uint32_t y, uint32_t z, uint32_t w) { asm volatile("st.volatile.shared.v4.b32 [%0],{%1,%2,%3,%4};" ::"r"(a), "r"(x), "r"(y), "r"(z), "r"(w) : "memory"); }
DEVI void lds128(uint32_t a, uint32_t& x, uint32_t& y, uint32_t& z, uint32_t& w) { asm volatile("ld.shared.v4.b32 {%0,%1,%2,%3},[%4];" : "=r"(x), "=r"(y), "=r"(z), "=r"(w) : "r"(a) : "memory"); }
DEVI void ldsm4(uint32_t& r0, uint32_t& r1, uint32_t& r2, uint32_t& r3, uint32_t addr) {
  asm volatile("ldmatrix.sync.aligned.m8n8.x4.shared.b16 {%0,%1,%2,%3}, [%4];" : "=r"(r0), "=r"(r1), "=r"(r2), "=r"(r3) : "r"(addr) : "memory");
}
DEVI void ldsm4t(uint32_t& r0, uint32_t& r1, uint32_t& r2, uint32_t& r3, uint32_t addr) {
  asm volatile("ldmatrix.sync.aligned.m8n8.x4.trans.shared.b16 {%0,%1,%2,%3}, [%4];" : "=r"(r0), "=r"(r1), "=r"(r2), "=r"(r3) : "r"(addr) : "memory");
}
DEVI void stsm4(uint32_t addr, uint32_t r0, uint32_t r1, uint32_t r2, uint32_t r3) {
  asm volatile("stmatrix.sync.aligned.m8n8.x4.shared.b16 [%0], {%1,%2,%3,%4};" ::"r"(addr), "r"(r0), "r"(r1), "r"(r2), "r"(r3) : "memory");
}
DEVI void stsm4t(uint32_t addr, uint32_t r0, uint32_t r1, uint32_t r2, uint32_t r3) {
  asm volatile("stmatrix.sync.aligned.m8n8.x4.trans.shared.b16 [%0], {%1,%2,%3,%4};" ::"r"(addr), "r"(r0), "r"(r1), "r"(r2), "r"(r3) : "memory");
}
DEVI uint32_t movm(uint32_t a) { uint32_t r; asm volatile("movmatrix.sync.aligned.m8n8.trans.b16 %0, %1;" : "=r"(r) : "r"(a)); return r; }
DEVI uint32_t pack_bf16(float lo, float hi) { uint32_t r; asm("cvt.rn.bf16x2.f32 %0, %1, %2;" : "=r"(r) : "f"(hi), "f"(lo)); return r; }
DEVI uint32_t hmul2(uint32_t a, uint32_t b) { uint32_t r; asm("mul.rn.bf16x2 %0,%1,%2;" : "=r"(r) : "r"(a), "r"(b)); return r; }
DEVI uint32_t hadd2(uint32_t a, uint32_t b) { uint32_t r; asm("add.rn.bf16x2 %0,%1,%2;" : "=r"(r) : "r"(a), "r"(b)); return r; }
DEVI float bf_lo(uint32_t a) { return __uint_as_float(prmt(a, 0, 0x1044)); }
DEVI float bf_hi(uint32_t a) { return __uint_as_float(a & 0xFFFF0000u); }
DEVI void mma16(float (&c)[4], uint32_t a0, uint32_t a1, uint32_t a2, uint32_t a3, uint32_t b0, uint32_t b1) {
  asm("mma.sync.aligned.m16n8k16.row.col.f32.bf16.bf16.f32 {%0,%1,%2,%3},{%4,%5,%6,%7},{%8,%9},{%0,%1,%2,%3};"
      : "+f"(c[0]), "+f"(c[1]), "+f"(c[2]), "+f"(c[3]) : "r"(a0), "r"(a1), "r"(a2), "r"(a3), "r"(b0), "r"(b1));
}
DEVI void mma8(float (&c)[4], uint32_t a0, uint32_t a1, uint32_t b0) {
  asm("mma.sync.aligned.m16n8k8.row.col.f32.bf16.bf16.f32 {%0,%1,%2,%3},{%4,%5},{%6},{%0,%1,%2,%3};"
      : "+f"(c[0]), "+f"(c[1]), "+f"(c[2]), "+f"(c[3]) : "r"(a0), "r"(a1), "r"(b0));
}
DEVI float ex2(float x) { float r; asm("ex2.approx.ftz.f32 %0, %1;" : "=f"(r) : "f"(x)); return r; }

DEVI uint32_t clk() { uint32_t c; asm volatile("mov.u32 %0, %%clock;" : "=r"(c)); return c; }
DEVI void wait_until(uint32_t t0, int dt) { while ((int)(clk() - t0) < dt) __nanosleep(40); }
DEVI void spin_until(uint32_t t0, int dt) { while ((int)(clk() - t0) < dt) {} }
DEVI uint32_t hfma2(uint32_t a, uint32_t b, uint32_t c) { uint32_t r; asm("fma.rn.bf16x2 %0,%1,%2,%3;" : "=r"(r) : "r"(a), "r"(b), "r"(c)); return r; }
DEVI void bar_sync_p(int on, int id, int n) { asm volatile("{\n.reg .pred p;\nsetp.ne.b32 p, %0, 0;\n@p bar.sync %1, %2;\n}" ::"r"(on), "r"(id), "r"(n) : "memory"); }
DEVI void bar_arrive_p(int on, int id, int n) { asm volatile("{\n.reg .pred p;\nsetp.ne.b32 p, %0, 0;\n@p bar.arrive %1, %2;\n}" ::"r"(on), "r"(id), "r"(n) : "memory"); }
DEVI void mbar_arrive_p(int on, uint32_t bar) { asm volatile("{\n.reg .pred p;\nsetp.ne.b32 p, %1, 0;\n@p mbarrier.arrive.shared::cta.b64 _, [%0];\n}" ::"r"(bar), "r"(on) : "memory"); }
DEVI void mbar_arrive2_p(int on, uint32_t bar, uint32_t rbar) {
  asm volatile("{\n.reg .pred p;\nsetp.ne.b32 p, %2, 0;\n@p mbarrier.arrive.shared::cta.b64 _, [%0];\n@p mbarrier.arrive.shared::cluster.b64 _, [%1];\n}" ::"r"(bar), "r"(rbar), "r"(on) : "memory");
}
DEVI void st_relaxed(uint4* p, uint32_t x, uint32_t y, uint32_t z, uint32_t w) {
  asm volatile("st.relaxed.gpu.global.v4.b32 [%0], {%1,%2,%3,%4};" ::"l"(p), "r"(x), "r"(y), "r"(z), "r"(w) : "memory");
}
DEVI uint32_t mapa(uint32_t a, uint32_t cta) { uint32_t r; asm("mapa.shared::cluster.u32 %0, %1, %2;" : "=r"(r) : "r"(a), "r"(cta)); return r; }
DEVI void st_async128(uint32_t a, uint32_t x, uint32_t y, uint32_t z, uint32_t w, uint32_t bar) {
  asm volatile("st.async.weak.shared::cluster.mbarrier::complete_tx::bytes.v4.b32 [%0], {%1,%2,%3,%4}, [%5];" ::"r"(a), "r"(x), "r"(y), "r"(z), "r"(w), "r"(bar) : "memory");
}

template<int OFF, int TB, int S> __device__ __forceinline__ void wgmma_rs_n192(float (&d)[S], uint32_t a0, uint32_t a1, uint32_t a2, uint32_t a3, uint64_t db, int sd) {
  asm volatile("{\n.reg .pred p;\nsetp.ne.b32 p, %101, 0;\n"
    "wgmma.mma_async.sync.aligned.m64n192k16.f32.bf16.bf16 {%0, %1, %2, %3, %4, %5, %6, %7, %8, %9, %10, %11, %12, %13, %14, %15, %16, %17, %18, %19, %20, %21, %22, %23, %24, %25, %26, %27, %28, %29, %30, %31, %32, %33, %34, %35, %36, %37, %38, %39, %40, %41, %42, %43, %44, %45, %46, %47, %48, %49, %50, %51, %52, %53, %54, %55, %56, %57, %58, %59, %60, %61, %62, %63, %64, %65, %66, %67, %68, %69, %70, %71, %72, %73, %74, %75, %76, %77, %78, %79, %80, %81, %82, %83, %84, %85, %86, %87, %88, %89, %90, %91, %92, %93, %94, %95}, {%96, %97, %98, %99}, %100, p, 1, 1, %102;\n}\n"
    : "+f"(d[OFF+0]), "+f"(d[OFF+1]), "+f"(d[OFF+2]), "+f"(d[OFF+3]), "+f"(d[OFF+4]), "+f"(d[OFF+5]), "+f"(d[OFF+6]), "+f"(d[OFF+7]), "+f"(d[OFF+8]), "+f"(d[OFF+9]), "+f"(d[OFF+10]), "+f"(d[OFF+11]), "+f"(d[OFF+12]), "+f"(d[OFF+13]), "+f"(d[OFF+14]), "+f"(d[OFF+15]), "+f"(d[OFF+16]), "+f"(d[OFF+17]), "+f"(d[OFF+18]), "+f"(d[OFF+19]), "+f"(d[OFF+20]), "+f"(d[OFF+21]), "+f"(d[OFF+22]), "+f"(d[OFF+23]), "+f"(d[OFF+24]), "+f"(d[OFF+25]), "+f"(d[OFF+26]), "+f"(d[OFF+27]), "+f"(d[OFF+28]), "+f"(d[OFF+29]), "+f"(d[OFF+30]), "+f"(d[OFF+31]), "+f"(d[OFF+32]), "+f"(d[OFF+33]), "+f"(d[OFF+34]), "+f"(d[OFF+35]), "+f"(d[OFF+36]), "+f"(d[OFF+37]), "+f"(d[OFF+38]), "+f"(d[OFF+39]), "+f"(d[OFF+40]), "+f"(d[OFF+41]), "+f"(d[OFF+42]), "+f"(d[OFF+43]), "+f"(d[OFF+44]), "+f"(d[OFF+45]), "+f"(d[OFF+46]), "+f"(d[OFF+47]), "+f"(d[OFF+48]), "+f"(d[OFF+49]), "+f"(d[OFF+50]), "+f"(d[OFF+51]), "+f"(d[OFF+52]), "+f"(d[OFF+53]), "+f"(d[OFF+54]), "+f"(d[OFF+55]), "+f"(d[OFF+56]), "+f"(d[OFF+57]), "+f"(d[OFF+58]), "+f"(d[OFF+59]), "+f"(d[OFF+60]), "+f"(d[OFF+61]), "+f"(d[OFF+62]), "+f"(d[OFF+63]), "+f"(d[OFF+64]), "+f"(d[OFF+65]), "+f"(d[OFF+66]), "+f"(d[OFF+67]), "+f"(d[OFF+68]), "+f"(d[OFF+69]), "+f"(d[OFF+70]), "+f"(d[OFF+71]), "+f"(d[OFF+72]), "+f"(d[OFF+73]), "+f"(d[OFF+74]), "+f"(d[OFF+75]), "+f"(d[OFF+76]), "+f"(d[OFF+77]), "+f"(d[OFF+78]), "+f"(d[OFF+79]), "+f"(d[OFF+80]), "+f"(d[OFF+81]), "+f"(d[OFF+82]), "+f"(d[OFF+83]), "+f"(d[OFF+84]), "+f"(d[OFF+85]), "+f"(d[OFF+86]), "+f"(d[OFF+87]), "+f"(d[OFF+88]), "+f"(d[OFF+89]), "+f"(d[OFF+90]), "+f"(d[OFF+91]), "+f"(d[OFF+92]), "+f"(d[OFF+93]), "+f"(d[OFF+94]), "+f"(d[OFF+95]) : "r"(a0), "r"(a1), "r"(a2), "r"(a3), "l"(db), "r"(sd), "n"(TB));
}
template<int OFF, int TB, int S> __device__ __forceinline__ void wgmma_rs_n48(float (&d)[S], uint32_t a0, uint32_t a1, uint32_t a2, uint32_t a3, uint64_t db, int sd) {
  asm volatile("{\n.reg .pred p;\nsetp.ne.b32 p, %29, 0;\n"
    "wgmma.mma_async.sync.aligned.m64n48k16.f32.bf16.bf16 {%0, %1, %2, %3, %4, %5, %6, %7, %8, %9, %10, %11, %12, %13, %14, %15, %16, %17, %18, %19, %20, %21, %22, %23}, {%24, %25, %26, %27}, %28, p, 1, 1, %30;\n}\n"
    : "+f"(d[OFF+0]), "+f"(d[OFF+1]), "+f"(d[OFF+2]), "+f"(d[OFF+3]), "+f"(d[OFF+4]), "+f"(d[OFF+5]), "+f"(d[OFF+6]), "+f"(d[OFF+7]), "+f"(d[OFF+8]), "+f"(d[OFF+9]), "+f"(d[OFF+10]), "+f"(d[OFF+11]), "+f"(d[OFF+12]), "+f"(d[OFF+13]), "+f"(d[OFF+14]), "+f"(d[OFF+15]), "+f"(d[OFF+16]), "+f"(d[OFF+17]), "+f"(d[OFF+18]), "+f"(d[OFF+19]), "+f"(d[OFF+20]), "+f"(d[OFF+21]), "+f"(d[OFF+22]), "+f"(d[OFF+23]) : "r"(a0), "r"(a1), "r"(a2), "r"(a3), "l"(db), "r"(sd), "n"(TB));
}
template<int OFF, int TB, int S> __device__ __forceinline__ void wgmma_rs_n16(float (&d)[S], uint32_t a0, uint32_t a1, uint32_t a2, uint32_t a3, uint64_t db, int sd) {
  asm volatile("{\n.reg .pred p;\nsetp.ne.b32 p, %13, 0;\n"
    "wgmma.mma_async.sync.aligned.m64n16k16.f32.bf16.bf16 {%0, %1, %2, %3, %4, %5, %6, %7}, {%8, %9, %10, %11}, %12, p, 1, 1, %14;\n}\n"
    : "+f"(d[OFF+0]), "+f"(d[OFF+1]), "+f"(d[OFF+2]), "+f"(d[OFF+3]), "+f"(d[OFF+4]), "+f"(d[OFF+5]), "+f"(d[OFF+6]), "+f"(d[OFF+7]) : "r"(a0), "r"(a1), "r"(a2), "r"(a3), "l"(db), "r"(sd), "n"(TB));
}
template<int OFF, int TA, int TB, int S> __device__ __forceinline__ void wgmma_ss_n160(float (&d)[S], uint64_t da, uint64_t db, int sd) {
  asm volatile("{\n.reg .pred p;\nsetp.ne.b32 p, %82, 0;\n"
    "wgmma.mma_async.sync.aligned.m64n160k16.f32.bf16.bf16 {%0, %1, %2, %3, %4, %5, %6, %7, %8, %9, %10, %11, %12, %13, %14, %15, %16, %17, %18, %19, %20, %21, %22, %23, %24, %25, %26, %27, %28, %29, %30, %31, %32, %33, %34, %35, %36, %37, %38, %39, %40, %41, %42, %43, %44, %45, %46, %47, %48, %49, %50, %51, %52, %53, %54, %55, %56, %57, %58, %59, %60, %61, %62, %63, %64, %65, %66, %67, %68, %69, %70, %71, %72, %73, %74, %75, %76, %77, %78, %79}, %80, %81, p, 1, 1, %83, %84;\n}\n"
    : "+f"(d[OFF+0]), "+f"(d[OFF+1]), "+f"(d[OFF+2]), "+f"(d[OFF+3]), "+f"(d[OFF+4]), "+f"(d[OFF+5]), "+f"(d[OFF+6]), "+f"(d[OFF+7]), "+f"(d[OFF+8]), "+f"(d[OFF+9]), "+f"(d[OFF+10]), "+f"(d[OFF+11]), "+f"(d[OFF+12]), "+f"(d[OFF+13]), "+f"(d[OFF+14]), "+f"(d[OFF+15]), "+f"(d[OFF+16]), "+f"(d[OFF+17]), "+f"(d[OFF+18]), "+f"(d[OFF+19]), "+f"(d[OFF+20]), "+f"(d[OFF+21]), "+f"(d[OFF+22]), "+f"(d[OFF+23]), "+f"(d[OFF+24]), "+f"(d[OFF+25]), "+f"(d[OFF+26]), "+f"(d[OFF+27]), "+f"(d[OFF+28]), "+f"(d[OFF+29]), "+f"(d[OFF+30]), "+f"(d[OFF+31]), "+f"(d[OFF+32]), "+f"(d[OFF+33]), "+f"(d[OFF+34]), "+f"(d[OFF+35]), "+f"(d[OFF+36]), "+f"(d[OFF+37]), "+f"(d[OFF+38]), "+f"(d[OFF+39]), "+f"(d[OFF+40]), "+f"(d[OFF+41]), "+f"(d[OFF+42]), "+f"(d[OFF+43]), "+f"(d[OFF+44]), "+f"(d[OFF+45]), "+f"(d[OFF+46]), "+f"(d[OFF+47]), "+f"(d[OFF+48]), "+f"(d[OFF+49]), "+f"(d[OFF+50]), "+f"(d[OFF+51]), "+f"(d[OFF+52]), "+f"(d[OFF+53]), "+f"(d[OFF+54]), "+f"(d[OFF+55]), "+f"(d[OFF+56]), "+f"(d[OFF+57]), "+f"(d[OFF+58]), "+f"(d[OFF+59]), "+f"(d[OFF+60]), "+f"(d[OFF+61]), "+f"(d[OFF+62]), "+f"(d[OFF+63]), "+f"(d[OFF+64]), "+f"(d[OFF+65]), "+f"(d[OFF+66]), "+f"(d[OFF+67]), "+f"(d[OFF+68]), "+f"(d[OFF+69]), "+f"(d[OFF+70]), "+f"(d[OFF+71]), "+f"(d[OFF+72]), "+f"(d[OFF+73]), "+f"(d[OFF+74]), "+f"(d[OFF+75]), "+f"(d[OFF+76]), "+f"(d[OFF+77]), "+f"(d[OFF+78]), "+f"(d[OFF+79]) : "l"(da), "l"(db), "r"(sd), "n"(TA), "n"(TB));
}
template<int OFF, int TA, int TB, int S> __device__ __forceinline__ void wgmma_ss_n192(float (&d)[S], uint64_t da, uint64_t db, int sd) {
  asm volatile("{\n.reg .pred p;\nsetp.ne.b32 p, %98, 0;\n"
    "wgmma.mma_async.sync.aligned.m64n192k16.f32.bf16.bf16 {%0, %1, %2, %3, %4, %5, %6, %7, %8, %9, %10, %11, %12, %13, %14, %15, %16, %17, %18, %19, %20, %21, %22, %23, %24, %25, %26, %27, %28, %29, %30, %31, %32, %33, %34, %35, %36, %37, %38, %39, %40, %41, %42, %43, %44, %45, %46, %47, %48, %49, %50, %51, %52, %53, %54, %55, %56, %57, %58, %59, %60, %61, %62, %63, %64, %65, %66, %67, %68, %69, %70, %71, %72, %73, %74, %75, %76, %77, %78, %79, %80, %81, %82, %83, %84, %85, %86, %87, %88, %89, %90, %91, %92, %93, %94, %95}, %96, %97, p, 1, 1, %99, %100;\n}\n"
    : "+f"(d[OFF+0]), "+f"(d[OFF+1]), "+f"(d[OFF+2]), "+f"(d[OFF+3]), "+f"(d[OFF+4]), "+f"(d[OFF+5]), "+f"(d[OFF+6]), "+f"(d[OFF+7]), "+f"(d[OFF+8]), "+f"(d[OFF+9]), "+f"(d[OFF+10]), "+f"(d[OFF+11]), "+f"(d[OFF+12]), "+f"(d[OFF+13]), "+f"(d[OFF+14]), "+f"(d[OFF+15]), "+f"(d[OFF+16]), "+f"(d[OFF+17]), "+f"(d[OFF+18]), "+f"(d[OFF+19]), "+f"(d[OFF+20]), "+f"(d[OFF+21]), "+f"(d[OFF+22]), "+f"(d[OFF+23]), "+f"(d[OFF+24]), "+f"(d[OFF+25]), "+f"(d[OFF+26]), "+f"(d[OFF+27]), "+f"(d[OFF+28]), "+f"(d[OFF+29]), "+f"(d[OFF+30]), "+f"(d[OFF+31]), "+f"(d[OFF+32]), "+f"(d[OFF+33]), "+f"(d[OFF+34]), "+f"(d[OFF+35]), "+f"(d[OFF+36]), "+f"(d[OFF+37]), "+f"(d[OFF+38]), "+f"(d[OFF+39]), "+f"(d[OFF+40]), "+f"(d[OFF+41]), "+f"(d[OFF+42]), "+f"(d[OFF+43]), "+f"(d[OFF+44]), "+f"(d[OFF+45]), "+f"(d[OFF+46]), "+f"(d[OFF+47]), "+f"(d[OFF+48]), "+f"(d[OFF+49]), "+f"(d[OFF+50]), "+f"(d[OFF+51]), "+f"(d[OFF+52]), "+f"(d[OFF+53]), "+f"(d[OFF+54]), "+f"(d[OFF+55]), "+f"(d[OFF+56]), "+f"(d[OFF+57]), "+f"(d[OFF+58]), "+f"(d[OFF+59]), "+f"(d[OFF+60]), "+f"(d[OFF+61]), "+f"(d[OFF+62]), "+f"(d[OFF+63]), "+f"(d[OFF+64]), "+f"(d[OFF+65]), "+f"(d[OFF+66]), "+f"(d[OFF+67]), "+f"(d[OFF+68]), "+f"(d[OFF+69]), "+f"(d[OFF+70]), "+f"(d[OFF+71]), "+f"(d[OFF+72]), "+f"(d[OFF+73]), "+f"(d[OFF+74]), "+f"(d[OFF+75]), "+f"(d[OFF+76]), "+f"(d[OFF+77]), "+f"(d[OFF+78]), "+f"(d[OFF+79]), "+f"(d[OFF+80]), "+f"(d[OFF+81]), "+f"(d[OFF+82]), "+f"(d[OFF+83]), "+f"(d[OFF+84]), "+f"(d[OFF+85]), "+f"(d[OFF+86]), "+f"(d[OFF+87]), "+f"(d[OFF+88]), "+f"(d[OFF+89]), "+f"(d[OFF+90]), "+f"(d[OFF+91]), "+f"(d[OFF+92]), "+f"(d[OFF+93]), "+f"(d[OFF+94]), "+f"(d[OFF+95]) : "l"(da), "l"(db), "r"(sd), "n"(TA), "n"(TB));
}
template<int OFF, int TA, int TB, int S> __device__ __forceinline__ void wgmma_ss_n48(float (&d)[S], uint64_t da, uint64_t db, int sd) {
  asm volatile("{\n.reg .pred p;\nsetp.ne.b32 p, %26, 0;\n"
    "wgmma.mma_async.sync.aligned.m64n48k16.f32.bf16.bf16 {%0, %1, %2, %3, %4, %5, %6, %7, %8, %9, %10, %11, %12, %13, %14, %15, %16, %17, %18, %19, %20, %21, %22, %23}, %24, %25, p, 1, 1, %27, %28;\n}\n"
    : "+f"(d[OFF+0]), "+f"(d[OFF+1]), "+f"(d[OFF+2]), "+f"(d[OFF+3]), "+f"(d[OFF+4]), "+f"(d[OFF+5]), "+f"(d[OFF+6]), "+f"(d[OFF+7]), "+f"(d[OFF+8]), "+f"(d[OFF+9]), "+f"(d[OFF+10]), "+f"(d[OFF+11]), "+f"(d[OFF+12]), "+f"(d[OFF+13]), "+f"(d[OFF+14]), "+f"(d[OFF+15]), "+f"(d[OFF+16]), "+f"(d[OFF+17]), "+f"(d[OFF+18]), "+f"(d[OFF+19]), "+f"(d[OFF+20]), "+f"(d[OFF+21]), "+f"(d[OFF+22]), "+f"(d[OFF+23]) : "l"(da), "l"(db), "r"(sd), "n"(TA), "n"(TB));
}

__device__ __align__(1024) uint16_t g_kvT[2 * 640 * 2048];
__device__ __align__(1024) uint16_t g_y2T[2 * 640 * 2048];
__device__ __align__(1024) uint16_t g_o[2048 * 640];
__device__ __align__(1024) uint16_t g_gate[2080];
__device__ __align__(1024) uint4 g_halo[128 * 5 * 32];
__device__ __align__(1024) unsigned g_cnt[46 * 32];
__device__ __align__(1024) unsigned g_launch[132 * 32];
#define CNT_KV(i) (g_cnt + 32 * (i))
#define CNT_O(i) (g_cnt + 32 * (10 + (i)))
#define CNT_Y(i) (g_cnt + 32 * (26 + (i)))
#define PTL(i) do {} while (0)
#define PTPL(on, i) do {} while (0)
#define PT(i) do {} while (0)
#define PTP(on, i) do {} while (0)

constexpr uint32_t SB = 1024;
constexpr uint32_t STG = 23552, WST = 15360;
DEVI constexpr uint32_t o_px(int ks) { return (((ks >> 1) + 1) & 3) * 2 * STG; }
DEVI constexpr uint32_t o_pw(int ks) { return o_px(ks) + 16384 + (ks & 1) * WST; }
constexpr uint32_t O_HALO = 0, O_OST = STG;
constexpr uint32_t P3S = 28672;
constexpr uint32_t HC = 8320, UC = 4624, UZ = 528;
constexpr uint32_t O_H0 = 5 * P3S, O_U2 = O_H0 + 3 * HC, O_H3 = O_U2 + UC, O_U0 = O_H3 + 2 * HC;
DEVI constexpr uint32_t o_h(int c) { return O_H0 + c * HC + (c > 2 ? UC : 0); }
DEVI constexpr uint32_t o_u(int c) { return c == 2 ? O_U2 : O_U0 + (c > 2 ? c - 1 : c) * UC; }
constexpr uint32_t O_Y = 208896;
DEVI constexpr uint32_t o_x(int c) { return c < 2 ? O_Y + c * 5120 : O_U0 + (c & 1) * UC; }
constexpr uint32_t O_HIN = O_Y + 16384;
DEVI constexpr uint32_t o_kin(int c) { return ((O_U0 + 127) & ~127u) + ((c & 1) ? 0 : 73 * 128); }
DEVI constexpr uint32_t o_p3(int ks) { return (ks < 6 ? ks : ks - 6) * P3S; }
constexpr uint32_t O_BT = 4 * P3S;
constexpr uint32_t O_GT = O_Y + 20480, O_GW = O_GT + 320;
constexpr uint32_t O_BAR = 231040;
constexpr uint32_t B_FULL = O_BAR, B_EMPTY = O_BAR + 8 * 8, B_P3F = O_BAR + 8 * 16, B_P3R = O_BAR + 8 * 26, B_G = O_BAR + 8 * 27, B_U = O_BAR + 8 * 28,
                   B_KVD = O_BAR + 8 * 33, B_KF = O_BAR + 8 * 36, B_Y = O_BAR + 8 * 38, B_EP = O_BAR + 8 * 40, B_LAST = O_BAR + 8 * 41, B_DONE = O_BAR + 8 * 42,
                   B_P1E = O_BAR + 8 * 43, B_HX = O_BAR + 8 * 43  , B_P3E = O_BAR + 8 * 52, B_HX0 = O_BAR + 8 * 57, B_KVS = O_BAR + 8 * 58, B_QD = O_BAR + 8 * 60, B_Q = O_BAR + 8 * 51;
constexpr uint32_t B_S13 = B_EMPTY + 8 * 5, B_S15 = B_EMPTY + 8 * 7, B_S19 = B_EMPTY + 8 * 3;
constexpr uint32_t O_GP = O_BAR + 512, O_EPOCH = O_GW + 1280;
constexpr uint32_t SMEM_BYTES = 232448;
static_assert(O_U0 + 127 + 146 * 128 <= O_Y && o_kin(0) >= O_U0 + 2 * UC && O_EPOCH + 4 <= O_BAR && O_U0 >= 8 * STG, "smem map");
enum { NB_LEAD = 1, NB_HELP = 2, NB_HALO = 3, NB_ATT = 4, NB_G = 5, NB_TOK = 6, NB_RFULL = 8, NB_RFREE = 10 };

struct Maps { CUtensorMap x_par, w_main, w_tail, k_ld, v_ld, o_st, kv_st, wo, o_ld, y_ld, q_ld; };

template <int M, class F> DEVI void conv_step(float (&acc)[128], uint32_t a0, uint32_t a1, uint32_t a2, uint32_t a3, uint32_t dl, F&& gap) {
  auto D = [&](int off) { return ((uint64_t)8 << 32) | (uint64_t)(uint32_t)(dl + off - 16 * M); };
  if constexpr (M == 0) wgmma_rs_n16<0, 0>(acc, a0, a1, a2, a3, D(0), 0);
  if constexpr (M <= 3) { wgmma_rs_n48<8, 0>(acc, a0, a1, a2, a3, D(16), M == 0 ? 0 : 1); gap(); }
  if constexpr (M <= 6) { wgmma_rs_n48<32, 0>(acc, a0, a1, a2, a3, D(64), M == 0 ? 0 : 1); gap(); }
  if constexpr (M <= 9) { wgmma_rs_n48<56, 0>(acc, a0, a1, a2, a3, D(112), M == 0 ? 0 : 1); gap(); }
  if constexpr (M <= 12) { wgmma_rs_n48<80, 0>(acc, a0, a1, a2, a3, D(160), M == 0 ? 0 : 1); gap(); }
  wgmma_rs_n48<104, 0>(acc, a0, a1, a2, a3, D(208), M == 0 ? 0 : 1); gap();
}
DEVI constexpr int a_off(int P, int i) { return -4 * (64 * ((i & 4) ? 15 - P : P) + (i & 1) * 32 - (i & 2) * 2); }
template <int P> DEVI void load_pair(uint32_t (&a)[8], uint32_t ab) {
#pragma unroll
  for (int i = 0; i < 8; i++) a[i] = lds32(ab + a_off(P, i));
}
template <int P> DEVI void mma_pair(float (&acc)[128], uint32_t (&a)[8], uint32_t db) {
  wg_fence();
  conv_step<P>(acc, a[0], a[1], a[2], a[3], db, []() {});
  conv_step<15 - P>(acc, a[4], a[5], a[6], a[7], db, []() {});
  wg_commit();
}
template <int P, int Q, int W> DEVI void mma_pair_ld(float (&acc)[128], uint32_t (&a)[8], uint32_t db, uint32_t (&nx)[8], uint32_t ab, int on) {
  int n = 0, j = 0;
  auto ld = [&](int cnt) {
#pragma unroll
    for (int r = 0; r < cnt; r++, n++) {
      if (Q >= 4) nx[n] = lds32(ab + a_off(Q, n));
      else asm volatile("{\n.reg .pred p;\nsetp.ne.b32 p, %2, 0;\n@p ld.shared.b32 %0, [%1];\n}" : "+r"(nx[n]) : "r"(ab + a_off(Q, n)), "r"(on));
    }
  };
  auto gap = [&]() {
    if (j == 1) { wg_commit(); wg_wait<W + 1>(); ld(3); wg_fence(); }
    if (j == 3) { wg_commit(); ld(3); wg_fence(); }
    j++;
  };
  wg_fence();
  conv_step<P>(acc, a[0], a[1], a[2], a[3], db, gap);
  conv_step<15 - P>(acc, a[4], a[5], a[6], a[7], db, gap);
  wg_commit();
  ld(2);
}

template <int I0, int I1> DEVI void conv_reduce(uint32_t sb, int c, int ht, int chan, int bar, int nthr) {
  const uint32_t a0 = sb + o_h(c) + ht * 16, a2 = sb + o_u(c) + ht * 16, a3 = sb + o_x(c) + ht * 16;
  uint4* yp = (uint4*)(g_y2T + (size_t)chan * 2048) + ht;
#pragma unroll
  for (int i = I0; i < I1; i++) {
    uint4 p, q, r, s;
    if (i == I0) bar_sync(bar, nthr);
    lds128(a0 + i * 2048, p.x, p.y, p.z, p.w); lds128(a0 + 4160 + i * 2048, q.x, q.y, q.z, q.w);
    lds128(a2 + i * 2048, r.x, r.y, r.z, r.w); lds128(a3 + i * 2048, s.x, s.y, s.z, s.w);
    auto sum = [](uint32_t a, uint32_t b, uint32_t c, uint32_t d) { return hadd2(hadd2(hadd2(a, b), 0u), hadd2(c, d)) ^ 0x80008000u; };
    yp[i * 128] = make_uint4(sum(p.x, q.x, r.x, s.x), sum(p.y, q.y, r.y, s.y), sum(p.z, q.z, r.z, s.z), sum(p.w, q.w, r.w, s.w));
  }
}

template <int ODD, int PART> DEVI void pack_qkv(const float (&acc)[120], uint32_t (&Q)[10][2], uint32_t (&K)[10][2], uint32_t (&V)[10][2]) {
#pragma unroll
  for (int f = 0; f < 10; f++) {
    const bool tail = ODD ? (f < 2) : (f >= 8);
    const int fm = ODD ? f - 2 : f, ft = ODD ? f : f - 8;
    const int nq = tail ? 24 + ft : fm, nk = tail ? 26 + ft : 8 + fm, nv = tail ? 28 + ft : 16 + fm;
    if (PART == 0) {
      V[f][1] = pack_bf16(acc[4 * nv + 2], acc[4 * nv + 3]);
      K[f][1] = pack_bf16(acc[4 * nk + 2], acc[4 * nk + 3]);
    } else {
      Q[f][0] = pack_bf16(acc[4 * nq], acc[4 * nq + 1]); Q[f][1] = pack_bf16(acc[4 * nq + 2], acc[4 * nq + 3]);
      K[f][0] = pack_bf16(acc[4 * nk], acc[4 * nk + 1]); V[f][0] = pack_bf16(acc[4 * nv], acc[4 * nv + 1]);
    }
  }
}
DEVI void softmax8(float (&l)[8][2], uint32_t (&P)[8]) {
  const float C = 0.22360679774997896f * 1.4426950408889634f;
  float m[8];
#pragma unroll
  for (int j = 0; j < 8; j++) m[j] = fmaxf(l[j][0], l[j][1]);
#pragma unroll
  for (int j = 0; j < 8; j++) m[j] = fmaxf(m[j], __shfl_xor_sync(~0u, m[j], 1));
#pragma unroll
  for (int j = 0; j < 8; j++) m[j] = fmaxf(m[j], __shfl_xor_sync(~0u, m[j], 2));
#pragma unroll
  for (int j = 0; j < 8; j++) { const float mc = m[j] * C; l[j][0] = ex2(fmaf(l[j][0], C, -mc)); l[j][1] = ex2(fmaf(l[j][1], C, -mc)); }
#pragma unroll
  for (int j = 0; j < 4; j++) {
    float s[4] = {0.f, 0.f, 0.f, 0.f}, r0, r1;
    mma8(s, pack_bf16(l[j][0], l[j][1]), pack_bf16(l[4 + j][0], l[4 + j][1]), 0x3F803F80u);
    asm("rcp.approx.ftz.f32 %0, %1;" : "=f"(r0) : "f"(s[0]));
    asm("rcp.approx.ftz.f32 %0, %1;" : "=f"(r1) : "f"(s[2]));
    P[j] = pack_bf16(l[j][0] * r0, l[j][1] * r0); P[4 + j] = pack_bf16(l[4 + j][0] * r1, l[4 + j][1] * r1);
  }
}

DEVI int pair_of(int c) {
  const int lo = 32 + 8 * c, hi = c - 4 + ((max(c - 29, 0) * 37) >> 8);
  int p; asm("{\n.reg .pred q;\nsetp.lt.s32 q, %1, 4;\nselp.b32 %0, %2, %3, q;\n}" : "=r"(p) : "r"(c), "r"(lo), "r"(hi));
  return p;
}
DEVI uint32_t make_ctx() {
  int b; asm volatile("mov.u32 %0, %%ctaid.x;" : "=r"(b));
  b += clk() & threadIdx.y;
  const int p = pair_of(b >> 1);
  const int j = b < 128 ? 8 * (p & 7) + (p >> 3) : 64, cp = (j * 79) >> 10;
  return ((2 * p + (b & 1)) & 255) | (j - 13 * cp) << 8 | (2 * cp + (b & 1)) << 12 | (b >> 7) << 16;
}
#define CTX() asm volatile("" : "+r"(ctx)); CTXU()
#define CTXU() int tid; asm volatile("mov.u32 %0, %%tid.x;" : "=r"(tid)); \
  const int lane = tid & 31, vb = ctx & 255, hg = (ctx >> 4) & 7, rt = ctx & 15, par = (ctx >> 3) & 1, mt = ctx & 7, rank = ctx & 1, \
  tb = (ctx >> 8) & 15, cb = (ctx >> 12) & 15; const bool main_cta = ctx < 65536; \
  (void)tid; (void)lane; (void)vb; (void)hg; (void)rt; (void)par; (void)mt; (void)rank; (void)tb; (void)cb; (void)main_cta
#define CTXW() CTX(); const int wg = warp >> 2, w = warp & 3, g = lane >> 2, t = lane & 3; const bool lead = (tid & 127) == 0; \
  (void)wg; (void)w; (void)g; (void)t; (void)lead

__global__ void __cluster_dims__(2, 1, 1) __launch_bounds__(512, 1)
fused_kernel(const uint16_t* __restrict__ xq, const uint16_t* __restrict__ wqkv, const uint16_t* __restrict__ gate_w, const __grid_constant__ Maps M, const uint16_t* __restrict__ shift_k, const uint16_t* __restrict__ ssm_k, const uint16_t* __restrict__ ssm_D,
             uint16_t* __restrict__ outp) {
  extern __shared__ __align__(1024) uint8_t smem_raw[];
  const uint32_t sb = smem_u32(smem_raw);
  const uint32_t t0 = clk();
  auto get_epoch = [&]() { mbar_wait(sb + B_EP, 0); return lds32(sb + O_EPOCH); };

  auto p1_load_x = [&](int ks, int p, int rank) {
    tma3(sb + o_px(ks), &M.x_par, ks * 32, (p >> 2) & 1, (p & 3) * 256 + rank * 128, sb + B_FULL + 8 * (ks & 7));
  };
  auto p1_load_w = [&](int ks, int p, int rank) {
    const uint32_t st = sb + o_pw(ks), fb = sb + B_FULL + 8 * (ks & 7);
    tma3_mc(st + rank * 6144, &M.w_main, (p >> 3) * 80 + 2 * (p & 8), ks * 32 + rank * 16, 0, fb);
    tma3_mc(st + 12288 + rank * 1536, &M.w_tail, (p >> 3) * 80 + 8 * (~p & 8), ks * 32 + rank * 16, 0, fb);
  };
  auto cta_pair = [&]() { return pair_of(blockIdx.x >> 1); };

  const uint16_t* pfp = nullptr;
  if (threadIdx.x < 32) {
    const unsigned b = blockIdx.x, l = threadIdx.x;
    pfp = l < 16 ? xq + (16 * b + l) * 640 : wqkv + (15 * b + l - 16) * 64;
    if ((l | b >> 7 << 5) < 31) pf_l2(pfp);
  }
  const int warp = __shfl_sync(~0u, threadIdx.x >> 5, 0);
  if ((warp & 14) == 8) {
    if (elect_one()) {
#pragma unroll
      for (int s = 0; s < 8; s++) mbar_init(sb + O_BAR - 512 + 64 * warp + 8 * s, 5 * warp - 39);
      asm volatile("fence.mbarrier_init.release.cluster;" ::: "memory");
    }
    __syncwarp();
  }
  asm volatile("barrier.cluster.arrive.relaxed.aligned;" ::: "memory");
  if (warp == 8 && blockIdx.x < 128) {
    const int p = cta_pair(), rank = blockIdx.x & 1;
    if (elect_one()) { mbar_expect_tx(sb + B_FULL, 16384 + WST); p1_load_x(0, p, rank); }
    __syncwarp();
    asm volatile("barrier.cluster.wait.aligned;" ::: "memory");
    if (elect_one()) { p1_load_w(0, p, rank); PT(100); }
    __syncwarp();
  } else if (warp != 15) {
    asm volatile("barrier.cluster.wait.aligned;" ::: "memory");
    spin_until(t0, HOLD);
  }
  auto init_rest = [&]() {
    if (warp >= 11 && elect_one()) {
#pragma unroll
      for (int s = 0; s < 12; s++) mbar_init(sb + O_BAR + 128 - 11 * 96 + 96 * warp + 8 * s, warp == 14 ? 2 : 1);
      asm volatile("fence.mbarrier_init.release.cluster;" ::: "memory");
    }
    __syncwarp();
    bar_sync(0, blockIdx.x < 128 ? 224 : 512);
  };
  uint32_t ctx = 0;

  if (warp < 8) {
    if (PF2 && warp == 0) {
#pragma unroll 1
      for (int i = 1; i <= NPF; i++) {
        spin_until(t0, PF2 + (i - 1) * PFD);
        if ((threadIdx.x | blockIdx.x >> 7 << 5) < 31) pf_l2(pfp + (threadIdx.x < 16 ? 64 : 64 * 1920) * i);
        __syncwarp();
      }
    }
    reg_inc<RC>();
    ctx = make_ctx();
    if (blockIdx.x >= 128) bar_sync(0, 512);
    else {
      {
        uint32_t Q[10][2], K[10][2], V[10][2];
        {
          {
            float acc[120];
            {
              CTXW();
              const uint32_t aa = sb + (warp * 16 + (lane & 15)) * 128 + (((lane >> 4) ^ (lane & 7)) << 4);
              const uint32_t rsb = mapa(sb, (blockIdx.x & 1) ^ 1);
              uint32_t a0[8], a1[8], a2[8];
              auto load_a = [&](uint32_t (&r)[8], int ks) {
                mbar_wait(sb + B_FULL + 8 * (ks & 7), (ks >> 3) & 1);
                PTP(lead && (wg || !(ks & 3)), wg ? 60 + ks : 80 + (ks >> 2));
                if (SSMASK >> ks & 1) return;
                ldsm4(r[0], r[1], r[2], r[3], (aa ^ ((ks & 1) * 64)) + o_px(ks)); ldsm4(r[4], r[5], r[6], r[7], (aa ^ ((ks & 1) * 64 + 32)) + o_px(ks));
              };
              auto stage = [&](uint32_t (&r)[8], uint32_t (&nx)[8], int ks, int u) {
                const uint32_t dl = o_pw(ks) >> 4;
                const uint64_t db = mkdesc(SB, 2048, 1024, 1), dt = mkdesc(SB + 12288, 512, 256, 3);
                auto D = [&](uint64_t d) { return (d & ~0xFFFFFFFFull) | (uint32_t)((uint32_t)d + dl); };
                if (LEAD && u == (20 - LEAD) % 3) bar_sync_p(wg == 0 && ks == 20 - LEAD, NB_LEAD, 256);
                wg_fence();
                const uint64_t da = mkdesc(SB + o_px(ks) + (ks & 1) * 64, 16, 1024, 1) + wg * 512;
                if (SSMASK >> ks & 1) { wgmma_ss_n192<0, 0, 1>(acc, da, D(db), ks); wgmma_ss_n48<96, 0, 1>(acc, da, D(dt), ks); }
                else { wgmma_rs_n192<0, 1>(acc, r[0], r[1], r[2], r[3], D(db), ks); wgmma_rs_n48<96, 1>(acc, r[0], r[1], r[2], r[3], D(dt), ks); }
                wg_commit();
                if (LEAD && u == 1) bar_arrive_p(wg && ks == 19, NB_LEAD, 256);
                if (ks < 19) load_a(nx, ks + 1);
                wg_fence();
                if (SSMASK >> ks & 1) { wgmma_ss_n192<0, 0, 1>(acc, da + 2, D(db + 384), 1); wgmma_ss_n48<96, 0, 1>(acc, da + 2, D(dt + 96), 1); }
                else { wgmma_rs_n192<0, 1>(acc, r[4], r[5], r[6], r[7], D(db + 384), 1); wgmma_rs_n48<96, 1>(acc, r[4], r[5], r[6], r[7], D(dt + 96), 1); }
                wg_commit();
                wg_wait<2>();
                mbar_arrive2_p(lead && (u || ks), sb + B_EMPTY + 8 * ((ks - 1) & 7), rsb + B_EMPTY + 8 * ((ks - 1) & 7));
              };
              if (lead) PT(1 + wg);
              load_a(a0, 0);
              constexpr int p1u = P1U;
#pragma unroll p1u
              for (int ks = 0; ks < 21; ks += 3) {
                stage(a0, a1, ks, 0);
                stage(a1, a2, ks + 1, 1);
                if (ks == 18) break;
                stage(a2, a0, ks + 2, 2);
              }
              mbar_wait(sb + B_S15, 1);
              wg_wait<1>();
              mbar_arrive_p(tid == 0, sb + B_P1E);
              wg_wait<0>();
              fence_regs(acc);
              mbar_arrive2_p(lead, sb + B_S19, rsb + B_S19);
              PTPL(lead, 50 + wg);
            }
            CTXW();
            if (hg & 1) pack_qkv<1, 0>(acc, Q, K, V); else pack_qkv<0, 0>(acc, Q, K, V);
            if (warp == 7 && rank) {
              uint4* hp = g_halo + vb * 160 + lane;
              st_relaxed(hp, K[0][1], K[1][1], K[3][1], K[4][1]); st_relaxed(hp + 32, K[5][1], K[6][1], K[8][1], K[9][1]);
              st_relaxed(hp + 64, K[2][1], K[7][1], V[0][1], V[1][1]);
              st_relaxed(hp + 96, V[2][1], V[3][1], V[4][1], V[5][1]); st_relaxed(hp + 128, V[6][1], V[7][1], V[8][1], V[9][1]);
            }
            const uint32_t ho = sb + O_HALO + warp * 2560 + lane * 16;
            stsm4(ho, K[0][1], K[1][1], K[3][1], K[4][1]); stsm4(ho + 512, K[5][1], K[6][1], K[8][1], K[9][1]);
            stsm4(ho + 1024, K[2][1], K[7][1], V[0][1], V[1][1]);
            stsm4(ho + 1536, V[2][1], V[3][1], V[4][1], V[5][1]); stsm4(ho + 2048, V[6][1], V[7][1], V[8][1], V[9][1]);
            if (warp == 7) {
              if (!rank) {
                fence_async_smem();
                __syncwarp();
                if (elect_one())
                  asm volatile("cp.async.bulk.shared::cluster.shared::cta.mbarrier::complete_tx::bytes [%0], [%1], 2560, [%2];"
                               ::"r"(mapa(sb + O_HIN, 1)), "r"(sb + O_HALO + 7 * 2560), "r"(mapa(sb + B_HX0, 1)) : "memory");
              }
              __syncwarp();
            } else {
              __syncwarp();
              if (lane == 0) mbar_arrive(sb + B_HX + 8 + 8 * warp);
            }
            if (hg & 1) pack_qkv<1, 1>(acc, Q, K, V); else pack_qkv<0, 1>(acc, Q, K, V);
#pragma unroll
            for (int f = 0; f < 10; f++) V[f][0] = movm(V[f][0]);
            if (lead) PT(52 + wg);
            if (wg) mbar_wait(sb + B_P1E, 0);
          }
          CTXW();
          const bool gt0 = 2 * t > g, gt1 = 2 * t + 1 > g;
          const uint32_t pmask = (gt0 ? 0xFFFFu : 0u) | (gt1 ? 0xFFFF0000u : 0u);
          uint32_t Qh[4][2];
          float lg[8][2];
#pragma unroll
          for (int j = 0; j < 4; j++) {
            const int fa = (j >> 1) * 5 + (j & 1) * 3, fh = (j >> 1) * 5 + 2;
            const bool mine = (j & 1) ? (t >= 2) : (t < 2);
            Qh[j][0] = mine ? Q[fh][0] : 0u; Qh[j][1] = mine ? Q[fh][1] : 0u;
            float c1[4] = {0.f, 0.f, 0.f, 0.f}, c2[4] = {0.f, 0.f, 0.f, 0.f};
            mma16(c1, Q[fa][0], Q[fa][1], Q[fa + 1][0], Q[fa + 1][1], K[fa][0], K[fa + 1][0]);
            mma16(c2, Q[fa][0], Q[fa][1], Q[fa + 1][0], Q[fa + 1][1], K[fa][1], K[fa + 1][1]);
            mma8(c1, Qh[j][0], Qh[j][1], K[fh][0]);
            mma8(c2, Qh[j][0], Qh[j][1], K[fh][1]);
            lg[j][0] = c1[0]; lg[j][1] = c1[1];
            lg[4 + j][0] = gt0 ? c1[2] : c2[2]; lg[4 + j][1] = gt1 ? c1[3] : c2[3];
          }
          if (lead) PT(54 + wg);
          mbar_wait(sb + (warp ? B_HX + 8 * warp : B_HX0), 0);
          if (lead) PT(56 + wg);
          const uint32_t hs = warp ? O_HALO + (warp - 1) * 2560 : O_HIN, ha = sb + hs + lane * 16;
          const uint32_t va = sb + ((lane & 8) ? O_HALO + warp * 2560 : hs) + 1280 + (lane >> 4) * 128 + (lane & 7) * 16;
          uint32_t Kh[10], Vh[10];
          ldsm4(Kh[0], Kh[1], Kh[3], Kh[4], ha); ldsm4(Kh[5], Kh[6], Kh[8], Kh[9], ha + 512);
          asm volatile("ldmatrix.sync.aligned.m8n8.x2.shared.b16 {%0,%1}, [%2];" : "=r"(Kh[2]), "=r"(Kh[7]) : "r"(ha + 1024) : "memory");
#pragma unroll
          for (int i = 0; i < 5; i++) ldsm4t(Vh[2 * i], V[2 * i][1], Vh[2 * i + 1], V[2 * i + 1][1], va + i * 256);
          const bool have_halo = warp > 0 || mt > 0;
#pragma unroll
          for (int j = 0; j < 4; j++) {
            const int fa = (j >> 1) * 5 + (j & 1) * 3, fh = (j >> 1) * 5 + 2;
            float c0[4] = {0.f, 0.f, 0.f, 0.f};
            mma16(c0, Q[fa][0], Q[fa][1], Q[fa + 1][0], Q[fa + 1][1], Kh[fa], Kh[fa + 1]);
            mma8(c0, Qh[j][0], Qh[j][1], Kh[fh]);
            if (!have_halo) c0[0] = c0[1] = -INFINITY;
            lg[j][0] = gt0 ? c0[0] : lg[j][0]; lg[j][1] = gt1 ? c0[1] : lg[j][1];
          }
          uint32_t Pv[8], O[10][2];
          softmax8(lg, Pv);
#pragma unroll
          for (int j = 0; j < 4; j++) {
            const int fa = (j >> 1) * 5 + (j & 1) * 3, fh = (j >> 1) * 5 + 2;
            const uint32_t a0 = Pv[j] & pmask, a2 = Pv[j] & ~pmask, a3 = Pv[4 + j] & pmask, a5 = Pv[4 + j] & ~pmask;
#pragma unroll
            for (int q = 0; q < 3; q++) {
              const int f = q < 2 ? fa + q : fh;
              float o[4] = {0.f, 0.f, 0.f, 0.f};
              mma8(o, a2, a3, V[f][0]);
              mma16(o, a0, 0u, 0u, a5, Vh[f], V[f][1]);
              const uint32_t o0 = pack_bf16(o[0], o[1]), o1 = pack_bf16(o[2], o[3]);
              if (q < 2 || !(j & 1)) { O[f][0] = o0; O[f][1] = o1; }
              else { O[f][0] = t >= 2 ? o0 : O[f][0]; O[f][1] = t >= 2 ? o1 : O[f][1]; }
            }
          }
          {
            uint32_t z = threadIdx.y;
#pragma unroll
            for (int f = 0; f < 10; f++) z &= O[f][0];
            bar_arrive_p(wg == 0, NB_HALO + z, 256);
          }
          mbar_wait(sb + B_QD, 0);
          const uint32_t oa = sb + O_OST + (warp * 16 + (lane & 15)) * 160 + (lane >> 4) * 16;
#pragma unroll
          for (int i = 0; i < 5; i++) stsm4(oa + i * 32, O[2 * i][0], O[2 * i][1], O[2 * i + 1][0], O[2 * i + 1][1]);
        }
      }
      {
        CTXW();
        fence_async_smem();
        bar_arrive(NB_ATT, 288);
        if (lead) PT(58 + wg);
        const uint32_t abase = sb + (g & 1) * 4160 + 4 * (1023 - 4 - 8 * w - (g >> 1) + t);
        float acc[128];
        uint32_t a0[8], a1[8], a2[8], a3[8];
#pragma unroll 1
        for (int c = wg ^ 1; c < 5; c += 2) {
          const uint32_t ab = abase + o_h(c);
          const uint32_t db = __shfl_sync(~0u, ((SB + o_u(c) + UZ - 16) >> 4) | 0x10000u, 0);
          mbar_wait(sb + B_U + 8 * c, 0);
          load_pair<0>(a0, ab); load_pair<1>(a1, ab);
          load_pair<2>(a2, ab); load_pair<3>(a3, ab);
          if (lead) PT(85 + c);
          bar_sync(c ? NB_TOK + wg : NB_HALO, 256);
          fence_regs(acc);
          auto tok = [&](int p) { if (p == TOKP) bar_arrive_p(P3GO == 0 || c < 4, NB_TOK + (wg ^ 1), 256); };
          const uint32_t an = abase + o_h(c + 2);
          auto nxt = [&](auto P, uint32_t (&a)[8]) {
#pragma unroll
            for (int i = 0; i < 8; i++)
              asm volatile("{\n.reg .pred p;\nsetp.ne.b32 p, %2, 0;\n@p ld.shared.b32 %0, [%1];\n}" : "+r"(a[i]) : "r"(an + a_off(P, i)), "r"((int)(c < 3)));
          };
          mma_pair<0>(acc, a0, db);
          mma_pair<1>(acc, a1, db); wg_wait<1>();  load_pair<4>(a0, ab);
          if (lead) PT(90 + c);
          mma_pair<2>(acc, a2, db); wg_wait<1>();  load_pair<5>(a1, ab);
          mma_pair<3>(acc, a3, db); tok(3); wg_wait<1>();  load_pair<6>(a2, ab);
          mma_pair<4>(acc, a0, db); tok(4); wg_wait<1>();  load_pair<7>(a3, ab);
          mma_pair<5>(acc, a1, db); tok(5);
          mma_pair<6>(acc, a2, db); tok(6);
          mma_pair<7>(acc, a3, db);
          if (P3GO == 5) wg_wait<1>();
          if (P3GO == 3 || P3GO == 5) bar_arrive_p(c == 4, NB_TOK, 256);
          wg_wait<0>();
          if (P3GO == 4) bar_arrive_p(c == 4, NB_TOK, 256);
          fence_regs(acc);
          PTPL(lead, 95 + c);
          bar_sync(NB_RFREE + wg, 256);
          const uint32_t pb = sb + (w < 2 ? o_h(c) + w * 4160 : w == 2 ? o_u(c) : o_x(c)) + lane * 16;
          if (lane < 2 * w) sts128(pb, 0, 0, 0, 0);
#pragma unroll
          for (int q = 0; q < 8; q++) {
            uint32_t p[4];
#pragma unroll
            for (int i = 0; i < 4; i++) {
              const int nu = 4 * q + i;
              float v0 = acc[4 * nu], v1 = acc[4 * nu + 1];
              p[i] = pack_bf16(v0, v1);
              if (nu > 0) p[i] = hadd2(p[i], pack_bf16(acc[4 * nu - 2], acc[4 * nu - 1]));
            }
            stsm4t(pb + w * 32 + q * 512, p[0], p[1], p[2], p[3]);
            if (SPLIT4 && q == 3) bar_arrive_p(c == 4, NB_RFULL + 1, 256);
          }
          if (c < 4) bar_arrive(NB_RFULL + wg, 256);
          if (P3GO == 1 && c == 4) bar_arrive(NB_TOK, 256);
          if (lead) PT(140 + c);
        }
        if (wg) {
          if (YE == 1 && warp == 7 && elect_one()) flag_add(CNT_Y(16 + (vb >> 5)), 1);
          const int yb = (lds32(sb + O_EPOCH) & 1) * 640;
          conv_reduce<SPLIT4, 2>(sb, 4, tid - 128, yb + 512 + ((vb & 0x61) | (vb & 6) << 2 | (vb >> 2 & 6)), 14, 128);
          if (P3GO == 2) bar_arrive(NB_TOK, 256);
          if (!YE && warp == 7 && elect_one()) flag_add(CNT_Y(16 + (vb >> 5)), 1);
          if (MIXW) bar_arrive(12, 256);
          PTPL(lead, 45);
        }
      }
    }
    if (warp < 4) {
      CTXW();
      const uint32_t rsb = mapa(sb, (blockIdx.x & 1) ^ 1);
      const uint32_t ba = sb + O_BT + ((lane >> 4) * 8 + (lane & 7)) * 128 + (((2 * w + ((lane >> 3) & 1)) ^ ((lane & 1) << 2 | (lane >> 1 & 3))) << 4);
      mbar_wait(sb + B_P3F, 0);
      if (lead) PT(145);
      float acc[80];
#pragma unroll
      for (int ks = 0; ks < 10; ks++) {
        if (ks == NPRE) {
          if (NPRE) { wg_wait<0>(); mbar_arrive2_p(lead, sb + B_P3E + 8 * NPRE, rsb + B_P3E + 8 * NPRE); }
          bar_sync_p(blockIdx.x < 128, NB_TOK, 256);
        }
        PTP(lead, 146 + ks);
        const uint64_t da = mkdesc(SB + o_p3(ks), 1024, 1024, 1), db = mkdesc(SB + o_p3(ks) + 8192, 16, 1024, 1);
        wg_fence();
#pragma unroll
        for (int j = 0; j < 4; j++) wgmma_ss_n160<0, 1, 0>(acc, da + j * 128, db + j * 2, j | ks);
        wg_commit();
        if (ks < 9) mbar_wait(sb + B_P3F + 8 * (ks + 1), 0);
        if (ks >= 1 && ks <= 4 && ks != NPRE) { wg_wait<1>(); mbar_arrive2_p(lead, sb + B_P3E + 8 * ks, rsb + B_P3E + 8 * ks); }
      }
      wg_wait<0>();
      fence_regs(acc);
      PTPL(lead, 156);
#pragma unroll
      for (int i = 0; i < 10; i++) {
        stsm4t(ba + i * 2048, pack_bf16(acc[8 * i], acc[8 * i + 1]), pack_bf16(acc[8 * i + 2], acc[8 * i + 3]),
               pack_bf16(acc[8 * i + 4], acc[8 * i + 5]), pack_bf16(acc[8 * i + 6], acc[8 * i + 7]));
        if (i & 1) bar_arrive(1 + (i >> 1), 256);
      }
      if (lead) PT(157);
    }
  } else if (warp < 12) {
    reg_dec<RH>();
    const int hw = warp - 8;
    init_rest();
    ctx = __shfl_sync(~0u, make_ctx(), 0);
    const int yrow = (ctx & 0x61) | (ctx & 6) << 2 | (ctx >> 2 & 6);
    if (ctx < 65536) {
      CTXU();
      const int pr = hw >> 1, hh = hw & 1, tk = vb & 63, odd = (lane >> 2) & 1;
      const uint32_t sel0 = odd ? 0x7632 : 0x5410, sel1 = odd ? 0x5410 : 0x7632;
      const uint32_t in = sb + o_kin(pr), fb = sb + B_KF + 8 * pr, out = sb + O_Y + pr * 8192;
      const uint32_t oa = out + (2 * lane + odd) * 64 + (((3 - 2 * hh) ^ (lane & 3)) << 4), ia = in + hh * 2048 + lane * 4;
      auto fetch = [&](int c) {
        wait_until(t0, KT0 + c * KTD + ((((vb * 37) & 63) * KPH) >> 6));
        if (elect_one()) {
          const int kb = 2 * c + (vb >> 6);
          mbar_expect_tx(fb, 69 * 128);
          tma2(in, &M.k_ld, kb * 64, 32 * tk - 4, fb);
          tma2(in + 36 * 128, &M.v_ld, kb * 64, 32 * tk - 1, fb);
          PT(20 + c);
        }
        __syncwarp();
      };
      if (hh == 0) fetch(pr);
      const uint4* skp = (const uint4*)shift_k + (2 * pr + (vb >> 6)) * 32 + lane;
      uint4 sk = __ldg(skp), sk1 = __ldg(skp + 128), sk2 = __ldg(skp + (pr ? 0 : 256));
#pragma unroll 1
      for (int c = pr; c < 5; c += 2) {
        {
          mbar_wait(fb, (c >> 1) & 1);
          if (hh == 0 && lane == 0) PT(25 + c);
          uint32_t k[20], o[17];
#pragma unroll
          for (int i = 0; i < 20; i++) { k[i] = lds32(ia + i * 128); if (i >= 3) o[i - 3] = lds32(ia + (33 + i) * 128); }
          fence_async_smem();
          bar_sync(12 + pr, 64);
          if (hh == 0) {
            if (c < 3) fetch(c + 2);
            else if (lane == 0) mbar_arrive(sb + B_KVD + 8 * (c - 3));
          }
          const uint32_t w0 = prmt(sk.x, sk.z, 0x5410), w1 = prmt(sk.x, sk.z, 0x7632), w2 = prmt(sk.y, sk.w, 0x5410), w3 = prmt(sk.y, sk.w, 0x7632);
#pragma unroll
          for (int i = 0; i < 17; i++) o[i] = hmul2(hfma2(k[i + 3], w0, hfma2(k[i + 2], w1, hfma2(k[i + 1], w2, hmul2(k[i], w3)))), o[i]);
          sk = sk1; sk1 = sk2;
#pragma unroll
          for (int i = 0; i < 4; i++) {
            const int e = 8 * (i >> 1) + (i & 1);
            const uint32_t a = (oa ^ ((i >> 1) * 16)) + (i & 1) * 4096;
            sts128(a, prmt(o[7 + e], o[6 + e], sel0), prmt(o[5 + e], o[4 + e], sel0), prmt(o[3 + e], o[2 + e], sel0), prmt(o[1 + e], o[e], sel0));
            sts128(a ^ 64, prmt(o[7 + e], o[6 + e], sel1), prmt(o[5 + e], o[4 + e], sel1), prmt(o[3 + e], o[2 + e], sel1), prmt(o[1 + e], o[e], sel1));
          }
          bar_sync(12 + pr, 64);
        }
        if (hh) {
          fence_async_smem();
          if (elect_one()) {
            const int kb = 2 * c + (vb >> 6);
            tma3_store(&M.kv_st, 0, kb * 64, 63 - tk, out);
            tma3_store(&M.kv_st, 0, 640 + kb * 64, 63 - tk, out + 4096);
            bulk_commit(); bulk_wait_all();
            mbar_arrive(sb + (c == 2 ? B_KVD + 16 : c < 2 ? B_KVS : B_KVS + 8));
            PTL(35 + c);
          }
          __syncwarp();
        }
      }
    }
    CTXU();
    const int g = lane >> 2, t = lane & 3, row = 8 * hw + g;
    const uint32_t go = (tb * 160 + row) * 80 + cb * 8 + t;
    const int yb = __shfl_sync(~0u, get_epoch() & 1, 0) * 640;
    uint4 T[10];
    if (hw == 2) {
      if (main_cta) { mbar_wait(sb + B_LAST, 0); mbar_wait(sb + B_S15, 1); }
      if (elect_one()) {
        mbar_expect_tx(sb + B_Q, 20480);
#pragma unroll
        for (int h = 0; h < 2; h++) tma2(sb + O_OST + h * 10240, &M.q_ld, cb * 64 + 32 * h, tb * 160, sb + B_Q);
      }
      __syncwarp();
    }
    mbar_wait(sb + B_Q, 0);
#pragma unroll
    for (int i = 0; i < 10; i++) lds128(sb + O_OST + (i & 1) * 10240 + (i >> 1) * 2048 + row * 64 + t * 16, T[i].x, T[i].y, T[i].z, T[i].w);
    fence_async_smem();
    bar_sync(12 + (hw >> 1), 64);
    if (!(tid & 63)) mbar_arrive(sb + B_QD);
    if (tid == 256) PTL(40);
    if (main_cta) {
      bar_arrive(NB_RFREE, 256);
      bar_arrive(NB_RFREE + 1, 256);
      auto red = [&](int c) {
        const int wg = (c & 1) ^ 1;
        conv_reduce<0, 2>(sb, c, tid - 256, yb + 128 * c + yrow, NB_RFULL + wg, 256);
        if (hw == 3 && elect_one()) flag_add(CNT_Y(4 * c + (vb >> 5)), 1);
        if (tid == 256) PTL(41 + c);
        if (c < 3) bar_arrive(NB_RFREE + wg, 256);
        if (c == 2) {
          bar_sync(NB_HELP, 128);
          if (tid == 256) { mbar_arrive(sb + B_P3E); mbar_arrive_remote(sb + B_P3E, rank ^ 1); }
        }
      };
      if (hw == 3) {
        mbar_wait(sb + B_KVS + 8, 0);
        if (elect_one()) { flag_release(CNT_KV(4 + (vb >> 6))); PTL(32); }
        __syncwarp();
      }
#pragma unroll 1
      for (int c = 0; c < 4; c++) red(c);
    }
    uint32_t G[5];
    mbar_wait(sb + B_G, 0);
#pragma unroll
    for (int q = 0; q < 5; q++) { uint16_t v; asm volatile("ld.shared.u16 %0, [%1];" : "=h"(v) : "r"(sb + O_GT + (32 * q + row) * 2)); G[q] = prmt(v, 0, 0x1010); }
#pragma unroll
    for (int i = 0; i < 10; i++) { const uint32_t c = G[i >> 1] ^ 0x80008000u; T[i] = make_uint4(hmul2(T[i].x, c), hmul2(T[i].y, c), hmul2(T[i].z, c), hmul2(T[i].w, c)); }
    if (main_cta) {
      if (SPLIT4) {
        conv_reduce<0, 1>(sb, 4, tid - 256, yb + 512 + yrow, NB_RFULL + 1, 256);
        if (YE == 2 && hw == 3 && elect_one()) flag_add(CNT_Y(16 + (vb >> 5)), 1);
      }
      if (MIXW) bar_sync(12, 256);
    }
#pragma unroll
    for (int h = 0; h < 2; h++) {
      mbar_wait_wd(sb + B_Y + 8 * h, 0, t0);
      if (tid == 256) PT(46);
      const uint32_t ya = sb + O_Y + h * 10240 + lane * 64 + ((hw ^ ((lane >> 1) & 3)) << 4);
      uint4 y[5];
      for (;;) {
        uint32_t m = ~0u;
#pragma unroll
        for (int q = 4; q >= 0; q--) {
          ldsm4t(y[q].x, y[q].y, y[q].z, y[q].w, ya + q * 2048);
          m = __vimin3_u16x2(__vimin3_u16x2(m, y[q].x, y[q].y), y[q].z, y[q].w);
          if (q == 4 && tb == 12) m = ~0u;
        }
        if (!__any_sync(~0u, (m & 0xFFFFu) == 0 || m < 0x10000u)) break;
#pragma unroll
        for (int q = 0; q < 5; q++)
          asm volatile("ld.relaxed.gpu.global.v4.b32 {%0,%1,%2,%3}, [%4];" : "=r"(y[q].x), "=r"(y[q].y), "=r"(y[q].z), "=r"(y[q].w)
                       : "l"((const uint4*)g_y2T + (yb + cb * 64 + 32 * h + lane) * 256 + tb * 20 + (q == 4 && tb == 12 ? 0 : 4 * q) + hw) : "memory");
#pragma unroll
        for (int q = 0; q < 5; q++) sts128(ya + q * 2048, y[q].x, y[q].y, y[q].z, y[q].w);
        __syncwarp();
        PTL(49);
      }
#pragma unroll
      for (int q = 0; q < 5; q++) {
        uint4& r = T[2 * q + h];
        r = make_uint4(hmul2(r.x, y[q].x), hmul2(r.y, y[q].y), hmul2(r.z, y[q].z), hmul2(r.w, y[q].w));
      }
    }
    const uint32_t so = sb + O_BT + row * 128 + ((t ^ ((g & 1) << 2 | g >> 1)) << 4);
    if (tid == 256) PTL(47);
#pragma unroll
    for (int q = 0; q < 5; q++) {
      const uint32_t c = hfma2(G[q], 0xBF80BF80u, 0x3F803F80u);
      bar_sync(1 + q, 256);
      if (q == 4) mbar_arrive_p(tid == 256, sb + B_DONE);
#pragma unroll
      for (int h = 0; h < 2; h++) {
        uint4 u;
        lds128((so ^ (h * 64)) + q * 4096, u.x, u.y, u.z, u.w);
        const uint4& r = T[2 * q + h];
        if (q < 4 || tb < 12) ((uint4*)outp)[go + q * 2560 + h * 4] = make_uint4(hfma2(u.x, c, r.x), hfma2(u.y, c, r.y), hfma2(u.z, c, r.z), hfma2(u.w, c, r.w));
      }
    }
  } else {
    reg_dec<RP>();
    uint4 gwv = make_uint4(0, 0, 0, 0);
    if (warp == 15) {
      const int p = cta_pair(), rank = blockIdx.x & 1;
      asm volatile("barrier.cluster.wait.aligned;" ::: "memory");
      if (blockIdx.x >= 128) bar_sync(0, 512);
      else {
#pragma unroll 1
        for (int ks = 1;; ks += 2) {
          mbar_wait(sb + B_EMPTY + 8 * (ks & 7), ((ks >> 3) & 1) ^ 1);
          spin_until(t0, PT1 + (ks - 1) * PTD);
          if (elect_one()) { mbar_expect_tx(sb + B_FULL + 8 * (ks & 7), WST); p1_load_w(ks, p, rank); PT(100 + ks); }
          if (ks == 19) break;
          const int kn = ks + 1;
          mbar_wait(sb + B_EMPTY + 8 * (kn & 7), ((kn >> 3) & 1) ^ 1);
          spin_until(t0, PT1 + ks * PTD - PTE);
          if (elect_one()) { mbar_expect_tx(sb + B_FULL + 8 * (kn & 7), 16384 + WST); p1_load_x(kn, p, rank); p1_load_w(kn, p, rank); PT(100 + kn); }
        }
        if (elect_one()) mbar_arrive(sb + B_LAST);
#pragma unroll 1
        for (int i = 0; i < 2; i++) {
          mbar_wait(sb + (i ? B_KVD + 16 : B_KVS), 0);
          if (elect_one()) { flag_release(CNT_KV(2 * i + (p >> 5))); PTL(30 + i); }
          __syncwarp();
        }
        mbar_wait(sb + B_S19, 0);
      }
    } else {
      if (threadIdx.x < 384 + 80) gwv = __ldg((const uint4*)gate_w + threadIdx.x - 384);
      init_rest();
    }
    ctx = __shfl_sync(~0u, make_ctx(), 0);
    CTXU();
    if (warp == 12) {
        unsigned epoch = 0;
      if (lane == 0) epoch = *(volatile unsigned*)(g_launch + 32 * vb) + 1;
      if (main_cta) { sts128(sb + O_GW + lane * 16, gwv.x, gwv.y, gwv.z, gwv.w); bar_arrive(NB_G, 96); }
      if (lane == 0) {
        if ((sb & 0xFFFFFF) != SB) __trap();
        sts32(sb + O_EPOCH, epoch);
        mbar_arrive(sb + B_EP);
#pragma unroll 1
        for (int i = 5; i < 11; i++) asm volatile("prefetch.tensormap [%0];" ::"l"(&M.x_par + i) : "memory");
      }
      if (main_cta && rank) {
#pragma unroll
        for (int f = 0; f < 5; f++) st_relaxed(g_halo + vb * 160 + lane + 32 * f, ~0u, ~0u, ~0u, ~0u);
      }
      __syncwarp();
      if (elect_one()) flag_release(g_launch + 32 * vb);
      __syncwarp();
      if (main_cta) {
        uint4 h0 = make_uint4(0, 0, 0, 0);
        if (lane < 5) {
          h0 = __ldg((const uint4*)(ssm_k + (size_t)(128 * lane + vb) * 2048));
          h0.x = prmt(pack_bf16(bf_lo(h0.x) + bf_lo(__ldg(ssm_D + 128 * lane + vb)), 0.f), h0.x, 0x7610);
        }
        epoch = __shfl_sync(~0u, epoch, 0);
        const int ze = lane & 7;
        const uint32_t za = sb + (lane < 8 ? o_u(ze) + UZ : lane < 24 ? o_h(ze) + (lane >> 4) * 4160 + 4096 : o_u(ze) + 512);
        const uint16_t* hp = ssm_k + (size_t)vb * 2048 + 8;
        const uint16_t* up = g_kvT + (size_t)vb * 2048;
        const unsigned* fp = CNT_KV(vb >> 6);
        sts128(sb + O_Y - 512 + lane * 16, 0, 0, 0, 0);
        mbar_wait(sb + B_LAST, 0);
        mbar_wait(sb + B_S13, 1);
#pragma unroll
        for (int c = 0; c < 5; c++) {
          if (c == 0 || c == 3) {
            mbar_wait(sb + B_KVD + (c ? 8 : 0), 0);
#pragma unroll
            for (int e = c; e < (c ? 5 : 3); e++) sts128(sb + o_u(e) + lane * 16, 0, 0, 0, 0);
            if (ze >= c && ze < (c ? 5 : 3)) sts128(za, h0.x, h0.y, h0.z, h0.w);
            fence_async_smem();
            __syncwarp();
            if (elect_one()) {
#pragma unroll
              for (int e = c; e < (c ? 5 : 3); e++) {
                mbar_expect_tx(sb + B_U + 8 * e, 3 * 4096 - 16);
                bulk_load(sb + o_u(e) + UZ + 16, hp + 128 * 2048 * e, 4080, sb + B_U + 8 * e);
              }
            }
          }
          if (c != 1 && c != 4) { flag_wait(fp + 32 * ((c + 1) & 6), 64 * epoch); __syncwarp(); }
          if (elect_one()) {
            bulk_load(sb + o_h(c), up + 128 * 2048 * c, 4096, sb + B_U + 8 * c);
            bulk_load(sb + o_h(c) + 4160, up + (640 + 128 * c) * 2048, 4096, sb + B_U + 8 * c);
            PTL(10 + c);
          }
        }
        if (ZW == 1) mbar_wait(sb + B_LAST, 1);
        if (ZW == 2) mbar_wait(sb + B_G, 0);
        if (ZW == 3) mbar_wait(sb + B_P3F + 32, 0);
        if (elect_one()) {
#pragma unroll 1
          for (int i = 0; i < ZD; i++) bulk_store(g_y2T + (size_t)((~epoch & 1) * 640 + 5 * vb) * 2048 + i * 256, sb + O_Y - 512, 512);
          bulk_commit(); bulk_wait_read();
          PTL(33);
        }
      }
    } else if (warp != 15) {
        const int r = warp - 13;
      if (main_cta) {
        if (rank && lane == 0) mbar_expect_tx(sb + B_HX0, 1280);
        const int t = lane & 3, grow = hg * 16 + (lane & 15);
        const uint32_t ga = sb + grow * 128 + (((4 * r + (lane >> 4)) ^ (lane & 7)) << 4);
        const uint32_t gp = sb + O_GW + 64 * r + 4 * t;
        float s0 = 0.f, s1 = 0.f;
        if (tid < 384 + 80) sts128(sb + O_GW + (tid - 384) * 16, gwv.x, gwv.y, gwv.z, gwv.w);
        bar_sync(NB_G, 96);
#pragma unroll 1
        for (int ks = 0; ks < 20; ks += 2) {
          uint32_t x[8], gw[4];
#pragma unroll
          for (int i = 0; i < 4; i++) gw[i] = lds32(gp + ks * 64 + i * 16);
          mbar_wait_wd(sb + B_FULL + 8 * (ks & 7), (ks >> 3) & 1, t0);
          if (r == 0 && lane == 0) PT(120 + ks);
          ldsm4(x[0], x[1], x[2], x[3], ga + o_px(ks)); ldsm4(x[4], x[5], x[6], x[7], (ga ^ 32) + o_px(ks));
#pragma unroll
          for (int i = 0; i < 8; i++) x[i] = hmul2(x[i], gw[i >> 1]);
          if (lane < 2) mbar_arrive(sb + B_EMPTY + 8 * (ks & 7) + 8 * lane + (x[0] & x[7] & threadIdx.y));
#pragma unroll
          for (int i = 0; i < 8; i += 4) {
            s0 += (bf_lo(x[i]) + bf_hi(x[i])) + (bf_lo(x[i + 2]) + bf_hi(x[i + 2]));
            s1 += (bf_lo(x[i + 1]) + bf_hi(x[i + 1])) + (bf_lo(x[i + 3]) + bf_hi(x[i + 3]));
          }
        }
        s0 += __shfl_xor_sync(~0u, s0, 1); s1 += __shfl_xor_sync(~0u, s1, 1);
        s0 += __shfl_xor_sync(~0u, s0, 2); s1 += __shfl_xor_sync(~0u, s1, 2);
        if (t < 2) sts32(sb + O_GP + r * 64 + (8 * t + (lane >> 2)) * 4, __float_as_uint(t ? s1 : s0));
        if (r == 0) bar_arrive(NB_G, 64);
        if (!rank) {
          uint4 d[3];
          if (mt > 0) {
            const uint4* hp = g_halo + (vb - 1) * 160 + r * 64 + lane;
            mbar_wait_wd(sb + B_EP, 0, t0);
            flag_wait_wd(g_launch + 32 * (vb - 1), lds32(sb + O_EPOCH), t0);
            mbar_wait_wd(sb + B_HX + 56, 0, t0);
            if (HDL) { const uint32_t t1 = clk(); spin_until(t1, HDL); }
            for (;;) {
              bool ok = true;
#pragma unroll
              for (int f = 0; f < 3; f++) {
                asm volatile("ld.relaxed.gpu.global.v4.b32 {%0,%1,%2,%3}, [%4];" : "=r"(d[f].x), "=r"(d[f].y), "=r"(d[f].z), "=r"(d[f].w) : "l"(hp + 32 * f) : "memory");
              }
#pragma unroll
              for (int f = 0; f < 3; f++) ok = ok && max(max(d[f].x, d[f].y), max(d[f].z, d[f].w)) != ~0u;
              if (__all_sync(~0u, ok)) break;
              if (clk() - t0 > 0x70000000u) __trap();
            }
          } else {
#pragma unroll
            for (int f = 0; f < 3; f++) d[f] = make_uint4(0, 0, 0, 0);
          }
#pragma unroll
          for (int f = 0; f < 3; f++) stsm4(sb + O_HIN + r * 1024 + f * 512 + lane * 16, d[f].x, d[f].y, d[f].z, d[f].w);
          __syncwarp();
          if (lane == 0) { mbar_arrive(sb + B_HX0); PTL(15 + r); }
        }
        if (r == 1) {
          bar_sync(NB_G, 64);
          if (lane < 16) {
            const uint32_t pa = sb + O_GP + lane * 4;
            const float z = __uint_as_float(lds32(pa)) + __uint_as_float(lds32(pa + 64));
            g_gate[2 * (mt * 128 + hg * 16 + lane) + par] = (uint16_t)pack_bf16(__fdividef(1.f, 1.f + __expf(-bf_lo(pack_bf16(z, 0.f)))), 0.f);
          }
          __syncwarp();
          if (elect_one()) flag_release(CNT_O(rt));
        }
      }
      mbar_wait_wd(sb + B_EP, 0, t0);
      const unsigned epoch = lds32(sb + O_EPOCH);
      if (main_cta) mbar_wait_wd(sb + B_P3E, 0, t0);
      flag_wait_wd(CNT_Y(2 * cb + r), 32 * epoch, t0);
      __syncwarp();
      if (elect_one()) {
        mbar_expect_tx(sb + B_Y + 8 * r, 10240);
        tma3(sb + O_Y + r * 10240, &M.y_ld, 0, (epoch & 1) * 640 + cb * 64 + 32 * r, tb * 5, sb + B_Y + 8 * r);
        PTL(17 + r);
      }
      __syncwarp();
      mbar_wait_wd(sb + B_DONE, 0, t0);
    } else {
      const unsigned epoch = get_epoch();
      if (main_cta) bar_sync(NB_ATT, 288); else mbar_wait(sb + B_QD, 0);
      if (elect_one()) {
        if (main_cta) {
          tma3_store(&M.o_st, hg * 80, par, mt * 128, sb + O_OST);
          bulk_commit(); bulk_wait_all();
          flag_release(CNT_O(rt));
          if (ZW == 1) mbar_arrive(sb + B_LAST);
        }
        PTL(3);
      }
      __syncwarp();
#pragma unroll 1
      for (int ks = 0; ks < 5; ks++)
        if (elect_one()) tma2(sb + o_p3(ks), &M.wo, cb * 64, ks * 64, sb + B_P3F + 8 * ks);
      if (lane < 4) flag_wait(CNT_O(8 * (lane & 1) + min(7, (80 * tb + 79 * (lane >> 1)) >> 7)), 16 * epoch);
      __syncwarp();
      if (elect_one()) {
        PTL(4);
        mbar_arrive_remote(sb + B_P3R, rank ^ 1);
        mbar_expect_tx(sb + B_G, 320);
        bulk_load(sb + O_GT, g_gate + tb * 160, 320, sb + B_G);
      }
      mbar_wait(sb + B_P3R, 0);
#pragma unroll 1
      for (int ks = 0; ks < 10; ks++) {
        if (ks > 5 || (ks == 5 && main_cta)) mbar_wait(sb + B_P3E + 8 * (ks - 5), 0);
        if (elect_one()) {
          PTP(ks >= 5, ks);
          tma2_mc(sb + o_p3(ks) + 8192 + rank * 10240, &M.o_ld, ks * 64, tb * 160 + rank * 80, sb + B_P3F + 8 * ks);
          if (ks >= 5) tma2(sb + o_p3(ks), &M.wo, cb * 64, ks * 64, sb + B_P3F + 8 * ks);
          mbar_expect_tx(sb + B_P3F + 8 * ks, P3S);
        }
      }
    }
  }
}

typedef CUresult (*PFN_enc)(CUtensorMap*, CUtensorMapDataType, cuuint32_t, void*, const cuuint64_t*, const cuuint64_t*, const cuuint32_t*,
                            const cuuint32_t*, CUtensorMapInterleave, CUtensorMapSwizzle, CUtensorMapL2promotion, CUtensorMapFloatOOBfill);
static void enc(PFN_enc f, CUtensorMap* m, const void* base, int rank, const cuuint64_t* dims, const cuuint64_t* strides, const cuuint32_t* box,
                CUtensorMapSwizzle sw) {
  const cuuint32_t es[5] = {1, 1, 1, 1, 1};
  f(m, CU_TENSOR_MAP_DATA_TYPE_BFLOAT16, rank, (void*)base, dims, strides, box, es, CU_TENSOR_MAP_INTERLEAVE_NONE, sw,
    CU_TENSOR_MAP_L2_PROMOTION_NONE, CU_TENSOR_MAP_FLOAT_OOB_FILL_NONE);
}

extern "C" void kernel_launch(void* const* d_in, const int* in_sizes, int n_in, void* d_out, int out_size) {
  (void)in_sizes; (void)n_in; (void)out_size;
  static PFN_enc f = nullptr;
  static void *kvT, *y2T, *o;
  if (!f) {
    void* p = nullptr;
    cudaDriverEntryPointQueryResult q;
    cudaGetDriverEntryPoint("cuTensorMapEncodeTiled", &p, cudaEnableDefault, &q);
    f = (PFN_enc)p;
    cudaGetSymbolAddress(&kvT, g_kvT); cudaGetSymbolAddress(&y2T, g_y2T); cudaGetSymbolAddress(&o, g_o);
    cudaFuncSetAttribute(fused_kernel, cudaFuncAttributeMaxDynamicSharedMemorySize, SMEM_BYTES);
  }
  Maps M;
  const CUtensorMapSwizzle S0 = CU_TENSOR_MAP_SWIZZLE_NONE, S32 = CU_TENSOR_MAP_SWIZZLE_32B, S64 = CU_TENSOR_MAP_SWIZZLE_64B, S128 = CU_TENSOR_MAP_SWIZZLE_128B;
  const cuuint64_t dpar[3] = {640, 2, 1024}, spar[2] = {1280, 2560};
  const cuuint64_t dw[3] = {640, 640, 3}, sw[2] = {3840, 1280};
  const cuuint64_t dnat[2] = {640, 2048}, snat[1] = {1280};
  const cuuint64_t dT2[3] = {32, 1280, 64}, sT[2] = {4096, 64};
  const cuuint64_t dwo[2] = {640, 640};
  { const cuuint32_t bx[3] = {64, 1, 128}; enc(f, &M.x_par, d_in[0], 3, dpar, spar, bx, S128); }
  { const cuuint32_t bx[3] = {64, 16, 3}; enc(f, &M.w_main, d_in[7], 3, dw, sw, bx, S128); }
  { const cuuint32_t bx[3] = {16, 16, 3}; enc(f, &M.w_tail, d_in[7], 3, dw, sw, bx, S32); }
  { const cuuint32_t bx[3] = {80, 1, 128}; enc(f, &M.o_st, o, 3, dpar, spar, bx, S0); }
  { const cuuint32_t bx[3] = {32, 64, 1}; enc(f, &M.kv_st, kvT, 3, dT2, sT, bx, S64); }
  { const cuuint32_t bx[3] = {32, 32, 5}; enc(f, &M.y_ld, y2T, 3, dT2, sT, bx, S64); }
  { const cuuint32_t bx[2] = {64, 36}; enc(f, &M.k_ld, d_in[1], 2, dnat, snat, bx, S0); }
  { const cuuint32_t bx[2] = {64, 33}; enc(f, &M.v_ld, d_in[2], 2, dnat, snat, bx, S0); }
  { const cuuint32_t bx[2] = {32, 160}; enc(f, &M.q_ld, d_in[0], 2, dnat, snat, bx, S0); }
  { const cuuint32_t bx[2] = {64, 64}; enc(f, &M.wo, d_in[8], 2, dwo, snat, bx, S128); }
  { const cuuint32_t bx[2] = {64, 80}; enc(f, &M.o_ld, o, 2, dnat, snat, bx, S128); }
  fused_kernel<<<130, 512, SMEM_BYTES, cudaStreamPerThread>>>((const uint16_t*)d_in[0], (const uint16_t*)d_in[7], (const uint16_t*)d_in[9], M, (const uint16_t*)d_in[3], (const uint16_t*)d_in[4], (const uint16_t*)d_in[5],
                                                              (uint16_t*)d_out);
}
```

```cpp
#include <cuda_runtime.h>
#include <cuda_bf16.h>
#include <cuda.h>
#include <stdint.h>

#define DEVI __device__ __forceinline__
#define PT1 100
#define PTD 460
#define PTE 200
#define PF2 0
#define NPF 1
#define PFD 0
#define DEFER 4
#define LATE 1
#define KPH KTD
#define CV 0
#define TOKP 6
#define NPRE 1
#define P3GO 3
#define SPLIT4 1
#define MIXW 1
#define YE 2
#define HDL 0
#define ZD 40
#define BACKOFF 0
#define ZW 1
#define HP0 0
#define HPD 1500
#define HPN 2
#define HN0 1
#define QT 0
#define VP 5
#define SFM 16
#define KT0 1500
#define KTD 1000
#define RC 192
#define RH 96
#define RP 32
#define HOLD 750
#define LEAD 3

DEVI uint32_t smem_u32(const void* p) { return (uint32_t)__cvta_generic_to_shared(p); }
DEVI void wg_fence() { asm volatile("wgmma.fence.sync.aligned;" ::: "memory"); }
DEVI void wg_commit() { asm volatile("wgmma.commit_group.sync.aligned;" ::: "memory"); }
template <int N> DEVI void wg_wait() { asm volatile("wgmma.wait_group.sync.aligned %0;" ::"n"(N) : "memory"); }
template <int S> DEVI void fence_regs(float (&d)[S]) {
#pragma unroll
  for (int i = 0; i < S; i++) asm volatile("" : "+f"(d[i])::"memory");
}
DEVI uint64_t mkdesc(uint32_t addr, uint32_t lbo, uint32_t sbo, int swz) {
  return (uint64_t)((addr & 0x3FFFF) >> 4) | ((uint64_t)(lbo >> 4) << 16) | ((uint64_t)(sbo >> 4) << 32) | ((uint64_t)swz << 62);
}
DEVI void mbar_init(uint32_t bar, uint32_t cnt) { asm volatile("mbarrier.init.shared::cta.b64 [%0], %1;" ::"r"(bar), "r"(cnt) : "memory"); }
DEVI void mbar_expect_tx(uint32_t bar, uint32_t bytes) { asm volatile("mbarrier.arrive.expect_tx.shared::cta.b64 _, [%0], %1;" ::"r"(bar), "r"(bytes) : "memory"); }
DEVI void mbar_arrive(uint32_t bar) { asm volatile("mbarrier.arrive.shared::cta.b64 _, [%0];" ::"r"(bar) : "memory"); }
DEVI void mbar_wait(uint32_t bar, uint32_t parity) {
  asm volatile("{\n.reg .pred p;\nLAB_WAIT:\nmbarrier.try_wait.parity.shared::cta.b64 p, [%0], %1;\n@!p bra LAB_WAIT;\n}" ::"r"(bar), "r"(parity) : "memory");
}
DEVI void mbar_wait_wd(uint32_t bar, uint32_t parity, uint32_t t0) {
  asm volatile("{\n.reg .pred p;\n.reg .u32 c;\nLAB_WAIT:\nmbarrier.try_wait.parity.shared::cta.b64 p, [%0], %1;\n@p bra DONE;\nmov.u32 c, %%clock;\nsub.u32 c, c, %2;\nsetp.lt.u32 p, c, 0x70000000;\n@p bra LAB_WAIT;\ntrap;\nDONE:\n}" ::"r"(bar), "r"(parity), "r"(t0) : "memory");
}
DEVI void flag_wait(const unsigned* p, unsigned target) {
  asm volatile("{\n.reg .pred p;\n.reg .s32 v;\nLAB_WAIT:\nld.relaxed.gpu.global.u32 v, [%0];\nsub.s32 v, v, %1;\nsetp.lt.s32 p, v, 0;\n@p nanosleep.u32 %2;\n@p bra LAB_WAIT;\n}" ::"l"(p), "r"(target), "n"(BACKOFF) : "memory");
}
DEVI void flag_wait_wd(const unsigned* p, unsigned target, uint32_t t0) {
  asm volatile("{\n.reg .pred p;\n.reg .s32 v;\nLAB_WAIT:\nld.relaxed.gpu.global.u32 v, [%0];\nsub.s32 v, v, %1;\nsetp.ge.s32 p, v, 0;\n@p bra DONE;\nmov.u32 v, %%clock;\nsub.s32 v, v, %2;\nsetp.lt.u32 p, v, 0x70000000;\n@p bra LAB_WAIT;\ntrap;\nDONE:\n}" ::"l"(p), "r"(target), "r"(t0) : "memory");
}
DEVI void flag_add(unsigned* p, unsigned v) { asm volatile("red.relaxed.gpu.global.add.u32 [%0], %1;" ::"l"(p), "r"(v) : "memory"); }
DEVI void flag_release(unsigned* p) { asm volatile("fence.proxy.async;\nred.relaxed.gpu.global.add.u32 [%0], 1;" ::"l"(p) : "memory"); }
DEVI void fence_async_smem() { asm volatile("fence.proxy.async.shared::cta;" ::: "memory"); }
DEVI bool elect_one() { uint32_t p; asm volatile("{\n.reg .pred P;\nelect.sync _|P, 0xffffffff;\nselp.u32 %0, 1, 0, P;\n}" : "=r"(p)); return p; }
DEVI void bar_sync(int id, int n) { asm volatile("bar.sync %0, %1;" ::"r"(id), "r"(n) : "memory"); }
DEVI void bar_arrive(int id, int n) { asm volatile("bar.arrive %0, %1;" ::"r"(id), "r"(n) : "memory"); }
DEVI void tma2(uint32_t dst, const CUtensorMap* m, int c0, int c1, uint32_t bar) {
  asm volatile("cp.async.bulk.tensor.2d.shared::cluster.global.mbarrier::complete_tx::bytes [%0], [%1, {%3, %4}], [%2];" ::"r"(dst), "l"(m), "r"(bar), "r"(c0), "r"(c1) : "memory");
}
DEVI void tma3(uint32_t dst, const CUtensorMap* m, int c0, int c1, int c2, uint32_t bar) {
  asm volatile("cp.async.bulk.tensor.3d.shared::cluster.global.mbarrier::complete_tx::bytes [%0], [%1, {%3, %4, %5}], [%2];" ::"r"(dst), "l"(m), "r"(bar), "r"(c0), "r"(c1), "r"(c2) : "memory");
}
DEVI void tma3_mc(uint32_t dst, const CUtensorMap* m, int c0, int c1, int c2, uint32_t bar) {
  asm volatile("cp.async.bulk.tensor.3d.shared::cluster.global.mbarrier::complete_tx::bytes.multicast::cluster [%0], [%1, {%3, %4, %5}], [%2], %6;" ::"r"(dst), "l"(m), "r"(bar), "r"(c0), "r"(c1), "r"(c2), "h"((uint16_t)3) : "memory");
}
DEVI void tma2_mc(uint32_t dst, const CUtensorMap* m, int c0, int c1, uint32_t bar) {
  asm volatile("cp.async.bulk.tensor.2d.shared::cluster.global.mbarrier::complete_tx::bytes.multicast::cluster [%0], [%1, {%3, %4}], [%2], %5;" ::"r"(dst), "l"(m), "r"(bar), "r"(c0), "r"(c1), "h"((uint16_t)3) : "memory");
}
DEVI void mbar_arrive_remote(uint32_t bar, uint32_t cta) {
  asm volatile("{\n.reg .b32 ra;\nmapa.shared::cluster.u32 ra, %0, %1;\nmbarrier.arrive.shared::cluster.b64 _, [ra];\n}" ::"r"(bar), "r"(cta) : "memory");
}
DEVI void tma3_store(const CUtensorMap* m, int c0, int c1, int c2, uint32_t src) {
  asm volatile("cp.async.bulk.tensor.3d.global.shared::cta.bulk_group [%0, {%2, %3, %4}], [%1];" ::"l"(m), "r"(src), "r"(c0), "r"(c1), "r"(c2) : "memory");
}
DEVI void bulk_load(uint32_t dst, const void* src, uint32_t bytes, uint32_t bar) {
  asm volatile("cp.async.bulk.shared::cluster.global.mbarrier::complete_tx::bytes [%0], [%1], %2, [%3];" ::"r"(dst), "l"(src), "r"(bytes), "r"(bar) : "memory");
}
DEVI void bulk_store(void* dst, uint32_t src, uint32_t bytes) {
  asm volatile("cp.async.bulk.global.shared::cta.bulk_group [%0], [%1], %2;" ::"l"(dst), "r"(src), "r"(bytes) : "memory");
}
DEVI void pf_l2(const void* p) { asm volatile("prefetch.global.L2 [%0];" ::"l"(p)); }
template <int OFF> DEVI uint32_t ldg_v(const void* p) { uint32_t v; asm volatile("ld.volatile.global.b32 %0, [%1 + %2];" : "=r"(v) : "l"(p), "n"(OFF)); return v; }
DEVI void bulk_commit() { asm volatile("cp.async.bulk.commit_group;" ::: "memory"); }
DEVI void bulk_wait_all() { asm volatile("cp.async.bulk.wait_group 0;" ::: "memory"); }
DEVI void bulk_wait_read() { asm volatile("cp.async.bulk.wait_group.read 0;" ::: "memory"); }
template <int R> DEVI void reg_inc() { asm volatile("setmaxnreg.inc.sync.aligned.u32 %0;" ::"n"(R)); }
template <int R> DEVI void reg_dec() { asm volatile("setmaxnreg.dec.sync.aligned.u32 %0;" ::"n"(R)); }
DEVI uint32_t prmt(uint32_t a, uint32_t b, uint32_t s) { uint32_t r; asm("prmt.b32 %0,%1,%2,%3;" : "=r"(r) : "r"(a), "r"(b), "r"(s)); return r; }
DEVI uint32_t lds32(uint32_t a) { uint32_t r; asm volatile("ld.shared.b32 %0,[%1];" : "=r"(r) : "r"(a)); return r; }
DEVI void sts32(uint32_t a, uint32_t x) { asm volatile("st.shared.b32 [%0],%1;" ::"r"(a), "r"(x) : "memory"); }
DEVI void sts128(uint32_t a, uint32_t x, uint32_t y, uint32_t z, uint32_t w) { asm volatile("st.shared.v4.b32 [%0],{%1,%2,%3,%4};" ::"r"(a), "r"(x), "r"(y), "r"(z), "r"(w) : "memory"); }
DEVI void sts128v(uint32_t a, uint32_t x, uint32_t y, uint32_t z, uint32_t w) { asm volatile("st.volatile.shared.v4.b32 [%0],{%1,%2,%3,%4};" ::"r"(a), "r"(x), "r"(y), "r"(z), "r"(w) : "memory"); }
DEVI void lds128(uint32_t a, uint32_t& x, uint32_t& y, uint32_t& z, uint32_t& w) { asm volatile("ld.shared.v4.b32 {%0,%1,%2,%3},[%4];" : "=r"(x), "=r"(y), "=r"(z), "=r"(w) : "r"(a) : "memory"); }
DEVI void ldsm4(uint32_t& r0, uint32_t& r1, uint32_t& r2, uint32_t& r3, uint32_t addr) {
  asm volatile("ldmatrix.sync.aligned.m8n8.x4.shared.b16 {%0,%1,%2,%3}, [%4];" : "=r"(r0), "=r"(r1), "=r"(r2), "=r"(r3) : "r"(addr) : "memory");
}
DEVI void ldsm4t(uint32_t& r0, uint32_t& r1, uint32_t& r2, uint32_t& r3, uint32_t addr) {
  asm volatile("ldmatrix.sync.aligned.m8n8.x4.trans.shared.b16 {%0,%1,%2,%3}, [%4];" : "=r"(r0), "=r"(r1), "=r"(r2), "=r"(r3) : "r"(addr) : "memory");
}
DEVI void stsm4(uint32_t addr, uint32_t r0, uint32_t r1, uint32_t r2, uint32_t r3) {
  asm volatile("stmatrix.sync.aligned.m8n8.x4.shared.b16 [%0], {%1,%2,%3,%4};" ::"r"(addr), "r"(r0), "r"(r1), "r"(r2), "r"(r3) : "memory");
}
DEVI void stsm4t(uint32_t addr, uint32_t r0, uint32_t r1, uint32_t r2, uint32_t r3) {
  asm volatile("stmatrix.sync.aligned.m8n8.x4.trans.shared.b16 [%0], {%1,%2,%3,%4};" ::"r"(addr), "r"(r0), "r"(r1), "r"(r2), "r"(r3) : "memory");
}
DEVI uint32_t movm(uint32_t a) { uint32_t r; asm volatile("movmatrix.sync.aligned.m8n8.trans.b16 %0, %1;" : "=r"(r) : "r"(a)); return r; }
DEVI uint32_t pack_bf16(float lo, float hi) { uint32_t r; asm("cvt.rn.bf16x2.f32 %0, %1, %2;" : "=r"(r) : "f"(hi), "f"(lo)); return r; }
DEVI uint32_t hmul2(uint32_t a, uint32_t b) { uint32_t r; asm("mul.rn.bf16x2 %0,%1,%2;" : "=r"(r) : "r"(a), "r"(b)); return r; }
DEVI uint32_t hadd2(uint32_t a, uint32_t b) { uint32_t r; asm("add.rn.bf16x2 %0,%1,%2;" : "=r"(r) : "r"(a), "r"(b)); return r; }
DEVI float bf_lo(uint32_t a) { return __uint_as_float(prmt(a, 0, 0x1044)); }
DEVI float bf_hi(uint32_t a) { return __uint_as_float(a & 0xFFFF0000u); }
DEVI void mma16(float (&c)[4], uint32_t a0, uint32_t a1, uint32_t a2, uint32_t a3, uint32_t b0, uint32_t b1) {
  asm volatile("mma.sync.aligned.m16n8k16.row.col.f32.bf16.bf16.f32 {%0,%1,%2,%3},{%4,%5,%6,%7},{%8,%9},{%0,%1,%2,%3};"
      : "+f"(c[0]), "+f"(c[1]), "+f"(c[2]), "+f"(c[3]) : "r"(a0), "r"(a1), "r"(a2), "r"(a3), "r"(b0), "r"(b1));
}
DEVI void mma8(float (&c)[4], uint32_t a0, uint32_t a1, uint32_t b0) {
  asm volatile("mma.sync.aligned.m16n8k8.row.col.f32.bf16.bf16.f32 {%0,%1,%2,%3},{%4,%5},{%6},{%0,%1,%2,%3};"
      : "+f"(c[0]), "+f"(c[1]), "+f"(c[2]), "+f"(c[3]) : "r"(a0), "r"(a1), "r"(b0));
}
DEVI float ex2(float x) { float r; asm volatile("ex2.approx.ftz.f32 %0, %1;" : "=f"(r) : "f"(x)); return r; }

DEVI uint32_t clk() { uint32_t c; asm volatile("mov.u32 %0, %%clock;" : "=r"(c)); return c; }
DEVI void wait_until(uint32_t t0, int dt) { while ((int)(clk() - t0) < dt) __nanosleep(40); }
DEVI void spin_until(uint32_t t0, int dt) { while ((int)(clk() - t0) < dt) {} }
DEVI uint32_t hfma2(uint32_t a, uint32_t b, uint32_t c) { uint32_t r; asm("fma.rn.bf16x2 %0,%1,%2,%3;" : "=r"(r) : "r"(a), "r"(b), "r"(c)); return r; }
DEVI void bar_sync_p(int on, int id, int n) { asm volatile("{\n.reg .pred p;\nsetp.ne.b32 p, %0, 0;\n@p bar.sync %1, %2;\n}" ::"r"(on), "r"(id), "r"(n) : "memory"); }
DEVI void bar_arrive_p(int on, int id, int n) { asm volatile("{\n.reg .pred p;\nsetp.ne.b32 p, %0, 0;\n@p bar.arrive %1, %2;\n}" ::"r"(on), "r"(id), "r"(n) : "memory"); }
DEVI void mbar_arrive_p(int on, uint32_t bar) { asm volatile("{\n.reg .pred p;\nsetp.ne.b32 p, %1, 0;\n@p mbarrier.arrive.shared::cta.b64 _, [%0];\n}" ::"r"(bar), "r"(on) : "memory"); }
DEVI void mbar_arrive2_p(int on, uint32_t bar, uint32_t rbar) {
  asm volatile("{\n.reg .pred p;\nsetp.ne.b32 p, %2, 0;\n@p mbarrier.arrive.shared::cta.b64 _, [%0];\n@p mbarrier.arrive.shared::cluster.b64 _, [%1];\n}" ::"r"(bar), "r"(rbar), "r"(on) : "memory");
}
DEVI void st_relaxed(uint4* p, uint32_t x, uint32_t y, uint32_t z, uint32_t w) {
  asm volatile("st.relaxed.gpu.global.v4.b32 [%0], {%1,%2,%3,%4};" ::"l"(p), "r"(x), "r"(y), "r"(z), "r"(w) : "memory");
}
DEVI uint32_t mapa(uint32_t a, uint32_t cta) { uint32_t r; asm("mapa.shared::cluster.u32 %0, %1, %2;" : "=r"(r) : "r"(a), "r"(cta)); return r; }
DEVI void st_async128(uint32_t a, uint32_t x, uint32_t y, uint32_t z, uint32_t w, uint32_t bar) {
  asm volatile("st.async.weak.shared::cluster.mbarrier::complete_tx::bytes.v4.b32 [%0], {%1,%2,%3,%4}, [%5];" ::"r"(a), "r"(x), "r"(y), "r"(z), "r"(w), "r"(bar) : "memory");
}

template<int OFF, int TB, int S> __device__ __forceinline__ void wgmma_rs_n128(float (&d)[S], uint32_t a0, uint32_t a1, uint32_t a2, uint32_t a3, uint64_t db, int sd) {
  asm volatile("{\n.reg .pred p;\nsetp.ne.b32 p, %69, 0;\n"
    "wgmma.mma_async.sync.aligned.m64n128k16.f32.bf16.bf16 {%0, %1, %2, %3, %4, %5, %6, %7, %8, %9, %10, %11, %12, %13, %14, %15, %16, %17, %18, %19, %20, %21, %22, %23, %24, %25, %26, %27, %28, %29, %30, %31, %32, %33, %34, %35, %36, %37, %38, %39, %40, %41, %42, %43, %44, %45, %46, %47, %48, %49, %50, %51, %52, %53, %54, %55, %56, %57, %58, %59, %60, %61, %62, %63}, {%64, %65, %66, %67}, %68, p, 1, 1, %70;\n}\n"
    : "+f"(d[OFF+0]), "+f"(d[OFF+1]), "+f"(d[OFF+2]), "+f"(d[OFF+3]), "+f"(d[OFF+4]), "+f"(d[OFF+5]), "+f"(d[OFF+6]), "+f"(d[OFF+7]), "+f"(d[OFF+8]), "+f"(d[OFF+9]), "+f"(d[OFF+10]), "+f"(d[OFF+11]), "+f"(d[OFF+12]), "+f"(d[OFF+13]), "+f"(d[OFF+14]), "+f"(d[OFF+15]), "+f"(d[OFF+16]), "+f"(d[OFF+17]), "+f"(d[OFF+18]), "+f"(d[OFF+19]), "+f"(d[OFF+20]), "+f"(d[OFF+21]), "+f"(d[OFF+22]), "+f"(d[OFF+23]), "+f"(d[OFF+24]), "+f"(d[OFF+25]), "+f"(d[OFF+26]), "+f"(d[OFF+27]), "+f"(d[OFF+28]), "+f"(d[OFF+29]), "+f"(d[OFF+30]), "+f"(d[OFF+31]), "+f"(d[OFF+32]), "+f"(d[OFF+33]), "+f"(d[OFF+34]), "+f"(d[OFF+35]), "+f"(d[OFF+36]), "+f"(d[OFF+37]), "+f"(d[OFF+38]), "+f"(d[OFF+39]), "+f"(d[OFF+40]), "+f"(d[OFF+41]), "+f"(d[OFF+42]), "+f"(d[OFF+43]), "+f"(d[OFF+44]), "+f"(d[OFF+45]), "+f"(d[OFF+46]), "+f"(d[OFF+47]), "+f"(d[OFF+48]), "+f"(d[OFF+49]), "+f"(d[OFF+50]), "+f"(d[OFF+51]), "+f"(d[OFF+52]), "+f"(d[OFF+53]), "+f"(d[OFF+54]), "+f"(d[OFF+55]), "+f"(d[OFF+56]), "+f"(d[OFF+57]), "+f"(d[OFF+58]), "+f"(d[OFF+59]), "+f"(d[OFF+60]), "+f"(d[OFF+61]), "+f"(d[OFF+62]), "+f"(d[OFF+63]) : "r"(a0), "r"(a1), "r"(a2), "r"(a3), "l"(db), "r"(sd), "n"(TB));
}
template<int OFF, int TB, int S> __device__ __forceinline__ void wgmma_rs_n64(float (&d)[S], uint32_t a0, uint32_t a1, uint32_t a2, uint32_t a3, uint64_t db, int sd) {
  asm volatile("{\n.reg .pred p;\nsetp.ne.b32 p, %37, 0;\n"
    "wgmma.mma_async.sync.aligned.m64n64k16.f32.bf16.bf16 {%0, %1, %2, %3, %4, %5, %6, %7, %8, %9, %10, %11, %12, %13, %14, %15, %16, %17, %18, %19, %20, %21, %22, %23, %24, %25, %26, %27, %28, %29, %30, %31}, {%32, %33, %34, %35}, %36, p, 1, 1, %38;\n}\n"
    : "+f"(d[OFF+0]), "+f"(d[OFF+1]), "+f"(d[OFF+2]), "+f"(d[OFF+3]), "+f"(d[OFF+4]), "+f"(d[OFF+5]), "+f"(d[OFF+6]), "+f"(d[OFF+7]), "+f"(d[OFF+8]), "+f"(d[OFF+9]), "+f"(d[OFF+10]), "+f"(d[OFF+11]), "+f"(d[OFF+12]), "+f"(d[OFF+13]), "+f"(d[OFF+14]), "+f"(d[OFF+15]), "+f"(d[OFF+16]), "+f"(d[OFF+17]), "+f"(d[OFF+18]), "+f"(d[OFF+19]), "+f"(d[OFF+20]), "+f"(d[OFF+21]), "+f"(d[OFF+22]), "+f"(d[OFF+23]), "+f"(d[OFF+24]), "+f"(d[OFF+25]), "+f"(d[OFF+26]), "+f"(d[OFF+27]), "+f"(d[OFF+28]), "+f"(d[OFF+29]), "+f"(d[OFF+30]), "+f"(d[OFF+31]) : "r"(a0), "r"(a1), "r"(a2), "r"(a3), "l"(db), "r"(sd), "n"(TB));
}
template<int OFF, int TB, int S> __device__ __forceinline__ void wgmma_rs_n48(float (&d)[S], uint32_t a0, uint32_t a1, uint32_t a2, uint32_t a3, uint64_t db, int sd) {
  asm volatile("{\n.reg .pred p;\nsetp.ne.b32 p, %29, 0;\n"
    "wgmma.mma_async.sync.aligned.m64n48k16.f32.bf16.bf16 {%0, %1, %2, %3, %4, %5, %6, %7, %8, %9, %10, %11, %12, %13, %14, %15, %16, %17, %18, %19, %20, %21, %22, %23}, {%24, %25, %26, %27}, %28, p, 1, 1, %30;\n}\n"
    : "+f"(d[OFF+0]), "+f"(d[OFF+1]), "+f"(d[OFF+2]), "+f"(d[OFF+3]), "+f"(d[OFF+4]), "+f"(d[OFF+5]), "+f"(d[OFF+6]), "+f"(d[OFF+7]), "+f"(d[OFF+8]), "+f"(d[OFF+9]), "+f"(d[OFF+10]), "+f"(d[OFF+11]), "+f"(d[OFF+12]), "+f"(d[OFF+13]), "+f"(d[OFF+14]), "+f"(d[OFF+15]), "+f"(d[OFF+16]), "+f"(d[OFF+17]), "+f"(d[OFF+18]), "+f"(d[OFF+19]), "+f"(d[OFF+20]), "+f"(d[OFF+21]), "+f"(d[OFF+22]), "+f"(d[OFF+23]) : "r"(a0), "r"(a1), "r"(a2), "r"(a3), "l"(db), "r"(sd), "n"(TB));
}
template<int OFF, int TB, int S> __device__ __forceinline__ void wgmma_rs_n16(float (&d)[S], uint32_t a0, uint32_t a1, uint32_t a2, uint32_t a3, uint64_t db, int sd) {
  asm volatile("{\n.reg .pred p;\nsetp.ne.b32 p, %13, 0;\n"
    "wgmma.mma_async.sync.aligned.m64n16k16.f32.bf16.bf16 {%0, %1, %2, %3, %4, %5, %6, %7}, {%8, %9, %10, %11}, %12, p, 1, 1, %14;\n}\n"
    : "+f"(d[OFF+0]), "+f"(d[OFF+1]), "+f"(d[OFF+2]), "+f"(d[OFF+3]), "+f"(d[OFF+4]), "+f"(d[OFF+5]), "+f"(d[OFF+6]), "+f"(d[OFF+7]) : "r"(a0), "r"(a1), "r"(a2), "r"(a3), "l"(db), "r"(sd), "n"(TB));
}
template<int OFF, int TA, int TB, int S> __device__ __forceinline__ void wgmma_ss_n160(float (&d)[S], uint64_t da, uint64_t db, int sd) {
  asm volatile("{\n.reg .pred p;\nsetp.ne.b32 p, %82, 0;\n"
    "wgmma.mma_async.sync.aligned.m64n160k16.f32.bf16.bf16 {%0, %1, %2, %3, %4, %5, %6, %7, %8, %9, %10, %11, %12, %13, %14, %15, %16, %17, %18, %19, %20, %21, %22, %23, %24, %25, %26, %27, %28, %29, %30, %31, %32, %33, %34, %35, %36, %37, %38, %39, %40, %41, %42, %43, %44, %45, %46, %47, %48, %49, %50, %51, %52, %53, %54, %55, %56, %57, %58, %59, %60, %61, %62, %63, %64, %65, %66, %67, %68, %69, %70, %71, %72, %73, %74, %75, %76, %77, %78, %79}, %80, %81, p, 1, 1, %83, %84;\n}\n"
    : "+f"(d[OFF+0]), "+f"(d[OFF+1]), "+f"(d[OFF+2]), "+f"(d[OFF+3]), "+f"(d[OFF+4]), "+f"(d[OFF+5]), "+f"(d[OFF+6]), "+f"(d[OFF+7]), "+f"(d[OFF+8]), "+f"(d[OFF+9]), "+f"(d[OFF+10]), "+f"(d[OFF+11]), "+f"(d[OFF+12]), "+f"(d[OFF+13]), "+f"(d[OFF+14]), "+f"(d[OFF+15]), "+f"(d[OFF+16]), "+f"(d[OFF+17]), "+f"(d[OFF+18]), "+f"(d[OFF+19]), "+f"(d[OFF+20]), "+f"(d[OFF+21]), "+f"(d[OFF+22]), "+f"(d[OFF+23]), "+f"(d[OFF+24]), "+f"(d[OFF+25]), "+f"(d[OFF+26]), "+f"(d[OFF+27]), "+f"(d[OFF+28]), "+f"(d[OFF+29]), "+f"(d[OFF+30]), "+f"(d[OFF+31]), "+f"(d[OFF+32]), "+f"(d[OFF+33]), "+f"(d[OFF+34]), "+f"(d[OFF+35]), "+f"(d[OFF+36]), "+f"(d[OFF+37]), "+f"(d[OFF+38]), "+f"(d[OFF+39]), "+f"(d[OFF+40]), "+f"(d[OFF+41]), "+f"(d[OFF+42]), "+f"(d[OFF+43]), "+f"(d[OFF+44]), "+f"(d[OFF+45]), "+f"(d[OFF+46]), "+f"(d[OFF+47]), "+f"(d[OFF+48]), "+f"(d[OFF+49]), "+f"(d[OFF+50]), "+f"(d[OFF+51]), "+f"(d[OFF+52]), "+f"(d[OFF+53]), "+f"(d[OFF+54]), "+f"(d[OFF+55]), "+f"(d[OFF+56]), "+f"(d[OFF+57]), "+f"(d[OFF+58]), "+f"(d[OFF+59]), "+f"(d[OFF+60]), "+f"(d[OFF+61]), "+f"(d[OFF+62]), "+f"(d[OFF+63]), "+f"(d[OFF+64]), "+f"(d[OFF+65]), "+f"(d[OFF+66]), "+f"(d[OFF+67]), "+f"(d[OFF+68]), "+f"(d[OFF+69]), "+f"(d[OFF+70]), "+f"(d[OFF+71]), "+f"(d[OFF+72]), "+f"(d[OFF+73]), "+f"(d[OFF+74]), "+f"(d[OFF+75]), "+f"(d[OFF+76]), "+f"(d[OFF+77]), "+f"(d[OFF+78]), "+f"(d[OFF+79]) : "l"(da), "l"(db), "r"(sd), "n"(TA), "n"(TB));
}

__device__ __align__(1024) uint16_t g_kvT[2 * 640 * 2048];
__device__ __align__(1024) uint16_t g_y2T[2 * 640 * 2048];
__device__ __align__(1024) uint16_t g_o[2048 * 640];
__device__ __align__(1024) uint16_t g_gate[2080];
__device__ __align__(1024) uint4 g_halo[128 * 5 * 32];
__device__ __align__(1024) unsigned g_cnt[46 * 32];
__device__ __align__(1024) unsigned g_launch[132 * 32];
#define CNT_KV(i) (g_cnt + 32 * (i))
#define CNT_O(i) (g_cnt + 32 * (10 + (i)))
#define CNT_Y(i) (g_cnt + 32 * (26 + (i)))
#define PTL(i) do {} while (0)
#define PTPL(on, i) do {} while (0)
#define PT(i) do {} while (0)
#define PTP(on, i) do {} while (0)

constexpr uint32_t SB = 1024;
constexpr uint32_t STG = 23552, WST = 15360;
DEVI constexpr uint32_t o_px(int ks) { return (((ks >> 1) + 1) & 3) * 2 * STG; }
DEVI constexpr uint32_t o_pw(int ks) { return o_px(ks) + 16384 + (ks & 1) * WST; }
constexpr uint32_t O_HALO = 0, O_OST = STG;
constexpr uint32_t P3S = 28672;
constexpr uint32_t HC = 8320, UC = 4624, UZ = 528;
constexpr uint32_t O_H0 = 5 * P3S, O_U2 = O_H0 + 3 * HC, O_H3 = O_U2 + UC, O_U0 = O_H3 + 2 * HC;
DEVI constexpr uint32_t o_h(int c) { return O_H0 + c * HC + (c > 2 ? UC : 0); }
DEVI constexpr uint32_t o_u(int c) { return c == 2 ? O_U2 : O_U0 + (c > 2 ? c - 1 : c) * UC; }
constexpr uint32_t O_Y = 208896;
DEVI constexpr uint32_t o_x(int c) { return c < 2 ? O_Y + c * 5120 : O_U0 + (c & 1) * UC; }
constexpr uint32_t O_HIN = O_Y + 16384;
DEVI constexpr uint32_t o_kin(int c) { return ((O_U0 + 127) & ~127u) + ((c & 1) ? 0 : 73 * 128); }
DEVI constexpr uint32_t o_p3(int ks) { return (ks < 6 ? ks : ks - 6) * P3S; }
constexpr uint32_t O_BT = 4 * P3S;
constexpr uint32_t O_GT = O_Y + 20480, O_GW = O_GT + 320;
constexpr uint32_t O_BAR = 231040;
constexpr uint32_t B_FULL = O_BAR, B_EMPTY = O_BAR + 8 * 8, B_P3F = O_BAR + 8 * 16, B_P3R = O_BAR + 8 * 26, B_G = O_BAR + 8 * 27, B_U = O_BAR + 8 * 28,
                   B_KVD = O_BAR + 8 * 33, B_KF = O_BAR + 8 * 36, B_Y = O_BAR + 8 * 38, B_EP = O_BAR + 8 * 40, B_LAST = O_BAR + 8 * 41, B_DONE = O_BAR + 8 * 42,
                   B_P1E = O_BAR + 8 * 43, B_HX = O_BAR + 8 * 43  , B_P3E = O_BAR + 8 * 52, B_HX0 = O_BAR + 8 * 57, B_KVS = O_BAR + 8 * 58, B_QD = O_BAR + 8 * 60, B_Q = O_BAR + 8 * 51;
constexpr uint32_t B_S13 = B_EMPTY + 8 * 5, B_S15 = B_EMPTY + 8 * 7, B_S19 = B_EMPTY + 8 * 3;
constexpr uint32_t O_GP = O_BAR + 512, O_EPOCH = O_GW + 1280;
constexpr uint32_t SMEM_BYTES = 232448;
static_assert(O_U0 + 127 + 146 * 128 <= O_Y && o_kin(0) >= O_U0 + 2 * UC && O_EPOCH + 4 <= O_BAR && O_U0 >= 8 * STG, "smem map");
enum { NB_LEAD = 1, NB_HELP = 2, NB_HALO = 3, NB_ATT = 4, NB_G = 5, NB_TOK = 6, NB_RFULL = 8, NB_RFREE = 10 };

struct Maps { CUtensorMap x_par, w_main, w_tail, k_ld, v_ld, o_st, kv_st, wo, o_ld, y_ld, q_ld; };

template <int M, class F> DEVI void conv_step(float (&acc)[128], uint32_t a0, uint32_t a1, uint32_t a2, uint32_t a3, uint32_t dl, F&& gap) {
  auto D = [&](int off) { return ((uint64_t)8 << 32) | (uint64_t)(uint32_t)(dl + off - 16 * M); };
  if constexpr (M == 0) wgmma_rs_n16<0, 0>(acc, a0, a1, a2, a3, D(0), 0);
  if constexpr (M <= 3) { wgmma_rs_n48<8, 0>(acc, a0, a1, a2, a3, D(16), M == 0 ? 0 : 1); gap(); }
  if constexpr (M <= 6) { wgmma_rs_n48<32, 0>(acc, a0, a1, a2, a3, D(64), M == 0 ? 0 : 1); gap(); }
  if constexpr (M <= 9) { wgmma_rs_n48<56, 0>(acc, a0, a1, a2, a3, D(112), M == 0 ? 0 : 1); gap(); }
  if constexpr (M <= 12) { wgmma_rs_n48<80, 0>(acc, a0, a1, a2, a3, D(160), M == 0 ? 0 : 1); gap(); }
  wgmma_rs_n48<104, 0>(acc, a0, a1, a2, a3, D(208), M == 0 ? 0 : 1); gap();
}
DEVI constexpr int a_off(int P, int i) { return -4 * (64 * ((i & 4) ? 15 - P : P) + (i & 1) * 32 - (i & 2) * 2); }
template <int P> DEVI void load_pair(uint32_t (&a)[8], uint32_t ab) {
#pragma unroll
  for (int i = 0; i < 8; i++) a[i] = lds32(ab + a_off(P, i));
}
template <int P> DEVI void mma_pair(float (&acc)[128], uint32_t (&a)[8], uint32_t db) {
  wg_fence();
  conv_step<P>(acc, a[0], a[1], a[2], a[3], db, []() {});
  conv_step<15 - P>(acc, a[4], a[5], a[6], a[7], db, []() {});
  wg_commit();
}
template <int P, int Q, int W> DEVI void mma_pair_ld(float (&acc)[128], uint32_t (&a)[8], uint32_t db, uint32_t (&nx)[8], uint32_t ab, int on) {
  int n = 0, j = 0;
  auto ld = [&](int cnt) {
#pragma unroll
    for (int r = 0; r < cnt; r++, n++) {
      if (Q >= 4) nx[n] = lds32(ab + a_off(Q, n));
      else asm volatile("{\n.reg .pred p;\nsetp.ne.b32 p, %2, 0;\n@p ld.shared.b32 %0, [%1];\n}" : "+r"(nx[n]) : "r"(ab + a_off(Q, n)), "r"(on));
    }
  };
  auto gap = [&]() {
    if (j == 1) { wg_commit(); wg_wait<W + 1>(); ld(3); wg_fence(); }
    if (j == 3) { wg_commit(); ld(3); wg_fence(); }
    j++;
  };
  wg_fence();
  conv_step<P>(acc, a[0], a[1], a[2], a[3], db, gap);
  conv_step<15 - P>(acc, a[4], a[5], a[6], a[7], db, gap);
  wg_commit();
  ld(2);
}

template <int I0, int I1> DEVI void conv_reduce(uint32_t sb, int c, int ht, int chan, int bar, int nthr) {
  const uint32_t a0 = sb + o_h(c) + ht * 16, a2 = sb + o_u(c) + ht * 16, a3 = sb + o_x(c) + ht * 16;
  uint4* yp = (uint4*)(g_y2T + (size_t)chan * 2048) + ht;
#pragma unroll
  for (int i = I0; i < I1; i++) {
    uint4 p, q, r, s;
    if (i == I0) bar_sync(bar, nthr);
    lds128(a0 + i * 2048, p.x, p.y, p.z, p.w); lds128(a0 + 4160 + i * 2048, q.x, q.y, q.z, q.w);
    lds128(a2 + i * 2048, r.x, r.y, r.z, r.w); lds128(a3 + i * 2048, s.x, s.y, s.z, s.w);
    auto sum = [](uint32_t a, uint32_t b, uint32_t c, uint32_t d) { return hadd2(hadd2(hadd2(a, b), 0u), hadd2(c, d)) ^ 0x80008000u; };
    yp[i * 128] = make_uint4(sum(p.x, q.x, r.x, s.x), sum(p.y, q.y, r.y, s.y), sum(p.z, q.z, r.z, s.z), sum(p.w, q.w, r.w, s.w));
  }
}

template <int ODD, int PART> DEVI void pack_qkv(const float (&aq)[32], const float (&acc)[88], uint32_t (&Q)[10][2], uint32_t (&K)[10][2], uint32_t (&V)[10][2]) {
#pragma unroll
  for (int f = 0; f < 10; f++) {
    const bool tail = ODD ? (f < 2) : (f >= 8);
    const int fm = tail ? 0 : ODD ? f - 2 : f, ft = ODD ? f : f - 8;
    const int nq = tail ? 16 + ft : 0, nk = tail ? 18 + ft : fm, nv = tail ? 20 + ft : 8 + fm;
    if (PART == 0) {
      K[f][1] = pack_bf16(acc[4 * nk + 2], acc[4 * nk + 3]);
      V[f][1] = pack_bf16(acc[4 * nv + 2], acc[4 * nv + 3]);
    } else if (PART == 1) {
      V[f][0] = pack_bf16(acc[4 * nv], acc[4 * nv + 1]); K[f][0] = pack_bf16(acc[4 * nk], acc[4 * nk + 1]);
    } else if (tail) {
      Q[f][0] = pack_bf16(acc[4 * nq], acc[4 * nq + 1]); Q[f][1] = pack_bf16(acc[4 * nq + 2], acc[4 * nq + 3]);
    } else {
      Q[f][0] = pack_bf16(aq[4 * fm], aq[4 * fm + 1]); Q[f][1] = pack_bf16(aq[4 * fm + 2], aq[4 * fm + 3]);
    }
  }
}
DEVI void sched_fence(uint32_t& z) {
  asm volatile("{\n.reg .pred p;\nL:\nshr.u32 %0, %0, 1;\nsetp.ne.u32 p, %0, 0;\n@p bra.uni L;\n}" : "+r"(z));
}

DEVI int pair_of(int c) {
  const int lo = 32 + 8 * c, hi = c - 4 + ((max(c - 29, 0) * 37) >> 8);
  int p; asm("{\n.reg .pred q;\nsetp.lt.s32 q, %1, 4;\nselp.b32 %0, %2, %3, q;\n}" : "=r"(p) : "r"(c), "r"(lo), "r"(hi));
  return p;
}
DEVI uint32_t make_ctx() {
  int b; asm volatile("mov.u32 %0, %%ctaid.x;" : "=r"(b));
  b += clk() & threadIdx.y;
  const int p = pair_of(b >> 1);
  const int j = b < 128 ? 8 * (p & 7) + (p >> 3) : 64, cp = (j * 79) >> 10;
  return ((2 * p + (b & 1)) & 255) | (j - 13 * cp) << 8 | (2 * cp + (b & 1)) << 12 | (b >> 7) << 16;
}
#define CTX() asm volatile("" : "+r"(ctx)); CTXU()
#define CTXU() int tid; asm volatile("mov.u32 %0, %%tid.x;" : "=r"(tid)); \
  const int lane = tid & 31, vb = ctx & 255, hg = (ctx >> 4) & 7, rt = ctx & 15, par = (ctx >> 3) & 1, mt = ctx & 7, rank = ctx & 1, \
  tb = (ctx >> 8) & 15, cb = (ctx >> 12) & 15; const bool main_cta = ctx < 65536; \
  (void)tid; (void)lane; (void)vb; (void)hg; (void)rt; (void)par; (void)mt; (void)rank; (void)tb; (void)cb; (void)main_cta
#define CTXW() CTX(); const int wg = warp >> 2, w = warp & 3, g = lane >> 2, t = lane & 3; const bool lead = (tid & 127) == 0; \
  (void)wg; (void)w; (void)g; (void)t; (void)lead

__global__ void __cluster_dims__(2, 1, 1) __launch_bounds__(512, 1)
fused_kernel(const uint16_t* __restrict__ xq, const uint16_t* __restrict__ wqkv, const uint16_t* __restrict__ gate_w, const __grid_constant__ Maps M, const uint16_t* __restrict__ shift_k, const uint16_t* __restrict__ ssm_k, const uint16_t* __restrict__ ssm_D,
             uint16_t* __restrict__ outp) {
  extern __shared__ __align__(1024) uint8_t smem_raw[];
  const uint32_t sb = smem_u32(smem_raw);
  const uint32_t t0 = clk();
  auto get_epoch = [&]() { mbar_wait(sb + B_EP, 0); return lds32(sb + O_EPOCH); };

  auto p1_load_x = [&](int ks, int p, int rank) {
    tma3(sb + o_px(ks), &M.x_par, ks * 32, (p >> 2) & 1, (p & 3) * 256 + rank * 128, sb + B_FULL + 8 * (ks & 7));
  };
  auto p1_load_w = [&](int ks, int p, int rank) {
    const uint32_t st = sb + o_pw(ks), fb = sb + B_FULL + 8 * (ks & 7);
    tma3_mc(st + rank * 6144, &M.w_main, (p >> 3) * 80 + 2 * (p & 8), ks * 32 + rank * 16, 0, fb);
    tma3_mc(st + 12288 + rank * 1536, &M.w_tail, (p >> 3) * 80 + 8 * (~p & 8), ks * 32 + rank * 16, 0, fb);
  };
  auto cta_pair = [&]() { return pair_of(blockIdx.x >> 1); };

  const uint16_t* pfp = nullptr;
  if (threadIdx.x < 32) {
    const unsigned b = blockIdx.x, l = threadIdx.x;
    pfp = l < 16 ? xq + (16 * b + l) * 640 : wqkv + (15 * b + l - 16) * 64;
    if ((l | b >> 7 << 5) < 31) pf_l2(pfp);
  }
  const int warp = __shfl_sync(~0u, threadIdx.x >> 5, 0);
  if ((warp & 14) == 8) {
    if (elect_one()) {
#pragma unroll
      for (int s = 0; s < 8; s++) mbar_init(sb + O_BAR - 512 + 64 * warp + 8 * s, 5 * warp - 39);
      asm volatile("fence.mbarrier_init.release.cluster;" ::: "memory");
    }
    __syncwarp();
  }
  asm volatile("barrier.cluster.arrive.relaxed.aligned;" ::: "memory");
  if (warp == 8 && blockIdx.x < 128) {
    const int p = cta_pair(), rank = blockIdx.x & 1;
    if (elect_one()) { mbar_expect_tx(sb + B_FULL, 16384 + WST); p1_load_x(0, p, rank); }
    __syncwarp();
    asm volatile("barrier.cluster.wait.aligned;" ::: "memory");
    if (elect_one()) { p1_load_w(0, p, rank); PT(100); }
    __syncwarp();
  } else if (warp != 15) {
    asm volatile("barrier.cluster.wait.aligned;" ::: "memory");
    spin_until(t0, HOLD);
  }
  auto init_rest = [&]() {
    if (warp >= 11 && elect_one()) {
#pragma unroll
      for (int s = 0; s < 12; s++) mbar_init(sb + O_BAR + 128 - 11 * 96 + 96 * warp + 8 * s, warp == 14 ? 2 : 1);
      asm volatile("fence.mbarrier_init.release.cluster;" ::: "memory");
    }
    __syncwarp();
    bar_sync(0, blockIdx.x < 128 ? 224 : 512);
  };
  uint32_t ctx = 0;

  if (warp < 8) {
    if (PF2 && warp == 0) {
#pragma unroll 1
      for (int i = 1; i <= NPF; i++) {
        spin_until(t0, PF2 + (i - 1) * PFD);
        if ((threadIdx.x | blockIdx.x >> 7 << 5) < 31) pf_l2(pfp + (threadIdx.x < 16 ? 64 : 64 * 1920) * i);
        __syncwarp();
      }
    }
    reg_inc<RC>();
    ctx = make_ctx();
    if (blockIdx.x >= 128) bar_sync(0, 512);
    else {
      {
        uint32_t Q[10][2], K[10][2], V[10][2];
        {
          {
            float aq[32], acc[88];
            CTXW();
            const int odd = (cta_pair() >> 3) & 1;
            const uint32_t rsb = mapa(sb, (blockIdx.x & 1) ^ 1);
            {
              const uint32_t aa = sb + (warp * 16 + (lane & 15)) * 128 + (((lane >> 4) ^ (lane & 7)) << 4);
              constexpr int NA = DEFER > 3 ? DEFER : 3;
              uint32_t a[NA][8];
              auto load_a = [&](int ks) {
                uint32_t(&r)[8] = a[ks % NA];
                mbar_wait(sb + B_FULL + 8 * (ks & 7), (ks >> 3) & 1);
                PTP(lead && (wg || !(ks & 3)), wg ? 60 + ks : 80 + (ks >> 2));
                ldsm4(r[0], r[1], r[2], r[3], (aa ^ ((ks & 1) * 64)) + o_px(ks)); ldsm4(r[4], r[5], r[6], r[7], (aa ^ ((ks & 1) * 64 + 32)) + o_px(ks));
              };
              auto mma_q = [&](int ks, int h) {
                uint32_t(&r)[8] = a[ks % NA];
                wgmma_rs_n64<0, 1>(aq, r[4 * h], r[4 * h + 1], r[4 * h + 2], r[4 * h + 3], mkdesc(SB + o_pw(ks) + h * 6144, 2048, 1024, 1), ks | h);
              };
              auto mma_step = [&](int ks, int h) {
                uint32_t(&r)[8] = a[ks % NA];
                wg_fence();
                wgmma_rs_n128<0, 1>(acc, r[4 * h], r[4 * h + 1], r[4 * h + 2], r[4 * h + 3], mkdesc(SB + o_pw(ks) + h * 6144 + 2048, 2048, 1024, 1), ks | h);
                if (ks < 20 - DEFER) mma_q(ks, h);
                wgmma_rs_n48<64, 1>(acc, r[4 * h], r[4 * h + 1], r[4 * h + 2], r[4 * h + 3], mkdesc(SB + o_pw(ks) + 12288 + h * 1536, 512, 256, 3), ks | h);
                wg_commit();
              };
              if (lead) PT(1 + wg);
              load_a(0);
#pragma unroll
              for (int ks = 0; ks < 20; ks++) {
                if (LEAD && ks == 20 - LEAD) bar_sync_p(wg == 0, NB_LEAD, 256);
                mma_step(ks, 0);
                if (ks < 19) load_a(ks + 1);
                else if (LEAD && !LATE) bar_arrive_p(wg, NB_LEAD, 256);
                mma_step(ks, 1);
                if (ks >= 1 && ks <= 16) {
                  wg_wait<2>();
                  mbar_arrive2_p(lead, sb + B_EMPTY + 8 * ((ks - 1) & 7), rsb + B_EMPTY + 8 * ((ks - 1) & 7));
                } else if (ks < 19 && ks + 2 - NA >= 16) wg_wait<2>();
              }
              if (LEAD && LATE == 1) bar_arrive_p(wg, NB_LEAD, 256);
              if (DEFER) {
                wg_fence();
#pragma unroll
                for (int i = 40 - 2 * DEFER; i < 40; i++) mma_q(i >> 1, i & 1);
                wg_commit();
              }
              if (LEAD && LATE == 2) bar_arrive_p(wg, NB_LEAD, 256);
              mbar_wait(sb + B_S15, 1);
              wg_wait<1>();
              mbar_arrive_p(tid == 0, sb + B_P1E);
              if (!DEFER) wg_wait<0>();
              fence_regs(acc);
              PTP(lead, 158 + wg);
            }
            if (odd) pack_qkv<1, 0>(aq, acc, Q, K, V); else pack_qkv<0, 0>(aq, acc, Q, K, V);
            if (warp == 7 && (blockIdx.x & 1)) {
              uint4* hp = g_halo + vb * 160 + lane;
              st_relaxed(hp, K[0][1], K[1][1], K[3][1], K[4][1]); st_relaxed(hp + 32, K[5][1], K[6][1], K[8][1], K[9][1]);
              st_relaxed(hp + 64, K[2][1], K[7][1], V[0][1], V[1][1]);
              st_relaxed(hp + 96, V[2][1], V[3][1], V[4][1], V[5][1]); st_relaxed(hp + 128, V[6][1], V[7][1], V[8][1], V[9][1]);
            }
            const uint32_t ho = sb + O_HALO + warp * 2560 + lane * 16;
            stsm4(ho, K[0][1], K[1][1], K[3][1], K[4][1]); stsm4(ho + 512, K[5][1], K[6][1], K[8][1], K[9][1]);
            stsm4(ho + 1024, K[2][1], K[7][1], V[0][1], V[1][1]);
            stsm4(ho + 1536, V[2][1], V[3][1], V[4][1], V[5][1]); stsm4(ho + 2048, V[6][1], V[7][1], V[8][1], V[9][1]);
            if (warp == 7) {
              if (!(blockIdx.x & 1)) {
                fence_async_smem();
                __syncwarp();
                if (elect_one())
                  asm volatile("cp.async.bulk.shared::cluster.shared::cta.mbarrier::complete_tx::bytes [%0], [%1], 2560, [%2];"
                               ::"r"(mapa(sb + O_HIN, 1)), "r"(sb + O_HALO + 7 * 2560), "r"(mapa(sb + B_HX0, 1)) : "memory");
              }
              __syncwarp();
            } else {
              __syncwarp();
              if (lane == 0) mbar_arrive(sb + B_HX + 8 + 8 * warp);
            }
            if (odd) pack_qkv<1, 1>(aq, acc, Q, K, V); else pack_qkv<0, 1>(aq, acc, Q, K, V);
#pragma unroll
            for (int f = 0; f < 10; f++) V[f][0] = movm(V[f][0]);
            wg_wait<0>();
            fence_regs(aq);
            PTPL(lead, 50 + wg);
            mbar_arrive2_p(lead, sb + B_S19, rsb + B_S19);
            if (odd) pack_qkv<1, 2>(aq, acc, Q, K, V); else pack_qkv<0, 2>(aq, acc, Q, K, V);
            if (lead) PT(52 + wg);
            if (wg) mbar_wait(sb + B_P1E, 0);
          }
          CTXW();
          uint32_t z = threadIdx.y;
          const bool gt0 = 2 * t > g, gt1 = 2 * t + 1 > g;
          const uint32_t pmask = (gt0 ? 0xFFFFu : 0u) | (gt1 ? 0xFFFF0000u : 0u);
          const uint32_t hs = warp ? O_HALO + (warp - 1) * 2560 : O_HIN, ha = sb + hs + lane * 16;
          const uint32_t va = sb + ((lane & 8) ? O_HALO + warp * 2560 : hs) + 1280 + (lane >> 4) * 128 + (lane & 7) * 16;
          uint32_t Qh[4][2], Kh[10], Vh[10];
          float c1[4][4] = {}, c2[4][4] = {}, c0[4][4] = {}, l[8][2], m[8], x[8];
#pragma unroll
          for (int j = 0; j < 4; j++) {
            const int fa = (j >> 1) * 5 + (j & 1) * 3, fh = (j >> 1) * 5 + 2;
            const bool mine = (j & 1) ? (t >= 2) : (t < 2);
            Qh[j][0] = mine ? Q[fh][0] : 0u; Qh[j][1] = mine ? Q[fh][1] : 0u;
            mma16(c1[j], Q[fa][0], Q[fa][1], Q[fa + 1][0], Q[fa + 1][1], K[fa][0], K[fa + 1][0]);
            mma16(c2[j], Q[fa][0], Q[fa][1], Q[fa + 1][0], Q[fa + 1][1], K[fa][1], K[fa + 1][1]);
            mma8(c1[j], Qh[j][0], Qh[j][1], K[fh][0]);
            mma8(c2[j], Qh[j][0], Qh[j][1], K[fh][1]);
          }
          if (lead) PT(54 + wg);
          mbar_wait(sb + (warp ? B_HX + 8 * warp : B_HX0), 0);
          if (lead) PT(56 + wg);
          ldsm4(Kh[0], Kh[1], Kh[3], Kh[4], ha); ldsm4(Kh[5], Kh[6], Kh[8], Kh[9], ha + 512);
          asm volatile("ldmatrix.sync.aligned.m8n8.x2.shared.b16 {%0,%1}, [%2];" : "=r"(Kh[2]), "=r"(Kh[7]) : "r"(ha + 1024) : "memory");
          auto load_v = [&]() {
#pragma unroll
            for (int i = 0; i < 5; i++) ldsm4t(Vh[2 * i], V[2 * i][1], Vh[2 * i + 1], V[2 * i + 1][1], va + i * 256);
          };
          if (VP == 1) load_v();
          const float C = 0.22360679774997896f * 1.4426950408889634f;
          auto max1 = [&](int r) { m[r] = fmaxf(l[r][0], l[r][1]); x[r] = __shfl_xor_sync(~0u, m[r], 1); };
          auto max2 = [&](int r) { m[r] = fmaxf(m[r], x[r]); x[r] = __shfl_xor_sync(~0u, m[r], 2); };
          auto exps = [&](int r) { const float mc = fmaxf(m[r], x[r]) * C; l[r][0] = ex2(fmaf(l[r][0], C, -mc)); l[r][1] = ex2(fmaf(l[r][1], C, -mc)); };
#pragma unroll
          for (int j = 0; j < 4; j++) { l[4 + j][0] = gt0 ? c1[j][2] : c2[j][2]; l[4 + j][1] = gt1 ? c1[j][3] : c2[j][3]; max1(4 + j); }
          if (SFM >> 0 & 1) sched_fence(z);
#pragma unroll
          for (int j = 0; j < 4; j++) {
            const int fa = (j >> 1) * 5 + (j & 1) * 3, fh = (j >> 1) * 5 + 2;
            mma16(c0[j], Q[fa][0], Q[fa][1], Q[fa + 1][0], Q[fa + 1][1], Kh[fa], Kh[fa + 1]);
            mma8(c0[j], Qh[j][0], Qh[j][1], Kh[fh]);
            max2(4 + j);
          }
          if (VP == 2) load_v();
          if (SFM >> 1 & 1) sched_fence(z);
          const bool have_halo = warp > 0 || mt > 0;
#pragma unroll
          for (int j = 0; j < 4; j++) {
            if (!have_halo) c0[j][0] = c0[j][1] = -INFINITY;
            l[j][0] = gt0 ? c0[j][0] : c1[j][0]; l[j][1] = gt1 ? c0[j][1] : c1[j][1];
            max1(j);
          }
          exps(4); exps(5);
          if (SFM >> 2 & 1) sched_fence(z);
#pragma unroll
          for (int j = 0; j < 4; j++) max2(j);
          exps(6); exps(7);
          if (VP == 4) load_v();
          if (SFM >> 3 & 1) sched_fence(z);
          if (VP == 5) load_v();
#pragma unroll
          for (int j = 0; j < 4; j++) exps(j);
          float o[12][4] = {}, sm[4][4] = {};
#pragma unroll
          for (int j = 0; j < 4; j++) {
            const int fa = (j >> 1) * 5 + (j & 1) * 3, fh = (j >> 1) * 5 + 2;
            const uint32_t pl = pack_bf16(l[j][0], l[j][1]), pu = pack_bf16(l[4 + j][0], l[4 + j][1]);
            const uint32_t a0 = pl & pmask, a2 = pl & ~pmask, a3 = pu & pmask, a5 = pu & ~pmask, z0 = z << (2 * j + 1), z1 = z << (2 * j + 2);
            mma8(sm[j], pl, pu, 0x3F803F80u);
#pragma unroll
            for (int q = 0; q < 3; q++) {
              const int f = q < 2 ? fa + q : fh;
              mma8(o[3 * j + q], a2, a3, V[f][0]);
              mma16(o[3 * j + q], a0, z0, z1, a5, Vh[f], V[f][1]);
            }
          }
          if (SFM >> 4 & 1) sched_fence(z);
          bar_arrive_p(wg == 0, NB_HALO + z, 256);
          uint32_t O[10][2];
#pragma unroll
          for (int j = 0; j < 4; j++) {
            const int fa = (j >> 1) * 5 + (j & 1) * 3, fh = (j >> 1) * 5 + 2;
            float r0, r1;
            asm("rcp.approx.ftz.f32 %0, %1;" : "=f"(r0) : "f"(sm[j][0]));
            asm("rcp.approx.ftz.f32 %0, %1;" : "=f"(r1) : "f"(sm[j][2]));
#pragma unroll
            for (int q = 0; q < 3; q++) {
              const int f = q < 2 ? fa + q : fh;
              const float* e = o[3 * j + q];
              const uint32_t o0 = pack_bf16(e[0] * r0, e[1] * r0), o1 = pack_bf16(e[2] * r1, e[3] * r1);
              if (q < 2 || !(j & 1)) { O[f][0] = o0; O[f][1] = o1; }
              else { O[f][0] = t >= 2 ? o0 : O[f][0]; O[f][1] = t >= 2 ? o1 : O[f][1]; }
            }
          }
          mbar_wait(sb + B_QD, 0);
          const uint32_t oa = sb + O_OST + (warp * 16 + (lane & 15)) * 160 + (lane >> 4) * 16;
#pragma unroll
          for (int i = 0; i < 5; i++) stsm4(oa + i * 32, O[2 * i][0], O[2 * i][1], O[2 * i + 1][0], O[2 * i + 1][1]);
        }
      }
      {
        CTXW();
        fence_async_smem();
        bar_arrive(NB_ATT, 288);
        if (lead) PT(58 + wg);
        const uint32_t abase = sb + (g & 1) * 4160 + 4 * (1023 - 4 - 8 * w - (g >> 1) + t);
        float acc[128];
        uint32_t a0[8], a1[8], a2[8], a3[8];
#pragma unroll 1
        for (int c = wg ^ 1; c < 5; c += 2) {
          const uint32_t ab = abase + o_h(c);
          const uint32_t db = __shfl_sync(~0u, ((SB + o_u(c) + UZ - 16) >> 4) | 0x10000u, 0);
          mbar_wait(sb + B_U + 8 * c, 0);
          load_pair<0>(a0, ab); load_pair<1>(a1, ab);
          load_pair<2>(a2, ab); load_pair<3>(a3, ab);
          if (lead) PT(85 + c);
          bar_sync(c ? NB_TOK + wg : NB_HALO, 256);
          fence_regs(acc);
          auto tok = [&](int p) { if (p == TOKP) bar_arrive_p(P3GO == 0 || c < 4, NB_TOK + (wg ^ 1), 256); };
          const uint32_t an = abase + o_h(c + 2);
          auto nxt = [&](auto P, uint32_t (&a)[8]) {
#pragma unroll
            for (int i = 0; i < 8; i++)
              asm volatile("{\n.reg .pred p;\nsetp.ne.b32 p, %2, 0;\n@p ld.shared.b32 %0, [%1];\n}" : "+r"(a[i]) : "r"(an + a_off(P, i)), "r"((int)(c < 3)));
          };
          mma_pair<0>(acc, a0, db);
          mma_pair<1>(acc, a1, db); wg_wait<1>();  load_pair<4>(a0, ab);
          if (lead) PT(90 + c);
          mma_pair<2>(acc, a2, db); wg_wait<1>();  load_pair<5>(a1, ab);
          mma_pair<3>(acc, a3, db); tok(3); wg_wait<1>();  load_pair<6>(a2, ab);
          mma_pair<4>(acc, a0, db); tok(4); wg_wait<1>();  load_pair<7>(a3, ab);
          mma_pair<5>(acc, a1, db); tok(5);
          mma_pair<6>(acc, a2, db); tok(6);
          mma_pair<7>(acc, a3, db);
          if (P3GO == 5) wg_wait<1>();
          if (P3GO == 3 || P3GO == 5) bar_arrive_p(c == 4, NB_TOK, 256);
          wg_wait<0>();
          if (P3GO == 4) bar_arrive_p(c == 4, NB_TOK, 256);
          fence_regs(acc);
          PTPL(lead, 95 + c);
          bar_sync(NB_RFREE + wg, 256);
          const uint32_t pb = sb + (w < 2 ? o_h(c) + w * 4160 : w == 2 ? o_u(c) : o_x(c)) + lane * 16;
          if (lane < 2 * w) sts128(pb, 0, 0, 0, 0);
#pragma unroll
          for (int q = 0; q < 8; q++) {
            uint32_t p[4];
#pragma unroll
            for (int i = 0; i < 4; i++) {
              const int nu = 4 * q + i;
              float v0 = acc[4 * nu], v1 = acc[4 * nu + 1];
              p[i] = pack_bf16(v0, v1);
              if (nu > 0) p[i] = hadd2(p[i], pack_bf16(acc[4 * nu - 2], acc[4 * nu - 1]));
            }
            stsm4t(pb + w * 32 + q * 512, p[0], p[1], p[2], p[3]);
            if (SPLIT4 && q == 3) bar_arrive_p(c == 4, NB_RFULL + 1, 256);
          }
          if (c < 4) bar_arrive(NB_RFULL + wg, 256);
          if (P3GO == 1 && c == 4) bar_arrive(NB_TOK, 256);
          if (lead) PT(140 + c);
        }
        if (wg) {
          if (YE == 1 && warp == 7 && elect_one()) flag_add(CNT_Y(16 + (vb >> 5)), 1);
          const int yb = (lds32(sb + O_EPOCH) & 1) * 640;
          conv_reduce<SPLIT4, 2>(sb, 4, tid - 128, yb + 512 + ((vb & 0x61) | (vb & 6) << 2 | (vb >> 2 & 6)), 14, 128);
          if (P3GO == 2) bar_arrive(NB_TOK, 256);
          if (!YE && warp == 7 && elect_one()) flag_add(CNT_Y(16 + (vb >> 5)), 1);
          if (MIXW) bar_arrive(12, 256);
          PTPL(lead, 45);
        }
      }
    }
    if (warp < 4) {
      CTXW();
      const uint32_t rsb = mapa(sb, (blockIdx.x & 1) ^ 1);
      const uint32_t ba = sb + O_BT + ((lane >> 4) * 8 + (lane & 7)) * 128 + (((2 * w + ((lane >> 3) & 1)) ^ ((lane & 1) << 2 | (lane >> 1 & 3))) << 4);
      mbar_wait(sb + B_P3F, 0);
      if (lead) PT(145);
      float acc[80];
#pragma unroll
      for (int ks = 0; ks < 10; ks++) {
        if (ks == NPRE) {
          if (NPRE) { wg_wait<0>(); mbar_arrive2_p(lead, sb + B_P3E + 8 * NPRE, rsb + B_P3E + 8 * NPRE); }
          bar_sync_p(blockIdx.x < 128, NB_TOK, 256);
        }
        PTP(lead, 146 + ks);
        const uint64_t da = mkdesc(SB + o_p3(ks), 1024, 1024, 1), db = mkdesc(SB + o_p3(ks) + 8192, 16, 1024, 1);
        wg_fence();
#pragma unroll
        for (int j = 0; j < 4; j++) wgmma_ss_n160<0, 1, 0>(acc, da + j * 128, db + j * 2, j | ks);
        wg_commit();
        if (ks < 9) mbar_wait(sb + B_P3F + 8 * (ks + 1), 0);
        if (ks >= 1 && ks <= 4 && ks != NPRE) { wg_wait<1>(); mbar_arrive2_p(lead, sb + B_P3E + 8 * ks, rsb + B_P3E + 8 * ks); }
      }
      wg_wait<0>();
      fence_regs(acc);
      PTPL(lead, 156);
#pragma unroll
      for (int i = 0; i < 10; i++) {
        stsm4t(ba + i * 2048, pack_bf16(acc[8 * i], acc[8 * i + 1]), pack_bf16(acc[8 * i + 2], acc[8 * i + 3]),
               pack_bf16(acc[8 * i + 4], acc[8 * i + 5]), pack_bf16(acc[8 * i + 6], acc[8 * i + 7]));
        if (i & 1) bar_arrive(1 + (i >> 1), 256);
      }
      if (lead) PT(157);
    }
  } else if (warp < 12) {
    reg_dec<RH>();
    const int hw = warp - 8;
    init_rest();
    ctx = __shfl_sync(~0u, make_ctx(), 0);
    const int yrow = (ctx & 0x61) | (ctx & 6) << 2 | (ctx >> 2 & 6);
    if (ctx < 65536) {
      CTXU();
      const int pr = hw >> 1, hh = hw & 1, tk = vb & 63, odd = (lane >> 2) & 1;
      const uint32_t sel0 = odd ? 0x7632 : 0x5410, sel1 = odd ? 0x5410 : 0x7632;
      const uint32_t in = sb + o_kin(pr), fb = sb + B_KF + 8 * pr, out = sb + O_Y + pr * 8192;
      const uint32_t oa = out + (2 * lane + odd) * 64 + (((3 - 2 * hh) ^ (lane & 3)) << 4), ia = in + hh * 2048 + lane * 4;
      auto fetch = [&](int c) {
        wait_until(t0, KT0 + c * KTD + ((((vb * 37) & 63) * KPH) >> 6));
        if (elect_one()) {
          const int kb = 2 * c + (vb >> 6);
          mbar_expect_tx(fb, 69 * 128);
          tma2(in, &M.k_ld, kb * 64, 32 * tk - 4, fb);
          tma2(in + 36 * 128, &M.v_ld, kb * 64, 32 * tk - 1, fb);
          PT(20 + c);
        }
        __syncwarp();
      };
      if (hh == 0) fetch(pr);
      const uint4* skp = (const uint4*)shift_k + (2 * pr + (vb >> 6)) * 32 + lane;
      uint4 sk = __ldg(skp), sk1 = __ldg(skp + 128), sk2 = __ldg(skp + (pr ? 0 : 256));
#pragma unroll 1
      for (int c = pr; c < 5; c += 2) {
        {
          mbar_wait(fb, (c >> 1) & 1);
          if (hh == 0 && lane == 0) PT(25 + c);
          uint32_t k[20], o[17];
#pragma unroll
          for (int i = 0; i < 20; i++) { k[i] = lds32(ia + i * 128); if (i >= 3) o[i - 3] = lds32(ia + (33 + i) * 128); }
          fence_async_smem();
          bar_sync(12 + pr, 64);
          if (hh == 0) {
            if (c < 3) fetch(c + 2);
            else if (lane == 0) mbar_arrive(sb + B_KVD + 8 * (c - 3));
          }
          const uint32_t w0 = prmt(sk.x, sk.z, 0x5410), w1 = prmt(sk.x, sk.z, 0x7632), w2 = prmt(sk.y, sk.w, 0x5410), w3 = prmt(sk.y, sk.w, 0x7632);
#pragma unroll
          for (int i = 0; i < 17; i++) o[i] = hmul2(hfma2(k[i + 3], w0, hfma2(k[i + 2], w1, hfma2(k[i + 1], w2, hmul2(k[i], w3)))), o[i]);
          sk = sk1; sk1 = sk2;
#pragma unroll
          for (int i = 0; i < 4; i++) {
            const int e = 8 * (i >> 1) + (i & 1);
            const uint32_t a = (oa ^ ((i >> 1) * 16)) + (i & 1) * 4096;
            sts128(a, prmt(o[7 + e], o[6 + e], sel0), prmt(o[5 + e], o[4 + e], sel0), prmt(o[3 + e], o[2 + e], sel0), prmt(o[1 + e], o[e], sel0));
            sts128(a ^ 64, prmt(o[7 + e], o[6 + e], sel1), prmt(o[5 + e], o[4 + e], sel1), prmt(o[3 + e], o[2 + e], sel1), prmt(o[1 + e], o[e], sel1));
          }
          bar_sync(12 + pr, 64);
        }
        if (hh) {
          fence_async_smem();
          if (elect_one()) {
            const int kb = 2 * c + (vb >> 6);
            tma3_store(&M.kv_st, 0, kb * 64, 63 - tk, out);
            tma3_store(&M.kv_st, 0, 640 + kb * 64, 63 - tk, out + 4096);
            bulk_commit(); bulk_wait_all();
            mbar_arrive(sb + (c == 4 ? B_KVD + 16 : B_KVS + 4 * (c & 2)));
            PTL(35 + c);
          }
          __syncwarp();
        }
      }
    }
    CTXU();
    const int g = lane >> 2, t = lane & 3, row = 8 * hw + g;
    const uint32_t go = (tb * 160 + row) * 80 + cb * 8 + t;
    const int yb = __shfl_sync(~0u, get_epoch() & 1, 0) * 640;
    uint4 T[10];
    if (hw == 2) {
      if (main_cta) { mbar_wait(sb + B_LAST, 0); mbar_wait(sb + B_S15, 1); if (QT) wait_until(t0, QT); }
      if (elect_one()) {
        mbar_expect_tx(sb + B_Q, 20480);
#pragma unroll
        for (int h = 0; h < 2; h++) tma2(sb + O_OST + h * 10240, &M.q_ld, cb * 64 + 32 * h, tb * 160, sb + B_Q);
      }
      __syncwarp();
    }
    mbar_wait(sb + B_Q, 0);
#pragma unroll
    for (int i = 0; i < 10; i++) lds128(sb + O_OST + (i & 1) * 10240 + (i >> 1) * 2048 + row * 64 + t * 16, T[i].x, T[i].y, T[i].z, T[i].w);
    fence_async_smem();
    bar_sync(12 + (hw >> 1), 64);
    if (!(tid & 63)) mbar_arrive(sb + B_QD);
    if (tid == 256) PTL(40);
    if (main_cta) {
      bar_arrive(NB_RFREE, 256);
      bar_arrive(NB_RFREE + 1, 256);
      auto red = [&](int c) {
        const int wg = (c & 1) ^ 1;
        conv_reduce<0, 2>(sb, c, tid - 256, yb + 128 * c + yrow, NB_RFULL + wg, 256);
        if (hw == 3 && elect_one()) flag_add(CNT_Y(4 * c + (vb >> 5)), 1);
        if (tid == 256) PTL(41 + c);
        if (c < 3) bar_arrive(NB_RFREE + wg, 256);
        if (c == 2) {
          bar_sync(NB_HELP, 128);
          if (tid == 256) { mbar_arrive(sb + B_P3E); mbar_arrive_remote(sb + B_P3E, rank ^ 1); }
        }
      };
      if (hw == 3) {
        mbar_wait(sb + B_KVD + 16, 0);
        if (elect_one()) { flag_release(CNT_KV(4 + (vb >> 6))); PTL(32); }
        __syncwarp();
      }
#pragma unroll 1
      for (int c = 0; c < 4; c++) red(c);
    }
    uint32_t G[5];
    mbar_wait(sb + B_G, 0);
#pragma unroll
    for (int q = 0; q < 5; q++) { uint16_t v; asm volatile("ld.shared.u16 %0, [%1];" : "=h"(v) : "r"(sb + O_GT + (32 * q + row) * 2)); G[q] = prmt(v, 0, 0x1010); }
#pragma unroll
    for (int i = 0; i < 10; i++) { const uint32_t c = G[i >> 1] ^ 0x80008000u; T[i] = make_uint4(hmul2(T[i].x, c), hmul2(T[i].y, c), hmul2(T[i].z, c), hmul2(T[i].w, c)); }
    if (main_cta) {
      if (SPLIT4) {
        conv_reduce<0, 1>(sb, 4, tid - 256, yb + 512 + yrow, NB_RFULL + 1, 256);
        if (YE == 2 && hw == 3 && elect_one()) flag_add(CNT_Y(16 + (vb >> 5)), 1);
      }
      if (MIXW) bar_sync(12, 256);
    }
#pragma unroll
    for (int h = 0; h < 2; h++) {
      mbar_wait_wd(sb + B_Y + 8 * h, 0, t0);
      if (tid == 256) PT(46);
      const uint32_t ya = sb + O_Y + h * 10240 + lane * 64 + ((hw ^ ((lane >> 1) & 3)) << 4);
      uint4 y[5];
      for (;;) {
        uint32_t m = ~0u;
#pragma unroll
        for (int q = 4; q >= 0; q--) {
          ldsm4t(y[q].x, y[q].y, y[q].z, y[q].w, ya + q * 2048);
          m = __vimin3_u16x2(__vimin3_u16x2(m, y[q].x, y[q].y), y[q].z, y[q].w);
          if (q == 4 && tb == 12) m = ~0u;
        }
        if (!__any_sync(~0u, (m & 0xFFFFu) == 0 || m < 0x10000u)) break;
#pragma unroll
        for (int q = 0; q < 5; q++)
          asm volatile("ld.relaxed.gpu.global.v4.b32 {%0,%1,%2,%3}, [%4];" : "=r"(y[q].x), "=r"(y[q].y), "=r"(y[q].z), "=r"(y[q].w)
                       : "l"((const uint4*)g_y2T + (yb + cb * 64 + 32 * h + lane) * 256 + tb * 20 + (q == 4 && tb == 12 ? 0 : 4 * q) + hw) : "memory");
#pragma unroll
        for (int q = 0; q < 5; q++) sts128(ya + q * 2048, y[q].x, y[q].y, y[q].z, y[q].w);
        __syncwarp();
        PTL(49);
      }
#pragma unroll
      for (int q = 0; q < 5; q++) {
        uint4& r = T[2 * q + h];
        r = make_uint4(hmul2(r.x, y[q].x), hmul2(r.y, y[q].y), hmul2(r.z, y[q].z), hmul2(r.w, y[q].w));
      }
    }
    const uint32_t so = sb + O_BT + row * 128 + ((t ^ ((g & 1) << 2 | g >> 1)) << 4);
    if (tid == 256) PTL(47);
#pragma unroll
    for (int q = 0; q < 5; q++) {
      const uint32_t c = hfma2(G[q], 0xBF80BF80u, 0x3F803F80u);
      bar_sync(1 + q, 256);
      if (q == 4) mbar_arrive_p(tid == 256, sb + B_DONE);
#pragma unroll
      for (int h = 0; h < 2; h++) {
        uint4 u;
        lds128((so ^ (h * 64)) + q * 4096, u.x, u.y, u.z, u.w);
        const uint4& r = T[2 * q + h];
        if (q < 4 || tb < 12) ((uint4*)outp)[go + q * 2560 + h * 4] = make_uint4(hfma2(u.x, c, r.x), hfma2(u.y, c, r.y), hfma2(u.z, c, r.z), hfma2(u.w, c, r.w));
      }
    }
  } else {
    reg_dec<RP>();
    uint4 gwv = make_uint4(0, 0, 0, 0);
    if (warp == 15) {
      const int p = cta_pair(), rank = blockIdx.x & 1;
      asm volatile("barrier.cluster.wait.aligned;" ::: "memory");
      if (blockIdx.x >= 128) bar_sync(0, 512);
      else {
#pragma unroll 1
        for (int ks = 1;; ks += 2) {
          mbar_wait(sb + B_EMPTY + 8 * (ks & 7), ((ks >> 3) & 1) ^ 1);
          spin_until(t0, PT1 + (ks - 1) * PTD);
          if (elect_one()) { mbar_expect_tx(sb + B_FULL + 8 * (ks & 7), WST); p1_load_w(ks, p, rank); PT(100 + ks); }
          if (ks == 19) break;
          const int kn = ks + 1;
          mbar_wait(sb + B_EMPTY + 8 * (kn & 7), ((kn >> 3) & 1) ^ 1);
          spin_until(t0, PT1 + ks * PTD - PTE);
          if (elect_one()) { mbar_expect_tx(sb + B_FULL + 8 * (kn & 7), 16384 + WST); p1_load_x(kn, p, rank); p1_load_w(kn, p, rank); PT(100 + kn); }
        }
        if (elect_one()) mbar_arrive(sb + B_LAST);
#pragma unroll 1
        for (int i = 0; i < 2; i++) {
          mbar_wait(sb + B_KVS + 8 * i, 0);
          if (elect_one()) { flag_release(CNT_KV(2 * i + (p >> 5))); PTL(30 + i); }
          __syncwarp();
        }
        mbar_wait(sb + B_S19, 0);
      }
    } else {
      if (threadIdx.x < 384 + 80) gwv = __ldg((const uint4*)gate_w + threadIdx.x - 384);
      init_rest();
    }
    ctx = __shfl_sync(~0u, make_ctx(), 0);
    CTXU();
    if (warp == 12) {
        unsigned epoch = 0;
      if (lane == 0) epoch = *(volatile unsigned*)(g_launch + 32 * vb) + 1;
      if (main_cta) { sts128(sb + O_GW + lane * 16, gwv.x, gwv.y, gwv.z, gwv.w); bar_arrive(NB_G, 96); }
      if (lane == 0) {
        if ((sb & 0xFFFFFF) != SB) __trap();
        sts32(sb + O_EPOCH, epoch);
        mbar_arrive(sb + B_EP);
#pragma unroll 1
        for (int i = 5; i < 11; i++) asm volatile("prefetch.tensormap [%0];" ::"l"(&M.x_par + i) : "memory");
      }
      if (main_cta && rank) {
#pragma unroll
        for (int f = 0; f < 5; f++) st_relaxed(g_halo + vb * 160 + lane + 32 * f, ~0u, ~0u, ~0u, ~0u);
      }
      __syncwarp();
      if (elect_one()) flag_release(g_launch + 32 * vb);
      __syncwarp();
      if (main_cta) {
        uint4 h0 = make_uint4(0, 0, 0, 0);
        if (lane < 5) {
          h0 = __ldg((const uint4*)(ssm_k + (size_t)(128 * lane + vb) * 2048));
          h0.x = prmt(pack_bf16(bf_lo(h0.x) + bf_lo(__ldg(ssm_D + 128 * lane + vb)), 0.f), h0.x, 0x7610);
        }
        epoch = __shfl_sync(~0u, epoch, 0);
        const int ze = lane & 7;
        const uint32_t za = sb + (lane < 8 ? o_u(ze) + UZ : lane < 24 ? o_h(ze) + (lane >> 4) * 4160 + 4096 : o_u(ze) + 512);
        const uint16_t* hp = ssm_k + (size_t)vb * 2048 + 8;
        const uint16_t* up = g_kvT + (size_t)vb * 2048;
        const unsigned* fp = CNT_KV(vb >> 6);
        sts128(sb + O_Y - 512 + lane * 16, 0, 0, 0, 0);
        if (HP0) {
#pragma unroll 1
          for (int c = 0; c < HPN; c++) { wait_until(t0, HP0 + c * HPD + ((((vb * 37) & 63) * HPD) >> 6)); pf_l2(hp + 128 * 2048 * c + lane * 64); }
        }
        mbar_wait(sb + B_LAST, 0);
        mbar_wait(sb + B_S13, 1);
#pragma unroll
        for (int c = 0; c < 5; c++) {
          if (c == 0 || c == 3) {
            mbar_wait(sb + B_KVD + (c ? 8 : 0), 0);
#pragma unroll
            for (int e = c; e < (c ? 5 : 3); e++) sts128(sb + o_u(e) + lane * 16, 0, 0, 0, 0);
            if (ze >= c && ze < (c ? 5 : 3)) sts128(za, h0.x, h0.y, h0.z, h0.w);
            fence_async_smem();
            __syncwarp();
            if (elect_one()) {
#pragma unroll
              for (int e = c; e < (c ? 5 : 3); e++) {
                mbar_expect_tx(sb + B_U + 8 * e, 3 * 4096 - 16);
                if (c || e < HN0) bulk_load(sb + o_u(e) + UZ + 16, hp + 128 * 2048 * e, 4080, sb + B_U + 8 * e);
              }
            }
          }
          if (c == 0 && lane == 0) PTL(34);
          if (!(c & 1)) { flag_wait(fp + 32 * c, 64 * epoch); __syncwarp(); }
          if (elect_one()) {
            bulk_load(sb + o_h(c), up + 128 * 2048 * c, 4096, sb + B_U + 8 * c);
            bulk_load(sb + o_h(c) + 4160, up + (640 + 128 * c) * 2048, 4096, sb + B_U + 8 * c);
            if (c == 1) {
#pragma unroll
              for (int e = HN0; e < 3; e++) bulk_load(sb + o_u(e) + UZ + 16, hp + 128 * 2048 * e, 4080, sb + B_U + 8 * e);
            }
            PTL(10 + c);
          }
        }
        if (ZW == 1) mbar_wait(sb + B_LAST, 1);
        if (ZW == 2) mbar_wait(sb + B_G, 0);
        if (ZW == 3) mbar_wait(sb + B_P3F + 32, 0);
        if (elect_one()) {
#pragma unroll 1
          for (int i = 0; i < ZD; i++) bulk_store(g_y2T + (size_t)((~epoch & 1) * 640 + 5 * vb) * 2048 + i * 256, sb + O_Y - 512, 512);
          bulk_commit(); bulk_wait_read();
          PTL(33);
        }
      }
    } else if (warp != 15) {
        const int r = warp - 13;
      if (main_cta) {
        if (rank && lane == 0) mbar_expect_tx(sb + B_HX0, 1280);
        const int t = lane & 3, grow = hg * 16 + (lane & 15);
        const uint32_t ga = sb + grow * 128 + (((4 * r + (lane >> 4)) ^ (lane & 7)) << 4);
        const uint32_t gp = sb + O_GW + 64 * r + 4 * t;
        float s0 = 0.f, s1 = 0.f;
        if (tid < 384 + 80) sts128(sb + O_GW + (tid - 384) * 16, gwv.x, gwv.y, gwv.z, gwv.w);
        bar_sync(NB_G, 96);
#pragma unroll 1
        for (int ks = 0; ks < 20; ks += 2) {
          uint32_t x[8], gw[4];
#pragma unroll
          for (int i = 0; i < 4; i++) gw[i] = lds32(gp + ks * 64 + i * 16);
          mbar_wait_wd(sb + B_FULL + 8 * (ks & 7), (ks >> 3) & 1, t0);
          if (r == 0 && lane == 0) PT(120 + ks);
          ldsm4(x[0], x[1], x[2], x[3], ga + o_px(ks)); ldsm4(x[4], x[5], x[6], x[7], (ga ^ 32) + o_px(ks));
#pragma unroll
          for (int i = 0; i < 8; i++) x[i] = hmul2(x[i], gw[i >> 1]);
          if (lane < 2) mbar_arrive(sb + B_EMPTY + 8 * (ks & 7) + 8 * lane + (x[0] & x[7] & threadIdx.y));
#pragma unroll
          for (int i = 0; i < 8; i += 4) {
            s0 += (bf_lo(x[i]) + bf_hi(x[i])) + (bf_lo(x[i + 2]) + bf_hi(x[i + 2]));
            s1 += (bf_lo(x[i + 1]) + bf_hi(x[i + 1])) + (bf_lo(x[i + 3]) + bf_hi(x[i + 3]));
          }
        }
        s0 += __shfl_xor_sync(~0u, s0, 1); s1 += __shfl_xor_sync(~0u, s1, 1);
        s0 += __shfl_xor_sync(~0u, s0, 2); s1 += __shfl_xor_sync(~0u, s1, 2);
        if (t < 2) sts32(sb + O_GP + r * 64 + (8 * t + (lane >> 2)) * 4, __float_as_uint(t ? s1 : s0));
        if (r == 0) bar_arrive(NB_G, 64);
        if (!rank) {
          uint4 d[3];
          if (mt > 0) {
            const uint4* hp = g_halo + (vb - 1) * 160 + r * 64 + lane;
            mbar_wait_wd(sb + B_EP, 0, t0);
            flag_wait_wd(g_launch + 32 * (vb - 1), lds32(sb + O_EPOCH), t0);
            mbar_wait_wd(sb + B_HX + 56, 0, t0);
            if (HDL) { const uint32_t t1 = clk(); spin_until(t1, HDL); }
            for (;;) {
              bool ok = true;
#pragma unroll
              for (int f = 0; f < 3; f++) {
                asm volatile("ld.relaxed.gpu.global.v4.b32 {%0,%1,%2,%3}, [%4];" : "=r"(d[f].x), "=r"(d[f].y), "=r"(d[f].z), "=r"(d[f].w) : "l"(hp + 32 * f) : "memory");
              }
#pragma unroll
              for (int f = 0; f < 3; f++) ok = ok && max(max(d[f].x, d[f].y), max(d[f].z, d[f].w)) != ~0u;
              if (__all_sync(~0u, ok)) break;
              if (clk() - t0 > 0x70000000u) __trap();
            }
          } else {
#pragma unroll
            for (int f = 0; f < 3; f++) d[f] = make_uint4(0, 0, 0, 0);
          }
#pragma unroll
          for (int f = 0; f < 3; f++) stsm4(sb + O_HIN + r * 1024 + f * 512 + lane * 16, d[f].x, d[f].y, d[f].z, d[f].w);
          __syncwarp();
          if (lane == 0) { mbar_arrive(sb + B_HX0); PTL(15 + r); }
        }
        if (r == 1) {
          bar_sync(NB_G, 64);
          if (lane < 16) {
            const uint32_t pa = sb + O_GP + lane * 4;
            const float z = __uint_as_float(lds32(pa)) + __uint_as_float(lds32(pa + 64));
            g_gate[2 * (mt * 128 + hg * 16 + lane) + par] = (uint16_t)pack_bf16(__fdividef(1.f, 1.f + __expf(-bf_lo(pack_bf16(z, 0.f)))), 0.f);
          }
          __syncwarp();
          if (elect_one()) flag_release(CNT_O(rt));
        }
      }
      mbar_wait_wd(sb + B_EP, 0, t0);
      const unsigned epoch = lds32(sb + O_EPOCH);
      if (main_cta) mbar_wait_wd(sb + B_P3E, 0, t0);
      flag_wait_wd(CNT_Y(2 * cb + r), 32 * epoch, t0);
      __syncwarp();
      if (elect_one()) {
        mbar_expect_tx(sb + B_Y + 8 * r, 10240);
        tma3(sb + O_Y + r * 10240, &M.y_ld, 0, (epoch & 1) * 640 + cb * 64 + 32 * r, tb * 5, sb + B_Y + 8 * r);
        PTL(17 + r);
      }
      __syncwarp();
      mbar_wait_wd(sb + B_DONE, 0, t0);
    } else {
      const unsigned epoch = get_epoch();
      if (main_cta) bar_sync(NB_ATT, 288); else mbar_wait(sb + B_QD, 0);
      if (elect_one()) {
        if (main_cta) {
          tma3_store(&M.o_st, hg * 80, par, mt * 128, sb + O_OST);
          bulk_commit(); bulk_wait_all();
          flag_release(CNT_O(rt));
          if (ZW == 1) mbar_arrive(sb + B_LAST);
        }
        PTL(3);
      }
      __syncwarp();
#pragma unroll 1
      for (int ks = 0; ks < 5; ks++)
        if (elect_one()) tma2(sb + o_p3(ks), &M.wo, cb * 64, ks * 64, sb + B_P3F + 8 * ks);
      if (lane < 4) flag_wait(CNT_O(8 * (lane & 1) + min(7, (80 * tb + 79 * (lane >> 1)) >> 7)), 16 * epoch);
      __syncwarp();
      if (elect_one()) {
        PTL(4);
        mbar_arrive_remote(sb + B_P3R, rank ^ 1);
        mbar_expect_tx(sb + B_G, 320);
        bulk_load(sb + O_GT, g_gate + tb * 160, 320, sb + B_G);
      }
      mbar_wait(sb + B_P3R, 0);
#pragma unroll 1
      for (int ks = 0; ks < 10; ks++) {
        if (ks > 5 || (ks == 5 && main_cta)) mbar_wait(sb + B_P3E + 8 * (ks - 5), 0);
        if (elect_one()) {
          PTP(ks >= 5, ks);
          tma2_mc(sb + o_p3(ks) + 8192 + rank * 10240, &M.o_ld, ks * 64, tb * 160 + rank * 80, sb + B_P3F + 8 * ks);
          if (ks >= 5) tma2(sb + o_p3(ks), &M.wo, cb * 64, ks * 64, sb + B_P3F + 8 * ks);
          mbar_expect_tx(sb + B_P3F + 8 * ks, P3S);
        }
      }
    }
  }
}

typedef CUresult (*PFN_enc)(CUtensorMap*, CUtensorMapDataType, cuuint32_t, void*, const cuuint64_t*, const cuuint64_t*, const cuuint32_t*,
                            const cuuint32_t*, CUtensorMapInterleave, CUtensorMapSwizzle, CUtensorMapL2promotion, CUtensorMapFloatOOBfill);
static void enc(PFN_enc f, CUtensorMap* m, const void* base, int rank, const cuuint64_t* dims, const cuuint64_t* strides, const cuuint32_t* box,
                CUtensorMapSwizzle sw) {
  const cuuint32_t es[5] = {1, 1, 1, 1, 1};
  f(m, CU_TENSOR_MAP_DATA_TYPE_BFLOAT16, rank, (void*)base, dims, strides, box, es, CU_TENSOR_MAP_INTERLEAVE_NONE, sw,
    CU_TENSOR_MAP_L2_PROMOTION_NONE, CU_TENSOR_MAP_FLOAT_OOB_FILL_NONE);
}

extern "C" void kernel_launch(void* const* d_in, const int* in_sizes, int n_in, void* d_out, int out_size) {
  (void)in_sizes; (void)n_in; (void)out_size;
  static PFN_enc f = nullptr;
  static void *kvT, *y2T, *o;
  if (!f) {
    void* p = nullptr;
    cudaDriverEntryPointQueryResult q;
    cudaGetDriverEntryPoint("cuTensorMapEncodeTiled", &p, cudaEnableDefault, &q);
    f = (PFN_enc)p;
    cudaGetSymbolAddress(&kvT, g_kvT); cudaGetSymbolAddress(&y2T, g_y2T); cudaGetSymbolAddress(&o, g_o);
    cudaFuncSetAttribute(fused_kernel, cudaFuncAttributeMaxDynamicSharedMemorySize, SMEM_BYTES);
  }
  Maps M;
  const CUtensorMapSwizzle S0 = CU_TENSOR_MAP_SWIZZLE_NONE, S32 = CU_TENSOR_MAP_SWIZZLE_32B, S64 = CU_TENSOR_MAP_SWIZZLE_64B, S128 = CU_TENSOR_MAP_SWIZZLE_128B;
  const cuuint64_t dpar[3] = {640, 2, 1024}, spar[2] = {1280, 2560};
  const cuuint64_t dw[3] = {640, 640, 3}, sw[2] = {3840, 1280};
  const cuuint64_t dnat[2] = {640, 2048}, snat[1] = {1280};
  const cuuint64_t dT2[3] = {32, 1280, 64}, sT[2] = {4096, 64};
  const cuuint64_t dwo[2] = {640, 640};
  { const cuuint32_t bx[3] = {64, 1, 128}; enc(f, &M.x_par, d_in[0], 3, dpar, spar, bx, S128); }
  { const cuuint32_t bx[3] = {64, 16, 3}; enc(f, &M.w_main, d_in[7], 3, dw, sw, bx, S128); }
  { const cuuint32_t bx[3] = {16, 16, 3}; enc(f, &M.w_tail, d_in[7], 3, dw, sw, bx, S32); }
  { const cuuint32_t bx[3] = {80, 1, 128}; enc(f, &M.o_st, o, 3, dpar, spar, bx, S0); }
  { const cuuint32_t bx[3] = {32, 64, 1}; enc(f, &M.kv_st, kvT, 3, dT2, sT, bx, S64); }
  { const cuuint32_t bx[3] = {32, 32, 5}; enc(f, &M.y_ld, y2T, 3, dT2, sT, bx, S64); }
  { const cuuint32_t bx[2] = {64, 36}; enc(f, &M.k_ld, d_in[1], 2, dnat, snat, bx, S0); }
  { const cuuint32_t bx[2] = {64, 33}; enc(f, &M.v_ld, d_in[2], 2, dnat, snat, bx, S0); }
  { const cuuint32_t bx[2] = {32, 160}; enc(f, &M.q_ld, d_in[0], 2, dnat, snat, bx, S0); }
  { const cuuint32_t bx[2] = {64, 64}; enc(f, &M.wo, d_in[8], 2, dwo, snat, bx, S128); }
  { const cuuint32_t bx[2] = {64, 80}; enc(f, &M.o_ld, o, 2, dnat, snat, bx, S128); }
  fused_kernel<<<130, 512, SMEM_BYTES, cudaStreamPerThread>>>((const uint16_t*)d_in[0], (const uint16_t*)d_in[7], (const uint16_t*)d_in[9], M, (const uint16_t*)d_in[3], (const uint16_t*)d_in[4], (const uint16_t*)d_in[5],
                                                              (uint16_t*)d_out);
}
```

```cpp
#include <cuda_runtime.h>
#include <cuda_bf16.h>
#include <cuda.h>
#include <stdint.h>

#define DEVI __device__ __forceinline__
#define PT1 100
#define PTD 460
#define PTE 200
#define PF2 0
#define NPF 1
#define PFD 0
#define DEFER 4
#define LATE 1
#define KPH KTD
#define TOKP 6
#define NPRE 1
#define P3GO 3
#define SPLIT4 1
#define MIXW 1
#define YE 2
#define HDL 0
#define ZD 40
#define BACKOFF 0
#define ZW 1
#define HP0 0
#define HPD 1500
#define HPN 2
#define HN0 1
#define QT 0
#define VP 5
#define SFM 16
#define RLATE 0
#define P3L 1
#define WOP 0
#define OSPLIT 1
#define KT0 1500
#define KTD 1000
#define RC 192
#define RH 96
#define RP 32
#define HOLD 750
#define LEAD 3

DEVI uint32_t smem_u32(const void* p) { return (uint32_t)__cvta_generic_to_shared(p); }
DEVI void wg_fence() { asm volatile("wgmma.fence.sync.aligned;" ::: "memory"); }
DEVI void wg_commit() { asm volatile("wgmma.commit_group.sync.aligned;" ::: "memory"); }
template <int N> DEVI void wg_wait() { asm volatile("wgmma.wait_group.sync.aligned %0;" ::"n"(N) : "memory"); }
template <int S> DEVI void fence_regs(float (&d)[S]) {
#pragma unroll
  for (int i = 0; i < S; i++) asm volatile("" : "+f"(d[i])::"memory");
}
DEVI uint64_t mkdesc(uint32_t addr, uint32_t lbo, uint32_t sbo, int swz) {
  return (uint64_t)((addr & 0x3FFFF) >> 4) | ((uint64_t)(lbo >> 4) << 16) | ((uint64_t)(sbo >> 4) << 32) | ((uint64_t)swz << 62);
}
DEVI void mbar_init(uint32_t bar, uint32_t cnt) { asm volatile("mbarrier.init.shared::cta.b64 [%0], %1;" ::"r"(bar), "r"(cnt) : "memory"); }
DEVI void mbar_expect_tx(uint32_t bar, uint32_t bytes) { asm volatile("mbarrier.arrive.expect_tx.shared::cta.b64 _, [%0], %1;" ::"r"(bar), "r"(bytes) : "memory"); }
DEVI void mbar_arrive(uint32_t bar) { asm volatile("mbarrier.arrive.shared::cta.b64 _, [%0];" ::"r"(bar) : "memory"); }
DEVI void mbar_wait(uint32_t bar, uint32_t parity) {
  asm volatile("{\n.reg .pred p;\nLAB_WAIT:\nmbarrier.try_wait.parity.shared::cta.b64 p, [%0], %1;\n@!p bra LAB_WAIT;\n}" ::"r"(bar), "r"(parity) : "memory");
}
DEVI void mbar_wait_wd(uint32_t bar, uint32_t parity, uint32_t t0) {
  asm volatile("{\n.reg .pred p;\n.reg .u32 c;\nLAB_WAIT:\nmbarrier.try_wait.parity.shared::cta.b64 p, [%0], %1;\n@p bra DONE;\nmov.u32 c, %%clock;\nsub.u32 c, c, %2;\nsetp.lt.u32 p, c, 0x70000000;\n@p bra LAB_WAIT;\ntrap;\nDONE:\n}" ::"r"(bar), "r"(parity), "r"(t0) : "memory");
}
DEVI void flag_wait(const unsigned* p, unsigned target) {
  asm volatile("{\n.reg .pred p;\n.reg .s32 v;\nLAB_WAIT:\nld.relaxed.gpu.global.u32 v, [%0];\nsub.s32 v, v, %1;\nsetp.lt.s32 p, v, 0;\n@p nanosleep.u32 %2;\n@p bra LAB_WAIT;\n}" ::"l"(p), "r"(target), "n"(BACKOFF) : "memory");
}
DEVI void flag_wait_wd(const unsigned* p, unsigned target, uint32_t t0) {
  asm volatile("{\n.reg .pred p;\n.reg .s32 v;\nLAB_WAIT:\nld.relaxed.gpu.global.u32 v, [%0];\nsub.s32 v, v, %1;\nsetp.ge.s32 p, v, 0;\n@p bra DONE;\nmov.u32 v, %%clock;\nsub.s32 v, v, %2;\nsetp.lt.u32 p, v, 0x70000000;\n@p bra LAB_WAIT;\ntrap;\nDONE:\n}" ::"l"(p), "r"(target), "r"(t0) : "memory");
}
DEVI void flag_add(unsigned* p, unsigned v) { asm volatile("red.relaxed.gpu.global.add.u32 [%0], %1;" ::"l"(p), "r"(v) : "memory"); }
DEVI void flag_release(unsigned* p) { asm volatile("fence.proxy.async;\nred.relaxed.gpu.global.add.u32 [%0], 1;" ::"l"(p) : "memory"); }
DEVI void fence_async_smem() { asm volatile("fence.proxy.async.shared::cta;" ::: "memory"); }
DEVI bool elect_one() { uint32_t p; asm volatile("{\n.reg .pred P;\nelect.sync _|P, 0xffffffff;\nselp.u32 %0, 1, 0, P;\n}" : "=r"(p)); return p; }
DEVI void bar_sync(int id, int n) { asm volatile("bar.sync %0, %1;" ::"r"(id), "r"(n) : "memory"); }
DEVI void bar_arrive(int id, int n) { asm volatile("bar.arrive %0, %1;" ::"r"(id), "r"(n) : "memory"); }
DEVI void tma2(uint32_t dst, const CUtensorMap* m, int c0, int c1, uint32_t bar) {
  asm volatile("cp.async.bulk.tensor.2d.shared::cluster.global.mbarrier::complete_tx::bytes [%0], [%1, {%3, %4}], [%2];" ::"r"(dst), "l"(m), "r"(bar), "r"(c0), "r"(c1) : "memory");
}
DEVI void tma3(uint32_t dst, const CUtensorMap* m, int c0, int c1, int c2, uint32_t bar) {
  asm volatile("cp.async.bulk.tensor.3d.shared::cluster.global.mbarrier::complete_tx::bytes [%0], [%1, {%3, %4, %5}], [%2];" ::"r"(dst), "l"(m), "r"(bar), "r"(c0), "r"(c1), "r"(c2) : "memory");
}
DEVI void tma3_mc(uint32_t dst, const CUtensorMap* m, int c0, int c1, int c2, uint32_t bar) {
  asm volatile("cp.async.bulk.tensor.3d.shared::cluster.global.mbarrier::complete_tx::bytes.multicast::cluster [%0], [%1, {%3, %4, %5}], [%2], %6;" ::"r"(dst), "l"(m), "r"(bar), "r"(c0), "r"(c1), "r"(c2), "h"((uint16_t)3) : "memory");
}
DEVI void tma2_mc(uint32_t dst, const CUtensorMap* m, int c0, int c1, uint32_t bar) {
  asm volatile("cp.async.bulk.tensor.2d.shared::cluster.global.mbarrier::complete_tx::bytes.multicast::cluster [%0], [%1, {%3, %4}], [%2], %5;" ::"r"(dst), "l"(m), "r"(bar), "r"(c0), "r"(c1), "h"((uint16_t)3) : "memory");
}
DEVI void mbar_arrive_remote(uint32_t bar, uint32_t cta) {
  asm volatile("{\n.reg .b32 ra;\nmapa.shared::cluster.u32 ra, %0, %1;\nmbarrier.arrive.shared::cluster.b64 _, [ra];\n}" ::"r"(bar), "r"(cta) : "memory");
}
DEVI void tma3_store(const CUtensorMap* m, int c0, int c1, int c2, uint32_t src) {
  asm volatile("cp.async.bulk.tensor.3d.global.shared::cta.bulk_group [%0, {%2, %3, %4}], [%1];" ::"l"(m), "r"(src), "r"(c0), "r"(c1), "r"(c2) : "memory");
}
DEVI void bulk_load(uint32_t dst, const void* src, uint32_t bytes, uint32_t bar) {
  asm volatile("cp.async.bulk.shared::cluster.global.mbarrier::complete_tx::bytes [%0], [%1], %2, [%3];" ::"r"(dst), "l"(src), "r"(bytes), "r"(bar) : "memory");
}
DEVI void bulk_store(void* dst, uint32_t src, uint32_t bytes) {
  asm volatile("cp.async.bulk.global.shared::cta.bulk_group [%0], [%1], %2;" ::"l"(dst), "r"(src), "r"(bytes) : "memory");
}
DEVI void pf_l2(const void* p) { asm volatile("prefetch.global.L2 [%0];" ::"l"(p)); }
template <int OFF> DEVI uint32_t ldg_v(const void* p) { uint32_t v; asm volatile("ld.volatile.global.b32 %0, [%1 + %2];" : "=r"(v) : "l"(p), "n"(OFF)); return v; }
DEVI void bulk_commit() { asm volatile("cp.async.bulk.commit_group;" ::: "memory"); }
DEVI void bulk_wait_all() { asm volatile("cp.async.bulk.wait_group 0;" ::: "memory"); }
DEVI void bulk_wait_read() { asm volatile("cp.async.bulk.wait_group.read 0;" ::: "memory"); }
template <int R> DEVI void reg_inc() { asm volatile("setmaxnreg.inc.sync.aligned.u32 %0;" ::"n"(R)); }
template <int R> DEVI void reg_dec() { asm volatile("setmaxnreg.dec.sync.aligned.u32 %0;" ::"n"(R)); }
DEVI uint32_t prmt(uint32_t a, uint32_t b, uint32_t s) { uint32_t r; asm("prmt.b32 %0,%1,%2,%3;" : "=r"(r) : "r"(a), "r"(b), "r"(s)); return r; }
DEVI uint32_t lds32(uint32_t a) { uint32_t r; asm volatile("ld.shared.b32 %0,[%1];" : "=r"(r) : "r"(a)); return r; }
DEVI void sts32(uint32_t a, uint32_t x) { asm volatile("st.shared.b32 [%0],%1;" ::"r"(a), "r"(x) : "memory"); }
DEVI void sts128(uint32_t a, uint32_t x, uint32_t y, uint32_t z, uint32_t w) { asm volatile("st.shared.v4.b32 [%0],{%1,%2,%3,%4};" ::"r"(a), "r"(x), "r"(y), "r"(z), "r"(w) : "memory"); }
DEVI void sts128v(uint32_t a, uint32_t x, uint32_t y, uint32_t z, uint32_t w) { asm volatile("st.volatile.shared.v4.b32 [%0],{%1,%2,%3,%4};" ::"r"(a), "r"(x), "r"(y), "r"(z), "r"(w) : "memory"); }
DEVI void lds128(uint32_t a, uint32_t& x, uint32_t& y, uint32_t& z, uint32_t& w) { asm volatile("ld.shared.v4.b32 {%0,%1,%2,%3},[%4];" : "=r"(x), "=r"(y), "=r"(z), "=r"(w) : "r"(a) : "memory"); }
DEVI void ldsm4(uint32_t& r0, uint32_t& r1, uint32_t& r2, uint32_t& r3, uint32_t addr) {
  asm volatile("ldmatrix.sync.aligned.m8n8.x4.shared.b16 {%0,%1,%2,%3}, [%4];" : "=r"(r0), "=r"(r1), "=r"(r2), "=r"(r3) : "r"(addr) : "memory");
}
DEVI void ldsm4t(uint32_t& r0, uint32_t& r1, uint32_t& r2, uint32_t& r3, uint32_t addr) {
  asm volatile("ldmatrix.sync.aligned.m8n8.x4.trans.shared.b16 {%0,%1,%2,%3}, [%4];" : "=r"(r0), "=r"(r1), "=r"(r2), "=r"(r3) : "r"(addr) : "memory");
}
DEVI void stsm4(uint32_t addr, uint32_t r0, uint32_t r1, uint32_t r2, uint32_t r3) {
  asm volatile("stmatrix.sync.aligned.m8n8.x4.shared.b16 [%0], {%1,%2,%3,%4};" ::"r"(addr), "r"(r0), "r"(r1), "r"(r2), "r"(r3) : "memory");
}
DEVI void stsm4t(uint32_t addr, uint32_t r0, uint32_t r1, uint32_t r2, uint32_t r3) {
  asm volatile("stmatrix.sync.aligned.m8n8.x4.trans.shared.b16 [%0], {%1,%2,%3,%4};" ::"r"(addr), "r"(r0), "r"(r1), "r"(r2), "r"(r3) : "memory");
}
DEVI uint32_t movm(uint32_t a) { uint32_t r; asm volatile("movmatrix.sync.aligned.m8n8.trans.b16 %0, %1;" : "=r"(r) : "r"(a)); return r; }
DEVI uint32_t pack_bf16(float lo, float hi) { uint32_t r; asm("cvt.rn.bf16x2.f32 %0, %1, %2;" : "=r"(r) : "f"(hi), "f"(lo)); return r; }
DEVI uint32_t hmul2(uint32_t a, uint32_t b) { uint32_t r; asm("mul.rn.bf16x2 %0,%1,%2;" : "=r"(r) : "r"(a), "r"(b)); return r; }
DEVI uint32_t hadd2(uint32_t a, uint32_t b) { uint32_t r; asm("add.rn.bf16x2 %0,%1,%2;" : "=r"(r) : "r"(a), "r"(b)); return r; }
DEVI float bf_lo(uint32_t a) { return __uint_as_float(prmt(a, 0, 0x1044)); }
DEVI float bf_hi(uint32_t a) { return __uint_as_float(a & 0xFFFF0000u); }
DEVI void mma16(float (&c)[4], uint32_t a0, uint32_t a1, uint32_t a2, uint32_t a3, uint32_t b0, uint32_t b1) {
  asm volatile("mma.sync.aligned.m16n8k16.row.col.f32.bf16.bf16.f32 {%0,%1,%2,%3},{%4,%5,%6,%7},{%8,%9},{%0,%1,%2,%3};"
      : "+f"(c[0]), "+f"(c[1]), "+f"(c[2]), "+f"(c[3]) : "r"(a0), "r"(a1), "r"(a2), "r"(a3), "r"(b0), "r"(b1));
}
DEVI void mma8(float (&c)[4], uint32_t a0, uint32_t a1, uint32_t b0) {
  asm volatile("mma.sync.aligned.m16n8k8.row.col.f32.bf16.bf16.f32 {%0,%1,%2,%3},{%4,%5},{%6},{%0,%1,%2,%3};"
      : "+f"(c[0]), "+f"(c[1]), "+f"(c[2]), "+f"(c[3]) : "r"(a0), "r"(a1), "r"(b0));
}
DEVI float ex2(float x) { float r; asm volatile("ex2.approx.ftz.f32 %0, %1;" : "=f"(r) : "f"(x)); return r; }

DEVI uint32_t clk() { uint32_t c; asm volatile("mov.u32 %0, %%clock;" : "=r"(c)); return c; }
DEVI void wait_until(uint32_t t0, int dt) { while ((int)(clk() - t0) < dt) __nanosleep(40); }
DEVI void spin_until(uint32_t t0, int dt) { while ((int)(clk() - t0) < dt) {} }
DEVI uint32_t hfma2(uint32_t a, uint32_t b, uint32_t c) { uint32_t r; asm("fma.rn.bf16x2 %0,%1,%2,%3;" : "=r"(r) : "r"(a), "r"(b), "r"(c)); return r; }
DEVI void bar_sync_p(int on, int id, int n) { asm volatile("{\n.reg .pred p;\nsetp.ne.b32 p, %0, 0;\n@p bar.sync %1, %2;\n}" ::"r"(on), "r"(id), "r"(n) : "memory"); }
DEVI void bar_arrive_p(int on, int id, int n) { asm volatile("{\n.reg .pred p;\nsetp.ne.b32 p, %0, 0;\n@p bar.arrive %1, %2;\n}" ::"r"(on), "r"(id), "r"(n) : "memory"); }
DEVI void mbar_arrive_p(int on, uint32_t bar) { asm volatile("{\n.reg .pred p;\nsetp.ne.b32 p, %1, 0;\n@p mbarrier.arrive.shared::cta.b64 _, [%0];\n}" ::"r"(bar), "r"(on) : "memory"); }
DEVI void mbar_arrive2_p(int on, uint32_t bar, uint32_t rbar) {
  asm volatile("{\n.reg .pred p;\nsetp.ne.b32 p, %2, 0;\n@p mbarrier.arrive.shared::cta.b64 _, [%0];\n@p mbarrier.arrive.shared::cluster.b64 _, [%1];\n}" ::"r"(bar), "r"(rbar), "r"(on) : "memory");
}
DEVI void st_relaxed(uint4* p, uint32_t x, uint32_t y, uint32_t z, uint32_t w) {
  asm volatile("st.relaxed.gpu.global.v4.b32 [%0], {%1,%2,%3,%4};" ::"l"(p), "r"(x), "r"(y), "r"(z), "r"(w) : "memory");
}
DEVI uint32_t mapa(uint32_t a, uint32_t cta) { uint32_t r; asm("mapa.shared::cluster.u32 %0, %1, %2;" : "=r"(r) : "r"(a), "r"(cta)); return r; }
DEVI void st_async128(uint32_t a, uint32_t x, uint32_t y, uint32_t z, uint32_t w, uint32_t bar) {
  asm volatile("st.async.weak.shared::cluster.mbarrier::complete_tx::bytes.v4.b32 [%0], {%1,%2,%3,%4}, [%5];" ::"r"(a), "r"(x), "r"(y), "r"(z), "r"(w), "r"(bar) : "memory");
}

template<int OFF, int TB, int S> __device__ __forceinline__ void wgmma_rs_n128(float (&d)[S], uint32_t a0, uint32_t a1, uint32_t a2, uint32_t a3, uint64_t db, int sd) {
  asm volatile("{\n.reg .pred p;\nsetp.ne.b32 p, %69, 0;\n"
    "wgmma.mma_async.sync.aligned.m64n128k16.f32.bf16.bf16 {%0, %1, %2, %3, %4, %5, %6, %7, %8, %9, %10, %11, %12, %13, %14, %15, %16, %17, %18, %19, %20, %21, %22, %23, %24, %25, %26, %27, %28, %29, %30, %31, %32, %33, %34, %35, %36, %37, %38, %39, %40, %41, %42, %43, %44, %45, %46, %47, %48, %49, %50, %51, %52, %53, %54, %55, %56, %57, %58, %59, %60, %61, %62, %63}, {%64, %65, %66, %67}, %68, p, 1, 1, %70;\n}\n"
    : "+f"(d[OFF+0]), "+f"(d[OFF+1]), "+f"(d[OFF+2]), "+f"(d[OFF+3]), "+f"(d[OFF+4]), "+f"(d[OFF+5]), "+f"(d[OFF+6]), "+f"(d[OFF+7]), "+f"(d[OFF+8]), "+f"(d[OFF+9]), "+f"(d[OFF+10]), "+f"(d[OFF+11]), "+f"(d[OFF+12]), "+f"(d[OFF+13]), "+f"(d[OFF+14]), "+f"(d[OFF+15]), "+f"(d[OFF+16]), "+f"(d[OFF+17]), "+f"(d[OFF+18]), "+f"(d[OFF+19]), "+f"(d[OFF+20]), "+f"(d[OFF+21]), "+f"(d[OFF+22]), "+f"(d[OFF+23]), "+f"(d[OFF+24]), "+f"(d[OFF+25]), "+f"(d[OFF+26]), "+f"(d[OFF+27]), "+f"(d[OFF+28]), "+f"(d[OFF+29]), "+f"(d[OFF+30]), "+f"(d[OFF+31]), "+f"(d[OFF+32]), "+f"(d[OFF+33]), "+f"(d[OFF+34]), "+f"(d[OFF+35]), "+f"(d[OFF+36]), "+f"(d[OFF+37]), "+f"(d[OFF+38]), "+f"(d[OFF+39]), "+f"(d[OFF+40]), "+f"(d[OFF+41]), "+f"(d[OFF+42]), "+f"(d[OFF+43]), "+f"(d[OFF+44]), "+f"(d[OFF+45]), "+f"(d[OFF+46]), "+f"(d[OFF+47]), "+f"(d[OFF+48]), "+f"(d[OFF+49]), "+f"(d[OFF+50]), "+f"(d[OFF+51]), "+f"(d[OFF+52]), "+f"(d[OFF+53]), "+f"(d[OFF+54]), "+f"(d[OFF+55]), "+f"(d[OFF+56]), "+f"(d[OFF+57]), "+f"(d[OFF+58]), "+f"(d[OFF+59]), "+f"(d[OFF+60]), "+f"(d[OFF+61]), "+f"(d[OFF+62]), "+f"(d[OFF+63]) : "r"(a0), "r"(a1), "r"(a2), "r"(a3), "l"(db), "r"(sd), "n"(TB));
}
template<int OFF, int TB, int S> __device__ __forceinline__ void wgmma_rs_n64(float (&d)[S], uint32_t a0, uint32_t a1, uint32_t a2, uint32_t a3, uint64_t db, int sd) {
  asm volatile("{\n.reg .pred p;\nsetp.ne.b32 p, %37, 0;\n"
    "wgmma.mma_async.sync.aligned.m64n64k16.f32.bf16.bf16 {%0, %1, %2, %3, %4, %5, %6, %7, %8, %9, %10, %11, %12, %13, %14, %15, %16, %17, %18, %19, %20, %21, %22, %23, %24, %25, %26, %27, %28, %29, %30, %31}, {%32, %33, %34, %35}, %36, p, 1, 1, %38;\n}\n"
    : "+f"(d[OFF+0]), "+f"(d[OFF+1]), "+f"(d[OFF+2]), "+f"(d[OFF+3]), "+f"(d[OFF+4]), "+f"(d[OFF+5]), "+f"(d[OFF+6]), "+f"(d[OFF+7]), "+f"(d[OFF+8]), "+f"(d[OFF+9]), "+f"(d[OFF+10]), "+f"(d[OFF+11]), "+f"(d[OFF+12]), "+f"(d[OFF+13]), "+f"(d[OFF+14]), "+f"(d[OFF+15]), "+f"(d[OFF+16]), "+f"(d[OFF+17]), "+f"(d[OFF+18]), "+f"(d[OFF+19]), "+f"(d[OFF+20]), "+f"(d[OFF+21]), "+f"(d[OFF+22]), "+f"(d[OFF+23]), "+f"(d[OFF+24]), "+f"(d[OFF+25]), "+f"(d[OFF+26]), "+f"(d[OFF+27]), "+f"(d[OFF+28]), "+f"(d[OFF+29]), "+f"(d[OFF+30]), "+f"(d[OFF+31]) : "r"(a0), "r"(a1), "r"(a2), "r"(a3), "l"(db), "r"(sd), "n"(TB));
}
template<int OFF, int TB, int S> __device__ __forceinline__ void wgmma_rs_n48(float (&d)[S], uint32_t a0, uint32_t a1, uint32_t a2, uint32_t a3, uint64_t db, int sd) {
  asm volatile("{\n.reg .pred p;\nsetp.ne.b32 p, %29, 0;\n"
    "wgmma.mma_async.sync.aligned.m64n48k16.f32.bf16.bf16 {%0, %1, %2, %3, %4, %5, %6, %7, %8, %9, %10, %11, %12, %13, %14, %15, %16, %17, %18, %19, %20, %21, %22, %23}, {%24, %25, %26, %27}, %28, p, 1, 1, %30;\n}\n"
    : "+f"(d[OFF+0]), "+f"(d[OFF+1]), "+f"(d[OFF+2]), "+f"(d[OFF+3]), "+f"(d[OFF+4]), "+f"(d[OFF+5]), "+f"(d[OFF+6]), "+f"(d[OFF+7]), "+f"(d[OFF+8]), "+f"(d[OFF+9]), "+f"(d[OFF+10]), "+f"(d[OFF+11]), "+f"(d[OFF+12]), "+f"(d[OFF+13]), "+f"(d[OFF+14]), "+f"(d[OFF+15]), "+f"(d[OFF+16]), "+f"(d[OFF+17]), "+f"(d[OFF+18]), "+f"(d[OFF+19]), "+f"(d[OFF+20]), "+f"(d[OFF+21]), "+f"(d[OFF+22]), "+f"(d[OFF+23]) : "r"(a0), "r"(a1), "r"(a2), "r"(a3), "l"(db), "r"(sd), "n"(TB));
}
template<int OFF, int TB, int S> __device__ __forceinline__ void wgmma_rs_n16(float (&d)[S], uint32_t a0, uint32_t a1, uint32_t a2, uint32_t a3, uint64_t db, int sd) {
  asm volatile("{\n.reg .pred p;\nsetp.ne.b32 p, %13, 0;\n"
    "wgmma.mma_async.sync.aligned.m64n16k16.f32.bf16.bf16 {%0, %1, %2, %3, %4, %5, %6, %7}, {%8, %9, %10, %11}, %12, p, 1, 1, %14;\n}\n"
    : "+f"(d[OFF+0]), "+f"(d[OFF+1]), "+f"(d[OFF+2]), "+f"(d[OFF+3]), "+f"(d[OFF+4]), "+f"(d[OFF+5]), "+f"(d[OFF+6]), "+f"(d[OFF+7]) : "r"(a0), "r"(a1), "r"(a2), "r"(a3), "l"(db), "r"(sd), "n"(TB));
}
template<int OFF, int TA, int TB, int S> __device__ __forceinline__ void wgmma_ss_n160(float (&d)[S], uint64_t da, uint64_t db, int sd) {
  asm volatile("{\n.reg .pred p;\nsetp.ne.b32 p, %82, 0;\n"
    "wgmma.mma_async.sync.aligned.m64n160k16.f32.bf16.bf16 {%0, %1, %2, %3, %4, %5, %6, %7, %8, %9, %10, %11, %12, %13, %14, %15, %16, %17, %18, %19, %20, %21, %22, %23, %24, %25, %26, %27, %28, %29, %30, %31, %32, %33, %34, %35, %36, %37, %38, %39, %40, %41, %42, %43, %44, %45, %46, %47, %48, %49, %50, %51, %52, %53, %54, %55, %56, %57, %58, %59, %60, %61, %62, %63, %64, %65, %66, %67, %68, %69, %70, %71, %72, %73, %74, %75, %76, %77, %78, %79}, %80, %81, p, 1, 1, %83, %84;\n}\n"
    : "+f"(d[OFF+0]), "+f"(d[OFF+1]), "+f"(d[OFF+2]), "+f"(d[OFF+3]), "+f"(d[OFF+4]), "+f"(d[OFF+5]), "+f"(d[OFF+6]), "+f"(d[OFF+7]), "+f"(d[OFF+8]), "+f"(d[OFF+9]), "+f"(d[OFF+10]), "+f"(d[OFF+11]), "+f"(d[OFF+12]), "+f"(d[OFF+13]), "+f"(d[OFF+14]), "+f"(d[OFF+15]), "+f"(d[OFF+16]), "+f"(d[OFF+17]), "+f"(d[OFF+18]), "+f"(d[OFF+19]), "+f"(d[OFF+20]), "+f"(d[OFF+21]), "+f"(d[OFF+22]), "+f"(d[OFF+23]), "+f"(d[OFF+24]), "+f"(d[OFF+25]), "+f"(d[OFF+26]), "+f"(d[OFF+27]), "+f"(d[OFF+28]), "+f"(d[OFF+29]), "+f"(d[OFF+30]), "+f"(d[OFF+31]), "+f"(d[OFF+32]), "+f"(d[OFF+33]), "+f"(d[OFF+34]), "+f"(d[OFF+35]), "+f"(d[OFF+36]), "+f"(d[OFF+37]), "+f"(d[OFF+38]), "+f"(d[OFF+39]), "+f"(d[OFF+40]), "+f"(d[OFF+41]), "+f"(d[OFF+42]), "+f"(d[OFF+43]), "+f"(d[OFF+44]), "+f"(d[OFF+45]), "+f"(d[OFF+46]), "+f"(d[OFF+47]), "+f"(d[OFF+48]), "+f"(d[OFF+49]), "+f"(d[OFF+50]), "+f"(d[OFF+51]), "+f"(d[OFF+52]), "+f"(d[OFF+53]), "+f"(d[OFF+54]), "+f"(d[OFF+55]), "+f"(d[OFF+56]), "+f"(d[OFF+57]), "+f"(d[OFF+58]), "+f"(d[OFF+59]), "+f"(d[OFF+60]), "+f"(d[OFF+61]), "+f"(d[OFF+62]), "+f"(d[OFF+63]), "+f"(d[OFF+64]), "+f"(d[OFF+65]), "+f"(d[OFF+66]), "+f"(d[OFF+67]), "+f"(d[OFF+68]), "+f"(d[OFF+69]), "+f"(d[OFF+70]), "+f"(d[OFF+71]), "+f"(d[OFF+72]), "+f"(d[OFF+73]), "+f"(d[OFF+74]), "+f"(d[OFF+75]), "+f"(d[OFF+76]), "+f"(d[OFF+77]), "+f"(d[OFF+78]), "+f"(d[OFF+79]) : "l"(da), "l"(db), "r"(sd), "n"(TA), "n"(TB));
}

__device__ __align__(1024) uint16_t g_kvT[2 * 640 * 2048];
__device__ __align__(1024) uint16_t g_y2T[2 * 640 * 2048];
__device__ __align__(1024) uint16_t g_o[2048 * 640];
__device__ __align__(1024) uint16_t g_gate[2080];
__device__ __align__(1024) uint4 g_halo[128 * 5 * 32];
__device__ __align__(1024) unsigned g_cnt[46 * 32];
__device__ __align__(1024) unsigned g_launch[132 * 32];
#define CNT_KV(i) (g_cnt + 32 * (i))
#define CNT_O(i) (g_cnt + 32 * (10 + (i)))
#define CNT_Y(i) (g_cnt + 32 * (26 + (i)))
#define PTL(i) do {} while (0)
#define PTPL(on, i) do {} while (0)
#define PT(i) do {} while (0)
#define PTP(on, i) do {} while (0)

constexpr uint32_t SB = 1024;
constexpr uint32_t STG = 23552, WST = 15360;
DEVI constexpr uint32_t o_px(int ks) { return (((ks >> 1) + 1) & 3) * 2 * STG; }
DEVI constexpr uint32_t o_pw(int ks) { return o_px(ks) + 16384 + (ks & 1) * WST; }
constexpr uint32_t O_HALO = 0, O_OST = STG;
constexpr uint32_t P3S = 28672;
constexpr uint32_t HC = 8320, UC = 4624, UZ = 528;
constexpr uint32_t O_H0 = 5 * P3S, O_U2 = O_H0 + 3 * HC, O_H3 = O_U2 + UC, O_U0 = O_H3 + 2 * HC;
DEVI constexpr uint32_t o_h(int c) { return O_H0 + c * HC + (c > 2 ? UC : 0); }
DEVI constexpr uint32_t o_u(int c) { return c == 2 ? O_U2 : O_U0 + (c > 2 ? c - 1 : c) * UC; }
constexpr uint32_t O_Y = 208896;
DEVI constexpr uint32_t o_x(int c) { return c < 2 ? O_Y + c * 5120 : O_U0 + (c & 1) * UC; }
constexpr uint32_t O_HIN = O_Y + 16384;
DEVI constexpr uint32_t o_kin(int c) { return ((O_U0 + 127) & ~127u) + ((c & 1) ? 0 : 73 * 128); }
DEVI constexpr uint32_t o_p3(int ks) { return (ks < 6 ? ks : ks - 6) * P3S; }
constexpr uint32_t O_BT = 4 * P3S;
constexpr uint32_t O_GT = O_Y + 20480, O_GW = O_GT + 320;
constexpr uint32_t O_BAR = 231040;
constexpr uint32_t B_FULL = O_BAR, B_EMPTY = O_BAR + 8 * 8, B_P3F = O_BAR + 8 * 16, B_P3R = O_BAR + 8 * 26, B_G = O_BAR + 8 * 27, B_U = O_BAR + 8 * 28,
                   B_KVD = O_BAR + 8 * 33, B_KF = O_BAR + 8 * 36, B_Y = O_BAR + 8 * 38, B_EP = O_BAR + 8 * 40, B_LAST = O_BAR + 8 * 41, B_DONE = O_BAR + 8 * 42,
                   B_P1E = O_BAR + 8 * 43, B_HX = O_BAR + 8 * 43  , B_P3E = O_BAR + 8 * 52, B_HX0 = O_BAR + 8 * 57, B_KVS = O_BAR + 8 * 58, B_QD = O_BAR + 8 * 60, B_Q = O_BAR + 8 * 51;
constexpr uint32_t B_S13 = B_EMPTY + 8 * 5, B_S15 = B_EMPTY + 8 * 7, B_S19 = B_EMPTY + 8 * 3;
constexpr uint32_t O_GP = O_BAR + 512, O_EPOCH = O_GW + 1280;
constexpr uint32_t SMEM_BYTES = 232448;
static_assert(O_U0 + 127 + 146 * 128 <= O_Y && o_kin(0) >= O_U0 + 2 * UC && O_EPOCH + 4 <= O_BAR && O_U0 >= 8 * STG, "smem map");
enum { NB_LEAD = 1, NB_HELP = 2, NB_HALO = 3, NB_ATT = 4, NB_G = 5, NB_TOK = 6, NB_RFULL = 8, NB_RFREE = 10 };

struct Maps { CUtensorMap x_par, w_main, w_tail, k_ld, v_ld, o_st, kv_st, wo, o_ld, y_ld, q_ld; };

template <int M> DEVI void conv_step(float (&acc)[128], uint32_t a0, uint32_t a1, uint32_t a2, uint32_t a3, uint32_t dl) {
  auto D = [&](int off) { return ((uint64_t)8 << 32) | (uint64_t)(uint32_t)(dl + off - 16 * M); };
  if constexpr (M == 0) wgmma_rs_n16<0, 0>(acc, a0, a1, a2, a3, D(0), 0);
  if constexpr (M <= 3) wgmma_rs_n48<8, 0>(acc, a0, a1, a2, a3, D(16), M == 0 ? 0 : 1);
  if constexpr (M <= 6) wgmma_rs_n48<32, 0>(acc, a0, a1, a2, a3, D(64), M == 0 ? 0 : 1);
  if constexpr (M <= 9) wgmma_rs_n48<56, 0>(acc, a0, a1, a2, a3, D(112), M == 0 ? 0 : 1);
  if constexpr (M <= 12) wgmma_rs_n48<80, 0>(acc, a0, a1, a2, a3, D(160), M == 0 ? 0 : 1);
  wgmma_rs_n48<104, 0>(acc, a0, a1, a2, a3, D(208), M == 0 ? 0 : 1);
}
DEVI constexpr int a_off(int P, int i) { return -4 * (64 * ((i & 4) ? 15 - P : P) + (i & 1) * 32 - (i & 2) * 2); }
template <int P> DEVI void load_pair(uint32_t (&a)[8], uint32_t ab) {
#pragma unroll
  for (int i = 0; i < 8; i++) a[i] = lds32(ab + a_off(P, i));
}
template <int P> DEVI void mma_pair(float (&acc)[128], uint32_t (&a)[8], uint32_t db) {
  wg_fence();
  conv_step<P>(acc, a[0], a[1], a[2], a[3], db);
  conv_step<15 - P>(acc, a[4], a[5], a[6], a[7], db);
  wg_commit();
}

template <int I0, int I1> DEVI void conv_reduce(uint32_t sb, int c, int ht, int chan, int bar, int nthr) {
  const uint32_t a0 = sb + o_h(c) + ht * 16, a2 = sb + o_u(c) + ht * 16, a3 = sb + o_x(c) + ht * 16;
  uint4* yp = (uint4*)(g_y2T + (size_t)chan * 2048) + ht;
#pragma unroll
  for (int i = I0; i < I1; i++) {
    uint4 p, q, r, s;
    if (i == I0) bar_sync(bar, nthr);
    lds128(a0 + i * 2048, p.x, p.y, p.z, p.w); lds128(a0 + 4160 + i * 2048, q.x, q.y, q.z, q.w);
    lds128(a2 + i * 2048, r.x, r.y, r.z, r.w); lds128(a3 + i * 2048, s.x, s.y, s.z, s.w);
    auto sum = [](uint32_t a, uint32_t b, uint32_t c, uint32_t d) { return hadd2(hadd2(hadd2(a, b), 0u), hadd2(c, d)) ^ 0x80008000u; };
    yp[i * 128] = make_uint4(sum(p.x, q.x, r.x, s.x), sum(p.y, q.y, r.y, s.y), sum(p.z, q.z, r.z, s.z), sum(p.w, q.w, r.w, s.w));
  }
}

template <int ODD, int PART> DEVI void pack_qkv(const float (&aq)[32], const float (&acc)[88], uint32_t (&Q)[10][2], uint32_t (&K)[10][2], uint32_t (&V)[10][2]) {
#pragma unroll
  for (int f = 0; f < 10; f++) {
    const bool tail = ODD ? (f < 2) : (f >= 8);
    const int fm = tail ? 0 : ODD ? f - 2 : f, ft = ODD ? f : f - 8;
    const int nq = tail ? 16 + ft : 0, nk = tail ? 18 + ft : fm, nv = tail ? 20 + ft : 8 + fm;
    if (PART == 0) {
      K[f][1] = pack_bf16(acc[4 * nk + 2], acc[4 * nk + 3]);
      V[f][1] = pack_bf16(acc[4 * nv + 2], acc[4 * nv + 3]);
    } else if (PART == 1) {
      V[f][0] = pack_bf16(acc[4 * nv], acc[4 * nv + 1]); K[f][0] = pack_bf16(acc[4 * nk], acc[4 * nk + 1]);
    } else if (tail) {
      Q[f][0] = pack_bf16(acc[4 * nq], acc[4 * nq + 1]); Q[f][1] = pack_bf16(acc[4 * nq + 2], acc[4 * nq + 3]);
    } else {
      Q[f][0] = pack_bf16(aq[4 * fm], aq[4 * fm + 1]); Q[f][1] = pack_bf16(aq[4 * fm + 2], aq[4 * fm + 3]);
    }
  }
}
DEVI void sched_fence(uint32_t& z) {
  asm volatile("{\n.reg .pred p;\nL:\nshr.u32 %0, %0, 1;\nsetp.ne.u32 p, %0, 0;\n@p bra.uni L;\n}" : "+r"(z));
}

DEVI int pair_of(int c) {
  const int lo = 32 + 8 * c, hi = c - 4 + ((max(c - 29, 0) * 37) >> 8);
  int p; asm("{\n.reg .pred q;\nsetp.lt.s32 q, %1, 4;\nselp.b32 %0, %2, %3, q;\n}" : "=r"(p) : "r"(c), "r"(lo), "r"(hi));
  return p;
}
DEVI uint32_t make_ctx() {
  int b; asm volatile("mov.u32 %0, %%ctaid.x;" : "=r"(b));
  b += clk() & threadIdx.y;
  const int p = pair_of(b >> 1);
  const int j = b < 128 ? 8 * (p & 7) + (p >> 3) : 64, cp = (j * 79) >> 10;
  return ((2 * p + (b & 1)) & 255) | (j - 13 * cp) << 8 | (2 * cp + (b & 1)) << 12 | (b >> 7) << 16;
}
#define CTX() asm volatile("" : "+r"(ctx)); CTXU()
#define CTXU() int tid; asm volatile("mov.u32 %0, %%tid.x;" : "=r"(tid)); \
  const int lane = tid & 31, vb = ctx & 255, hg = (ctx >> 4) & 7, rt = ctx & 15, par = (ctx >> 3) & 1, mt = ctx & 7, rank = ctx & 1, \
  tb = (ctx >> 8) & 15, cb = (ctx >> 12) & 15; const bool main_cta = ctx < 65536; \
  (void)tid; (void)lane; (void)vb; (void)hg; (void)rt; (void)par; (void)mt; (void)rank; (void)tb; (void)cb; (void)main_cta
#define CTXW() CTX(); const int wg = warp >> 2, w = warp & 3, g = lane >> 2, t = lane & 3; const bool lead = (tid & 127) == 0; \
  (void)wg; (void)w; (void)g; (void)t; (void)lead

__global__ void __cluster_dims__(2, 1, 1) __launch_bounds__(512, 1)
fused_kernel(const uint16_t* __restrict__ xq, const uint16_t* __restrict__ wqkv, const uint16_t* __restrict__ gate_w, const __grid_constant__ Maps M, const uint16_t* __restrict__ shift_k, const uint16_t* __restrict__ ssm_k, const uint16_t* __restrict__ ssm_D,
             uint16_t* __restrict__ outp) {
  extern __shared__ __align__(1024) uint8_t smem_raw[];
  const uint32_t sb = smem_u32(smem_raw);
  const uint32_t t0 = clk();
  auto get_epoch = [&]() { mbar_wait(sb + B_EP, 0); return lds32(sb + O_EPOCH); };

  auto p1_load_x = [&](int ks, int p, int rank) {
    tma3(sb + o_px(ks), &M.x_par, ks * 32, (p >> 2) & 1, (p & 3) * 256 + rank * 128, sb + B_FULL + 8 * (ks & 7));
  };
  auto p1_load_w = [&](int ks, int p, int rank) {
    const uint32_t st = sb + o_pw(ks), fb = sb + B_FULL + 8 * (ks & 7);
    tma3_mc(st + rank * 6144, &M.w_main, (p >> 3) * 80 + 2 * (p & 8), ks * 32 + rank * 16, 0, fb);
    tma3_mc(st + 12288 + rank * 1536, &M.w_tail, (p >> 3) * 80 + 8 * (~p & 8), ks * 32 + rank * 16, 0, fb);
  };
  auto cta_pair = [&]() { return pair_of(blockIdx.x >> 1); };

  const uint16_t* pfp = nullptr;
  if (threadIdx.x < 32) {
    const unsigned b = blockIdx.x, l = threadIdx.x;
    pfp = l < 16 ? xq + (16 * b + l) * 640 : wqkv + (15 * b + l - 16) * 64;
    if ((l | b >> 7 << 5) < 31) pf_l2(pfp);
  }
  const int warp = __shfl_sync(~0u, threadIdx.x >> 5, 0);
  if ((warp & 14) == 8) {
    if (elect_one()) {
#pragma unroll
      for (int s = 0; s < 8; s++) mbar_init(sb + O_BAR - 512 + 64 * warp + 8 * s, 5 * warp - 39);
      asm volatile("fence.mbarrier_init.release.cluster;" ::: "memory");
    }
    __syncwarp();
  }
  asm volatile("barrier.cluster.arrive.relaxed.aligned;" ::: "memory");
  if (warp == 8 && blockIdx.x < 128) {
    const int p = cta_pair(), rank = blockIdx.x & 1;
    if (elect_one()) { mbar_expect_tx(sb + B_FULL, 16384 + WST); p1_load_x(0, p, rank); }
    __syncwarp();
    asm volatile("barrier.cluster.wait.aligned;" ::: "memory");
    if (elect_one()) { p1_load_w(0, p, rank); PT(100); }
    __syncwarp();
  } else if (warp != 15) {
    asm volatile("barrier.cluster.wait.aligned;" ::: "memory");
    spin_until(t0, HOLD);
  }
  auto init_rest = [&]() {
    if (warp >= 11 && elect_one()) {
#pragma unroll
      for (int s = 0; s < 12; s++) mbar_init(sb + O_BAR + 128 - 11 * 96 + 96 * warp + 8 * s, warp == 14 ? 2 : 1);
      asm volatile("fence.mbarrier_init.release.cluster;" ::: "memory");
    }
    __syncwarp();
    bar_sync(0, blockIdx.x < 128 ? 224 : 512);
  };
  uint32_t ctx = 0;

  if (warp < 8) {
    if (PF2 && warp == 0) {
#pragma unroll 1
      for (int i = 1; i <= NPF; i++) {
        spin_until(t0, PF2 + (i - 1) * PFD);
        if ((threadIdx.x | blockIdx.x >> 7 << 5) < 31) pf_l2(pfp + (threadIdx.x < 16 ? 64 : 64 * 1920) * i);
        __syncwarp();
      }
    }
    reg_inc<RC>();
    ctx = make_ctx();
    if (blockIdx.x >= 128) bar_sync(0, 512);
    else {
      {
        uint32_t Q[10][2], K[10][2], V[10][2];
        {
          {
            float aq[32], acc[88];
            CTXW();
            const int odd = (cta_pair() >> 3) & 1;
            const uint32_t rsb = mapa(sb, (blockIdx.x & 1) ^ 1);
            {
              const uint32_t aa = sb + (warp * 16 + (lane & 15)) * 128 + (((lane >> 4) ^ (lane & 7)) << 4);
              constexpr int NA = DEFER > 3 ? DEFER : 3;
              uint32_t a[NA][8];
              auto load_a = [&](int ks) {
                uint32_t(&r)[8] = a[ks % NA];
                mbar_wait(sb + B_FULL + 8 * (ks & 7), (ks >> 3) & 1);
                PTP(lead && (wg || !(ks & 3)), wg ? 60 + ks : 80 + (ks >> 2));
                ldsm4(r[0], r[1], r[2], r[3], (aa ^ ((ks & 1) * 64)) + o_px(ks)); ldsm4(r[4], r[5], r[6], r[7], (aa ^ ((ks & 1) * 64 + 32)) + o_px(ks));
              };
              auto mma_q = [&](int ks, int h) {
                uint32_t(&r)[8] = a[ks % NA];
                wgmma_rs_n64<0, 1>(aq, r[4 * h], r[4 * h + 1], r[4 * h + 2], r[4 * h + 3], mkdesc(SB + o_pw(ks) + h * 6144, 2048, 1024, 1), ks | h);
              };
              auto mma_step = [&](int ks, int h) {
                uint32_t(&r)[8] = a[ks % NA];
                wg_fence();
                wgmma_rs_n128<0, 1>(acc, r[4 * h], r[4 * h + 1], r[4 * h + 2], r[4 * h + 3], mkdesc(SB + o_pw(ks) + h * 6144 + 2048, 2048, 1024, 1), ks | h);
                if (ks < 20 - DEFER) mma_q(ks, h);
                wgmma_rs_n48<64, 1>(acc, r[4 * h], r[4 * h + 1], r[4 * h + 2], r[4 * h + 3], mkdesc(SB + o_pw(ks) + 12288 + h * 1536, 512, 256, 3), ks | h);
                wg_commit();
              };
              if (lead) PT(1 + wg);
              load_a(0);
#pragma unroll
              for (int ks = 0; ks < 20; ks++) {
                if (LEAD && ks == 20 - LEAD) bar_sync_p(wg == 0, NB_LEAD, 256);
                mma_step(ks, 0);
                if (ks < 19) load_a(ks + 1);
                else if (LEAD && !LATE) bar_arrive_p(wg, NB_LEAD, 256);
                mma_step(ks, 1);
                if (ks >= 1 && ks <= 16) {
                  wg_wait<2>();
                  mbar_arrive2_p(lead, sb + B_EMPTY + 8 * ((ks - 1) & 7), rsb + B_EMPTY + 8 * ((ks - 1) & 7));
                } else if (ks < 19 && ks + 2 - NA >= 16) wg_wait<2>();
              }
              if (LEAD && LATE == 1) bar_arrive_p(wg, NB_LEAD, 256);
              if (DEFER) {
                wg_fence();
#pragma unroll
                for (int i = 40 - 2 * DEFER; i < 40; i++) mma_q(i >> 1, i & 1);
                wg_commit();
              }
              if (LEAD && LATE == 2) bar_arrive_p(wg, NB_LEAD, 256);
              mbar_wait(sb + B_S15, 1);
              wg_wait<1>();
              mbar_arrive_p(tid == 0, sb + B_P1E);
              if (!DEFER) wg_wait<0>();
              fence_regs(acc);
              PTP(lead, 158 + wg);
            }
            if (odd) pack_qkv<1, 0>(aq, acc, Q, K, V); else pack_qkv<0, 0>(aq, acc, Q, K, V);
            if (warp == 7 && (blockIdx.x & 1)) {
              uint4* hp = g_halo + vb * 160 + lane;
              st_relaxed(hp, K[0][1], K[1][1], K[3][1], K[4][1]); st_relaxed(hp + 32, K[5][1], K[6][1], K[8][1], K[9][1]);
              st_relaxed(hp + 64, K[2][1], K[7][1], V[0][1], V[1][1]);
              st_relaxed(hp + 96, V[2][1], V[3][1], V[4][1], V[5][1]); st_relaxed(hp + 128, V[6][1], V[7][1], V[8][1], V[9][1]);
            }
            const uint32_t ho = sb + O_HALO + warp * 2560 + lane * 16;
            stsm4(ho, K[0][1], K[1][1], K[3][1], K[4][1]); stsm4(ho + 512, K[5][1], K[6][1], K[8][1], K[9][1]);
            stsm4(ho + 1024, K[2][1], K[7][1], V[0][1], V[1][1]);
            stsm4(ho + 1536, V[2][1], V[3][1], V[4][1], V[5][1]); stsm4(ho + 2048, V[6][1], V[7][1], V[8][1], V[9][1]);
            if (warp == 7) {
              if (!(blockIdx.x & 1)) {
                fence_async_smem();
                __syncwarp();
                if (elect_one())
                  asm volatile("cp.async.bulk.shared::cluster.shared::cta.mbarrier::complete_tx::bytes [%0], [%1], 2560, [%2];"
                               ::"r"(mapa(sb + O_HIN, 1)), "r"(sb + O_HALO + 7 * 2560), "r"(mapa(sb + B_HX0, 1)) : "memory");
              }
              __syncwarp();
            } else {
              __syncwarp();
              if (lane == 0) mbar_arrive(sb + B_HX + 8 + 8 * warp);
            }
            if (odd) pack_qkv<1, 1>(aq, acc, Q, K, V); else pack_qkv<0, 1>(aq, acc, Q, K, V);
#pragma unroll
            for (int f = 0; f < 10; f++) V[f][0] = movm(V[f][0]);
            wg_wait<0>();
            fence_regs(aq);
            PTPL(lead, 50 + wg);
            mbar_arrive2_p(lead, sb + B_S19, rsb + B_S19);
            if (odd) pack_qkv<1, 2>(aq, acc, Q, K, V); else pack_qkv<0, 2>(aq, acc, Q, K, V);
            if (lead) PT(52 + wg);
            if (wg) mbar_wait(sb + B_P1E, 0);
          }
          CTXW();
          uint32_t z = threadIdx.y;
          const bool gt0 = 2 * t > g, gt1 = 2 * t + 1 > g;
          const uint32_t pmask = (gt0 ? 0xFFFFu : 0u) | (gt1 ? 0xFFFF0000u : 0u);
          const uint32_t hs = warp ? O_HALO + (warp - 1) * 2560 : O_HIN, ha = sb + hs + lane * 16;
          const uint32_t va = sb + ((lane & 8) ? O_HALO + warp * 2560 : hs) + 1280 + (lane >> 4) * 128 + (lane & 7) * 16;
          uint32_t Qh[4][2], Kh[10], Vh[10];
          float c1[4][4] = {}, c2[4][4] = {}, c0[4][4] = {}, l[8][2], m[8], x[8];
#pragma unroll
          for (int j = 0; j < 4; j++) {
            const int fa = (j >> 1) * 5 + (j & 1) * 3, fh = (j >> 1) * 5 + 2;
            const bool mine = (j & 1) ? (t >= 2) : (t < 2);
            Qh[j][0] = mine ? Q[fh][0] : 0u; Qh[j][1] = mine ? Q[fh][1] : 0u;
            mma16(c1[j], Q[fa][0], Q[fa][1], Q[fa + 1][0], Q[fa + 1][1], K[fa][0], K[fa + 1][0]);
            mma16(c2[j], Q[fa][0], Q[fa][1], Q[fa + 1][0], Q[fa + 1][1], K[fa][1], K[fa + 1][1]);
            mma8(c1[j], Qh[j][0], Qh[j][1], K[fh][0]);
            mma8(c2[j], Qh[j][0], Qh[j][1], K[fh][1]);
          }
          if (lead) PT(54 + wg);
          mbar_wait(sb + (warp ? B_HX + 8 * warp : B_HX0), 0);
          if (lead) PT(56 + wg);
          ldsm4(Kh[0], Kh[1], Kh[3], Kh[4], ha); ldsm4(Kh[5], Kh[6], Kh[8], Kh[9], ha + 512);
          asm volatile("ldmatrix.sync.aligned.m8n8.x2.shared.b16 {%0,%1}, [%2];" : "=r"(Kh[2]), "=r"(Kh[7]) : "r"(ha + 1024) : "memory");
          auto load_v = [&]() {
#pragma unroll
            for (int i = 0; i < 5; i++) ldsm4t(Vh[2 * i], V[2 * i][1], Vh[2 * i + 1], V[2 * i + 1][1], va + i * 256);
          };
          if (VP == 1) load_v();
          const float C = 0.22360679774997896f * 1.4426950408889634f;
          auto max1 = [&](int r) { m[r] = fmaxf(l[r][0], l[r][1]); x[r] = __shfl_xor_sync(~0u, m[r], 1); };
          auto max2 = [&](int r) { m[r] = fmaxf(m[r], x[r]); x[r] = __shfl_xor_sync(~0u, m[r], 2); };
          auto exps = [&](int r) { const float mc = fmaxf(m[r], x[r]) * C; l[r][0] = ex2(fmaf(l[r][0], C, -mc)); l[r][1] = ex2(fmaf(l[r][1], C, -mc)); };
#pragma unroll
          for (int j = 0; j < 4; j++) { l[4 + j][0] = gt0 ? c1[j][2] : c2[j][2]; l[4 + j][1] = gt1 ? c1[j][3] : c2[j][3]; max1(4 + j); }
          if (SFM >> 0 & 1) sched_fence(z);
#pragma unroll
          for (int j = 0; j < 4; j++) {
            const int fa = (j >> 1) * 5 + (j & 1) * 3, fh = (j >> 1) * 5 + 2;
            mma16(c0[j], Q[fa][0], Q[fa][1], Q[fa + 1][0], Q[fa + 1][1], Kh[fa], Kh[fa + 1]);
            mma8(c0[j], Qh[j][0], Qh[j][1], Kh[fh]);
            max2(4 + j);
          }
          if (VP == 2) load_v();
          if (SFM >> 1 & 1) sched_fence(z);
          const bool have_halo = warp > 0 || mt > 0;
#pragma unroll
          for (int j = 0; j < 4; j++) {
            if (!have_halo) c0[j][0] = c0[j][1] = -INFINITY;
            l[j][0] = gt0 ? c0[j][0] : c1[j][0]; l[j][1] = gt1 ? c0[j][1] : c1[j][1];
            max1(j);
          }
          exps(4); exps(5);
          if (SFM >> 2 & 1) sched_fence(z);
#pragma unroll
          for (int j = 0; j < 4; j++) max2(j);
          exps(6); exps(7);
          if (VP == 4) load_v();
          if (SFM >> 3 & 1) sched_fence(z);
          if (VP == 5) load_v();
#pragma unroll
          for (int j = 0; j < 4; j++) exps(j);
          float o[12][4] = {}, sm[4][4] = {};
#pragma unroll
          for (int j = 0; j < 4; j++) {
            const int fa = (j >> 1) * 5 + (j & 1) * 3, fh = (j >> 1) * 5 + 2;
            const uint32_t pl = pack_bf16(l[j][0], l[j][1]), pu = pack_bf16(l[4 + j][0], l[4 + j][1]);
            const uint32_t a0 = pl & pmask, a2 = pl & ~pmask, a3 = pu & pmask, a5 = pu & ~pmask, z0 = z << (2 * j + 1), z1 = z << (2 * j + 2);
            mma8(sm[j], pl, pu, 0x3F803F80u);
#pragma unroll
            for (int q = 0; q < 3; q++) {
              const int f = q < 2 ? fa + q : fh;
              mma8(o[3 * j + q], a2, a3, V[f][0]);
              mma16(o[3 * j + q], a0, z0, z1, a5, Vh[f], V[f][1]);
            }
          }
          if (SFM >> 4 & 1) sched_fence(z);
          bar_arrive_p(wg == 0, NB_HALO + z, 256);
          uint32_t O[10][2];
#pragma unroll
          for (int j = 0; j < 4; j++) {
            const int fa = (j >> 1) * 5 + (j & 1) * 3, fh = (j >> 1) * 5 + 2;
            float r0, r1;
            asm("rcp.approx.ftz.f32 %0, %1;" : "=f"(r0) : "f"(sm[j][0]));
            asm("rcp.approx.ftz.f32 %0, %1;" : "=f"(r1) : "f"(sm[j][2]));
#pragma unroll
            for (int q = 0; q < 3; q++) {
              const int f = q < 2 ? fa + q : fh;
              const float* e = o[3 * j + q];
              const uint32_t o0 = pack_bf16(e[0] * r0, e[1] * r0), o1 = pack_bf16(e[2] * r1, e[3] * r1);
              if (q < 2 || !(j & 1)) { O[f][0] = o0; O[f][1] = o1; }
              else { O[f][0] = t >= 2 ? o0 : O[f][0]; O[f][1] = t >= 2 ? o1 : O[f][1]; }
            }
          }
          mbar_wait(sb + B_QD, 0);
          const uint32_t oa = sb + O_OST + (warp * 16 + (lane & 15)) * 160 + (lane >> 4) * 16;
#pragma unroll
          for (int i = 0; i < 5; i++) stsm4(oa + i * 32, O[2 * i][0], O[2 * i][1], O[2 * i + 1][0], O[2 * i + 1][1]);
        }
      }
      {
        CTXW();
        fence_async_smem();
        if (OSPLIT) bar_arrive(wg ? NB_LEAD : NB_ATT, 160); else bar_arrive(NB_ATT, 288);
        if (lead) PT(58 + wg);
        const uint32_t abase = sb + (g & 1) * 4160 + 4 * (1023 - 4 - 8 * w - (g >> 1) + t);
        float acc[128];
        uint32_t a0[8], a1[8], a2[8], a3[8];
#pragma unroll 1
        for (int c = wg ^ 1; c < 5; c += 2) {
          const uint32_t ab = abase + o_h(c);
          const uint32_t db = __shfl_sync(~0u, ((SB + o_u(c) + UZ - 16) >> 4) | 0x10000u, 0);
          mbar_wait(sb + B_U + 8 * c, 0);
          load_pair<0>(a0, ab);
          if (P3L < 3) load_pair<1>(a1, ab);
          if (P3L < 2) load_pair<2>(a2, ab);
          if (P3L < 1) load_pair<3>(a3, ab);
          if (RLATE) bar_arrive_p(c >= 2, NB_RFULL + wg, 256);
          if (lead) PT(85 + c);
          bar_sync(c ? NB_TOK + wg : NB_HALO, 256);
          fence_regs(acc);
          auto tok = [&](int p) { if (p == TOKP) bar_arrive_p(P3GO == 0 || c < 4, NB_TOK + (wg ^ 1), 256); };
          mma_pair<0>(acc, a0, db);
          if (P3L == 3) load_pair<1>(a1, ab);
          if (P3L >= 2) load_pair<2>(a2, ab);
          if (P3L == 1) load_pair<3>(a3, ab);
          mma_pair<1>(acc, a1, db);
          if (P3L >= 2) {
            load_pair<3>(a3, ab);
            mma_pair<2>(acc, a2, db); wg_wait<2>();  load_pair<4>(a0, ab);
            mma_pair<3>(acc, a3, db); tok(3); wg_wait<2>();  load_pair<5>(a1, ab);
            mma_pair<4>(acc, a0, db); tok(4); wg_wait<2>();  load_pair<6>(a2, ab);
            mma_pair<5>(acc, a1, db); tok(5); wg_wait<2>();  load_pair<7>(a3, ab);
          } else {
            wg_wait<1>();  load_pair<4>(a0, ab);
            if (lead) PT(90 + c);
            mma_pair<2>(acc, a2, db); wg_wait<1>();  load_pair<5>(a1, ab);
            mma_pair<3>(acc, a3, db); tok(3); wg_wait<1>();  load_pair<6>(a2, ab);
            mma_pair<4>(acc, a0, db); tok(4); wg_wait<1>();  load_pair<7>(a3, ab);
            mma_pair<5>(acc, a1, db); tok(5);
          }
          mma_pair<6>(acc, a2, db); tok(6);
          mma_pair<7>(acc, a3, db);
          if (P3GO == 3) bar_arrive_p(c == 4, NB_TOK, 256);
          wg_wait<0>();
          if (P3GO == 4) bar_arrive_p(c == 4, NB_TOK, 256);
          fence_regs(acc);
          PTPL(lead, 95 + c);
          bar_sync(NB_RFREE + wg, 256);
          const uint32_t pb = sb + (w < 2 ? o_h(c) + w * 4160 : w == 2 ? o_u(c) : o_x(c)) + lane * 16;
          if (lane < 2 * w) sts128(pb, 0, 0, 0, 0);
#pragma unroll
          for (int q = 0; q < 8; q++) {
            uint32_t p[4];
#pragma unroll
            for (int i = 0; i < 4; i++) {
              const int nu = 4 * q + i;
              float v0 = acc[4 * nu], v1 = acc[4 * nu + 1];
              p[i] = pack_bf16(v0, v1);
              if (nu > 0) p[i] = hadd2(p[i], pack_bf16(acc[4 * nu - 2], acc[4 * nu - 1]));
            }
            stsm4t(pb + w * 32 + q * 512, p[0], p[1], p[2], p[3]);
            if (SPLIT4 && q == 3) bar_arrive_p(c == 4, NB_RFULL + 1, 256);
          }
          if (RLATE ? c == 3 : c < 4) bar_arrive(NB_RFULL + wg, 256);
          if (P3GO == 1 && c == 4) bar_arrive(NB_TOK, 256);
          if (lead) PT(140 + c);
        }
        if (wg) {
          if (YE == 1 && warp == 7 && elect_one()) flag_add(CNT_Y(16 + (vb >> 5)), 1);
          const int yb = (lds32(sb + O_EPOCH) & 1) * 640;
          conv_reduce<SPLIT4, 2>(sb, 4, tid - 128, yb + 512 + ((vb & 0x61) | (vb & 6) << 2 | (vb >> 2 & 6)), 14, 128);
          if (P3GO == 2) bar_arrive(NB_TOK, 256);
          if (!YE && warp == 7 && elect_one()) flag_add(CNT_Y(16 + (vb >> 5)), 1);
          if (MIXW) bar_arrive(12, 256);
          PTPL(lead, 45);
        }
      }
    }
    if (warp < 4) {
      CTXW();
      const uint32_t rsb = mapa(sb, (blockIdx.x & 1) ^ 1);
      const uint32_t ba = sb + O_BT + ((lane >> 4) * 8 + (lane & 7)) * 128 + (((2 * w + ((lane >> 3) & 1)) ^ ((lane & 1) << 2 | (lane >> 1 & 3))) << 4);
      mbar_wait(sb + B_P3F, 0);
      if (lead) PT(145);
      float acc[80];
#pragma unroll
      for (int ks = 0; ks < 10; ks++) {
        if (ks == NPRE) {
          if (NPRE) { wg_wait<0>(); mbar_arrive2_p(lead, sb + B_P3E + 8 * NPRE, rsb + B_P3E + 8 * NPRE); }
          bar_sync_p(blockIdx.x < 128, NB_TOK, 256);
        }
        PTP(lead, 146 + ks);
        const uint64_t da = mkdesc(SB + o_p3(ks), 1024, 1024, 1), db = mkdesc(SB + o_p3(ks) + 8192, 16, 1024, 1);
        wg_fence();
#pragma unroll
        for (int j = 0; j < 4; j++) wgmma_ss_n160<0, 1, 0>(acc, da + j * 128, db + j * 2, j | ks);
        wg_commit();
        if (ks < 9) mbar_wait(sb + B_P3F + 8 * (ks + 1), 0);
        if (ks >= 1 && ks <= 4 && ks != NPRE) { wg_wait<1>(); mbar_arrive2_p(lead, sb + B_P3E + 8 * ks, rsb + B_P3E + 8 * ks); }
      }
      wg_wait<0>();
      fence_regs(acc);
      PTPL(lead, 156);
#pragma unroll
      for (int i = 0; i < 10; i++) {
        stsm4t(ba + i * 2048, pack_bf16(acc[8 * i], acc[8 * i + 1]), pack_bf16(acc[8 * i + 2], acc[8 * i + 3]),
               pack_bf16(acc[8 * i + 4], acc[8 * i + 5]), pack_bf16(acc[8 * i + 6], acc[8 * i + 7]));
        if (i & 1) bar_arrive(1 + (i >> 1), 256);
      }
      if (lead) PT(157);
    }
  } else if (warp < 12) {
    reg_dec<RH>();
    const int hw = warp - 8;
    init_rest();
    ctx = __shfl_sync(~0u, make_ctx(), 0);
    const int yrow = (ctx & 0x61) | (ctx & 6) << 2 | (ctx >> 2 & 6);
    if (ctx < 65536) {
      CTXU();
      const int pr = hw >> 1, hh = hw & 1, tk = vb & 63, odd = (lane >> 2) & 1;
      const uint32_t sel0 = odd ? 0x7632 : 0x5410, sel1 = odd ? 0x5410 : 0x7632;
      const uint32_t in = sb + o_kin(pr), fb = sb + B_KF + 8 * pr, out = sb + O_Y + pr * 8192;
      const uint32_t oa = out + (2 * lane + odd) * 64 + (((3 - 2 * hh) ^ (lane & 3)) << 4), ia = in + hh * 2048 + lane * 4;
      auto fetch = [&](int c) {
        wait_until(t0, KT0 + c * KTD + ((((vb * 37) & 63) * KPH) >> 6));
        if (elect_one()) {
          const int kb = 2 * c + (vb >> 6);
          mbar_expect_tx(fb, 69 * 128);
          tma2(in, &M.k_ld, kb * 64, 32 * tk - 4, fb);
          tma2(in + 36 * 128, &M.v_ld, kb * 64, 32 * tk - 1, fb);
          PT(20 + c);
        }
        __syncwarp();
      };
      if (hh == 0) fetch(pr);
      const uint4* skp = (const uint4*)shift_k + (2 * pr + (vb >> 6)) * 32 + lane;
      uint4 sk = __ldg(skp), sk1 = __ldg(skp + 128), sk2 = __ldg(skp + (pr ? 0 : 256));
#pragma unroll 1
      for (int c = pr; c < 5; c += 2) {
        {
          mbar_wait(fb, (c >> 1) & 1);
          if (hh == 0 && lane == 0) PT(25 + c);
          uint32_t k[20], o[17];
#pragma unroll
          for (int i = 0; i < 20; i++) { k[i] = lds32(ia + i * 128); if (i >= 3) o[i - 3] = lds32(ia + (33 + i) * 128); }
          fence_async_smem();
          bar_sync(12 + pr, 64);
          if (hh == 0) {
            if (c < 3) fetch(c + 2);
            else if (lane == 0) mbar_arrive(sb + B_KVD + 8 * (c - 3));
          }
          const uint32_t w0 = prmt(sk.x, sk.z, 0x5410), w1 = prmt(sk.x, sk.z, 0x7632), w2 = prmt(sk.y, sk.w, 0x5410), w3 = prmt(sk.y, sk.w, 0x7632);
#pragma unroll
          for (int i = 0; i < 17; i++) o[i] = hmul2(hfma2(k[i + 3], w0, hfma2(k[i + 2], w1, hfma2(k[i + 1], w2, hmul2(k[i], w3)))), o[i]);
          sk = sk1; sk1 = sk2;
#pragma unroll
          for (int i = 0; i < 4; i++) {
            const int e = 8 * (i >> 1) + (i & 1);
            const uint32_t a = (oa ^ ((i >> 1) * 16)) + (i & 1) * 4096;
            sts128(a, prmt(o[7 + e], o[6 + e], sel0), prmt(o[5 + e], o[4 + e], sel0), prmt(o[3 + e], o[2 + e], sel0), prmt(o[1 + e], o[e], sel0));
            sts128(a ^ 64, prmt(o[7 + e], o[6 + e], sel1), prmt(o[5 + e], o[4 + e], sel1), prmt(o[3 + e], o[2 + e], sel1), prmt(o[1 + e], o[e], sel1));
          }
          bar_sync(12 + pr, 64);
        }
        if (hh) {
          fence_async_smem();
          if (elect_one()) {
            const int kb = 2 * c + (vb >> 6);
            tma3_store(&M.kv_st, 0, kb * 64, 63 - tk, out);
            tma3_store(&M.kv_st, 0, 640 + kb * 64, 63 - tk, out + 4096);
            bulk_commit(); bulk_wait_all();
            mbar_arrive(sb + (c == 4 ? B_KVD + 16 : B_KVS + 4 * (c & 2)));
            PTL(35 + c);
          }
          __syncwarp();
        }
      }
    }
    CTXU();
    const int g = lane >> 2, t = lane & 3, row = 8 * hw + g;
    const uint32_t go = (tb * 160 + row) * 80 + cb * 8 + t;
    const int yb = __shfl_sync(~0u, get_epoch() & 1, 0) * 640;
    uint4 T[10];
    if (hw == 2) {
      if (main_cta) { mbar_wait(sb + B_LAST, 0); mbar_wait(sb + B_S15, 1); if (QT) wait_until(t0, QT); }
      if (elect_one()) {
        mbar_expect_tx(sb + B_Q, 20480);
#pragma unroll
        for (int h = 0; h < 2; h++) tma2(sb + O_OST + h * 10240, &M.q_ld, cb * 64 + 32 * h, tb * 160, sb + B_Q);
      }
      __syncwarp();
    }
    mbar_wait(sb + B_Q, 0);
#pragma unroll
    for (int i = 0; i < 10; i++) lds128(sb + O_OST + (i & 1) * 10240 + (i >> 1) * 2048 + row * 64 + t * 16, T[i].x, T[i].y, T[i].z, T[i].w);
    fence_async_smem();
    bar_sync(12 + (hw >> 1), 64);
    if (!(tid & 63)) mbar_arrive(sb + B_QD);
    if (tid == 256) PTL(40);
    if (main_cta) {
      bar_arrive(NB_RFREE, 256);
      bar_arrive(NB_RFREE + 1, 256);
      auto red = [&](int c) {
        const int wg = (c & 1) ^ 1;
        conv_reduce<0, 2>(sb, c, tid - 256, yb + 128 * c + yrow, NB_RFULL + wg, 256);
        if (hw == 3 && elect_one()) flag_add(CNT_Y(4 * c + (vb >> 5)), 1);
        if (tid == 256) PTL(41 + c);
        if (c < 3) bar_arrive(NB_RFREE + wg, 256);
        if (c == 2) {
          bar_sync(NB_HELP, 128);
          if (tid == 256) { mbar_arrive(sb + B_P3E); mbar_arrive_remote(sb + B_P3E, rank ^ 1); }
        }
      };
      if (hw == 3) {
        mbar_wait(sb + B_KVD + 16, 0);
        if (elect_one()) { flag_release(CNT_KV(4 + (vb >> 6))); PTL(32); }
        __syncwarp();
      }
#pragma unroll 1
      for (int c = 0; c < 4; c++) red(c);
    }
    uint32_t G[5];
    mbar_wait(sb + B_G, 0);
#pragma unroll
    for (int q = 0; q < 5; q++) { uint16_t v; asm volatile("ld.shared.u16 %0, [%1];" : "=h"(v) : "r"(sb + O_GT + (32 * q + row) * 2)); G[q] = prmt(v, 0, 0x1010); }
#pragma unroll
    for (int i = 0; i < 10; i++) { const uint32_t c = G[i >> 1] ^ 0x80008000u; T[i] = make_uint4(hmul2(T[i].x, c), hmul2(T[i].y, c), hmul2(T[i].z, c), hmul2(T[i].w, c)); }
    if (main_cta) {
      if (SPLIT4) {
        conv_reduce<0, 1>(sb, 4, tid - 256, yb + 512 + yrow, NB_RFULL + 1, 256);
        if (YE == 2 && hw == 3 && elect_one()) flag_add(CNT_Y(16 + (vb >> 5)), 1);
      }
      if (MIXW) bar_sync(12, 256);
    }
#pragma unroll
    for (int h = 0; h < 2; h++) {
      mbar_wait_wd(sb + B_Y + 8 * h, 0, t0);
      if (tid == 256) PT(46);
      const uint32_t ya = sb + O_Y + h * 10240 + lane * 64 + ((hw ^ ((lane >> 1) & 3)) << 4);
      uint4 y[5];
      for (;;) {
        uint32_t m = ~0u;
#pragma unroll
        for (int q = 4; q >= 0; q--) {
          ldsm4t(y[q].x, y[q].y, y[q].z, y[q].w, ya + q * 2048);
          m = __vimin3_u16x2(__vimin3_u16x2(m, y[q].x, y[q].y), y[q].z, y[q].w);
          if (q == 4 && tb == 12) m = ~0u;
        }
        if (!__any_sync(~0u, (m & 0xFFFFu) == 0 || m < 0x10000u)) break;
#pragma unroll
        for (int q = 0; q < 5; q++)
          asm volatile("ld.relaxed.gpu.global.v4.b32 {%0,%1,%2,%3}, [%4];" : "=r"(y[q].x), "=r"(y[q].y), "=r"(y[q].z), "=r"(y[q].w)
                       : "l"((const uint4*)g_y2T + (yb + cb * 64 + 32 * h + lane) * 256 + tb * 20 + (q == 4 && tb == 12 ? 0 : 4 * q) + hw) : "memory");
#pragma unroll
        for (int q = 0; q < 5; q++) sts128(ya + q * 2048, y[q].x, y[q].y, y[q].z, y[q].w);
        __syncwarp();
        PTL(49);
      }
#pragma unroll
      for (int q = 0; q < 5; q++) {
        uint4& r = T[2 * q + h];
        r = make_uint4(hmul2(r.x, y[q].x), hmul2(r.y, y[q].y), hmul2(r.z, y[q].z), hmul2(r.w, y[q].w));
      }
    }
    const uint32_t so = sb + O_BT + row * 128 + ((t ^ ((g & 1) << 2 | g >> 1)) << 4);
    if (tid == 256) PTL(47);
#pragma unroll
    for (int q = 0; q < 5; q++) {
      const uint32_t c = hfma2(G[q], 0xBF80BF80u, 0x3F803F80u);
      bar_sync(1 + q, 256);
      if (q == 4) mbar_arrive_p(tid == 256, sb + B_DONE);
#pragma unroll
      for (int h = 0; h < 2; h++) {
        uint4 u;
        lds128((so ^ (h * 64)) + q * 4096, u.x, u.y, u.z, u.w);
        const uint4& r = T[2 * q + h];
        if (q < 4 || tb < 12) ((uint4*)outp)[go + q * 2560 + h * 4] = make_uint4(hfma2(u.x, c, r.x), hfma2(u.y, c, r.y), hfma2(u.z, c, r.z), hfma2(u.w, c, r.w));
      }
    }
  } else {
    reg_dec<RP>();
    uint4 gwv = make_uint4(0, 0, 0, 0);
    if (warp == 15) {
      const int p = cta_pair(), rank = blockIdx.x & 1;
      asm volatile("barrier.cluster.wait.aligned;" ::: "memory");
      if (blockIdx.x >= 128) bar_sync(0, 512);
      else {
#pragma unroll 1
        for (int ks = 1;; ks += 2) {
          mbar_wait(sb + B_EMPTY + 8 * (ks & 7), ((ks >> 3) & 1) ^ 1);
          spin_until(t0, PT1 + (ks - 1) * PTD);
          if (elect_one()) { mbar_expect_tx(sb + B_FULL + 8 * (ks & 7), WST); p1_load_w(ks, p, rank); PT(100 + ks); }
          if (ks == 19) break;
          const int kn = ks + 1;
          mbar_wait(sb + B_EMPTY + 8 * (kn & 7), ((kn >> 3) & 1) ^ 1);
          spin_until(t0, PT1 + ks * PTD - PTE);
          if (elect_one()) { mbar_expect_tx(sb + B_FULL + 8 * (kn & 7), 16384 + WST); p1_load_x(kn, p, rank); p1_load_w(kn, p, rank); PT(100 + kn); }
        }
        if (elect_one()) mbar_arrive(sb + B_LAST);
#pragma unroll 1
        for (int i = 0; i < 2; i++) {
          mbar_wait(sb + B_KVS + 8 * i, 0);
          if (elect_one()) { flag_release(CNT_KV(2 * i + (p >> 5))); PTL(30 + i); }
          __syncwarp();
        }
        mbar_wait(sb + B_S19, 0);
      }
    } else {
      if (threadIdx.x < 384 + 80) gwv = __ldg((const uint4*)gate_w + threadIdx.x - 384);
      init_rest();
    }
    ctx = __shfl_sync(~0u, make_ctx(), 0);
    CTXU();
    if (warp == 12) {
        unsigned epoch = 0;
      if (lane == 0) epoch = *(volatile unsigned*)(g_launch + 32 * vb) + 1;
      if (main_cta) { sts128(sb + O_GW + lane * 16, gwv.x, gwv.y, gwv.z, gwv.w); bar_arrive(NB_G, 96); }
      if (lane == 0) {
        if ((sb & 0xFFFFFF) != SB) __trap();
        sts32(sb + O_EPOCH, epoch);
        mbar_arrive(sb + B_EP);
#pragma unroll 1
        for (int i = 5; i < 11; i++) asm volatile("prefetch.tensormap [%0];" ::"l"(&M.x_par + i) : "memory");
      }
      if (main_cta && rank) {
#pragma unroll
        for (int f = 0; f < 5; f++) st_relaxed(g_halo + vb * 160 + lane + 32 * f, ~0u, ~0u, ~0u, ~0u);
      }
      __syncwarp();
      if (elect_one()) flag_release(g_launch + 32 * vb);
      __syncwarp();
      if (main_cta) {
        uint4 h0 = make_uint4(0, 0, 0, 0);
        if (lane < 5) {
          h0 = __ldg((const uint4*)(ssm_k + (size_t)(128 * lane + vb) * 2048));
          h0.x = prmt(pack_bf16(bf_lo(h0.x) + bf_lo(__ldg(ssm_D + 128 * lane + vb)), 0.f), h0.x, 0x7610);
        }
        epoch = __shfl_sync(~0u, epoch, 0);
        const int ze = lane & 7;
        const uint32_t za = sb + (lane < 8 ? o_u(ze) + UZ : lane < 24 ? o_h(ze) + (lane >> 4) * 4160 + 4096 : o_u(ze) + 512);
        const uint16_t* hp = ssm_k + (size_t)vb * 2048 + 8;
        const uint16_t* up = g_kvT + (size_t)vb * 2048;
        const unsigned* fp = CNT_KV(vb >> 6);
        sts128(sb + O_Y - 512 + lane * 16, 0, 0, 0, 0);
        if (HP0) {
#pragma unroll 1
          for (int c = 0; c < HPN; c++) { wait_until(t0, HP0 + c * HPD + ((((vb * 37) & 63) * HPD) >> 6)); pf_l2(hp + 128 * 2048 * c + lane * 64); }
        }
        mbar_wait(sb + B_LAST, 0);
        mbar_wait(sb + B_S13, 1);
#pragma unroll
        for (int c = 0; c < 5; c++) {
          if (c == 0 || c == 3) {
            mbar_wait(sb + B_KVD + (c ? 8 : 0), 0);
#pragma unroll
            for (int e = c; e < (c ? 5 : 3); e++) sts128(sb + o_u(e) + lane * 16, 0, 0, 0, 0);
            if (ze >= c && ze < (c ? 5 : 3)) sts128(za, h0.x, h0.y, h0.z, h0.w);
            fence_async_smem();
            __syncwarp();
            if (elect_one()) {
#pragma unroll
              for (int e = c; e < (c ? 5 : 3); e++) {
                mbar_expect_tx(sb + B_U + 8 * e, 3 * 4096 - 16);
                if (c || e < HN0) bulk_load(sb + o_u(e) + UZ + 16, hp + 128 * 2048 * e, 4080, sb + B_U + 8 * e);
              }
            }
          }
          if (c == 0 && lane == 0) PTL(34);
          if (!(c & 1)) { flag_wait(fp + 32 * c, 64 * epoch); __syncwarp(); }
          if (elect_one()) {
            bulk_load(sb + o_h(c), up + 128 * 2048 * c, 4096, sb + B_U + 8 * c);
            bulk_load(sb + o_h(c) + 4160, up + (640 + 128 * c) * 2048, 4096, sb + B_U + 8 * c);
            if (c == 1) {
#pragma unroll
              for (int e = HN0; e < 3; e++) bulk_load(sb + o_u(e) + UZ + 16, hp + 128 * 2048 * e, 4080, sb + B_U + 8 * e);
            }
            PTL(10 + c);
          }
        }
        if (ZW == 1) mbar_wait(sb + B_LAST, 1);
        if (ZW == 2) mbar_wait(sb + B_G, 0);
        if (ZW == 3) mbar_wait(sb + B_P3F + 32, 0);
        if (elect_one()) {
#pragma unroll 1
          for (int i = 0; i < ZD; i++) bulk_store(g_y2T + (size_t)((~epoch & 1) * 640 + 5 * vb) * 2048 + i * 256, sb + O_Y - 512, 512);
          bulk_commit(); bulk_wait_read();
          PTL(33);
        }
      }
    } else if (warp != 15) {
        const int r = warp - 13;
      if (main_cta) {
        if (rank && lane == 0) mbar_expect_tx(sb + B_HX0, 1280);
        const int t = lane & 3, grow = hg * 16 + (lane & 15);
        const uint32_t ga = sb + grow * 128 + (((4 * r + (lane >> 4)) ^ (lane & 7)) << 4);
        const uint32_t gp = sb + O_GW + 64 * r + 4 * t;
        float s0 = 0.f, s1 = 0.f;
        if (tid < 384 + 80) sts128(sb + O_GW + (tid - 384) * 16, gwv.x, gwv.y, gwv.z, gwv.w);
        bar_sync(NB_G, 96);
#pragma unroll 1
        for (int ks = 0; ks < 20; ks += 2) {
          uint32_t x[8], gw[4];
#pragma unroll
          for (int i = 0; i < 4; i++) gw[i] = lds32(gp + ks * 64 + i * 16);
          mbar_wait_wd(sb + B_FULL + 8 * (ks & 7), (ks >> 3) & 1, t0);
          if (r == 0 && lane == 0) PT(120 + ks);
          ldsm4(x[0], x[1], x[2], x[3], ga + o_px(ks)); ldsm4(x[4], x[5], x[6], x[7], (ga ^ 32) + o_px(ks));
#pragma unroll
          for (int i = 0; i < 8; i++) x[i] = hmul2(x[i], gw[i >> 1]);
          if (lane < 2) mbar_arrive(sb + B_EMPTY + 8 * (ks & 7) + 8 * lane + (x[0] & x[7] & threadIdx.y));
#pragma unroll
          for (int i = 0; i < 8; i += 4) {
            s0 += (bf_lo(x[i]) + bf_hi(x[i])) + (bf_lo(x[i + 2]) + bf_hi(x[i + 2]));
            s1 += (bf_lo(x[i + 1]) + bf_hi(x[i + 1])) + (bf_lo(x[i + 3]) + bf_hi(x[i + 3]));
          }
        }
        s0 += __shfl_xor_sync(~0u, s0, 1); s1 += __shfl_xor_sync(~0u, s1, 1);
        s0 += __shfl_xor_sync(~0u, s0, 2); s1 += __shfl_xor_sync(~0u, s1, 2);
        if (t < 2) sts32(sb + O_GP + r * 64 + (8 * t + (lane >> 2)) * 4, __float_as_uint(t ? s1 : s0));
        if (r == 0) bar_arrive(NB_G, 64);
        if (!rank) {
          uint4 d[3];
          if (mt > 0) {
            const uint4* hp = g_halo + (vb - 1) * 160 + r * 64 + lane;
            mbar_wait_wd(sb + B_EP, 0, t0);
            flag_wait_wd(g_launch + 32 * (vb - 1), lds32(sb + O_EPOCH), t0);
            mbar_wait_wd(sb + B_HX + 56, 0, t0);
            if (HDL) { const uint32_t t1 = clk(); spin_until(t1, HDL); }
            for (;;) {
              bool ok = true;
#pragma unroll
              for (int f = 0; f < 3; f++) {
                asm volatile("ld.relaxed.gpu.global.v4.b32 {%0,%1,%2,%3}, [%4];" : "=r"(d[f].x), "=r"(d[f].y), "=r"(d[f].z), "=r"(d[f].w) : "l"(hp + 32 * f) : "memory");
              }
#pragma unroll
              for (int f = 0; f < 3; f++) ok = ok && max(max(d[f].x, d[f].y), max(d[f].z, d[f].w)) != ~0u;
              if (__all_sync(~0u, ok)) break;
              if (clk() - t0 > 0x70000000u) __trap();
            }
          } else {
#pragma unroll
            for (int f = 0; f < 3; f++) d[f] = make_uint4(0, 0, 0, 0);
          }
#pragma unroll
          for (int f = 0; f < 3; f++) stsm4(sb + O_HIN + r * 1024 + f * 512 + lane * 16, d[f].x, d[f].y, d[f].z, d[f].w);
          __syncwarp();
          if (lane == 0) { mbar_arrive(sb + B_HX0); PTL(15 + r); }
        }
        if (r == 1) {
          bar_sync(NB_G, 64);
          if (lane < 16) {
            const uint32_t pa = sb + O_GP + lane * 4;
            const float z = __uint_as_float(lds32(pa)) + __uint_as_float(lds32(pa + 64));
            g_gate[2 * (mt * 128 + hg * 16 + lane) + par] = (uint16_t)pack_bf16(__fdividef(1.f, 1.f + __expf(-bf_lo(pack_bf16(z, 0.f)))), 0.f);
          }
          __syncwarp();
          if (elect_one()) flag_release(CNT_O(rt));
        }
      }
      mbar_wait_wd(sb + B_EP, 0, t0);
      const unsigned epoch = lds32(sb + O_EPOCH);
      if (main_cta) mbar_wait_wd(sb + B_P3E, 0, t0);
      flag_wait_wd(CNT_Y(2 * cb + r), 32 * epoch, t0);
      __syncwarp();
      if (elect_one()) {
        mbar_expect_tx(sb + B_Y + 8 * r, 10240);
        tma3(sb + O_Y + r * 10240, &M.y_ld, 0, (epoch & 1) * 640 + cb * 64 + 32 * r, tb * 5, sb + B_Y + 8 * r);
        PTL(17 + r);
      }
      __syncwarp();
      mbar_wait_wd(sb + B_DONE, 0, t0);
    } else {
      const unsigned epoch = get_epoch();
      auto load_wo = [&]() {
#pragma unroll 1
        for (int ks = 0; ks < 5; ks++)
          if (elect_one()) tma2(sb + o_p3(ks), &M.wo, cb * 64, ks * 64, sb + B_P3F + 8 * ks);
      };
      if (main_cta) {
        if (OSPLIT) {
          bar_sync(NB_LEAD, 160);
          if (elect_one()) tma3_store(&M.o_st, hg * 80, par, mt * 128 + 64, sb + O_OST + 10240);
        }
        bar_sync(NB_ATT, OSPLIT ? 160 : 288);
        if (elect_one()) {
          if (!OSPLIT) tma3_store(&M.o_st, hg * 80, par, mt * 128 + 64, sb + O_OST + 10240);
          tma3_store(&M.o_st, hg * 80, par, mt * 128, sb + O_OST);
          bulk_commit(); bulk_wait_all();
        }
        __syncwarp();
        if (WOP == 1) load_wo();
        if (elect_one()) {
          flag_release(CNT_O(rt));
          if (ZW == 1) mbar_arrive(sb + B_LAST);
          PTL(3);
        }
        __syncwarp();
      } else mbar_wait(sb + B_QD, 0);
      if (WOP == 0 || (WOP == 1 && !main_cta)) load_wo();
      if (lane < 4) flag_wait(CNT_O(8 * (lane & 1) + min(7, (80 * tb + 79 * (lane >> 1)) >> 7)), 16 * epoch);
      __syncwarp();
      if (elect_one()) {
        PTL(4);
        mbar_arrive_remote(sb + B_P3R, rank ^ 1);
        mbar_expect_tx(sb + B_G, 320);
        bulk_load(sb + O_GT, g_gate + tb * 160, 320, sb + B_G);
      }
      mbar_wait(sb + B_P3R, 0);
#pragma unroll 1
      for (int ks = 0; ks < 10; ks++) {
        if (ks > 5 || (ks == 5 && main_cta)) mbar_wait(sb + B_P3E + 8 * (ks - 5), 0);
        if (elect_one()) {
          PTP(ks >= 5, ks);
          tma2_mc(sb + o_p3(ks) + 8192 + rank * 10240, &M.o_ld, ks * 64, tb * 160 + rank * 80, sb + B_P3F + 8 * ks);
          if (ks >= 5 || WOP == 2) tma2(sb + o_p3(ks), &M.wo, cb * 64, ks * 64, sb + B_P3F + 8 * ks);
          mbar_expect_tx(sb + B_P3F + 8 * ks, P3S);
        }
      }
    }
  }
}

typedef CUresult (*PFN_enc)(CUtensorMap*, CUtensorMapDataType, cuuint32_t, void*, const cuuint64_t*, const cuuint64_t*, const cuuint32_t*,
                            const cuuint32_t*, CUtensorMapInterleave, CUtensorMapSwizzle, CUtensorMapL2promotion, CUtensorMapFloatOOBfill);
static void enc(PFN_enc f, CUtensorMap* m, const void* base, int rank, const cuuint64_t* dims, const cuuint64_t* strides, const cuuint32_t* box,
                CUtensorMapSwizzle sw) {
  const cuuint32_t es[5] = {1, 1, 1, 1, 1};
  f(m, CU_TENSOR_MAP_DATA_TYPE_BFLOAT16, rank, (void*)base, dims, strides, box, es, CU_TENSOR_MAP_INTERLEAVE_NONE, sw,
    CU_TENSOR_MAP_L2_PROMOTION_NONE, CU_TENSOR_MAP_FLOAT_OOB_FILL_NONE);
}

extern "C" void kernel_launch(void* const* d_in, const int* in_sizes, int n_in, void* d_out, int out_size) {
  (void)in_sizes; (void)n_in; (void)out_size;
  static PFN_enc f = nullptr;
  static void *kvT, *y2T, *o;
  if (!f) {
    void* p = nullptr;
    cudaDriverEntryPointQueryResult q;
    cudaGetDriverEntryPoint("cuTensorMapEncodeTiled", &p, cudaEnableDefault, &q);
    f = (PFN_enc)p;
    cudaGetSymbolAddress(&kvT, g_kvT); cudaGetSymbolAddress(&y2T, g_y2T); cudaGetSymbolAddress(&o, g_o);
    cudaFuncSetAttribute(fused_kernel, cudaFuncAttributeMaxDynamicSharedMemorySize, SMEM_BYTES);
  }
  Maps M;
  const CUtensorMapSwizzle S0 = CU_TENSOR_MAP_SWIZZLE_NONE, S32 = CU_TENSOR_MAP_SWIZZLE_32B, S64 = CU_TENSOR_MAP_SWIZZLE_64B, S128 = CU_TENSOR_MAP_SWIZZLE_128B;
  const cuuint64_t dpar[3] = {640, 2, 1024}, spar[2] = {1280, 2560};
  const cuuint64_t dw[3] = {640, 640, 3}, sw[2] = {3840, 1280};
  const cuuint64_t dnat[2] = {640, 2048}, snat[1] = {1280};
  const cuuint64_t dT2[3] = {32, 1280, 64}, sT[2] = {4096, 64};
  const cuuint64_t dwo[2] = {640, 640};
  { const cuuint32_t bx[3] = {64, 1, 128}; enc(f, &M.x_par, d_in[0], 3, dpar, spar, bx, S128); }
  { const cuuint32_t bx[3] = {64, 16, 3}; enc(f, &M.w_main, d_in[7], 3, dw, sw, bx, S128); }
  { const cuuint32_t bx[3] = {16, 16, 3}; enc(f, &M.w_tail, d_in[7], 3, dw, sw, bx, S32); }
  { const cuuint32_t bx[3] = {80, 1, 64}; enc(f, &M.o_st, o, 3, dpar, spar, bx, S0); }
  { const cuuint32_t bx[3] = {32, 64, 1}; enc(f, &M.kv_st, kvT, 3, dT2, sT, bx, S64); }
  { const cuuint32_t bx[3] = {32, 32, 5}; enc(f, &M.y_ld, y2T, 3, dT2, sT, bx, S64); }
  { const cuuint32_t bx[2] = {64, 36}; enc(f, &M.k_ld, d_in[1], 2, dnat, snat, bx, S0); }
  { const cuuint32_t bx[2] = {64, 33}; enc(f, &M.v_ld, d_in[2], 2, dnat, snat, bx, S0); }
  { const cuuint32_t bx[2] = {32, 160}; enc(f, &M.q_ld, d_in[0], 2, dnat, snat, bx, S0); }
  { const cuuint32_t bx[2] = {64, 64}; enc(f, &M.wo, d_in[8], 2, dwo, snat, bx, S128); }
  { const cuuint32_t bx[2] = {64, 80}; enc(f, &M.o_ld, o, 2, dnat, snat, bx, S128); }
  fused_kernel<<<130, 512, SMEM_BYTES, cudaStreamPerThread>>>((const uint16_t*)d_in[0], (const uint16_t*)d_in[7], (const uint16_t*)d_in[9], M, (const uint16_t*)d_in[3], (const uint16_t*)d_in[4], (const uint16_t*)d_in[5],
                                                              (uint16_t*)d_out);
}
```

```cpp
#include <cuda_runtime.h>
#include <cuda_bf16.h>
#include <cuda.h>
#include <stdint.h>

#define DEVI __device__ __forceinline__
#define PT1 200
#define PTD 460
#define PTE 150
#define PF2 600
#define NPF 1
#define PFD 0
#define DEFER 4
#define KPH KTD
#define NPRE 1
#define QW 0
#define KT0 1500
#define KTD 1000
#define RC 192
#define RH 96
#define RP 32
#define HOLD 750
#define LEAD 3

DEVI uint32_t smem_u32(const void* p) { return (uint32_t)__cvta_generic_to_shared(p); }
DEVI void wg_fence() { asm volatile("wgmma.fence.sync.aligned;" ::: "memory"); }
DEVI void wg_commit() { asm volatile("wgmma.commit_group.sync.aligned;" ::: "memory"); }
template <int N> DEVI void wg_wait() { asm volatile("wgmma.wait_group.sync.aligned %0;" ::"n"(N) : "memory"); }
template <int A = 0, int B = -1, int S> DEVI void fence_regs(float (&d)[S]) {
#pragma unroll
  for (int i = A; i < (B < 0 ? S : B); i++) asm volatile("" : "+f"(d[i])::"memory");
}
DEVI uint64_t mkdesc(uint32_t addr, uint32_t lbo, uint32_t sbo, int swz) {
  return (uint64_t)((addr & 0x3FFFF) >> 4) | ((uint64_t)(lbo >> 4) << 16) | ((uint64_t)(sbo >> 4) << 32) | ((uint64_t)swz << 62);
}
DEVI void mbar_init(uint32_t bar, uint32_t cnt) { asm volatile("mbarrier.init.shared::cta.b64 [%0], %1;" ::"r"(bar), "r"(cnt) : "memory"); }
DEVI void mbar_expect_tx(uint32_t bar, uint32_t bytes) { asm volatile("mbarrier.arrive.expect_tx.shared::cta.b64 _, [%0], %1;" ::"r"(bar), "r"(bytes) : "memory"); }
DEVI void mbar_arrive(uint32_t bar) { asm volatile("mbarrier.arrive.shared::cta.b64 _, [%0];" ::"r"(bar) : "memory"); }
DEVI void mbar_wait(uint32_t bar, uint32_t parity) {
  asm volatile("{\n.reg .pred p;\nLAB_WAIT:\nmbarrier.try_wait.parity.shared::cta.b64 p, [%0], %1;\n@!p bra LAB_WAIT;\n}" ::"r"(bar), "r"(parity) : "memory");
}
DEVI void mbar_wait_wd(uint32_t bar, uint32_t parity, uint32_t t0) {
  asm volatile("{\n.reg .pred p;\n.reg .u32 c;\nLAB_WAIT:\nmbarrier.try_wait.parity.shared::cta.b64 p, [%0], %1;\n@p bra DONE;\nmov.u32 c, %%clock;\nsub.u32 c, c, %2;\nsetp.lt.u32 p, c, 0x70000000;\n@p bra LAB_WAIT;\ntrap;\nDONE:\n}" ::"r"(bar), "r"(parity), "r"(t0) : "memory");
}
DEVI void flag_wait(const unsigned* p, unsigned target) {
  asm volatile("{\n.reg .pred p;\n.reg .s32 v;\nLAB_WAIT:\nld.relaxed.gpu.global.u32 v, [%0];\nsub.s32 v, v, %1;\nsetp.lt.s32 p, v, 0;\n@p bra LAB_WAIT;\n}" ::"l"(p), "r"(target) : "memory");
}
DEVI void flag_wait_wd(const unsigned* p, unsigned target, uint32_t t0) {
  asm volatile("{\n.reg .pred p;\n.reg .s32 v;\nLAB_WAIT:\nld.relaxed.gpu.global.u32 v, [%0];\nsub.s32 v, v, %1;\nsetp.ge.s32 p, v, 0;\n@p bra DONE;\nmov.u32 v, %%clock;\nsub.s32 v, v, %2;\nsetp.lt.u32 p, v, 0x70000000;\n@p bra LAB_WAIT;\ntrap;\nDONE:\n}" ::"l"(p), "r"(target), "r"(t0) : "memory");
}
DEVI void flag_add(unsigned* p, unsigned v) { asm volatile("red.relaxed.gpu.global.add.u32 [%0], %1;" ::"l"(p), "r"(v) : "memory"); }
DEVI void flag_release(unsigned* p) { asm volatile("fence.proxy.async;\nred.relaxed.gpu.global.add.u32 [%0], 1;" ::"l"(p) : "memory"); }
DEVI void fence_async_smem() { asm volatile("fence.proxy.async.shared::cta;" ::: "memory"); }
DEVI bool elect_one() { uint32_t p; asm volatile("{\n.reg .pred P;\nelect.sync _|P, 0xffffffff;\nselp.u32 %0, 1, 0, P;\n}" : "=r"(p)); return p; }
DEVI void bar_sync(int id, int n) { asm volatile("bar.sync %0, %1;" ::"r"(id), "r"(n) : "memory"); }
DEVI void bar_arrive(int id, int n) { asm volatile("bar.arrive %0, %1;" ::"r"(id), "r"(n) : "memory"); }
DEVI void tma2(uint32_t dst, const CUtensorMap* m, int c0, int c1, uint32_t bar) {
  asm volatile("cp.async.bulk.tensor.2d.shared::cluster.global.mbarrier::complete_tx::bytes [%0], [%1, {%3, %4}], [%2];" ::"r"(dst), "l"(m), "r"(bar), "r"(c0), "r"(c1) : "memory");
}
DEVI void tma3(uint32_t dst, const CUtensorMap* m, int c0, int c1, int c2, uint32_t bar) {
  asm volatile("cp.async.bulk.tensor.3d.shared::cluster.global.mbarrier::complete_tx::bytes [%0], [%1, {%3, %4, %5}], [%2];" ::"r"(dst), "l"(m), "r"(bar), "r"(c0), "r"(c1), "r"(c2) : "memory");
}
DEVI void tma3_mc(uint32_t dst, const CUtensorMap* m, int c0, int c1, int c2, uint32_t bar) {
  asm volatile("cp.async.bulk.tensor.3d.shared::cluster.global.mbarrier::complete_tx::bytes.multicast::cluster [%0], [%1, {%3, %4, %5}], [%2], %6;" ::"r"(dst), "l"(m), "r"(bar), "r"(c0), "r"(c1), "r"(c2), "h"((uint16_t)3) : "memory");
}
DEVI void tma2_mc(uint32_t dst, const CUtensorMap* m, int c0, int c1, uint32_t bar) {
  asm volatile("cp.async.bulk.tensor.2d.shared::cluster.global.mbarrier::complete_tx::bytes.multicast::cluster [%0], [%1, {%3, %4}], [%2], %5;" ::"r"(dst), "l"(m), "r"(bar), "r"(c0), "r"(c1), "h"((uint16_t)3) : "memory");
}
DEVI void mbar_arrive_remote(uint32_t bar, uint32_t cta) {
  asm volatile("{\n.reg .b32 ra;\nmapa.shared::cluster.u32 ra, %0, %1;\nmbarrier.arrive.shared::cluster.b64 _, [ra];\n}" ::"r"(bar), "r"(cta) : "memory");
}
DEVI void tma3_store(const CUtensorMap* m, int c0, int c1, int c2, uint32_t src) {
  asm volatile("cp.async.bulk.tensor.3d.global.shared::cta.bulk_group [%0, {%2, %3, %4}], [%1];" ::"l"(m), "r"(src), "r"(c0), "r"(c1), "r"(c2) : "memory");
}
DEVI void bulk_load(uint32_t dst, const void* src, uint32_t bytes, uint32_t bar) {
  asm volatile("cp.async.bulk.shared::cluster.global.mbarrier::complete_tx::bytes [%0], [%1], %2, [%3];" ::"r"(dst), "l"(src), "r"(bytes), "r"(bar) : "memory");
}
DEVI void bulk_store(void* dst, uint32_t src, uint32_t bytes) {
  asm volatile("cp.async.bulk.global.shared::cta.bulk_group [%0], [%1], %2;" ::"l"(dst), "r"(src), "r"(bytes) : "memory");
}
DEVI void pf_l2(const void* p) { asm volatile("prefetch.global.L2 [%0];" ::"l"(p)); }
template <int OFF> DEVI uint32_t ldg_v(const void* p) { uint32_t v; asm volatile("ld.volatile.global.b32 %0, [%1 + %2];" : "=r"(v) : "l"(p), "n"(OFF)); return v; }
DEVI void bulk_commit() { asm volatile("cp.async.bulk.commit_group;" ::: "memory"); }
DEVI void bulk_wait_all() { asm volatile("cp.async.bulk.wait_group 0;" ::: "memory"); }
DEVI void bulk_wait_read() { asm volatile("cp.async.bulk.wait_group.read 0;" ::: "memory"); }
template <int R> DEVI void reg_inc() { asm volatile("setmaxnreg.inc.sync.aligned.u32 %0;" ::"n"(R)); }
template <int R> DEVI void reg_dec() { asm volatile("setmaxnreg.dec.sync.aligned.u32 %0;" ::"n"(R)); }
DEVI uint32_t prmt(uint32_t a, uint32_t b, uint32_t s) { uint32_t r; asm("prmt.b32 %0,%1,%2,%3;" : "=r"(r) : "r"(a), "r"(b), "r"(s)); return r; }
DEVI uint32_t lds32(uint32_t a) { uint32_t r; asm volatile("ld.shared.b32 %0,[%1];" : "=r"(r) : "r"(a)); return r; }
DEVI void sts32(uint32_t a, uint32_t x) { asm volatile("st.shared.b32 [%0],%1;" ::"r"(a), "r"(x) : "memory"); }
DEVI void sts128(uint32_t a, uint32_t x, uint32_t y, uint32_t z, uint32_t w) { asm volatile("st.shared.v4.b32 [%0],{%1,%2,%3,%4};" ::"r"(a), "r"(x), "r"(y), "r"(z), "r"(w) : "memory"); }
DEVI void sts128v(uint32_t a, uint32_t x, uint32_t y, uint32_t z, uint32_t w) { asm volatile("st.volatile.shared.v4.b32 [%0],{%1,%2,%3,%4};" ::"r"(a), "r"(x), "r"(y), "r"(z), "r"(w) : "memory"); }
DEVI void lds128(uint32_t a, uint32_t& x, uint32_t& y, uint32_t& z, uint32_t& w) { asm volatile("ld.shared.v4.b32 {%0,%1,%2,%3},[%4];" : "=r"(x), "=r"(y), "=r"(z), "=r"(w) : "r"(a) : "memory"); }
DEVI void ldsm4(uint32_t& r0, uint32_t& r1, uint32_t& r2, uint32_t& r3, uint32_t addr) {
  asm volatile("ldmatrix.sync.aligned.m8n8.x4.shared.b16 {%0,%1,%2,%3}, [%4];" : "=r"(r0), "=r"(r1), "=r"(r2), "=r"(r3) : "r"(addr) : "memory");
}
DEVI void ldsm4t(uint32_t& r0, uint32_t& r1, uint32_t& r2, uint32_t& r3, uint32_t addr) {
  asm volatile("ldmatrix.sync.aligned.m8n8.x4.trans.shared.b16 {%0,%1,%2,%3}, [%4];" : "=r"(r0), "=r"(r1), "=r"(r2), "=r"(r3) : "r"(addr) : "memory");
}
DEVI void stsm4(uint32_t addr, uint32_t r0, uint32_t r1, uint32_t r2, uint32_t r3) {
  asm volatile("stmatrix.sync.aligned.m8n8.x4.shared.b16 [%0], {%1,%2,%3,%4};" ::"r"(addr), "r"(r0), "r"(r1), "r"(r2), "r"(r3) : "memory");
}
DEVI void stsm4t(uint32_t addr, uint32_t r0, uint32_t r1, uint32_t r2, uint32_t r3) {
  asm volatile("stmatrix.sync.aligned.m8n8.x4.trans.shared.b16 [%0], {%1,%2,%3,%4};" ::"r"(addr), "r"(r0), "r"(r1), "r"(r2), "r"(r3) : "memory");
}
DEVI uint32_t movm(uint32_t a) { uint32_t r; asm volatile("movmatrix.sync.aligned.m8n8.trans.b16 %0, %1;" : "=r"(r) : "r"(a)); return r; }
DEVI uint32_t pack_bf16(float lo, float hi) { uint32_t r; asm("cvt.rn.bf16x2.f32 %0, %1, %2;" : "=r"(r) : "f"(hi), "f"(lo)); return r; }
DEVI uint32_t hmul2(uint32_t a, uint32_t b) { uint32_t r; asm("mul.rn.bf16x2 %0,%1,%2;" : "=r"(r) : "r"(a), "r"(b)); return r; }
DEVI uint32_t hadd2(uint32_t a, uint32_t b) { uint32_t r; asm("add.rn.bf16x2 %0,%1,%2;" : "=r"(r) : "r"(a), "r"(b)); return r; }
DEVI float bf_lo(uint32_t a) { return __uint_as_float(prmt(a, 0, 0x1044)); }
DEVI float bf_hi(uint32_t a) { return __uint_as_float(a & 0xFFFF0000u); }
DEVI void mma16(float (&c)[4], uint32_t a0, uint32_t a1, uint32_t a2, uint32_t a3, uint32_t b0, uint32_t b1) {
  asm volatile("mma.sync.aligned.m16n8k16.row.col.f32.bf16.bf16.f32 {%0,%1,%2,%3},{%4,%5,%6,%7},{%8,%9},{%0,%1,%2,%3};"
      : "+f"(c[0]), "+f"(c[1]), "+f"(c[2]), "+f"(c[3]) : "r"(a0), "r"(a1), "r"(a2), "r"(a3), "r"(b0), "r"(b1));
}
DEVI void mma8(float (&c)[4], uint32_t a0, uint32_t a1, uint32_t b0) {
  asm volatile("mma.sync.aligned.m16n8k8.row.col.f32.bf16.bf16.f32 {%0,%1,%2,%3},{%4,%5},{%6},{%0,%1,%2,%3};"
      : "+f"(c[0]), "+f"(c[1]), "+f"(c[2]), "+f"(c[3]) : "r"(a0), "r"(a1), "r"(b0));
}
DEVI float ex2(float x) { float r; asm volatile("ex2.approx.ftz.f32 %0, %1;" : "=f"(r) : "f"(x)); return r; }

DEVI uint32_t clk() { uint32_t c; asm volatile("mov.u32 %0, %%clock;" : "=r"(c)); return c; }
DEVI void wait_until(uint32_t t0, int dt) { while ((int)(clk() - t0) < dt) __nanosleep(40); }
DEVI void spin_until(uint32_t t0, int dt) { while ((int)(clk() - t0) < dt) {} }
DEVI uint32_t hfma2(uint32_t a, uint32_t b, uint32_t c) { uint32_t r; asm("fma.rn.bf16x2 %0,%1,%2,%3;" : "=r"(r) : "r"(a), "r"(b), "r"(c)); return r; }
DEVI void bar_sync_p(int on, int id, int n) { asm volatile("{\n.reg .pred p;\nsetp.ne.b32 p, %0, 0;\n@p bar.sync %1, %2;\n}" ::"r"(on), "r"(id), "r"(n) : "memory"); }
DEVI void bar_arrive_p(int on, int id, int n) { asm volatile("{\n.reg .pred p;\nsetp.ne.b32 p, %0, 0;\n@p bar.arrive %1, %2;\n}" ::"r"(on), "r"(id), "r"(n) : "memory"); }
DEVI void mbar_arrive_p(int on, uint32_t bar) { asm volatile("{\n.reg .pred p;\nsetp.ne.b32 p, %1, 0;\n@p mbarrier.arrive.shared::cta.b64 _, [%0];\n}" ::"r"(bar), "r"(on) : "memory"); }
DEVI void mbar_arrive2_p(int on, uint32_t bar, uint32_t rbar) {
  asm volatile("{\n.reg .pred p;\nsetp.ne.b32 p, %2, 0;\n@p mbarrier.arrive.shared::cta.b64 _, [%0];\n@p mbarrier.arrive.shared::cluster.b64 _, [%1];\n}" ::"r"(bar), "r"(rbar), "r"(on) : "memory");
}
DEVI void st_relaxed(uint4* p, uint32_t x, uint32_t y, uint32_t z, uint32_t w) {
  asm volatile("st.relaxed.gpu.global.v4.b32 [%0], {%1,%2,%3,%4};" ::"l"(p), "r"(x), "r"(y), "r"(z), "r"(w) : "memory");
}
DEVI uint32_t mapa(uint32_t a, uint32_t cta) { uint32_t r; asm("mapa.shared::cluster.u32 %0, %1, %2;" : "=r"(r) : "r"(a), "r"(cta)); return r; }
DEVI void st_async128(uint32_t a, uint32_t x, uint32_t y, uint32_t z, uint32_t w, uint32_t bar) {
  asm volatile("st.async.weak.shared::cluster.mbarrier::complete_tx::bytes.v4.b32 [%0], {%1,%2,%3,%4}, [%5];" ::"r"(a), "r"(x), "r"(y), "r"(z), "r"(w), "r"(bar) : "memory");
}

template<int OFF, int TB, int S> __device__ __forceinline__ void wgmma_rs_n128(float (&d)[S], uint32_t a0, uint32_t a1, uint32_t a2, uint32_t a3, uint64_t db, int sd) {
  asm volatile("{\n.reg .pred p;\nsetp.ne.b32 p, %69, 0;\n"
    "wgmma.mma_async.sync.aligned.m64n128k16.f32.bf16.bf16 {%0, %1, %2, %3, %4, %5, %6, %7, %8, %9, %10, %11, %12, %13, %14, %15, %16, %17, %18, %19, %20, %21, %22, %23, %24, %25, %26, %27, %28, %29, %30, %31, %32, %33, %34, %35, %36, %37, %38, %39, %40, %41, %42, %43, %44, %45, %46, %47, %48, %49, %50, %51, %52, %53, %54, %55, %56, %57, %58, %59, %60, %61, %62, %63}, {%64, %65, %66, %67}, %68, p, 1, 1, %70;\n}\n"
    : "+f"(d[OFF+0]), "+f"(d[OFF+1]), "+f"(d[OFF+2]), "+f"(d[OFF+3]), "+f"(d[OFF+4]), "+f"(d[OFF+5]), "+f"(d[OFF+6]), "+f"(d[OFF+7]), "+f"(d[OFF+8]), "+f"(d[OFF+9]), "+f"(d[OFF+10]), "+f"(d[OFF+11]), "+f"(d[OFF+12]), "+f"(d[OFF+13]), "+f"(d[OFF+14]), "+f"(d[OFF+15]), "+f"(d[OFF+16]), "+f"(d[OFF+17]), "+f"(d[OFF+18]), "+f"(d[OFF+19]), "+f"(d[OFF+20]), "+f"(d[OFF+21]), "+f"(d[OFF+22]), "+f"(d[OFF+23]), "+f"(d[OFF+24]), "+f"(d[OFF+25]), "+f"(d[OFF+26]), "+f"(d[OFF+27]), "+f"(d[OFF+28]), "+f"(d[OFF+29]), "+f"(d[OFF+30]), "+f"(d[OFF+31]), "+f"(d[OFF+32]), "+f"(d[OFF+33]), "+f"(d[OFF+34]), "+f"(d[OFF+35]), "+f"(d[OFF+36]), "+f"(d[OFF+37]), "+f"(d[OFF+38]), "+f"(d[OFF+39]), "+f"(d[OFF+40]), "+f"(d[OFF+41]), "+f"(d[OFF+42]), "+f"(d[OFF+43]), "+f"(d[OFF+44]), "+f"(d[OFF+45]), "+f"(d[OFF+46]), "+f"(d[OFF+47]), "+f"(d[OFF+48]), "+f"(d[OFF+49]), "+f"(d[OFF+50]), "+f"(d[OFF+51]), "+f"(d[OFF+52]), "+f"(d[OFF+53]), "+f"(d[OFF+54]), "+f"(d[OFF+55]), "+f"(d[OFF+56]), "+f"(d[OFF+57]), "+f"(d[OFF+58]), "+f"(d[OFF+59]), "+f"(d[OFF+60]), "+f"(d[OFF+61]), "+f"(d[OFF+62]), "+f"(d[OFF+63]) : "r"(a0), "r"(a1), "r"(a2), "r"(a3), "l"(db), "r"(sd), "n"(TB));
}
template<int OFF, int TB, int S> __device__ __forceinline__ void wgmma_rs_n64(float (&d)[S], uint32_t a0, uint32_t a1, uint32_t a2, uint32_t a3, uint64_t db, int sd) {
  asm volatile("{\n.reg .pred p;\nsetp.ne.b32 p, %37, 0;\n"
    "wgmma.mma_async.sync.aligned.m64n64k16.f32.bf16.bf16 {%0, %1, %2, %3, %4, %5, %6, %7, %8, %9, %10, %11, %12, %13, %14, %15, %16, %17, %18, %19, %20, %21, %22, %23, %24, %25, %26, %27, %28, %29, %30, %31}, {%32, %33, %34, %35}, %36, p, 1, 1, %38;\n}\n"
    : "+f"(d[OFF+0]), "+f"(d[OFF+1]), "+f"(d[OFF+2]), "+f"(d[OFF+3]), "+f"(d[OFF+4]), "+f"(d[OFF+5]), "+f"(d[OFF+6]), "+f"(d[OFF+7]), "+f"(d[OFF+8]), "+f"(d[OFF+9]), "+f"(d[OFF+10]), "+f"(d[OFF+11]), "+f"(d[OFF+12]), "+f"(d[OFF+13]), "+f"(d[OFF+14]), "+f"(d[OFF+15]), "+f"(d[OFF+16]), "+f"(d[OFF+17]), "+f"(d[OFF+18]), "+f"(d[OFF+19]), "+f"(d[OFF+20]), "+f"(d[OFF+21]), "+f"(d[OFF+22]), "+f"(d[OFF+23]), "+f"(d[OFF+24]), "+f"(d[OFF+25]), "+f"(d[OFF+26]), "+f"(d[OFF+27]), "+f"(d[OFF+28]), "+f"(d[OFF+29]), "+f"(d[OFF+30]), "+f"(d[OFF+31]) : "r"(a0), "r"(a1), "r"(a2), "r"(a3), "l"(db), "r"(sd), "n"(TB));
}
template<int OFF, int TB, int S> __device__ __forceinline__ void wgmma_rs_n48(float (&d)[S], uint32_t a0, uint32_t a1, uint32_t a2, uint32_t a3, uint64_t db, int sd) {
  asm volatile("{\n.reg .pred p;\nsetp.ne.b32 p, %29, 0;\n"
    "wgmma.mma_async.sync.aligned.m64n48k16.f32.bf16.bf16 {%0, %1, %2, %3, %4, %5, %6, %7, %8, %9, %10, %11, %12, %13, %14, %15, %16, %17, %18, %19, %20, %21, %22, %23}, {%24, %25, %26, %27}, %28, p, 1, 1, %30;\n}\n"
    : "+f"(d[OFF+0]), "+f"(d[OFF+1]), "+f"(d[OFF+2]), "+f"(d[OFF+3]), "+f"(d[OFF+4]), "+f"(d[OFF+5]), "+f"(d[OFF+6]), "+f"(d[OFF+7]), "+f"(d[OFF+8]), "+f"(d[OFF+9]), "+f"(d[OFF+10]), "+f"(d[OFF+11]), "+f"(d[OFF+12]), "+f"(d[OFF+13]), "+f"(d[OFF+14]), "+f"(d[OFF+15]), "+f"(d[OFF+16]), "+f"(d[OFF+17]), "+f"(d[OFF+18]), "+f"(d[OFF+19]), "+f"(d[OFF+20]), "+f"(d[OFF+21]), "+f"(d[OFF+22]), "+f"(d[OFF+23]) : "r"(a0), "r"(a1), "r"(a2), "r"(a3), "l"(db), "r"(sd), "n"(TB));
}
template<int OFF, int TB, int S> __device__ __forceinline__ void wgmma_rs_n16(float (&d)[S], uint32_t a0, uint32_t a1, uint32_t a2, uint32_t a3, uint64_t db, int sd) {
  asm volatile("{\n.reg .pred p;\nsetp.ne.b32 p, %13, 0;\n"
    "wgmma.mma_async.sync.aligned.m64n16k16.f32.bf16.bf16 {%0, %1, %2, %3, %4, %5, %6, %7}, {%8, %9, %10, %11}, %12, p, 1, 1, %14;\n}\n"
    : "+f"(d[OFF+0]), "+f"(d[OFF+1]), "+f"(d[OFF+2]), "+f"(d[OFF+3]), "+f"(d[OFF+4]), "+f"(d[OFF+5]), "+f"(d[OFF+6]), "+f"(d[OFF+7]) : "r"(a0), "r"(a1), "r"(a2), "r"(a3), "l"(db), "r"(sd), "n"(TB));
}
template<int OFF, int TA, int TB, int S> __device__ __forceinline__ void wgmma_ss_n160(float (&d)[S], uint64_t da, uint64_t db, int sd) {
  asm volatile("{\n.reg .pred p;\nsetp.ne.b32 p, %82, 0;\n"
    "wgmma.mma_async.sync.aligned.m64n160k16.f32.bf16.bf16 {%0, %1, %2, %3, %4, %5, %6, %7, %8, %9, %10, %11, %12, %13, %14, %15, %16, %17, %18, %19, %20, %21, %22, %23, %24, %25, %26, %27, %28, %29, %30, %31, %32, %33, %34, %35, %36, %37, %38, %39, %40, %41, %42, %43, %44, %45, %46, %47, %48, %49, %50, %51, %52, %53, %54, %55, %56, %57, %58, %59, %60, %61, %62, %63, %64, %65, %66, %67, %68, %69, %70, %71, %72, %73, %74, %75, %76, %77, %78, %79}, %80, %81, p, 1, 1, %83, %84;\n}\n"
    : "+f"(d[OFF+0]), "+f"(d[OFF+1]), "+f"(d[OFF+2]), "+f"(d[OFF+3]), "+f"(d[OFF+4]), "+f"(d[OFF+5]), "+f"(d[OFF+6]), "+f"(d[OFF+7]), "+f"(d[OFF+8]), "+f"(d[OFF+9]), "+f"(d[OFF+10]), "+f"(d[OFF+11]), "+f"(d[OFF+12]), "+f"(d[OFF+13]), "+f"(d[OFF+14]), "+f"(d[OFF+15]), "+f"(d[OFF+16]), "+f"(d[OFF+17]), "+f"(d[OFF+18]), "+f"(d[OFF+19]), "+f"(d[OFF+20]), "+f"(d[OFF+21]), "+f"(d[OFF+22]), "+f"(d[OFF+23]), "+f"(d[OFF+24]), "+f"(d[OFF+25]), "+f"(d[OFF+26]), "+f"(d[OFF+27]), "+f"(d[OFF+28]), "+f"(d[OFF+29]), "+f"(d[OFF+30]), "+f"(d[OFF+31]), "+f"(d[OFF+32]), "+f"(d[OFF+33]), "+f"(d[OFF+34]), "+f"(d[OFF+35]), "+f"(d[OFF+36]), "+f"(d[OFF+37]), "+f"(d[OFF+38]), "+f"(d[OFF+39]), "+f"(d[OFF+40]), "+f"(d[OFF+41]), "+f"(d[OFF+42]), "+f"(d[OFF+43]), "+f"(d[OFF+44]), "+f"(d[OFF+45]), "+f"(d[OFF+46]), "+f"(d[OFF+47]), "+f"(d[OFF+48]), "+f"(d[OFF+49]), "+f"(d[OFF+50]), "+f"(d[OFF+51]), "+f"(d[OFF+52]), "+f"(d[OFF+53]), "+f"(d[OFF+54]), "+f"(d[OFF+55]), "+f"(d[OFF+56]), "+f"(d[OFF+57]), "+f"(d[OFF+58]), "+f"(d[OFF+59]), "+f"(d[OFF+60]), "+f"(d[OFF+61]), "+f"(d[OFF+62]), "+f"(d[OFF+63]), "+f"(d[OFF+64]), "+f"(d[OFF+65]), "+f"(d[OFF+66]), "+f"(d[OFF+67]), "+f"(d[OFF+68]), "+f"(d[OFF+69]), "+f"(d[OFF+70]), "+f"(d[OFF+71]), "+f"(d[OFF+72]), "+f"(d[OFF+73]), "+f"(d[OFF+74]), "+f"(d[OFF+75]), "+f"(d[OFF+76]), "+f"(d[OFF+77]), "+f"(d[OFF+78]), "+f"(d[OFF+79]) : "l"(da), "l"(db), "r"(sd), "n"(TA), "n"(TB));
}

__device__ __align__(1024) uint16_t g_kvT[2 * 640 * 2048];
__device__ __align__(1024) uint16_t g_y2T[2 * 640 * 2048];
__device__ __align__(1024) uint16_t g_o[2048 * 640];
__device__ __align__(1024) uint16_t g_gate[2080];
__device__ __align__(1024) uint4 g_halo[128 * 5 * 32];
__device__ __align__(1024) unsigned g_cnt[46 * 32];
__device__ __align__(1024) unsigned g_launch[132 * 32];
#define CNT_KV(i) (g_cnt + 32 * (i))
#define CNT_O(i) (g_cnt + 32 * (10 + (i)))
#define CNT_Y(i) (g_cnt + 32 * (26 + (i)))
#define PTL(i) do {} while (0)
#define PTPL(on, i) do {} while (0)
#define PT(i) do {} while (0)
#define PTP(on, i) do {} while (0)

constexpr uint32_t SB = 1024;
constexpr uint32_t STG = 23552, WST = 15360;
DEVI constexpr uint32_t o_px(int ks) { return (((ks >> 1) + 1) & 3) * 2 * STG; }
DEVI constexpr uint32_t o_pw(int ks) { return o_px(ks) + 16384 + (ks & 1) * WST; }
constexpr uint32_t O_HALO = 0, O_QT = STG;
constexpr uint32_t O_OST = 2 * STG;
constexpr uint32_t P3S = 28672;
constexpr uint32_t HC = 8320, UC = 4624, UZ = 528;
constexpr uint32_t O_H0 = 5 * P3S, O_U2 = O_H0 + 3 * HC, O_H3 = O_U2 + UC, O_U0 = O_H3 + 2 * HC;
DEVI constexpr uint32_t o_h(int c) { return O_H0 + c * HC + (c > 2 ? UC : 0); }
DEVI constexpr uint32_t o_u(int c) { return c == 2 ? O_U2 : O_U0 + (c > 2 ? c - 1 : c) * UC; }
constexpr uint32_t O_Y = 208896;
DEVI constexpr uint32_t o_x(int c) { return c < 2 ? O_Y + c * 5120 : O_U0 + (c & 1) * UC; }
constexpr uint32_t O_HIN = O_Y + 16384;
DEVI constexpr uint32_t o_kin(int c) { return ((O_U0 + 127) & ~127u) + ((c & 1) ? 0 : 73 * 128); }
DEVI constexpr uint32_t o_p3(int ks) { return (ks < 6 ? ks : ks - 6) * P3S; }
constexpr uint32_t O_BT = 4 * P3S;
constexpr uint32_t O_GT = O_Y + 20480, O_GW = O_GT + 320;
constexpr uint32_t O_BAR = 231040;
constexpr uint32_t B_FULL = O_BAR, B_EMPTY = O_BAR + 8 * 8, B_P3F = O_BAR + 8 * 16, B_P3R = O_BAR + 8 * 26, B_G = O_BAR + 8 * 27, B_U = O_BAR + 8 * 28,
                   B_KVD = O_BAR + 8 * 33, B_KF = O_BAR + 8 * 36, B_Y = O_BAR + 8 * 38, B_EP = O_BAR + 8 * 40, B_LAST = O_BAR + 8 * 41, B_DONE = O_BAR + 8 * 42,
                   B_P1E = O_BAR + 8 * 43, B_HX = O_BAR + 8 * 43  , B_P3E = O_BAR + 8 * 52, B_HX0 = O_BAR + 8 * 57, B_KVS = O_BAR + 8 * 58, B_QD = O_BAR + 8 * 60, B_GD = O_BAR + 8 * 61, B_Q = O_BAR + 8 * 51;
constexpr uint32_t B_S13 = B_EMPTY + 8 * 5, B_S15 = B_EMPTY + 8 * 7, B_S19 = B_EMPTY + 8 * 3;
constexpr uint32_t O_GP = O_BAR + 512, O_EPOCH = O_GW + 1280;
constexpr uint32_t SMEM_BYTES = 232448;
static_assert(O_U0 + 127 + 146 * 128 <= O_Y && o_kin(0) >= O_U0 + 2 * UC && O_EPOCH + 4 <= O_BAR && O_U0 >= 8 * STG, "smem map");
enum { NB_LEAD = 1, NB_HELP = 2, NB_HALO = 3, NB_ATT = 4, NB_G = 5, NB_TOK = 6, NB_RFULL = 8, NB_RFREE = 10 };

struct Maps { CUtensorMap x_par, w_main, w_tail, k_ld, v_ld, o_st, kv_st, wo, o_ld, y_ld, q_ld; };

template <int M> DEVI void conv_step(float (&acc)[128], uint32_t a0, uint32_t a1, uint32_t a2, uint32_t a3, uint32_t dl) {
  auto D = [&](int off) { return ((uint64_t)8 << 32) | (uint64_t)(uint32_t)(dl + off - 16 * M); };
  if constexpr (M == 0) wgmma_rs_n16<0, 0>(acc, a0, a1, a2, a3, D(0), 0);
  if constexpr (M <= 3) wgmma_rs_n48<8, 0>(acc, a0, a1, a2, a3, D(16), M == 0 ? 0 : 1);
  if constexpr (M <= 6) wgmma_rs_n48<32, 0>(acc, a0, a1, a2, a3, D(64), M == 0 ? 0 : 1);
  if constexpr (M <= 9) wgmma_rs_n48<56, 0>(acc, a0, a1, a2, a3, D(112), M == 0 ? 0 : 1);
  if constexpr (M <= 12) wgmma_rs_n48<80, 0>(acc, a0, a1, a2, a3, D(160), M == 0 ? 0 : 1);
  wgmma_rs_n48<104, 0>(acc, a0, a1, a2, a3, D(208), M == 0 ? 0 : 1);
}
DEVI constexpr int a_off(int P, int i) { return -4 * (64 * ((i & 4) ? 15 - P : P) + (i & 1) * 32 - (i & 2) * 2); }
template <int P> DEVI void load_pair(uint32_t (&a)[8], uint32_t ab) {
#pragma unroll
  for (int i = 0; i < 8; i++) a[i] = lds32(ab + a_off(P, i));
}
template <int P> DEVI void mma_pair(float (&acc)[128], uint32_t (&a)[8], uint32_t db) {
  wg_fence();
  conv_step<P>(acc, a[0], a[1], a[2], a[3], db);
  conv_step<15 - P>(acc, a[4], a[5], a[6], a[7], db);
  wg_commit();
}

template <int I0, int I1> DEVI void conv_reduce(uint32_t sb, int c, int ht, int chan, int bar, int nthr) {
  const uint32_t a0 = sb + o_h(c) + ht * 16, a2 = sb + o_u(c) + ht * 16, a3 = sb + o_x(c) + ht * 16;
  uint4* yp = (uint4*)(g_y2T + (size_t)chan * 2048) + ht;
#pragma unroll
  for (int i = I0; i < I1; i++) {
    uint4 p, q, r, s;
    if (i == I0) bar_sync(bar, nthr);
    lds128(a0 + i * 2048, p.x, p.y, p.z, p.w); lds128(a0 + 4160 + i * 2048, q.x, q.y, q.z, q.w);
    lds128(a2 + i * 2048, r.x, r.y, r.z, r.w); lds128(a3 + i * 2048, s.x, s.y, s.z, s.w);
    auto sum = [](uint32_t a, uint32_t b, uint32_t c, uint32_t d) { return hadd2(hadd2(hadd2(a, b), 0u), hadd2(c, d)) ^ 0x80008000u; };
    yp[i * 128] = make_uint4(sum(p.x, q.x, r.x, s.x), sum(p.y, q.y, r.y, s.y), sum(p.z, q.z, r.z, s.z), sum(p.w, q.w, r.w, s.w));
  }
}

template <int ODD, int PART> DEVI void pack_qkv(const float (&acc)[120], uint32_t (&Q)[10][2], uint32_t (&K)[10][2], uint32_t (&V)[10][2]) {
#pragma unroll
  for (int f = 0; f < 10; f++) {
    const bool tail = ODD ? (f < 2) : (f >= 8);
    const int fm = ODD ? f - 2 : f, ft = ODD ? f : f - 8;
    const int nq = tail ? 24 + ft : fm, nk = tail ? 26 + ft : 8 + fm, nv = tail ? 28 + ft : 16 + fm;
    if (PART == 0) { K[f][1] = pack_bf16(acc[4 * nk + 2], acc[4 * nk + 3]); V[f][1] = pack_bf16(acc[4 * nv + 2], acc[4 * nv + 3]); }
    if (PART == 1) { V[f][0] = pack_bf16(acc[4 * nv], acc[4 * nv + 1]); K[f][0] = pack_bf16(acc[4 * nk], acc[4 * nk + 1]); }
    if (PART == 2) { Q[f][0] = pack_bf16(acc[4 * nq], acc[4 * nq + 1]); Q[f][1] = pack_bf16(acc[4 * nq + 2], acc[4 * nq + 3]); }
  }
}
DEVI void sched_fence(uint32_t& z) {
  asm volatile("{\n.reg .pred p;\nL:\nshr.u32 %0, %0, 1;\nsetp.ne.u32 p, %0, 0;\n@p bra.uni L;\n}" : "+r"(z));
}

DEVI int pair_of(int c) {
  const int lo = 32 + 8 * c, hi = c - 4 + ((max(c - 29, 0) * 37) >> 8);
  int p; asm("{\n.reg .pred q;\nsetp.lt.s32 q, %1, 4;\nselp.b32 %0, %2, %3, q;\n}" : "=r"(p) : "r"(c), "r"(lo), "r"(hi));
  return p;
}
DEVI uint32_t make_ctx() {
  int b; asm volatile("mov.u32 %0, %%ctaid.x;" : "=r"(b));
  b += clk() & threadIdx.y;
  const int p = pair_of(b >> 1);
  const int j = b < 128 ? 8 * (p & 7) + (p >> 3) : 64, cp = (j * 79) >> 10;
  return ((2 * p + (b & 1)) & 255) | (j - 13 * cp) << 8 | (2 * cp + (b & 1)) << 12 | (b >> 7) << 16;
}
#define CTX() asm volatile("" : "+r"(ctx)); CTXU()
#define CTXU() int tid; asm volatile("mov.u32 %0, %%tid.x;" : "=r"(tid)); \
  const int lane = tid & 31, vb = ctx & 255, hg = (ctx >> 4) & 7, rt = ctx & 15, par = (ctx >> 3) & 1, mt = ctx & 7, rank = ctx & 1, \
  tb = (ctx >> 8) & 15, cb = (ctx >> 12) & 15; const bool main_cta = ctx < 65536; \
  (void)tid; (void)lane; (void)vb; (void)hg; (void)rt; (void)par; (void)mt; (void)rank; (void)tb; (void)cb; (void)main_cta
#define CTXW() CTX(); const int wg = warp >> 2, w = warp & 3, g = lane >> 2, t = lane & 3; const bool lead = (tid & 127) == 0; \
  (void)wg; (void)w; (void)g; (void)t; (void)lead

__global__ void __cluster_dims__(2, 1, 1) __launch_bounds__(512, 1)
fused_kernel(const uint16_t* __restrict__ xq, const uint16_t* __restrict__ wqkv, const uint16_t* __restrict__ gate_w, const __grid_constant__ Maps M, const uint16_t* __restrict__ shift_k, const uint16_t* __restrict__ ssm_k, const uint16_t* __restrict__ ssm_D,
             uint16_t* __restrict__ outp) {
  extern __shared__ __align__(1024) uint8_t smem_raw[];
  const uint32_t sb = smem_u32(smem_raw);
  const uint32_t t0 = clk();
  auto get_epoch = [&]() { mbar_wait(sb + B_EP, 0); return lds32(sb + O_EPOCH); };

  auto p1_load_x = [&](int ks, int p, int rank) {
    tma3(sb + o_px(ks), &M.x_par, ks * 32, (p >> 2) & 1, (p & 3) * 256 + rank * 128, sb + B_FULL + 8 * (ks & 7));
  };
  auto p1_load_w = [&](int ks, int p, int rank) {
    const uint32_t st = sb + o_pw(ks), fb = sb + B_FULL + 8 * (ks & 7);
    tma3_mc(st + rank * 6144, &M.w_main, (p >> 3) * 80 + 2 * (p & 8), ks * 32 + rank * 16, 0, fb);
    tma3_mc(st + 12288 + rank * 1536, &M.w_tail, (p >> 3) * 80 + 8 * (~p & 8), ks * 32 + rank * 16, 0, fb);
  };
  auto cta_pair = [&]() { return pair_of(blockIdx.x >> 1); };

  const uint16_t* pfp = nullptr;
  if (threadIdx.x < 32) {
    const unsigned b = blockIdx.x, l = threadIdx.x;
    pfp = l < 16 ? xq + (16 * b + l) * 640 : wqkv + (15 * b + l - 16) * 64;
    if ((l | b >> 7 << 5) < 31) pf_l2(pfp);
  }
  const int warp = __shfl_sync(~0u, threadIdx.x >> 5, 0);
  if ((warp & 14) == 8) {
    if (elect_one()) {
#pragma unroll
      for (int s = 0; s < 8; s++) mbar_init(sb + O_BAR - 512 + 64 * warp + 8 * s, 5 * warp - 39);
      asm volatile("fence.mbarrier_init.release.cluster;" ::: "memory");
    }
    __syncwarp();
  }
  asm volatile("barrier.cluster.arrive.relaxed.aligned;" ::: "memory");
  if (warp == 8 && blockIdx.x < 128) {
    const int p = cta_pair(), rank = blockIdx.x & 1;
    if (elect_one()) { mbar_expect_tx(sb + B_FULL, 16384 + WST); p1_load_x(0, p, rank); }
    __syncwarp();
    asm volatile("barrier.cluster.wait.aligned;" ::: "memory");
    if (elect_one()) { p1_load_w(0, p, rank); PT(100); }
    __syncwarp();
  } else if (warp != 15) {
    asm volatile("barrier.cluster.wait.aligned;" ::: "memory");
    spin_until(t0, HOLD);
  }
  auto init_rest = [&]() {
    if (warp >= 11 && elect_one()) {
#pragma unroll
      for (int s = 0; s < 12; s++) mbar_init(sb + O_BAR + 128 - 11 * 96 + 96 * warp + 8 * s, warp == 14 ? 2 : 1);
      asm volatile("fence.mbarrier_init.release.cluster;" ::: "memory");
    }
    __syncwarp();
    bar_sync(0, blockIdx.x < 128 ? 224 : 512);
  };
  uint32_t ctx = 0;

  if (warp < 8) {
    if (PF2 && warp == 0) {
#pragma unroll 1
      for (int i = 1; i <= NPF; i++) {
        spin_until(t0, PF2 + (i - 1) * PFD);
        if ((threadIdx.x | blockIdx.x >> 7 << 5) < 31) pf_l2(pfp + (threadIdx.x < 16 ? 64 : 64 * 1920) * i);
        __syncwarp();
      }
    }
    reg_inc<RC>();
    ctx = make_ctx();
    if (blockIdx.x >= 128) bar_sync(0, 512);
    else {
      {
        uint32_t Q[10][2], K[10][2], V[10][2];
        {
          {
            float acc[120];
            CTXW();
            const int odd = (cta_pair() >> 3) & 1;
            const uint32_t rsb = mapa(sb, (blockIdx.x & 1) ^ 1);
            {
              const uint32_t aa = sb + (warp * 16 + (lane & 15)) * 128 + (((lane >> 4) ^ (lane & 7)) << 4);
              constexpr int NA = DEFER > 3 ? DEFER : 3;
              uint32_t a[NA][8];
              auto load_a = [&](int ks) {
                uint32_t(&r)[8] = a[ks % NA];
                mbar_wait(sb + B_FULL + 8 * (ks & 7), (ks >> 3) & 1);
                PTP(lead && (wg || !(ks & 3)), wg ? 60 + ks : 80 + (ks >> 2));
                ldsm4(r[0], r[1], r[2], r[3], (aa ^ ((ks & 1) * 64)) + o_px(ks)); ldsm4(r[4], r[5], r[6], r[7], (aa ^ ((ks & 1) * 64 + 32)) + o_px(ks));
              };
              auto mma_q = [&](int ks, int h) {
                uint32_t(&r)[8] = a[ks % NA];
                wgmma_rs_n64<0, 1>(acc, r[4 * h], r[4 * h + 1], r[4 * h + 2], r[4 * h + 3], mkdesc(SB + o_pw(ks) + h * 6144, 2048, 1024, 1), ks | h);
              };
              auto mma_step = [&](int ks, int h) {
                uint32_t(&r)[8] = a[ks % NA];
                wg_fence();
                wgmma_rs_n128<32, 1>(acc, r[4 * h], r[4 * h + 1], r[4 * h + 2], r[4 * h + 3], mkdesc(SB + o_pw(ks) + h * 6144 + 2048, 2048, 1024, 1), ks | h);
                if (ks < 20 - DEFER) mma_q(ks, h);
                wgmma_rs_n48<96, 1>(acc, r[4 * h], r[4 * h + 1], r[4 * h + 2], r[4 * h + 3], mkdesc(SB + o_pw(ks) + 12288 + h * 1536, 512, 256, 3), ks | h);
                wg_commit();
              };
              if (lead) PT(1 + wg);
              load_a(0);
#pragma unroll
              for (int ks = 0; ks < 20; ks++) {
                if (LEAD && ks == 20 - LEAD) bar_sync_p(wg == 0, NB_LEAD, 256);
                mma_step(ks, 0);
                if (ks < 19) load_a(ks + 1);
                mma_step(ks, 1);
                if (ks >= 1 && ks <= 16) {
                  wg_wait<2>();
                  mbar_arrive2_p(lead, sb + B_EMPTY + 8 * ((ks - 1) & 7), rsb + B_EMPTY + 8 * ((ks - 1) & 7));
                } else if (ks < 19 && ks + 2 - NA >= 16) wg_wait<2>();
              }
              if (LEAD) bar_arrive_p(wg, NB_LEAD, 256);
              if (DEFER) {
                wg_fence();
#pragma unroll
                for (int i = 40 - 2 * DEFER; i < 40; i++) mma_q(i >> 1, i & 1);
                wg_commit();
              }
              mbar_wait(sb + B_S15, 1);
              wg_wait<1>();
              mbar_arrive_p(tid == 0, sb + B_P1E);
              if (!DEFER) wg_wait<0>();
              fence_regs<32, 120>(acc);
              PTP(lead, 158 + wg);
            }
            if (odd) pack_qkv<1, 0>(acc, Q, K, V); else pack_qkv<0, 0>(acc, Q, K, V);
            if (warp == 7 && (blockIdx.x & 1)) {
              uint4* hp = g_halo + vb * 160 + lane;
              st_relaxed(hp, K[0][1], K[1][1], K[3][1], K[4][1]); st_relaxed(hp + 32, K[5][1], K[6][1], K[8][1], K[9][1]);
              st_relaxed(hp + 64, K[2][1], K[7][1], V[0][1], V[1][1]);
              st_relaxed(hp + 96, V[2][1], V[3][1], V[4][1], V[5][1]); st_relaxed(hp + 128, V[6][1], V[7][1], V[8][1], V[9][1]);
            }
            const uint32_t ho = sb + O_HALO + warp * 2560 + lane * 16;
            stsm4(ho, K[0][1], K[1][1], K[3][1], K[4][1]); stsm4(ho + 512, K[5][1], K[6][1], K[8][1], K[9][1]);
            stsm4(ho + 1024, K[2][1], K[7][1], V[0][1], V[1][1]);
            stsm4(ho + 1536, V[2][1], V[3][1], V[4][1], V[5][1]); stsm4(ho + 2048, V[6][1], V[7][1], V[8][1], V[9][1]);
            if (warp == 7) {
              if (!(blockIdx.x & 1)) {
                fence_async_smem();
                __syncwarp();
                if (elect_one())
                  asm volatile("cp.async.bulk.shared::cluster.shared::cta.mbarrier::complete_tx::bytes [%0], [%1], 2560, [%2];"
                               ::"r"(mapa(sb + O_HIN, 1)), "r"(sb + O_HALO + 7 * 2560), "r"(mapa(sb + B_HX0, 1)) : "memory");
              }
              __syncwarp();
            } else {
              __syncwarp();
              if (lane == 0) mbar_arrive(sb + B_HX + 8 + 8 * warp);
            }
            if (odd) pack_qkv<1, 1>(acc, Q, K, V); else pack_qkv<0, 1>(acc, Q, K, V);
#pragma unroll
            for (int f = 0; f < 10; f++) V[f][0] = movm(V[f][0]);
            wg_wait<0>();
            fence_regs<0, 32>(acc);
            PTPL(lead, 50 + wg);
            mbar_arrive2_p(lead, sb + B_S19, rsb + B_S19);
            if (odd) pack_qkv<1, 2>(acc, Q, K, V); else pack_qkv<0, 2>(acc, Q, K, V);
            if (lead) PT(52 + wg);
            if (wg) mbar_wait(sb + B_P1E, 0);
          }
          CTXW();
          uint32_t z = threadIdx.y;
          const bool gt0 = 2 * t > g, gt1 = 2 * t + 1 > g;
          const uint32_t pmask = (gt0 ? 0xFFFFu : 0u) | (gt1 ? 0xFFFF0000u : 0u);
          const uint32_t hs = warp ? O_HALO + (warp - 1) * 2560 : O_HIN, ha = sb + hs + lane * 16;
          const uint32_t va = sb + ((lane & 8) ? O_HALO + warp * 2560 : hs) + 1280 + (lane >> 4) * 128 + (lane & 7) * 16;
          uint32_t Qh[4][2], Kh[10], Vh[10];
          float c1[4][4] = {}, c2[4][4] = {}, c0[4][4] = {}, l[8][2], m[8], x[8];
#pragma unroll
          for (int j = 0; j < 4; j++) {
            const int fa = (j >> 1) * 5 + (j & 1) * 3, fh = (j >> 1) * 5 + 2;
            const bool mine = (j & 1) ? (t >= 2) : (t < 2);
            Qh[j][0] = mine ? Q[fh][0] : 0u; Qh[j][1] = mine ? Q[fh][1] : 0u;
            mma16(c1[j], Q[fa][0], Q[fa][1], Q[fa + 1][0], Q[fa + 1][1], K[fa][0], K[fa + 1][0]);
            mma16(c2[j], Q[fa][0], Q[fa][1], Q[fa + 1][0], Q[fa + 1][1], K[fa][1], K[fa + 1][1]);
            mma8(c1[j], Qh[j][0], Qh[j][1], K[fh][0]);
            mma8(c2[j], Qh[j][0], Qh[j][1], K[fh][1]);
          }
          if (lead) PT(54 + wg);
          mbar_wait(sb + (warp ? B_HX + 8 * warp : B_HX0), 0);
          if (lead) PT(56 + wg);
          ldsm4(Kh[0], Kh[1], Kh[3], Kh[4], ha); ldsm4(Kh[5], Kh[6], Kh[8], Kh[9], ha + 512);
          asm volatile("ldmatrix.sync.aligned.m8n8.x2.shared.b16 {%0,%1}, [%2];" : "=r"(Kh[2]), "=r"(Kh[7]) : "r"(ha + 1024) : "memory");
          auto load_v = [&]() {
#pragma unroll
            for (int i = 0; i < 5; i++) ldsm4t(Vh[2 * i], V[2 * i][1], Vh[2 * i + 1], V[2 * i + 1][1], va + i * 256);
          };
          load_v();
          const float C = 0.22360679774997896f * 1.4426950408889634f;
          auto max1 = [&](int r) { m[r] = fmaxf(l[r][0], l[r][1]); x[r] = __shfl_xor_sync(~0u, m[r], 1); };
          auto max2 = [&](int r) { m[r] = fmaxf(m[r], x[r]); x[r] = __shfl_xor_sync(~0u, m[r], 2); };
          auto exps = [&](int r) { const float mc = fmaxf(m[r], x[r]) * C; l[r][0] = ex2(fmaf(l[r][0], C, -mc)); l[r][1] = ex2(fmaf(l[r][1], C, -mc)); };
#pragma unroll
          for (int j = 0; j < 4; j++) { l[4 + j][0] = gt0 ? c1[j][2] : c2[j][2]; l[4 + j][1] = gt1 ? c1[j][3] : c2[j][3]; max1(4 + j); }
#pragma unroll
          for (int j = 0; j < 4; j++) {
            const int fa = (j >> 1) * 5 + (j & 1) * 3, fh = (j >> 1) * 5 + 2;
            mma16(c0[j], Q[fa][0], Q[fa][1], Q[fa + 1][0], Q[fa + 1][1], Kh[fa], Kh[fa + 1]);
            mma8(c0[j], Qh[j][0], Qh[j][1], Kh[fh]);
            max2(4 + j);
          }
          const bool have_halo = warp > 0 || mt > 0;
#pragma unroll
          for (int j = 0; j < 4; j++) {
            if (!have_halo) c0[j][0] = c0[j][1] = -INFINITY;
            l[j][0] = gt0 ? c0[j][0] : c1[j][0]; l[j][1] = gt1 ? c0[j][1] : c1[j][1];
            max1(j);
          }
          exps(4); exps(5);
#pragma unroll
          for (int j = 0; j < 4; j++) max2(j);
          exps(6); exps(7);
#pragma unroll
          for (int j = 0; j < 4; j++) exps(j);
          float o[12][4] = {}, sm[4][4] = {};
#pragma unroll
          for (int j = 0; j < 4; j++) {
            const int fa = (j >> 1) * 5 + (j & 1) * 3, fh = (j >> 1) * 5 + 2;
            const uint32_t pl = pack_bf16(l[j][0], l[j][1]), pu = pack_bf16(l[4 + j][0], l[4 + j][1]);
            const uint32_t a0 = pl & pmask, a2 = pl & ~pmask, a3 = pu & pmask, a5 = pu & ~pmask, z0 = z << (2 * j + 1), z1 = z << (2 * j + 2);
            mma8(sm[j], pl, pu, 0x3F803F80u);
#pragma unroll
            for (int q = 0; q < 3; q++) {
              const int f = q < 2 ? fa + q : fh;
              mma8(o[3 * j + q], a2, a3, V[f][0]);
              mma16(o[3 * j + q], a0, z0, z1, a5, Vh[f], V[f][1]);
            }
          }
          sched_fence(z);
          bar_arrive_p(wg == 0, NB_HALO + z, 256);
          uint32_t O[10][2];
#pragma unroll
          for (int j = 0; j < 4; j++) {
            const int fa = (j >> 1) * 5 + (j & 1) * 3, fh = (j >> 1) * 5 + 2;
            float r0, r1;
            asm("rcp.approx.ftz.f32 %0, %1;" : "=f"(r0) : "f"(sm[j][0]));
            asm("rcp.approx.ftz.f32 %0, %1;" : "=f"(r1) : "f"(sm[j][2]));
#pragma unroll
            for (int q = 0; q < 3; q++) {
              const int f = q < 2 ? fa + q : fh;
              const float* e = o[3 * j + q];
              const uint32_t o0 = pack_bf16(e[0] * r0, e[1] * r0), o1 = pack_bf16(e[2] * r1, e[3] * r1);
              if (q < 2 || !(j & 1)) { O[f][0] = o0; O[f][1] = o1; }
              else { O[f][0] = t >= 2 ? o0 : O[f][0]; O[f][1] = t >= 2 ? o1 : O[f][1]; }
            }
          }
          mbar_wait(sb + B_GD, 0);
          const uint32_t oa = sb + O_OST + wg * 2 * STG + (w * 16 + (lane & 15)) * 160 + (lane >> 4) * 16;
#pragma unroll
          for (int i = 0; i < 5; i++) stsm4(oa + i * 32, O[2 * i][0], O[2 * i][1], O[2 * i + 1][0], O[2 * i + 1][1]);
        }
      }
      {
        CTXW();
        fence_async_smem();
        bar_arrive(wg ? NB_LEAD : NB_ATT, 160);
        if (lead) PT(58 + wg);
        const uint32_t abase = sb + (g & 1) * 4160 + 4 * (1023 - 4 - 8 * w - (g >> 1) + t);
        float acc[128];
        uint32_t a0[8], a1[8], a2[8], a3[8];
#pragma unroll 1
        for (int c = wg ^ 1; c < 5; c += 2) {
          const uint32_t ab = abase + o_h(c);
          const uint32_t db = __shfl_sync(~0u, ((SB + o_u(c) + UZ - 16) >> 4) | 0x10000u, 0);
          mbar_wait(sb + B_U + 8 * c, 0);
          load_pair<0>(a0, ab); load_pair<1>(a1, ab); load_pair<2>(a2, ab);
          if (lead) PT(85 + c);
          bar_sync(c ? NB_TOK + wg : NB_HALO, 256);
          fence_regs(acc);
          mma_pair<0>(acc, a0, db);                load_pair<3>(a3, ab);
          mma_pair<1>(acc, a1, db); wg_wait<1>();  load_pair<4>(a0, ab);
          if (lead) PT(90 + c);
          mma_pair<2>(acc, a2, db); wg_wait<1>();  load_pair<5>(a1, ab);
          mma_pair<3>(acc, a3, db); wg_wait<1>();  load_pair<6>(a2, ab);
          mma_pair<4>(acc, a0, db); wg_wait<1>();  load_pair<7>(a3, ab);
          mma_pair<5>(acc, a1, db);
          mma_pair<6>(acc, a2, db);
          bar_arrive_p(c < 4, NB_TOK + (wg ^ 1), 256);
          mma_pair<7>(acc, a3, db);
          bar_arrive_p(c == 4, NB_TOK, 256);
          wg_wait<0>();
          fence_regs(acc);
          PTPL(lead, 95 + c);
          bar_sync(NB_RFREE + wg, 256);
          const uint32_t pb = sb + (w < 2 ? o_h(c) + w * 4160 : w == 2 ? o_u(c) : o_x(c)) + lane * 16;
          if (lane < 2 * w) sts128(pb, 0, 0, 0, 0);
#pragma unroll
          for (int q = 0; q < 8; q++) {
            uint32_t p[4];
#pragma unroll
            for (int i = 0; i < 4; i++) {
              const int nu = 4 * q + i;
              p[i] = pack_bf16(acc[4 * nu], acc[4 * nu + 1]);
              if (nu > 0) p[i] = hadd2(p[i], pack_bf16(acc[4 * nu - 2], acc[4 * nu - 1]));
            }
            stsm4t(pb + w * 32 + q * 512, p[0], p[1], p[2], p[3]);
            if (q == 3) bar_arrive_p(c == 4, NB_RFULL + 1, 256);
          }
          if (c < 4) bar_arrive(NB_RFULL + wg, 256);
          if (lead) PT(140 + c);
        }
        if (wg) {
          const int yb = (lds32(sb + O_EPOCH) & 1) * 640;
          conv_reduce<1, 2>(sb, 4, tid - 128, yb + 512 + ((vb & 0x61) | (vb & 6) << 2 | (vb >> 2 & 6)), 14, 128);
          bar_arrive(12, 256);
          PTPL(lead, 45);
        }
      }
    }
    if (warp < 4) {
      CTXW();
      const uint32_t rsb = mapa(sb, (blockIdx.x & 1) ^ 1);
      const uint32_t ba = sb + O_BT + ((lane >> 4) * 8 + (lane & 7)) * 128 + (((2 * w + ((lane >> 3) & 1)) ^ ((lane & 1) << 2 | (lane >> 1 & 3))) << 4);
      mbar_wait(sb + B_P3F, 0);
      if (lead) PT(145);
      float acc[80];
#pragma unroll
      for (int ks = 0; ks < 10; ks++) {
        if (ks == NPRE) {
          if (NPRE) { wg_wait<0>(); mbar_arrive2_p(lead, sb + B_P3E + 8 * NPRE, rsb + B_P3E + 8 * NPRE); }
          bar_sync_p(blockIdx.x < 128, NB_TOK, 256);
        }
        PTP(lead, 146 + ks);
        const uint64_t da = mkdesc(SB + o_p3(ks), 1024, 1024, 1), db = mkdesc(SB + o_p3(ks) + 8192, 16, 1024, 1);
        wg_fence();
#pragma unroll
        for (int j = 0; j < 4; j++) wgmma_ss_n160<0, 1, 0>(acc, da + j * 128, db + j * 2, j | ks);
        wg_commit();
        if (ks < 9) mbar_wait(sb + B_P3F + 8 * (ks + 1), 0);
        if (ks >= 1 && ks <= 4 && ks != NPRE) { wg_wait<1>(); mbar_arrive2_p(lead, sb + B_P3E + 8 * ks, rsb + B_P3E + 8 * ks); }
      }
      wg_wait<0>();
      fence_regs(acc);
      PTPL(lead, 156);
#pragma unroll
      for (int i = 0; i < 10; i++) {
        stsm4t(ba + i * 2048, pack_bf16(acc[8 * i], acc[8 * i + 1]), pack_bf16(acc[8 * i + 2], acc[8 * i + 3]),
               pack_bf16(acc[8 * i + 4], acc[8 * i + 5]), pack_bf16(acc[8 * i + 6], acc[8 * i + 7]));
        if (i & 1) bar_arrive(1 + (i >> 1), 256);
      }
      if (lead) PT(157);
    }
  } else if (warp < 12) {
    reg_dec<RH>();
    const int hw = warp - 8;
    init_rest();
    ctx = __shfl_sync(~0u, make_ctx(), 0);
    const int yrow = (ctx & 0x61) | (ctx & 6) << 2 | (ctx >> 2 & 6);
    if (ctx < 65536) {
      CTXU();
      const int pr = hw >> 1, hh = hw & 1, tk = vb & 63, odd = (lane >> 2) & 1;
      const uint32_t sel0 = odd ? 0x7632 : 0x5410, sel1 = odd ? 0x5410 : 0x7632;
      const uint32_t in = sb + o_kin(pr), fb = sb + B_KF + 8 * pr, out = sb + O_Y + pr * 8192;
      const uint32_t oa = out + (2 * lane + odd) * 64 + (((3 - 2 * hh) ^ (lane & 3)) << 4), ia = in + hh * 2048 + lane * 4;
      auto fetch = [&](int c) {
        wait_until(t0, KT0 + c * KTD + ((((vb * 37) & 63) * KPH) >> 6));
        if (elect_one()) {
          const int kb = 2 * c + (vb >> 6);
          mbar_expect_tx(fb, 69 * 128);
          tma2(in, &M.k_ld, kb * 64, 32 * tk - 4, fb);
          tma2(in + 36 * 128, &M.v_ld, kb * 64, 32 * tk - 1, fb);
          PT(20 + c);
        }
        __syncwarp();
      };
      if (hh == 0) fetch(pr);
      const uint4* skp = (const uint4*)shift_k + (2 * pr + (vb >> 6)) * 32 + lane;
      uint4 sk = __ldg(skp), sk1 = __ldg(skp + 128), sk2 = __ldg(skp + (pr ? 0 : 256));
#pragma unroll 1
      for (int c = pr; c < 5; c += 2) {
        {
          mbar_wait(fb, (c >> 1) & 1);
          if (hh == 0 && lane == 0) PT(25 + c);
          uint32_t k[20], o[17];
#pragma unroll
          for (int i = 0; i < 20; i++) { k[i] = lds32(ia + i * 128); if (i >= 3) o[i - 3] = lds32(ia + (33 + i) * 128); }
          fence_async_smem();
          bar_sync(12 + pr, 64);
          if (hh == 0) {
            if (c < 3) fetch(c + 2);
            else if (lane == 0) mbar_arrive(sb + B_KVD + 8 * (c - 3));
          }
          const uint32_t w0 = prmt(sk.x, sk.z, 0x5410), w1 = prmt(sk.x, sk.z, 0x7632), w2 = prmt(sk.y, sk.w, 0x5410), w3 = prmt(sk.y, sk.w, 0x7632);
#pragma unroll
          for (int i = 0; i < 17; i++) o[i] = hmul2(hfma2(k[i + 3], w0, hfma2(k[i + 2], w1, hfma2(k[i + 1], w2, hmul2(k[i], w3)))), o[i]);
          sk = sk1; sk1 = sk2;
#pragma unroll
          for (int i = 0; i < 4; i++) {
            const int e = 8 * (i >> 1) + (i & 1);
            const uint32_t a = (oa ^ ((i >> 1) * 16)) + (i & 1) * 4096;
            sts128(a, prmt(o[7 + e], o[6 + e], sel0), prmt(o[5 + e], o[4 + e], sel0), prmt(o[3 + e], o[2 + e], sel0), prmt(o[1 + e], o[e], sel0));
            sts128(a ^ 64, prmt(o[7 + e], o[6 + e], sel1), prmt(o[5 + e], o[4 + e], sel1), prmt(o[3 + e], o[2 + e], sel1), prmt(o[1 + e], o[e], sel1));
          }
          bar_sync(12 + pr, 64);
        }
        if (hh) {
          fence_async_smem();
          if (elect_one()) {
            const int kb = 2 * c + (vb >> 6);
            tma3_store(&M.kv_st, 0, kb * 64, 63 - tk, out);
            tma3_store(&M.kv_st, 0, 640 + kb * 64, 63 - tk, out + 4096);
            bulk_commit(); bulk_wait_all();
            mbar_arrive(sb + (c == 4 ? B_KVD + 16 : B_KVS + 4 * (c & 2)));
            PTL(35 + c);
          }
          __syncwarp();
        }
      }
    }
    CTXU();
    const int g = lane >> 2, t = lane & 3, row = 8 * hw + g;
    const uint32_t go = (tb * 160 + row) * 80 + cb * 8 + t;
    const int yb = __shfl_sync(~0u, get_epoch() & 1, 0) * 640;
    uint4 T[10];
    if (hw == 2) {
      if (main_cta) { mbar_wait(sb + B_LAST, 0); mbar_wait(sb + B_S15, 1); }
      if (elect_one()) {
        mbar_expect_tx(sb + B_Q, 20480);
#pragma unroll
        for (int h = 0; h < 2; h++) tma2(sb + O_QT + h * 10240, &M.q_ld, cb * 64 + 32 * h, tb * 160, sb + B_Q);
      }
      __syncwarp();
    }
    if (QW && main_cta) mbar_wait(sb + B_LAST, 0), mbar_wait(sb + B_U + 8 * (QW - 1), 0);
    mbar_wait(sb + B_Q, 0);
#pragma unroll
    for (int i = 0; i < 10; i++) lds128(sb + O_QT + (i & 1) * 10240 + (i >> 1) * 2048 + row * 64 + t * 16, T[i].x, T[i].y, T[i].z, T[i].w);
    fence_async_smem();
    bar_sync(12 + (hw >> 1), 64);
    if (!(tid & 63)) mbar_arrive(sb + B_QD);
    if (tid == 256) PTL(40);
    if (main_cta) {
      bar_arrive(NB_RFREE, 256);
      bar_arrive(NB_RFREE + 1, 256);
      auto red = [&](int c) {
        const int wg = (c & 1) ^ 1;
        conv_reduce<0, 2>(sb, c, tid - 256, yb + 128 * c + yrow, NB_RFULL + wg, 256);
        if (hw == 3 && elect_one()) flag_add(CNT_Y(4 * c + (vb >> 5)), 1);
        if (tid == 256) PTL(41 + c);
        if (c < 3) bar_arrive(NB_RFREE + wg, 256);
        if (c == 2) {
          bar_sync(NB_HELP, 128);
          if (tid == 256) { mbar_arrive(sb + B_P3E); mbar_arrive_remote(sb + B_P3E, rank ^ 1); }
        }
      };
      if (hw == 3) {
        mbar_wait(sb + B_KVD + 16, 0);
        if (elect_one()) { flag_release(CNT_KV(4 + (vb >> 6))); PTL(32); }
        __syncwarp();
      }
#pragma unroll 1
      for (int c = 0; c < 4; c++) red(c);
    }
    uint32_t G[5];
    mbar_wait(sb + B_G, 0);
#pragma unroll
    for (int q = 0; q < 5; q++) { uint16_t v; asm volatile("ld.shared.u16 %0, [%1];" : "=h"(v) : "r"(sb + O_GT + (32 * q + row) * 2)); G[q] = prmt(v, 0, 0x1010); }
#pragma unroll
    for (int i = 0; i < 10; i++) { const uint32_t c = G[i >> 1] ^ 0x80008000u; T[i] = make_uint4(hmul2(T[i].x, c), hmul2(T[i].y, c), hmul2(T[i].z, c), hmul2(T[i].w, c)); }
    if (main_cta) {
      conv_reduce<0, 1>(sb, 4, tid - 256, yb + 512 + yrow, NB_RFULL + 1, 256);
      if (hw == 3 && elect_one()) flag_add(CNT_Y(16 + (vb >> 5)), 1);
      bar_sync(12, 256);
    }
#pragma unroll
    for (int h = 0; h < 2; h++) {
      mbar_wait_wd(sb + B_Y + 8 * h, 0, t0);
      if (tid == 256) PT(46);
      const uint32_t ya = sb + O_Y + h * 10240 + lane * 64 + ((hw ^ ((lane >> 1) & 3)) << 4);
      uint4 y[5];
      for (;;) {
        uint32_t m = ~0u;
#pragma unroll
        for (int q = 4; q >= 0; q--) {
          ldsm4t(y[q].x, y[q].y, y[q].z, y[q].w, ya + q * 2048);
          m = __vimin3_u16x2(__vimin3_u16x2(m, y[q].x, y[q].y), y[q].z, y[q].w);
          if (q == 4 && tb == 12) m = ~0u;
        }
        if (!__any_sync(~0u, (m & 0xFFFFu) == 0 || m < 0x10000u)) break;
#pragma unroll
        for (int q = 0; q < 5; q++)
          asm volatile("ld.relaxed.gpu.global.v4.b32 {%0,%1,%2,%3}, [%4];" : "=r"(y[q].x), "=r"(y[q].y), "=r"(y[q].z), "=r"(y[q].w)
                       : "l"((const uint4*)g_y2T + (yb + cb * 64 + 32 * h + lane) * 256 + tb * 20 + (q == 4 && tb == 12 ? 0 : 4 * q) + hw) : "memory");
#pragma unroll
        for (int q = 0; q < 5; q++) sts128(ya + q * 2048, y[q].x, y[q].y, y[q].z, y[q].w);
        __syncwarp();
        PTL(49);
      }
#pragma unroll
      for (int q = 0; q < 5; q++) {
        uint4& r = T[2 * q + h];
        r = make_uint4(hmul2(r.x, y[q].x), hmul2(r.y, y[q].y), hmul2(r.z, y[q].z), hmul2(r.w, y[q].w));
      }
    }
    const uint32_t so = sb + O_BT + row * 128 + ((t ^ ((g & 1) << 2 | g >> 1)) << 4);
    if (tid == 256) PTL(47);
#pragma unroll
    for (int q = 0; q < 5; q++) {
      const uint32_t c = hfma2(G[q], 0xBF80BF80u, 0x3F803F80u);
      bar_sync(1 + q, 256);
      if (q == 4) mbar_arrive_p(tid == 256, sb + B_DONE);
#pragma unroll
      for (int h = 0; h < 2; h++) {
        uint4 u;
        lds128((so ^ (h * 64)) + q * 4096, u.x, u.y, u.z, u.w);
        const uint4& r = T[2 * q + h];
        if (q < 4 || tb < 12) ((uint4*)outp)[go + q * 2560 + h * 4] = make_uint4(hfma2(u.x, c, r.x), hfma2(u.y, c, r.y), hfma2(u.z, c, r.z), hfma2(u.w, c, r.w));
      }
    }
  } else {
    reg_dec<RP>();
    uint4 gwv = make_uint4(0, 0, 0, 0);
    if (warp == 15) {
      const int p = cta_pair(), rank = blockIdx.x & 1;
      asm volatile("barrier.cluster.wait.aligned;" ::: "memory");
      if (blockIdx.x >= 128) bar_sync(0, 512);
      else {
#pragma unroll 1
        for (int ks = 1;; ks += 2) {
          mbar_wait(sb + B_EMPTY + 8 * (ks & 7), ((ks >> 3) & 1) ^ 1);
          spin_until(t0, PT1 + (ks - 1) * PTD);
          if (elect_one()) { mbar_expect_tx(sb + B_FULL + 8 * (ks & 7), WST); p1_load_w(ks, p, rank); PT(100 + ks); }
          if (ks == 19) break;
          const int kn = ks + 1;
          mbar_wait(sb + B_EMPTY + 8 * (kn & 7), ((kn >> 3) & 1) ^ 1);
          spin_until(t0, PT1 + ks * PTD - PTE);
          if (elect_one()) { mbar_expect_tx(sb + B_FULL + 8 * (kn & 7), 16384 + WST); p1_load_x(kn, p, rank); p1_load_w(kn, p, rank); PT(100 + kn); }
        }
        if (elect_one()) mbar_arrive(sb + B_LAST);
#pragma unroll 1
        for (int i = 0; i < 2; i++) {
          mbar_wait(sb + B_KVS + 8 * i, 0);
          if (elect_one()) { flag_release(CNT_KV(2 * i + (p >> 5))); PTL(30 + i); }
          __syncwarp();
        }
        mbar_wait(sb + B_S19, 0);
      }
    } else {
      if (threadIdx.x < 384 + 80) gwv = __ldg((const uint4*)gate_w + threadIdx.x - 384);
      init_rest();
    }
    ctx = __shfl_sync(~0u, make_ctx(), 0);
    CTXU();
    if (warp == 12) {
        unsigned epoch = 0;
      if (lane == 0) epoch = *(volatile unsigned*)(g_launch + 32 * vb) + 1;
      if (main_cta) { sts128(sb + O_GW + lane * 16, gwv.x, gwv.y, gwv.z, gwv.w); bar_arrive(NB_G, 96); }
      if (lane == 0) {
        if ((sb & 0xFFFFFF) != SB) __trap();
        sts32(sb + O_EPOCH, epoch);
        mbar_arrive(sb + B_EP);
#pragma unroll 1
        for (int i = 5; i < 11; i++) asm volatile("prefetch.tensormap [%0];" ::"l"(&M.x_par + i) : "memory");
      }
      if (main_cta && rank) {
#pragma unroll
        for (int f = 0; f < 5; f++) st_relaxed(g_halo + vb * 160 + lane + 32 * f, ~0u, ~0u, ~0u, ~0u);
      }
      __syncwarp();
      if (elect_one()) flag_release(g_launch + 32 * vb);
      __syncwarp();
      if (main_cta) {
        uint4 h0 = make_uint4(0, 0, 0, 0);
        if (lane < 5) {
          h0 = __ldg((const uint4*)(ssm_k + (size_t)(128 * lane + vb) * 2048));
          h0.x = prmt(pack_bf16(bf_lo(h0.x) + bf_lo(__ldg(ssm_D + 128 * lane + vb)), 0.f), h0.x, 0x7610);
        }
        epoch = __shfl_sync(~0u, epoch, 0);
        const int ze = lane & 7;
        const uint32_t za = sb + (lane < 8 ? o_u(ze) + UZ : lane < 24 ? o_h(ze) + (lane >> 4) * 4160 + 4096 : o_u(ze) + 512);
        const uint16_t* hp = ssm_k + (size_t)vb * 2048 + 8;
        const uint16_t* up = g_kvT + (size_t)vb * 2048;
        const unsigned* fp = CNT_KV(vb >> 6);
        sts128(sb + O_Y - 512 + lane * 16, 0, 0, 0, 0);
        mbar_wait(sb + B_LAST, 0);
        mbar_wait(sb + B_S13, 1);
#pragma unroll
        for (int c = 0; c < 5; c++) {
          if (c == 0 || c == 3) {
            mbar_wait(sb + B_KVD + (c ? 8 : 0), 0);
#pragma unroll
            for (int e = c; e < (c ? 5 : 3); e++) sts128(sb + o_u(e) + lane * 16, 0, 0, 0, 0);
            if (ze >= c && ze < (c ? 5 : 3)) sts128(za, h0.x, h0.y, h0.z, h0.w);
            fence_async_smem();
            __syncwarp();
            if (elect_one()) {
#pragma unroll
              for (int e = c; e < (c ? 5 : 3); e++) {
                mbar_expect_tx(sb + B_U + 8 * e, 3 * 4096 - 16);
                if (c || e == 0) bulk_load(sb + o_u(e) + UZ + 16, hp + 128 * 2048 * e, 4080, sb + B_U + 8 * e);
              }
            }
          }
          if (c == 0 && lane == 0) PTL(34);
          if (!(c & 1)) { flag_wait(fp + 32 * c, 64 * epoch); __syncwarp(); }
          if (elect_one()) {
            bulk_load(sb + o_h(c), up + 128 * 2048 * c, 4096, sb + B_U + 8 * c);
            bulk_load(sb + o_h(c) + 4160, up + (640 + 128 * c) * 2048, 4096, sb + B_U + 8 * c);
            if (c == 1) {
#pragma unroll
              for (int e = 1; e < 3; e++) bulk_load(sb + o_u(e) + UZ + 16, hp + 128 * 2048 * e, 4080, sb + B_U + 8 * e);
            }
            PTL(10 + c);
          }
        }
        mbar_wait(sb + B_LAST, 1);
        if (elect_one()) {
#pragma unroll 1
          for (int i = 0; i < 40; i++) bulk_store(g_y2T + (size_t)((~epoch & 1) * 640 + 5 * vb) * 2048 + i * 256, sb + O_Y - 512, 512);
          bulk_commit(); bulk_wait_read();
          PTL(33);
        }
      }
    } else if (warp != 15) {
        const int r = warp - 13;
      if (main_cta) {
        if (rank && lane == 0) mbar_expect_tx(sb + B_HX0, 1280);
        const int t = lane & 3, grow = hg * 16 + (lane & 15);
        const uint32_t ga = sb + grow * 128 + (((4 * r + (lane >> 4)) ^ (lane & 7)) << 4);
        const uint32_t gp = sb + O_GW + 64 * r + 4 * t;
        float s0 = 0.f, s1 = 0.f;
        if (tid < 384 + 80) sts128(sb + O_GW + (tid - 384) * 16, gwv.x, gwv.y, gwv.z, gwv.w);
        bar_sync(NB_G, 96);
#pragma unroll 1
        for (int ks = 0; ks < 20; ks += 2) {
          uint32_t x[8], gw[4];
#pragma unroll
          for (int i = 0; i < 4; i++) gw[i] = lds32(gp + ks * 64 + i * 16);
          mbar_wait_wd(sb + B_FULL + 8 * (ks & 7), (ks >> 3) & 1, t0);
          if (r == 0 && lane == 0) PT(120 + ks);
          ldsm4(x[0], x[1], x[2], x[3], ga + o_px(ks)); ldsm4(x[4], x[5], x[6], x[7], (ga ^ 32) + o_px(ks));
#pragma unroll
          for (int i = 0; i < 8; i++) x[i] = hmul2(x[i], gw[i >> 1]);
          if (lane < 2) mbar_arrive(sb + B_EMPTY + 8 * (ks & 7) + 8 * lane + (x[0] & x[7] & threadIdx.y));
#pragma unroll
          for (int i = 0; i < 8; i += 4) {
            s0 += (bf_lo(x[i]) + bf_hi(x[i])) + (bf_lo(x[i + 2]) + bf_hi(x[i + 2]));
            s1 += (bf_lo(x[i + 1]) + bf_hi(x[i + 1])) + (bf_lo(x[i + 3]) + bf_hi(x[i + 3]));
          }
        }
        s0 += __shfl_xor_sync(~0u, s0, 1); s1 += __shfl_xor_sync(~0u, s1, 1);
        s0 += __shfl_xor_sync(~0u, s0, 2); s1 += __shfl_xor_sync(~0u, s1, 2);
        if (t < 2) sts32(sb + O_GP + r * 64 + (8 * t + (lane >> 2)) * 4, __float_as_uint(t ? s1 : s0));
        if (lane == 0) mbar_arrive(sb + B_GD);
        if (r == 0) bar_arrive(NB_G, 64);
        if (!rank) {
          uint4 d[3];
          if (mt > 0) {
            const uint4* hp = g_halo + (vb - 1) * 160 + r * 64 + lane;
            mbar_wait_wd(sb + B_EP, 0, t0);
            flag_wait_wd(g_launch + 32 * (vb - 1), lds32(sb + O_EPOCH), t0);
            mbar_wait_wd(sb + B_HX + 56, 0, t0);
            for (;;) {
              bool ok = true;
#pragma unroll
              for (int f = 0; f < 3; f++) {
                asm volatile("ld.relaxed.gpu.global.v4.b32 {%0,%1,%2,%3}, [%4];" : "=r"(d[f].x), "=r"(d[f].y), "=r"(d[f].z), "=r"(d[f].w) : "l"(hp + 32 * f) : "memory");
              }
#pragma unroll
              for (int f = 0; f < 3; f++) ok = ok && max(max(d[f].x, d[f].y), max(d[f].z, d[f].w)) != ~0u;
              if (__all_sync(~0u, ok)) break;
              if (clk() - t0 > 0x70000000u) __trap();
            }
          } else {
#pragma unroll
            for (int f = 0; f < 3; f++) d[f] = make_uint4(0, 0, 0, 0);
          }
#pragma unroll
          for (int f = 0; f < 3; f++) stsm4(sb + O_HIN + r * 1024 + f * 512 + lane * 16, d[f].x, d[f].y, d[f].z, d[f].w);
          __syncwarp();
          if (lane == 0) { mbar_arrive(sb + B_HX0); PTL(15 + r); }
        }
        if (r == 1) {
          bar_sync(NB_G, 64);
          if (lane < 16) {
            const uint32_t pa = sb + O_GP + lane * 4;
            const float z = __uint_as_float(lds32(pa)) + __uint_as_float(lds32(pa + 64));
            g_gate[2 * (mt * 128 + hg * 16 + lane) + par] = (uint16_t)pack_bf16(__fdividef(1.f, 1.f + __expf(-bf_lo(pack_bf16(z, 0.f)))), 0.f);
          }
          __syncwarp();
          if (elect_one()) flag_release(CNT_O(rt));
        }
      }
      mbar_wait_wd(sb + B_EP, 0, t0);
      const unsigned epoch = lds32(sb + O_EPOCH);
      if (main_cta) mbar_wait_wd(sb + B_P3E, 0, t0);
      flag_wait_wd(CNT_Y(2 * cb + r), 32 * epoch, t0);
      __syncwarp();
      if (elect_one()) {
        mbar_expect_tx(sb + B_Y + 8 * r, 10240);
        tma3(sb + O_Y + r * 10240, &M.y_ld, 0, (epoch & 1) * 640 + cb * 64 + 32 * r, tb * 5, sb + B_Y + 8 * r);
        PTL(17 + r);
      }
      __syncwarp();
      mbar_wait_wd(sb + B_DONE, 0, t0);
    } else {
      const unsigned epoch = get_epoch();
      if (main_cta) {
        bar_sync(NB_LEAD, 160);
        if (elect_one()) tma3_store(&M.o_st, hg * 80, par, mt * 128 + 64, sb + O_OST + 2 * STG);
        bar_sync(NB_ATT, 160);
        if (elect_one()) {
          tma3_store(&M.o_st, hg * 80, par, mt * 128, sb + O_OST);
          bulk_commit(); bulk_wait_all();
          flag_release(CNT_O(rt));
          mbar_arrive(sb + B_LAST);
          PTL(3);
        }
        __syncwarp();
      }
      mbar_wait(sb + B_QD, 0);
#pragma unroll 1
      for (int ks = 0; ks < 5; ks++)
        if (elect_one()) tma2(sb + o_p3(ks), &M.wo, cb * 64, ks * 64, sb + B_P3F + 8 * ks);
      if (lane < 4) flag_wait(CNT_O(8 * (lane & 1) + min(7, (80 * tb + 79 * (lane >> 1)) >> 7)), 16 * epoch);
      __syncwarp();
      if (elect_one()) {
        PTL(4);
        mbar_arrive_remote(sb + B_P3R, rank ^ 1);
        mbar_expect_tx(sb + B_G, 320);
        bulk_load(sb + O_GT, g_gate + tb * 160, 320, sb + B_G);
      }
      mbar_wait(sb + B_P3R, 0);
#pragma unroll 1
      for (int ks = 0; ks < 10; ks++) {
        if (ks > 5 || (ks == 5 && main_cta)) mbar_wait(sb + B_P3E + 8 * (ks - 5), 0);
        if (elect_one()) {
          PTP(ks >= 5, ks);
          tma2_mc(sb + o_p3(ks) + 8192 + rank * 10240, &M.o_ld, ks * 64, tb * 160 + rank * 80, sb + B_P3F + 8 * ks);
          if (ks >= 5) tma2(sb + o_p3(ks), &M.wo, cb * 64, ks * 64, sb + B_P3F + 8 * ks);
          mbar_expect_tx(sb + B_P3F + 8 * ks, P3S);
        }
      }
    }
  }
}

typedef CUresult (*PFN_enc)(CUtensorMap*, CUtensorMapDataType, cuuint32_t, void*, const cuuint64_t*, const cuuint64_t*, const cuuint32_t*,
                            const cuuint32_t*, CUtensorMapInterleave, CUtensorMapSwizzle, CUtensorMapL2promotion, CUtensorMapFloatOOBfill);
static void enc(PFN_enc f, CUtensorMap* m, const void* base, int rank, const cuuint64_t* dims, const cuuint64_t* strides, const cuuint32_t* box,
                CUtensorMapSwizzle sw) {
  const cuuint32_t es[5] = {1, 1, 1, 1, 1};
  f(m, CU_TENSOR_MAP_DATA_TYPE_BFLOAT16, rank, (void*)base, dims, strides, box, es, CU_TENSOR_MAP_INTERLEAVE_NONE, sw,
    CU_TENSOR_MAP_L2_PROMOTION_NONE, CU_TENSOR_MAP_FLOAT_OOB_FILL_NONE);
}

extern "C" void kernel_launch(void* const* d_in, const int* in_sizes, int n_in, void* d_out, int out_size) {
  (void)in_sizes; (void)n_in; (void)out_size;
  static PFN_enc f = nullptr;
  static void *kvT, *y2T, *o;
  if (!f) {
    void* p = nullptr;
    cudaDriverEntryPointQueryResult q;
    cudaGetDriverEntryPoint("cuTensorMapEncodeTiled", &p, cudaEnableDefault, &q);
    f = (PFN_enc)p;
    cudaGetSymbolAddress(&kvT, g_kvT); cudaGetSymbolAddress(&y2T, g_y2T); cudaGetSymbolAddress(&o, g_o);
    cudaFuncSetAttribute(fused_kernel, cudaFuncAttributeMaxDynamicSharedMemorySize, SMEM_BYTES);
  }
  Maps M;
  const CUtensorMapSwizzle S0 = CU_TENSOR_MAP_SWIZZLE_NONE, S32 = CU_TENSOR_MAP_SWIZZLE_32B, S64 = CU_TENSOR_MAP_SWIZZLE_64B, S128 = CU_TENSOR_MAP_SWIZZLE_128B;
  const cuuint64_t dpar[3] = {640, 2, 1024}, spar[2] = {1280, 2560};
  const cuuint64_t dw[3] = {640, 640, 3}, sw[2] = {3840, 1280};
  const cuuint64_t dnat[2] = {640, 2048}, snat[1] = {1280};
  const cuuint64_t dT2[3] = {32, 1280, 64}, sT[2] = {4096, 64};
  const cuuint64_t dwo[2] = {640, 640};
  { const cuuint32_t bx[3] = {64, 1, 128}; enc(f, &M.x_par, d_in[0], 3, dpar, spar, bx, S128); }
  { const cuuint32_t bx[3] = {64, 16, 3}; enc(f, &M.w_main, d_in[7], 3, dw, sw, bx, S128); }
  { const cuuint32_t bx[3] = {16, 16, 3}; enc(f, &M.w_tail, d_in[7], 3, dw, sw, bx, S32); }
  { const cuuint32_t bx[3] = {80, 1, 64}; enc(f, &M.o_st, o, 3, dpar, spar, bx, S0); }
  { const cuuint32_t bx[3] = {32, 64, 1}; enc(f, &M.kv_st, kvT, 3, dT2, sT, bx, S64); }
  { const cuuint32_t bx[3] = {32, 32, 5}; enc(f, &M.y_ld, y2T, 3, dT2, sT, bx, S64); }
  { const cuuint32_t bx[2] = {64, 36}; enc(f, &M.k_ld, d_in[1], 2, dnat, snat, bx, S0); }
  { const cuuint32_t bx[2] = {64, 33}; enc(f, &M.v_ld, d_in[2], 2, dnat, snat, bx, S0); }
  { const cuuint32_t bx[2] = {32, 160}; enc(f, &M.q_ld, d_in[0], 2, dnat, snat, bx, S0); }
  { const cuuint32_t bx[2] = {64, 64}; enc(f, &M.wo, d_in[8], 2, dwo, snat, bx, S128); }
  { const cuuint32_t bx[2] = {64, 80}; enc(f, &M.o_ld, o, 2, dnat, snat, bx, S128); }
  fused_kernel<<<130, 512, SMEM_BYTES, cudaStreamPerThread>>>((const uint16_t*)d_in[0], (const uint16_t*)d_in[7], (const uint16_t*)d_in[9], M, (const uint16_t*)d_in[3], (const uint16_t*)d_in[4], (const uint16_t*)d_in[5],
                                                              (uint16_t*)d_out);
}
```

```cpp
#include <cuda_runtime.h>
#include <cuda_bf16.h>
#include <cuda.h>
#include <stdint.h>

#define DEVI __device__ __forceinline__
#define PT1 300
#define PTD 460
#define PTE 150
#define DEFER 4
#define KPH KTD
#define NPRE 1
#define NLATE 4
#define P3L 1
#define TOKP 6
#define P3MAP 2
#define RLATE 0
#define KT0 1500
#define KTD 1000
#define RC 192
#define RH 96
#define RP 32
#define HOLD 750
#define LEAD 3

DEVI uint32_t smem_u32(const void* p) { return (uint32_t)__cvta_generic_to_shared(p); }
DEVI void wg_fence() { asm volatile("wgmma.fence.sync.aligned;" ::: "memory"); }
DEVI void wg_commit() { asm volatile("wgmma.commit_group.sync.aligned;" ::: "memory"); }
template <int N> DEVI void wg_wait() { asm volatile("wgmma.wait_group.sync.aligned %0;" ::"n"(N) : "memory"); }
template <int A = 0, int B = -1, int S> DEVI void fence_regs(float (&d)[S]) {
#pragma unroll
  for (int i = A; i < (B < 0 ? S : B); i++) asm volatile("" : "+f"(d[i])::"memory");
}
DEVI uint64_t mkdesc(uint32_t addr, uint32_t lbo, uint32_t sbo, int swz) {
  return (uint64_t)((addr & 0x3FFFF) >> 4) | ((uint64_t)(lbo >> 4) << 16) | ((uint64_t)(sbo >> 4) << 32) | ((uint64_t)swz << 62);
}
DEVI void mbar_init(uint32_t bar, uint32_t cnt) { asm volatile("mbarrier.init.shared::cta.b64 [%0], %1;" ::"r"(bar), "r"(cnt) : "memory"); }
DEVI void mbar_expect_tx(uint32_t bar, uint32_t bytes) { asm volatile("mbarrier.arrive.expect_tx.shared::cta.b64 _, [%0], %1;" ::"r"(bar), "r"(bytes) : "memory"); }
DEVI void mbar_arrive(uint32_t bar) { asm volatile("mbarrier.arrive.shared::cta.b64 _, [%0];" ::"r"(bar) : "memory"); }
DEVI void mbar_wait(uint32_t bar, uint32_t parity) {
  asm volatile("{\n.reg .pred p;\nLAB_WAIT:\nmbarrier.try_wait.parity.shared::cta.b64 p, [%0], %1;\n@!p bra LAB_WAIT;\n}" ::"r"(bar), "r"(parity) : "memory");
}
DEVI void mbar_wait_wd(uint32_t bar, uint32_t parity, uint32_t t0) {
  asm volatile("{\n.reg .pred p;\n.reg .u32 c;\nLAB_WAIT:\nmbarrier.try_wait.parity.shared::cta.b64 p, [%0], %1;\n@p bra DONE;\nmov.u32 c, %%clock;\nsub.u32 c, c, %2;\nsetp.lt.u32 p, c, 0x70000000;\n@p bra LAB_WAIT;\ntrap;\nDONE:\n}" ::"r"(bar), "r"(parity), "r"(t0) : "memory");
}
DEVI void flag_wait(const unsigned* p, unsigned target) {
  asm volatile("{\n.reg .pred p;\n.reg .s32 v;\nLAB_WAIT:\nld.relaxed.gpu.global.u32 v, [%0];\nsub.s32 v, v, %1;\nsetp.lt.s32 p, v, 0;\n@p bra LAB_WAIT;\n}" ::"l"(p), "r"(target) : "memory");
}
DEVI void flag_wait_wd(const unsigned* p, unsigned target, uint32_t t0) {
  asm volatile("{\n.reg .pred p;\n.reg .s32 v;\nLAB_WAIT:\nld.relaxed.gpu.global.u32 v, [%0];\nsub.s32 v, v, %1;\nsetp.ge.s32 p, v, 0;\n@p bra DONE;\nmov.u32 v, %%clock;\nsub.s32 v, v, %2;\nsetp.lt.u32 p, v, 0x70000000;\n@p bra LAB_WAIT;\ntrap;\nDONE:\n}" ::"l"(p), "r"(target), "r"(t0) : "memory");
}
DEVI void flag_add(unsigned* p, unsigned v) { asm volatile("red.relaxed.gpu.global.add.u32 [%0], %1;" ::"l"(p), "r"(v) : "memory"); }
DEVI void flag_release(unsigned* p) { asm volatile("fence.proxy.async;\nred.relaxed.gpu.global.add.u32 [%0], 1;" ::"l"(p) : "memory"); }
DEVI void fence_async_smem() { asm volatile("fence.proxy.async.shared::cta;" ::: "memory"); }
DEVI bool elect_one() { uint32_t p; asm volatile("{\n.reg .pred P;\nelect.sync _|P, 0xffffffff;\nselp.u32 %0, 1, 0, P;\n}" : "=r"(p)); return p; }
DEVI void bar_sync(int id, int n) { asm volatile("bar.sync %0, %1;" ::"r"(id), "r"(n) : "memory"); }
DEVI void bar_arrive(int id, int n) { asm volatile("bar.arrive %0, %1;" ::"r"(id), "r"(n) : "memory"); }
DEVI void tma2(uint32_t dst, const CUtensorMap* m, int c0, int c1, uint32_t bar) {
  asm volatile("cp.async.bulk.tensor.2d.shared::cluster.global.mbarrier::complete_tx::bytes [%0], [%1, {%3, %4}], [%2];" ::"r"(dst), "l"(m), "r"(bar), "r"(c0), "r"(c1) : "memory");
}
DEVI void tma3(uint32_t dst, const CUtensorMap* m, int c0, int c1, int c2, uint32_t bar) {
  asm volatile("cp.async.bulk.tensor.3d.shared::cluster.global.mbarrier::complete_tx::bytes [%0], [%1, {%3, %4, %5}], [%2];" ::"r"(dst), "l"(m), "r"(bar), "r"(c0), "r"(c1), "r"(c2) : "memory");
}
DEVI void tma3_mc(uint32_t dst, const CUtensorMap* m, int c0, int c1, int c2, uint32_t bar) {
  asm volatile("cp.async.bulk.tensor.3d.shared::cluster.global.mbarrier::complete_tx::bytes.multicast::cluster [%0], [%1, {%3, %4, %5}], [%2], %6;" ::"r"(dst), "l"(m), "r"(bar), "r"(c0), "r"(c1), "r"(c2), "h"((uint16_t)3) : "memory");
}
DEVI void tma2_mc(uint32_t dst, const CUtensorMap* m, int c0, int c1, uint32_t bar) {
  asm volatile("cp.async.bulk.tensor.2d.shared::cluster.global.mbarrier::complete_tx::bytes.multicast::cluster [%0], [%1, {%3, %4}], [%2], %5;" ::"r"(dst), "l"(m), "r"(bar), "r"(c0), "r"(c1), "h"((uint16_t)3) : "memory");
}
DEVI void mbar_arrive_remote(uint32_t bar, uint32_t cta) {
  asm volatile("{\n.reg .b32 ra;\nmapa.shared::cluster.u32 ra, %0, %1;\nmbarrier.arrive.shared::cluster.b64 _, [ra];\n}" ::"r"(bar), "r"(cta) : "memory");
}
DEVI void tma3_store(const CUtensorMap* m, int c0, int c1, int c2, uint32_t src) {
  asm volatile("cp.async.bulk.tensor.3d.global.shared::cta.bulk_group [%0, {%2, %3, %4}], [%1];" ::"l"(m), "r"(src), "r"(c0), "r"(c1), "r"(c2) : "memory");
}
DEVI void bulk_load(uint32_t dst, const void* src, uint32_t bytes, uint32_t bar) {
  asm volatile("cp.async.bulk.shared::cluster.global.mbarrier::complete_tx::bytes [%0], [%1], %2, [%3];" ::"r"(dst), "l"(src), "r"(bytes), "r"(bar) : "memory");
}
DEVI void bulk_store(void* dst, uint32_t src, uint32_t bytes) {
  asm volatile("cp.async.bulk.global.shared::cta.bulk_group [%0], [%1], %2;" ::"l"(dst), "r"(src), "r"(bytes) : "memory");
}
DEVI void pf_l2(const void* p) { asm volatile("prefetch.global.L2 [%0];" ::"l"(p)); }
template <int OFF> DEVI uint32_t ldg_v(const void* p) { uint32_t v; asm volatile("ld.volatile.global.b32 %0, [%1 + %2];" : "=r"(v) : "l"(p), "n"(OFF)); return v; }
DEVI void bulk_commit() { asm volatile("cp.async.bulk.commit_group;" ::: "memory"); }
DEVI void bulk_wait_all() { asm volatile("cp.async.bulk.wait_group 0;" ::: "memory"); }
DEVI void bulk_wait_read() { asm volatile("cp.async.bulk.wait_group.read 0;" ::: "memory"); }
template <int R> DEVI void reg_inc() { asm volatile("setmaxnreg.inc.sync.aligned.u32 %0;" ::"n"(R)); }
template <int R> DEVI void reg_dec() { asm volatile("setmaxnreg.dec.sync.aligned.u32 %0;" ::"n"(R)); }
DEVI uint32_t prmt(uint32_t a, uint32_t b, uint32_t s) { uint32_t r; asm("prmt.b32 %0,%1,%2,%3;" : "=r"(r) : "r"(a), "r"(b), "r"(s)); return r; }
DEVI uint32_t lds32(uint32_t a) { uint32_t r; asm volatile("ld.shared.b32 %0,[%1];" : "=r"(r) : "r"(a)); return r; }
DEVI void sts32(uint32_t a, uint32_t x) { asm volatile("st.shared.b32 [%0],%1;" ::"r"(a), "r"(x) : "memory"); }
DEVI void sts128(uint32_t a, uint32_t x, uint32_t y, uint32_t z, uint32_t w) { asm volatile("st.shared.v4.b32 [%0],{%1,%2,%3,%4};" ::"r"(a), "r"(x), "r"(y), "r"(z), "r"(w) : "memory"); }
DEVI void sts128v(uint32_t a, uint32_t x, uint32_t y, uint32_t z, uint32_t w) { asm volatile("st.volatile.shared.v4.b32 [%0],{%1,%2,%3,%4};" ::"r"(a), "r"(x), "r"(y), "r"(z), "r"(w) : "memory"); }
DEVI void lds128(uint32_t a, uint32_t& x, uint32_t& y, uint32_t& z, uint32_t& w) { asm volatile("ld.shared.v4.b32 {%0,%1,%2,%3},[%4];" : "=r"(x), "=r"(y), "=r"(z), "=r"(w) : "r"(a) : "memory"); }
DEVI void ldsm4(uint32_t& r0, uint32_t& r1, uint32_t& r2, uint32_t& r3, uint32_t addr) {
  asm volatile("ldmatrix.sync.aligned.m8n8.x4.shared.b16 {%0,%1,%2,%3}, [%4];" : "=r"(r0), "=r"(r1), "=r"(r2), "=r"(r3) : "r"(addr) : "memory");
}
DEVI void ldsm4t(uint32_t& r0, uint32_t& r1, uint32_t& r2, uint32_t& r3, uint32_t addr) {
  asm volatile("ldmatrix.sync.aligned.m8n8.x4.trans.shared.b16 {%0,%1,%2,%3}, [%4];" : "=r"(r0), "=r"(r1), "=r"(r2), "=r"(r3) : "r"(addr) : "memory");
}
DEVI void stsm4(uint32_t addr, uint32_t r0, uint32_t r1, uint32_t r2, uint32_t r3) {
  asm volatile("stmatrix.sync.aligned.m8n8.x4.shared.b16 [%0], {%1,%2,%3,%4};" ::"r"(addr), "r"(r0), "r"(r1), "r"(r2), "r"(r3) : "memory");
}
DEVI void stsm4t(uint32_t addr, uint32_t r0, uint32_t r1, uint32_t r2, uint32_t r3) {
  asm volatile("stmatrix.sync.aligned.m8n8.x4.trans.shared.b16 [%0], {%1,%2,%3,%4};" ::"r"(addr), "r"(r0), "r"(r1), "r"(r2), "r"(r3) : "memory");
}
DEVI uint32_t movm(uint32_t a) { uint32_t r; asm volatile("movmatrix.sync.aligned.m8n8.trans.b16 %0, %1;" : "=r"(r) : "r"(a)); return r; }
DEVI uint32_t pack_bf16(float lo, float hi) { uint32_t r; asm("cvt.rn.bf16x2.f32 %0, %1, %2;" : "=r"(r) : "f"(hi), "f"(lo)); return r; }
DEVI uint32_t hmul2(uint32_t a, uint32_t b) { uint32_t r; asm("mul.rn.bf16x2 %0,%1,%2;" : "=r"(r) : "r"(a), "r"(b)); return r; }
DEVI uint32_t hadd2(uint32_t a, uint32_t b) { uint32_t r; asm("add.rn.bf16x2 %0,%1,%2;" : "=r"(r) : "r"(a), "r"(b)); return r; }
DEVI float bf_lo(uint32_t a) { return __uint_as_float(prmt(a, 0, 0x1044)); }
DEVI float bf_hi(uint32_t a) { return __uint_as_float(a & 0xFFFF0000u); }
DEVI void mma16(float (&c)[4], uint32_t a0, uint32_t a1, uint32_t a2, uint32_t a3, uint32_t b0, uint32_t b1) {
  asm volatile("mma.sync.aligned.m16n8k16.row.col.f32.bf16.bf16.f32 {%0,%1,%2,%3},{%4,%5,%6,%7},{%8,%9},{%0,%1,%2,%3};"
      : "+f"(c[0]), "+f"(c[1]), "+f"(c[2]), "+f"(c[3]) : "r"(a0), "r"(a1), "r"(a2), "r"(a3), "r"(b0), "r"(b1));
}
DEVI void mma8(float (&c)[4], uint32_t a0, uint32_t a1, uint32_t b0) {
  asm volatile("mma.sync.aligned.m16n8k8.row.col.f32.bf16.bf16.f32 {%0,%1,%2,%3},{%4,%5},{%6},{%0,%1,%2,%3};"
      : "+f"(c[0]), "+f"(c[1]), "+f"(c[2]), "+f"(c[3]) : "r"(a0), "r"(a1), "r"(b0));
}
DEVI float ex2(float x) { float r; asm volatile("ex2.approx.ftz.f32 %0, %1;" : "=f"(r) : "f"(x)); return r; }

DEVI uint32_t clk() { uint32_t c; asm volatile("mov.u32 %0, %%clock;" : "=r"(c)); return c; }
DEVI void wait_until(uint32_t t0, int dt) { while ((int)(clk() - t0) < dt) __nanosleep(40); }
DEVI void spin_until(uint32_t t0, int dt) { while ((int)(clk() - t0) < dt) {} }
DEVI uint32_t hfma2(uint32_t a, uint32_t b, uint32_t c) { uint32_t r; asm("fma.rn.bf16x2 %0,%1,%2,%3;" : "=r"(r) : "r"(a), "r"(b), "r"(c)); return r; }
DEVI void bar_sync_p(int on, int id, int n) { asm volatile("{\n.reg .pred p;\nsetp.ne.b32 p, %0, 0;\n@p bar.sync %1, %2;\n}" ::"r"(on), "r"(id), "r"(n) : "memory"); }
DEVI void bar_arrive_p(int on, int id, int n) { asm volatile("{\n.reg .pred p;\nsetp.ne.b32 p, %0, 0;\n@p bar.arrive %1, %2;\n}" ::"r"(on), "r"(id), "r"(n) : "memory"); }
DEVI void mbar_arrive_p(int on, uint32_t bar) { asm volatile("{\n.reg .pred p;\nsetp.ne.b32 p, %1, 0;\n@p mbarrier.arrive.shared::cta.b64 _, [%0];\n}" ::"r"(bar), "r"(on) : "memory"); }
DEVI void mbar_arrive2_p(int on, uint32_t bar, uint32_t rbar) {
  asm volatile("{\n.reg .pred p;\nsetp.ne.b32 p, %2, 0;\n@p mbarrier.arrive.shared::cta.b64 _, [%0];\n@p mbarrier.arrive.shared::cluster.b64 _, [%1];\n}" ::"r"(bar), "r"(rbar), "r"(on) : "memory");
}
DEVI void st_relaxed(uint4* p, uint32_t x, uint32_t y, uint32_t z, uint32_t w) {
  asm volatile("st.relaxed.gpu.global.v4.b32 [%0], {%1,%2,%3,%4};" ::"l"(p), "r"(x), "r"(y), "r"(z), "r"(w) : "memory");
}
DEVI uint32_t mapa(uint32_t a, uint32_t cta) { uint32_t r; asm("mapa.shared::cluster.u32 %0, %1, %2;" : "=r"(r) : "r"(a), "r"(cta)); return r; }
DEVI void st_async128(uint32_t a, uint32_t x, uint32_t y, uint32_t z, uint32_t w, uint32_t bar) {
  asm volatile("st.async.weak.shared::cluster.mbarrier::complete_tx::bytes.v4.b32 [%0], {%1,%2,%3,%4}, [%5];" ::"r"(a), "r"(x), "r"(y), "r"(z), "r"(w), "r"(bar) : "memory");
}

template<int OFF, int TB, int S> __device__ __forceinline__ void wgmma_rs_n128(float (&d)[S], uint32_t a0, uint32_t a1, uint32_t a2, uint32_t a3, uint64_t db, int sd) {
  asm volatile("{\n.reg .pred p;\nsetp.ne.b32 p, %69, 0;\n"
    "wgmma.mma_async.sync.aligned.m64n128k16.f32.bf16.bf16 {%0, %1, %2, %3, %4, %5, %6, %7, %8, %9, %10, %11, %12, %13, %14, %15, %16, %17, %18, %19, %20, %21, %22, %23, %24, %25, %26, %27, %28, %29, %30, %31, %32, %33, %34, %35, %36, %37, %38, %39, %40, %41, %42, %43, %44, %45, %46, %47, %48, %49, %50, %51, %52, %53, %54, %55, %56, %57, %58, %59, %60, %61, %62, %63}, {%64, %65, %66, %67}, %68, p, 1, 1, %70;\n}\n"
    : "+f"(d[OFF+0]), "+f"(d[OFF+1]), "+f"(d[OFF+2]), "+f"(d[OFF+3]), "+f"(d[OFF+4]), "+f"(d[OFF+5]), "+f"(d[OFF+6]), "+f"(d[OFF+7]), "+f"(d[OFF+8]), "+f"(d[OFF+9]), "+f"(d[OFF+10]), "+f"(d[OFF+11]), "+f"(d[OFF+12]), "+f"(d[OFF+13]), "+f"(d[OFF+14]), "+f"(d[OFF+15]), "+f"(d[OFF+16]), "+f"(d[OFF+17]), "+f"(d[OFF+18]), "+f"(d[OFF+19]), "+f"(d[OFF+20]), "+f"(d[OFF+21]), "+f"(d[OFF+22]), "+f"(d[OFF+23]), "+f"(d[OFF+24]), "+f"(d[OFF+25]), "+f"(d[OFF+26]), "+f"(d[OFF+27]), "+f"(d[OFF+28]), "+f"(d[OFF+29]), "+f"(d[OFF+30]), "+f"(d[OFF+31]), "+f"(d[OFF+32]), "+f"(d[OFF+33]), "+f"(d[OFF+34]), "+f"(d[OFF+35]), "+f"(d[OFF+36]), "+f"(d[OFF+37]), "+f"(d[OFF+38]), "+f"(d[OFF+39]), "+f"(d[OFF+40]), "+f"(d[OFF+41]), "+f"(d[OFF+42]), "+f"(d[OFF+43]), "+f"(d[OFF+44]), "+f"(d[OFF+45]), "+f"(d[OFF+46]), "+f"(d[OFF+47]), "+f"(d[OFF+48]), "+f"(d[OFF+49]), "+f"(d[OFF+50]), "+f"(d[OFF+51]), "+f"(d[OFF+52]), "+f"(d[OFF+53]), "+f"(d[OFF+54]), "+f"(d[OFF+55]), "+f"(d[OFF+56]), "+f"(d[OFF+57]), "+f"(d[OFF+58]), "+f"(d[OFF+59]), "+f"(d[OFF+60]), "+f"(d[OFF+61]), "+f"(d[OFF+62]), "+f"(d[OFF+63]) : "r"(a0), "r"(a1), "r"(a2), "r"(a3), "l"(db), "r"(sd), "n"(TB));
}
template<int OFF, int TB, int S> __device__ __forceinline__ void wgmma_rs_n64(float (&d)[S], uint32_t a0, uint32_t a1, uint32_t a2, uint32_t a3, uint64_t db, int sd) {
  asm volatile("{\n.reg .pred p;\nsetp.ne.b32 p, %37, 0;\n"
    "wgmma.mma_async.sync.aligned.m64n64k16.f32.bf16.bf16 {%0, %1, %2, %3, %4, %5, %6, %7, %8, %9, %10, %11, %12, %13, %14, %15, %16, %17, %18, %19, %20, %21, %22, %23, %24, %25, %26, %27, %28, %29, %30, %31}, {%32, %33, %34, %35}, %36, p, 1, 1, %38;\n}\n"
    : "+f"(d[OFF+0]), "+f"(d[OFF+1]), "+f"(d[OFF+2]), "+f"(d[OFF+3]), "+f"(d[OFF+4]), "+f"(d[OFF+5]), "+f"(d[OFF+6]), "+f"(d[OFF+7]), "+f"(d[OFF+8]), "+f"(d[OFF+9]), "+f"(d[OFF+10]), "+f"(d[OFF+11]), "+f"(d[OFF+12]), "+f"(d[OFF+13]), "+f"(d[OFF+14]), "+f"(d[OFF+15]), "+f"(d[OFF+16]), "+f"(d[OFF+17]), "+f"(d[OFF+18]), "+f"(d[OFF+19]), "+f"(d[OFF+20]), "+f"(d[OFF+21]), "+f"(d[OFF+22]), "+f"(d[OFF+23]), "+f"(d[OFF+24]), "+f"(d[OFF+25]), "+f"(d[OFF+26]), "+f"(d[OFF+27]), "+f"(d[OFF+28]), "+f"(d[OFF+29]), "+f"(d[OFF+30]), "+f"(d[OFF+31]) : "r"(a0), "r"(a1), "r"(a2), "r"(a3), "l"(db), "r"(sd), "n"(TB));
}
template<int OFF, int TB, int S> __device__ __forceinline__ void wgmma_rs_n48(float (&d)[S], uint32_t a0, uint32_t a1, uint32_t a2, uint32_t a3, uint64_t db, int sd) {
  asm volatile("{\n.reg .pred p;\nsetp.ne.b32 p, %29, 0;\n"
    "wgmma.mma_async.sync.aligned.m64n48k16.f32.bf16.bf16 {%0, %1, %2, %3, %4, %5, %6, %7, %8, %9, %10, %11, %12, %13, %14, %15, %16, %17, %18, %19, %20, %21, %22, %23}, {%24, %25, %26, %27}, %28, p, 1, 1, %30;\n}\n"
    : "+f"(d[OFF+0]), "+f"(d[OFF+1]), "+f"(d[OFF+2]), "+f"(d[OFF+3]), "+f"(d[OFF+4]), "+f"(d[OFF+5]), "+f"(d[OFF+6]), "+f"(d[OFF+7]), "+f"(d[OFF+8]), "+f"(d[OFF+9]), "+f"(d[OFF+10]), "+f"(d[OFF+11]), "+f"(d[OFF+12]), "+f"(d[OFF+13]), "+f"(d[OFF+14]), "+f"(d[OFF+15]), "+f"(d[OFF+16]), "+f"(d[OFF+17]), "+f"(d[OFF+18]), "+f"(d[OFF+19]), "+f"(d[OFF+20]), "+f"(d[OFF+21]), "+f"(d[OFF+22]), "+f"(d[OFF+23]) : "r"(a0), "r"(a1), "r"(a2), "r"(a3), "l"(db), "r"(sd), "n"(TB));
}
template<int OFF, int TB, int S> __device__ __forceinline__ void wgmma_rs_n16(float (&d)[S], uint32_t a0, uint32_t a1, uint32_t a2, uint32_t a3, uint64_t db, int sd) {
  asm volatile("{\n.reg .pred p;\nsetp.ne.b32 p, %13, 0;\n"
    "wgmma.mma_async.sync.aligned.m64n16k16.f32.bf16.bf16 {%0, %1, %2, %3, %4, %5, %6, %7}, {%8, %9, %10, %11}, %12, p, 1, 1, %14;\n}\n"
    : "+f"(d[OFF+0]), "+f"(d[OFF+1]), "+f"(d[OFF+2]), "+f"(d[OFF+3]), "+f"(d[OFF+4]), "+f"(d[OFF+5]), "+f"(d[OFF+6]), "+f"(d[OFF+7]) : "r"(a0), "r"(a1), "r"(a2), "r"(a3), "l"(db), "r"(sd), "n"(TB));
}
template<int OFF, int TA, int TB, int S> __device__ __forceinline__ void wgmma_ss_n160(float (&d)[S], uint64_t da, uint64_t db, int sd) {
  asm volatile("{\n.reg .pred p;\nsetp.ne.b32 p, %82, 0;\n"
    "wgmma.mma_async.sync.aligned.m64n160k16.f32.bf16.bf16 {%0, %1, %2, %3, %4, %5, %6, %7, %8, %9, %10, %11, %12, %13, %14, %15, %16, %17, %18, %19, %20, %21, %22, %23, %24, %25, %26, %27, %28, %29, %30, %31, %32, %33, %34, %35, %36, %37, %38, %39, %40, %41, %42, %43, %44, %45, %46, %47, %48, %49, %50, %51, %52, %53, %54, %55, %56, %57, %58, %59, %60, %61, %62, %63, %64, %65, %66, %67, %68, %69, %70, %71, %72, %73, %74, %75, %76, %77, %78, %79}, %80, %81, p, 1, 1, %83, %84;\n}\n"
    : "+f"(d[OFF+0]), "+f"(d[OFF+1]), "+f"(d[OFF+2]), "+f"(d[OFF+3]), "+f"(d[OFF+4]), "+f"(d[OFF+5]), "+f"(d[OFF+6]), "+f"(d[OFF+7]), "+f"(d[OFF+8]), "+f"(d[OFF+9]), "+f"(d[OFF+10]), "+f"(d[OFF+11]), "+f"(d[OFF+12]), "+f"(d[OFF+13]), "+f"(d[OFF+14]), "+f"(d[OFF+15]), "+f"(d[OFF+16]), "+f"(d[OFF+17]), "+f"(d[OFF+18]), "+f"(d[OFF+19]), "+f"(d[OFF+20]), "+f"(d[OFF+21]), "+f"(d[OFF+22]), "+f"(d[OFF+23]), "+f"(d[OFF+24]), "+f"(d[OFF+25]), "+f"(d[OFF+26]), "+f"(d[OFF+27]), "+f"(d[OFF+28]), "+f"(d[OFF+29]), "+f"(d[OFF+30]), "+f"(d[OFF+31]), "+f"(d[OFF+32]), "+f"(d[OFF+33]), "+f"(d[OFF+34]), "+f"(d[OFF+35]), "+f"(d[OFF+36]), "+f"(d[OFF+37]), "+f"(d[OFF+38]), "+f"(d[OFF+39]), "+f"(d[OFF+40]), "+f"(d[OFF+41]), "+f"(d[OFF+42]), "+f"(d[OFF+43]), "+f"(d[OFF+44]), "+f"(d[OFF+45]), "+f"(d[OFF+46]), "+f"(d[OFF+47]), "+f"(d[OFF+48]), "+f"(d[OFF+49]), "+f"(d[OFF+50]), "+f"(d[OFF+51]), "+f"(d[OFF+52]), "+f"(d[OFF+53]), "+f"(d[OFF+54]), "+f"(d[OFF+55]), "+f"(d[OFF+56]), "+f"(d[OFF+57]), "+f"(d[OFF+58]), "+f"(d[OFF+59]), "+f"(d[OFF+60]), "+f"(d[OFF+61]), "+f"(d[OFF+62]), "+f"(d[OFF+63]), "+f"(d[OFF+64]), "+f"(d[OFF+65]), "+f"(d[OFF+66]), "+f"(d[OFF+67]), "+f"(d[OFF+68]), "+f"(d[OFF+69]), "+f"(d[OFF+70]), "+f"(d[OFF+71]), "+f"(d[OFF+72]), "+f"(d[OFF+73]), "+f"(d[OFF+74]), "+f"(d[OFF+75]), "+f"(d[OFF+76]), "+f"(d[OFF+77]), "+f"(d[OFF+78]), "+f"(d[OFF+79]) : "l"(da), "l"(db), "r"(sd), "n"(TA), "n"(TB));
}

__device__ __align__(1024) uint16_t g_kvT[2 * 640 * 2048];
__device__ __align__(1024) uint16_t g_y2T[2 * 640 * 2048];
__device__ __align__(1024) uint16_t g_o[2048 * 640];
__device__ __align__(1024) uint16_t g_gate[2080];
__device__ __align__(1024) uint4 g_halo[128 * 5 * 32];
__device__ __align__(1024) unsigned g_cnt[46 * 32];
__device__ __align__(1024) unsigned g_launch[132 * 32];
#define CNT_KV(i) (g_cnt + 32 * (i))
#define CNT_O(i) (g_cnt + 32 * (10 + (i)))
#define CNT_Y(i) (g_cnt + 32 * (26 + (i)))
#define PTL(i) do {} while (0)
#define PTPL(on, i) do {} while (0)
#define PT(i) do {} while (0)
#define PTP(on, i) do {} while (0)

constexpr uint32_t SB = 1024;
constexpr uint32_t STG = 23552, WST = 15360;
DEVI constexpr uint32_t o_px(int ks) { return (((ks >> 1) + 1) & 3) * 2 * STG; }
DEVI constexpr uint32_t o_pw(int ks) { return o_px(ks) + 16384 + (ks & 1) * WST; }
constexpr uint32_t O_HALO = 0, O_QT = STG;
constexpr uint32_t O_OST = 2 * STG;
constexpr uint32_t P3S = 28672;
constexpr uint32_t HC = 8320, UC = 4624, UZ = 528;
constexpr uint32_t O_H0 = 5 * P3S, O_U2 = O_H0 + 3 * HC, O_H3 = O_U2 + UC, O_U0 = O_H3 + 2 * HC;
DEVI constexpr uint32_t o_h(int c) { return O_H0 + c * HC + (c > 2 ? UC : 0); }
DEVI constexpr uint32_t o_u(int c) { return c == 2 ? O_U2 : O_U0 + (c > 2 ? c - 1 : c) * UC; }
constexpr uint32_t O_Y = 208896;
DEVI constexpr uint32_t o_x(int c) { return c < 2 ? O_Y + c * 5120 : O_U0 + (c & 1) * UC; }
constexpr uint32_t O_HIN = O_Y + 16384;
DEVI constexpr uint32_t o_kin(int c) { return ((O_U0 + 127) & ~127u) + ((c & 1) ? 0 : 73 * 128); }
DEVI constexpr uint32_t o_p3(int ks) { return (ks < 6 ? ks : ks - 6) * P3S; }
constexpr uint32_t O_BT = 4 * P3S;
constexpr uint32_t O_GT = O_Y + 20480, O_GW = O_GT + 320;
constexpr uint32_t O_BAR = 231040;
constexpr uint32_t B_FULL = O_BAR, B_EMPTY = O_BAR + 8 * 8, B_P3F = O_BAR + 8 * 16, B_P3R = O_BAR + 8 * 26, B_G = O_BAR + 8 * 27, B_U = O_BAR + 8 * 28,
                   B_KVD = O_BAR + 8 * 33, B_KF = O_BAR + 8 * 36, B_Y = O_BAR + 8 * 38, B_EP = O_BAR + 8 * 40, B_LAST = O_BAR + 8 * 41, B_DONE = O_BAR + 8 * 42,
                   B_P1E = O_BAR + 8 * 43, B_HX = O_BAR + 8 * 43  , B_P3E = O_BAR + 8 * 52, B_HX0 = O_BAR + 8 * 57, B_KVS = O_BAR + 8 * 58, B_QD = O_BAR + 8 * 60, B_GD = O_BAR + 8 * 61, B_Q = O_BAR + 8 * 51;
constexpr uint32_t B_S13 = B_EMPTY + 8 * 5, B_S15 = B_EMPTY + 8 * 7, B_S19 = B_EMPTY + 8 * 3;
constexpr uint32_t O_GP = O_BAR + 512, O_EPOCH = O_GW + 1280;
constexpr uint32_t SMEM_BYTES = 232448;
static_assert(O_U0 + 4 * UC <= O_Y - 512 && o_kin(0) >= O_U0 + 2 * UC && O_EPOCH + 4 <= O_BAR && O_U0 >= 8 * STG, "smem map");
enum { NB_LEAD = 1, NB_HELP = 2, NB_HALO = 3, NB_ATT = 4, NB_G = 5, NB_TOK = 6, NB_RFULL = 8, NB_RFREE = 10 };

struct Maps { CUtensorMap x_par, w_main, w_tail, k_ld, v_ld, o_st, kv_st, wo, o_ld, y_ld, q_ld; };

template <int M> DEVI void conv_step(float (&acc)[128], uint32_t a0, uint32_t a1, uint32_t a2, uint32_t a3, uint32_t dl) {
  auto D = [&](int off) { return ((uint64_t)8 << 32) | (uint64_t)(uint32_t)(dl + off - 16 * M); };
  if constexpr (M == 0) wgmma_rs_n16<0, 0>(acc, a0, a1, a2, a3, D(0), 0);
  if constexpr (M <= 3) wgmma_rs_n48<8, 0>(acc, a0, a1, a2, a3, D(16), M == 0 ? 0 : 1);
  if constexpr (M <= 6) wgmma_rs_n48<32, 0>(acc, a0, a1, a2, a3, D(64), M == 0 ? 0 : 1);
  if constexpr (M <= 9) wgmma_rs_n48<56, 0>(acc, a0, a1, a2, a3, D(112), M == 0 ? 0 : 1);
  if constexpr (M <= 12) wgmma_rs_n48<80, 0>(acc, a0, a1, a2, a3, D(160), M == 0 ? 0 : 1);
  wgmma_rs_n48<104, 0>(acc, a0, a1, a2, a3, D(208), M == 0 ? 0 : 1);
}
DEVI constexpr int a_off(int P, int i) { return -4 * (64 * ((i & 4) ? 15 - P : P) + (i & 1) * 32 - (i & 2) * 2); }
template <int P> DEVI void load_pair(uint32_t (&a)[8], uint32_t ab) {
#pragma unroll
  for (int i = 0; i < 8; i++) a[i] = lds32(ab + a_off(P, i));
}
template <int P> DEVI void mma_pair(float (&acc)[128], uint32_t (&a)[8], uint32_t db) {
  wg_fence();
  conv_step<P>(acc, a[0], a[1], a[2], a[3], db);
  conv_step<15 - P>(acc, a[4], a[5], a[6], a[7], db);
  wg_commit();
}

template <int I0, int I1> DEVI void conv_reduce(uint32_t sb, int c, int ht, int chan, int bar, int nthr) {
  const uint32_t a0 = sb + o_h(c) + ht * 16, a2 = sb + o_u(c) + ht * 16, a3 = sb + o_x(c) + ht * 16;
  uint4* yp = (uint4*)(g_y2T + (size_t)chan * 2048) + ht;
#pragma unroll
  for (int i = I0; i < I1; i++) {
    uint4 p, q, r, s;
    if (i == I0) bar_sync(bar, nthr);
    lds128(a0 + i * 2048, p.x, p.y, p.z, p.w); lds128(a0 + 4160 + i * 2048, q.x, q.y, q.z, q.w);
    lds128(a2 + i * 2048, r.x, r.y, r.z, r.w); lds128(a3 + i * 2048, s.x, s.y, s.z, s.w);
    auto sum = [](uint32_t a, uint32_t b, uint32_t c, uint32_t d) { return hadd2(hadd2(hadd2(a, b), 0u), hadd2(c, d)) ^ 0x80008000u; };
    yp[i * 128] = make_uint4(sum(p.x, q.x, r.x, s.x), sum(p.y, q.y, r.y, s.y), sum(p.z, q.z, r.z, s.z), sum(p.w, q.w, r.w, s.w));
  }
}

template <int ODD, int PART> DEVI void pack_qkv(const float (&acc)[120], uint32_t (&Q)[10][2], uint32_t (&K)[10][2], uint32_t (&V)[10][2]) {
#pragma unroll
  for (int f = 0; f < 10; f++) {
    const bool tail = ODD ? (f < 2) : (f >= 8);
    const int fm = ODD ? f - 2 : f, ft = ODD ? f : f - 8;
    const int nq = tail ? 24 + ft : fm, nk = tail ? 26 + ft : 8 + fm, nv = tail ? 28 + ft : 16 + fm;
    if (PART == 0) { K[f][1] = pack_bf16(acc[4 * nk + 2], acc[4 * nk + 3]); V[f][1] = pack_bf16(acc[4 * nv + 2], acc[4 * nv + 3]); }
    if (PART == 1) { V[f][0] = pack_bf16(acc[4 * nv], acc[4 * nv + 1]); K[f][0] = pack_bf16(acc[4 * nk], acc[4 * nk + 1]); }
    if (PART == 2) { Q[f][0] = pack_bf16(acc[4 * nq], acc[4 * nq + 1]); Q[f][1] = pack_bf16(acc[4 * nq + 2], acc[4 * nq + 3]); }
  }
}
DEVI void sched_fence(uint32_t& z) {
  asm volatile("{\n.reg .pred p;\nL:\nshr.u32 %0, %0, 1;\nsetp.ne.u32 p, %0, 0;\n@p bra.uni L;\n}" : "+r"(z));
}

DEVI int pair_of(int c) {
  const int lo = 32 + 8 * c, hi = c - 4 + ((max(c - 29, 0) * 37) >> 8);
  int p; asm("{\n.reg .pred q;\nsetp.lt.s32 q, %1, 4;\nselp.b32 %0, %2, %3, q;\n}" : "=r"(p) : "r"(c), "r"(lo), "r"(hi));
  return p;
}
DEVI uint32_t make_ctx() {
  int b; asm volatile("mov.u32 %0, %%ctaid.x;" : "=r"(b));
  b += clk() & threadIdx.y;
  const int p = pair_of(b >> 1);
  const int j = b < 128 ? 8 * (p & 7) + (p >> 3) : 64;
  const int q = (j * 205) >> 10, r = j - 5 * q, i = j - q, co = (i * 79) >> 10;
  const int cp = r == 4 ? 4 : co, tb = r == 4 ? q : i - 13 * co;
  return ((2 * p + (b & 1)) & 255) | tb << 8 | (2 * cp + (b & 1)) << 12 | (b >> 7) << 16;
}
#define CTX() asm volatile("" : "+r"(ctx)); CTXU()
#define CTXU() int tid; asm volatile("mov.u32 %0, %%tid.x;" : "=r"(tid)); \
  const int lane = tid & 31, vb = ctx & 255, hg = (ctx >> 4) & 7, rt = ctx & 15, par = (ctx >> 3) & 1, mt = ctx & 7, rank = ctx & 1, \
  tb = (ctx >> 8) & 15, cb = (ctx >> 12) & 15; const bool main_cta = ctx < 65536; \
  (void)tid; (void)lane; (void)vb; (void)hg; (void)rt; (void)par; (void)mt; (void)rank; (void)tb; (void)cb; (void)main_cta
#define CTXW() CTX(); const int wg = warp >> 2, w = warp & 3, g = lane >> 2, t = lane & 3; const bool lead = (tid & 127) == 0; \
  (void)wg; (void)w; (void)g; (void)t; (void)lead

__global__ void __cluster_dims__(2, 1, 1) __launch_bounds__(512, 1)
fused_kernel(const uint16_t* __restrict__ xq, const uint16_t* __restrict__ wqkv, const uint16_t* __restrict__ gate_w, const __grid_constant__ Maps M, const uint16_t* __restrict__ shift_k, const uint16_t* __restrict__ ssm_k, const uint16_t* __restrict__ ssm_D,
             uint16_t* __restrict__ outp) {
  extern __shared__ __align__(1024) uint8_t smem_raw[];
  const uint32_t sb = smem_u32(smem_raw);
  const uint32_t t0 = clk();
  auto get_epoch = [&]() { mbar_wait(sb + B_EP, 0); return lds32(sb + O_EPOCH); };

  auto p1_load_x = [&](int ks, int p, int rank) {
    tma3(sb + o_px(ks), &M.x_par, ks * 32, (p >> 2) & 1, (p & 3) * 256 + rank * 128, sb + B_FULL + 8 * (ks & 7));
  };
  auto p1_load_w = [&](int ks, int p, int rank) {
    const uint32_t st = sb + o_pw(ks), fb = sb + B_FULL + 8 * (ks & 7);
    tma3_mc(st + rank * 6144, &M.w_main, (p >> 3) * 80 + 2 * (p & 8), ks * 32 + rank * 16, 0, fb);
    tma3_mc(st + 12288 + rank * 1536, &M.w_tail, (p >> 3) * 80 + 8 * (~p & 8), ks * 32 + rank * 16, 0, fb);
  };
  auto cta_pair = [&]() { return pair_of(blockIdx.x >> 1); };

  if (threadIdx.x < 32) {
    const unsigned b = blockIdx.x, l = threadIdx.x;
    const uint16_t* pfp = l < 16 ? xq + (16 * b + l) * 640 : wqkv + (15 * b + l - 16) * 64;
    if ((l | b >> 7 << 5) < 31) pf_l2(pfp);
  }
  const int warp = __shfl_sync(~0u, threadIdx.x >> 5, 0);
  if ((warp & 14) == 8) {
    if (elect_one()) {
#pragma unroll
      for (int s = 0; s < 8; s++) mbar_init(sb + O_BAR - 512 + 64 * warp + 8 * s, 5 * warp - 39);
      asm volatile("fence.mbarrier_init.release.cluster;" ::: "memory");
    }
    __syncwarp();
  }
  asm volatile("barrier.cluster.arrive.relaxed.aligned;" ::: "memory");
  if (warp == 8 && blockIdx.x < 128) {
    const int p = cta_pair(), rank = blockIdx.x & 1;
    if (elect_one()) { mbar_expect_tx(sb + B_FULL, 16384 + WST); p1_load_x(0, p, rank); }
    __syncwarp();
    asm volatile("barrier.cluster.wait.aligned;" ::: "memory");
    if (elect_one()) { p1_load_w(0, p, rank); PT(100); }
    __syncwarp();
  } else if (warp != 15) {
    asm volatile("barrier.cluster.wait.aligned;" ::: "memory");
    spin_until(t0, HOLD);
  }
  auto init_rest = [&]() {
    if (warp >= 11 && elect_one()) {
#pragma unroll
      for (int s = 0; s < 12; s++) mbar_init(sb + O_BAR + 128 - 11 * 96 + 96 * warp + 8 * s, warp == 14 ? 2 : 1);
      asm volatile("fence.mbarrier_init.release.cluster;" ::: "memory");
    }
    __syncwarp();
    bar_sync(0, blockIdx.x < 128 ? 224 : 512);
  };
  uint32_t ctx = 0;

  if (warp < 8) {
    reg_inc<RC>();
    ctx = make_ctx();
    if (blockIdx.x >= 128) bar_sync(0, 512);
    else {
      {
        uint32_t Q[10][2], K[10][2], V[10][2];
        {
          {
            float acc[120];
            CTXW();
            const int odd = (cta_pair() >> 3) & 1;
            const uint32_t rsb = mapa(sb, (blockIdx.x & 1) ^ 1);
            {
              const uint32_t aa = sb + (warp * 16 + (lane & 15)) * 128 + (((lane >> 4) ^ (lane & 7)) << 4);
              constexpr int NA = DEFER > 3 ? DEFER : 3;
              uint32_t a[NA][8];
              auto load_a = [&](int ks) {
                uint32_t(&r)[8] = a[ks % NA];
                mbar_wait(sb + B_FULL + 8 * (ks & 7), (ks >> 3) & 1);
                PTP(lead && (wg || !(ks & 3)), wg ? 60 + ks : 80 + (ks >> 2));
                ldsm4(r[0], r[1], r[2], r[3], (aa ^ ((ks & 1) * 64)) + o_px(ks)); ldsm4(r[4], r[5], r[6], r[7], (aa ^ ((ks & 1) * 64 + 32)) + o_px(ks));
              };
              auto mma_q = [&](int ks, int h) {
                uint32_t(&r)[8] = a[ks % NA];
                wgmma_rs_n64<0, 1>(acc, r[4 * h], r[4 * h + 1], r[4 * h + 2], r[4 * h + 3], mkdesc(SB + o_pw(ks) + h * 6144, 2048, 1024, 1), ks | h);
              };
              auto mma_step = [&](int ks, int h) {
                uint32_t(&r)[8] = a[ks % NA];
                wg_fence();
                wgmma_rs_n128<32, 1>(acc, r[4 * h], r[4 * h + 1], r[4 * h + 2], r[4 * h + 3], mkdesc(SB + o_pw(ks) + h * 6144 + 2048, 2048, 1024, 1), ks | h);
                if (ks < 20 - DEFER) mma_q(ks, h);
                wgmma_rs_n48<96, 1>(acc, r[4 * h], r[4 * h + 1], r[4 * h + 2], r[4 * h + 3], mkdesc(SB + o_pw(ks) + 12288 + h * 1536, 512, 256, 3), ks | h);
                wg_commit();
              };
              if (lead) PT(1 + wg);
              load_a(0);
#pragma unroll
              for (int ks = 0; ks < 20; ks++) {
                if (LEAD && ks == 20 - LEAD) bar_sync_p(wg == 0, NB_LEAD, 256);
                mma_step(ks, 0);
                if (ks < 19 && ks >= NLATE) load_a(ks + 1);
                mma_step(ks, 1);
                if (ks < NLATE) load_a(ks + 1);
                if (ks >= 1 && ks <= 16) {
                  wg_wait<2>();
                  mbar_arrive2_p(lead, sb + B_EMPTY + 8 * ((ks - 1) & 7), rsb + B_EMPTY + 8 * ((ks - 1) & 7));
                } else if (ks < 19 && ks + 2 - NA >= 16) wg_wait<2>();
              }
              if (LEAD) bar_arrive_p(wg, NB_LEAD, 256);
              if (DEFER) {
                wg_fence();
#pragma unroll
                for (int i = 40 - 2 * DEFER; i < 40; i++) mma_q(i >> 1, i & 1);
                wg_commit();
              }
              mbar_wait(sb + B_S15, 1);
              wg_wait<1>();
              mbar_arrive_p(tid == 0, sb + B_P1E);
              if (!DEFER) wg_wait<0>();
              fence_regs<32, 120>(acc);
              PTPL(lead, 158 + wg);
            }
            if (odd) pack_qkv<1, 0>(acc, Q, K, V); else pack_qkv<0, 0>(acc, Q, K, V);
            if (warp == 7 && (blockIdx.x & 1)) {
              uint4* hp = g_halo + vb * 160 + lane;
              st_relaxed(hp, K[0][1], K[1][1], K[3][1], K[4][1]); st_relaxed(hp + 32, K[5][1], K[6][1], K[8][1], K[9][1]);
              st_relaxed(hp + 64, K[2][1], K[7][1], V[0][1], V[1][1]);
              st_relaxed(hp + 96, V[2][1], V[3][1], V[4][1], V[5][1]); st_relaxed(hp + 128, V[6][1], V[7][1], V[8][1], V[9][1]);
            }
            const uint32_t ho = sb + O_HALO + warp * 2560 + lane * 16;
            stsm4(ho, K[0][1], K[1][1], K[3][1], K[4][1]); stsm4(ho + 512, K[5][1], K[6][1], K[8][1], K[9][1]);
            stsm4(ho + 1024, K[2][1], K[7][1], V[0][1], V[1][1]);
            stsm4(ho + 1536, V[2][1], V[3][1], V[4][1], V[5][1]); stsm4(ho + 2048, V[6][1], V[7][1], V[8][1], V[9][1]);
            if (warp == 7) {
              if (!(blockIdx.x & 1)) {
                fence_async_smem();
                __syncwarp();
                if (elect_one())
                  asm volatile("cp.async.bulk.shared::cluster.shared::cta.mbarrier::complete_tx::bytes [%0], [%1], 2560, [%2];"
                               ::"r"(mapa(sb + O_HIN, 1)), "r"(sb + O_HALO + 7 * 2560), "r"(mapa(sb + B_HX0, 1)) : "memory");
              }
              __syncwarp();
            } else {
              __syncwarp();
              if (lane == 0) mbar_arrive(sb + B_HX + 8 + 8 * warp);
            }
            if (odd) pack_qkv<1, 1>(acc, Q, K, V); else pack_qkv<0, 1>(acc, Q, K, V);
#pragma unroll
            for (int f = 0; f < 10; f++) V[f][0] = movm(V[f][0]);
            wg_wait<0>();
            fence_regs<0, 32>(acc);
            PTPL(lead, 50 + wg);
            mbar_arrive2_p(lead, sb + B_S19, rsb + B_S19);
            if (odd) pack_qkv<1, 2>(acc, Q, K, V); else pack_qkv<0, 2>(acc, Q, K, V);
            if (lead) PT(52 + wg);
            if (wg) mbar_wait(sb + B_P1E, 0);
          }
          CTXW();
          uint32_t z = threadIdx.y;
          const bool gt0 = 2 * t > g, gt1 = 2 * t + 1 > g;
          const uint32_t pmask = (gt0 ? 0xFFFFu : 0u) | (gt1 ? 0xFFFF0000u : 0u);
          const uint32_t hs = warp ? O_HALO + (warp - 1) * 2560 : O_HIN, ha = sb + hs + lane * 16;
          const uint32_t va = sb + ((lane & 8) ? O_HALO + warp * 2560 : hs) + 1280 + (lane >> 4) * 128 + (lane & 7) * 16;
          uint32_t Qh[4][2], Kh[10], Vh[10];
          float c1[4][4] = {}, c2[4][4] = {}, c0[4][4] = {}, l[8][2], m[8], x[8];
#pragma unroll
          for (int j = 0; j < 4; j++) {
            const int fa = (j >> 1) * 5 + (j & 1) * 3, fh = (j >> 1) * 5 + 2;
            const bool mine = (j & 1) ? (t >= 2) : (t < 2);
            Qh[j][0] = mine ? Q[fh][0] : 0u; Qh[j][1] = mine ? Q[fh][1] : 0u;
            mma16(c1[j], Q[fa][0], Q[fa][1], Q[fa + 1][0], Q[fa + 1][1], K[fa][0], K[fa + 1][0]);
            mma16(c2[j], Q[fa][0], Q[fa][1], Q[fa + 1][0], Q[fa + 1][1], K[fa][1], K[fa + 1][1]);
            mma8(c1[j], Qh[j][0], Qh[j][1], K[fh][0]);
            mma8(c2[j], Qh[j][0], Qh[j][1], K[fh][1]);
          }
          if (lead) PT(54 + wg);
          mbar_wait(sb + (warp ? B_HX + 8 * warp : B_HX0), 0);
          if (lead) PT(56 + wg);
          ldsm4(Kh[0], Kh[1], Kh[3], Kh[4], ha); ldsm4(Kh[5], Kh[6], Kh[8], Kh[9], ha + 512);
          asm volatile("ldmatrix.sync.aligned.m8n8.x2.shared.b16 {%0,%1}, [%2];" : "=r"(Kh[2]), "=r"(Kh[7]) : "r"(ha + 1024) : "memory");
          auto load_v = [&]() {
#pragma unroll
            for (int i = 0; i < 5; i++) ldsm4t(Vh[2 * i], V[2 * i][1], Vh[2 * i + 1], V[2 * i + 1][1], va + i * 256);
          };
          load_v();
          const float C = 0.22360679774997896f * 1.4426950408889634f;
          auto max1 = [&](int r) { m[r] = fmaxf(l[r][0], l[r][1]); x[r] = __shfl_xor_sync(~0u, m[r], 1); };
          auto max2 = [&](int r) { m[r] = fmaxf(m[r], x[r]); x[r] = __shfl_xor_sync(~0u, m[r], 2); };
          auto exps = [&](int r) { const float mc = fmaxf(m[r], x[r]) * C; l[r][0] = ex2(fmaf(l[r][0], C, -mc)); l[r][1] = ex2(fmaf(l[r][1], C, -mc)); };
#pragma unroll
          for (int j = 0; j < 4; j++) { l[4 + j][0] = gt0 ? c1[j][2] : c2[j][2]; l[4 + j][1] = gt1 ? c1[j][3] : c2[j][3]; max1(4 + j); }
#pragma unroll
          for (int j = 0; j < 4; j++) {
            const int fa = (j >> 1) * 5 + (j & 1) * 3, fh = (j >> 1) * 5 + 2;
            mma16(c0[j], Q[fa][0], Q[fa][1], Q[fa + 1][0], Q[fa + 1][1], Kh[fa], Kh[fa + 1]);
            mma8(c0[j], Qh[j][0], Qh[j][1], Kh[fh]);
            max2(4 + j);
          }
          const bool have_halo = warp > 0 || mt > 0;
#pragma unroll
          for (int j = 0; j < 4; j++) {
            if (!have_halo) c0[j][0] = c0[j][1] = -INFINITY;
            l[j][0] = gt0 ? c0[j][0] : c1[j][0]; l[j][1] = gt1 ? c0[j][1] : c1[j][1];
            max1(j);
          }
          exps(4); exps(5);
#pragma unroll
          for (int j = 0; j < 4; j++) max2(j);
          exps(6); exps(7);
#pragma unroll
          for (int j = 0; j < 4; j++) exps(j);
          float o[12][4] = {}, sm[4][4] = {};
#pragma unroll
          for (int j = 0; j < 4; j++) {
            const int fa = (j >> 1) * 5 + (j & 1) * 3, fh = (j >> 1) * 5 + 2;
            const uint32_t pl = pack_bf16(l[j][0], l[j][1]), pu = pack_bf16(l[4 + j][0], l[4 + j][1]);
            const uint32_t a0 = pl & pmask, a2 = pl & ~pmask, a3 = pu & pmask, a5 = pu & ~pmask, z0 = z << (2 * j + 1), z1 = z << (2 * j + 2);
            mma8(sm[j], pl, pu, 0x3F803F80u);
#pragma unroll
            for (int q = 0; q < 3; q++) {
              const int f = q < 2 ? fa + q : fh;
              mma8(o[3 * j + q], a2, a3, V[f][0]);
              mma16(o[3 * j + q], a0, z0, z1, a5, Vh[f], V[f][1]);
            }
          }
          sched_fence(z);
          bar_arrive_p(wg == 0, NB_HALO + z, 256);
          uint32_t O[10][2];
#pragma unroll
          for (int j = 0; j < 4; j++) {
            const int fa = (j >> 1) * 5 + (j & 1) * 3, fh = (j >> 1) * 5 + 2;
            float r0, r1;
            asm("rcp.approx.ftz.f32 %0, %1;" : "=f"(r0) : "f"(sm[j][0]));
            asm("rcp.approx.ftz.f32 %0, %1;" : "=f"(r1) : "f"(sm[j][2]));
#pragma unroll
            for (int q = 0; q < 3; q++) {
              const int f = q < 2 ? fa + q : fh;
              const float* e = o[3 * j + q];
              const uint32_t o0 = pack_bf16(e[0] * r0, e[1] * r0), o1 = pack_bf16(e[2] * r1, e[3] * r1);
              if (q < 2 || !(j & 1)) { O[f][0] = o0; O[f][1] = o1; }
              else { O[f][0] = t >= 2 ? o0 : O[f][0]; O[f][1] = t >= 2 ? o1 : O[f][1]; }
            }
          }
          mbar_wait(sb + B_GD, 0);
          const uint32_t oa = sb + O_OST + wg * 2 * STG + (w * 16 + (lane & 15)) * 160 + (lane >> 4) * 16;
#pragma unroll
          for (int i = 0; i < 5; i++) stsm4(oa + i * 32, O[2 * i][0], O[2 * i][1], O[2 * i + 1][0], O[2 * i + 1][1]);
        }
      }
      {
        CTXW();
        fence_async_smem();
        bar_arrive(wg ? NB_LEAD : NB_ATT, 160);
        if (lead) PT(58 + wg);
        const uint32_t abase = sb + (g & 1) * 4160 + 4 * (1023 - 4 - 8 * w - (g >> 1) + t);
        float acc[128];
        uint32_t a0[8], a1[8], a2[8], a3[8];
#pragma unroll 1
        for (int c = wg ^ 1; c < 5; c += 2) {
          const uint32_t ab = abase + o_h(c);
          const uint32_t db = __shfl_sync(~0u, ((SB + o_u(c) + UZ - 16) >> 4) | 0x10000u, 0);
          mbar_wait(sb + B_U + 8 * c, 0);
          load_pair<0>(a0, ab); load_pair<1>(a1, ab); load_pair<2>(a2, ab);
          if (!P3L) load_pair<3>(a3, ab);
          if (RLATE) bar_arrive_p(c >= 2 && c < 2 + RLATE, NB_RFULL + wg, 256);
          if (lead) PT(85 + c);
          bar_sync(c ? NB_TOK + wg : NB_HALO, 256);
          fence_regs(acc);
          mma_pair<0>(acc, a0, db);                if (P3L) load_pair<3>(a3, ab);
          mma_pair<1>(acc, a1, db); wg_wait<1>();  load_pair<4>(a0, ab);
          if (lead) PT(90 + c);
          mma_pair<2>(acc, a2, db); wg_wait<1>();  load_pair<5>(a1, ab);
          mma_pair<3>(acc, a3, db); wg_wait<1>();  load_pair<6>(a2, ab);
          mma_pair<4>(acc, a0, db); wg_wait<1>();  load_pair<7>(a3, ab);
          mma_pair<5>(acc, a1, db);
          if (TOKP == 5) bar_arrive_p(c < 4, NB_TOK + (wg ^ 1), 256);
          mma_pair<6>(acc, a2, db);
          if (TOKP == 6) bar_arrive_p(c < 4, NB_TOK + (wg ^ 1), 256);
          mma_pair<7>(acc, a3, db);
          bar_arrive_p(c == 4 || TOKP == 7, NB_TOK + (wg ^ 1), 256);
          wg_wait<0>();
          fence_regs(acc);
          PTPL(lead, 95 + c);
          bar_sync(NB_RFREE + wg, 256);
          const uint32_t pb = sb + (w < 2 ? o_h(c) + w * 4160 : w == 2 ? o_u(c) : o_x(c)) + lane * 16;
          if (lane < 2 * w) sts128(pb, 0, 0, 0, 0);
#pragma unroll
          for (int q = 0; q < 8; q++) {
            uint32_t p[4];
#pragma unroll
            for (int i = 0; i < 4; i++) {
              const int nu = 4 * q + i;
              p[i] = pack_bf16(acc[4 * nu], acc[4 * nu + 1]);
              if (nu > 0) p[i] = hadd2(p[i], pack_bf16(acc[4 * nu - 2], acc[4 * nu - 1]));
            }
            stsm4t(pb + w * 32 + q * 512, p[0], p[1], p[2], p[3]);
            if (q == 3) bar_arrive_p(c == 4, NB_RFULL + 1, 256);
          }
          if (c < 4 && c >= RLATE) bar_arrive(NB_RFULL + wg, 256);
          if (lead) PT(140 + c);
        }
        if (wg) {
          const int yb = (lds32(sb + O_EPOCH) & 1) * 640;
          conv_reduce<1, 2>(sb, 4, tid - 128, yb + 512 + ((vb & 0x61) | (vb & 6) << 2 | (vb >> 2 & 6)), 14, 128);
          bar_arrive(12, 256);
          PTPL(lead, 45);
        }
      }
    }
    if (warp < 4) {
      CTXW();
      const uint32_t rsb = mapa(sb, (blockIdx.x & 1) ^ 1);
      const uint32_t ba = sb + O_BT + ((lane >> 4) * 8 + (lane & 7)) * 128 + (((2 * w + ((lane >> 3) & 1)) ^ ((lane & 1) << 2 | (lane >> 1 & 3))) << 4);
      mbar_wait(sb + B_P3F, 0);
      if (lead) PT(145);
      float acc[80];
#pragma unroll
      for (int ks = 0; ks < 10; ks++) {
        if (ks == NPRE) {
          if (NPRE) { wg_wait<0>(); mbar_arrive2_p(lead, sb + B_P3E + 8 * NPRE, rsb + B_P3E + 8 * NPRE); }
          bar_sync_p(blockIdx.x < 128, NB_TOK, 256);
        }
        PTP(lead, 146 + ks);
        const uint64_t da = mkdesc(SB + o_p3(ks), 1024, 1024, 1), db = mkdesc(SB + o_p3(ks) + 8192, 16, 1024, 1);
        wg_fence();
#pragma unroll
        for (int j = 0; j < 4; j++) wgmma_ss_n160<0, 1, 0>(acc, da + j * 128, db + j * 2, j | ks);
        wg_commit();
        if (ks < 9) mbar_wait(sb + B_P3F + 8 * (ks + 1), 0);
        if (ks >= 1 && ks <= 4 && ks != NPRE) { wg_wait<1>(); mbar_arrive2_p(lead, sb + B_P3E + 8 * ks, rsb + B_P3E + 8 * ks); }
      }
      wg_wait<0>();
      fence_regs(acc);
      PTPL(lead, 156);
#pragma unroll
      for (int i = 0; i < 10; i++) {
        stsm4t(ba + i * 2048, pack_bf16(acc[8 * i], acc[8 * i + 1]), pack_bf16(acc[8 * i + 2], acc[8 * i + 3]),
               pack_bf16(acc[8 * i + 4], acc[8 * i + 5]), pack_bf16(acc[8 * i + 6], acc[8 * i + 7]));
        if (i & 1) bar_arrive(1 + (i >> 1), 256);
      }
      if (lead) PT(157);
    }
  } else if (warp < 12) {
    reg_dec<RH>();
    const int hw = warp - 8;
    init_rest();
    ctx = __shfl_sync(~0u, make_ctx(), 0);
    const int yrow = (ctx & 0x61) | (ctx & 6) << 2 | (ctx >> 2 & 6);
    if (ctx < 65536) {
      CTXU();
      const int pr = hw >> 1, hh = hw & 1, tk = vb & 63, odd = (lane >> 2) & 1;
      const uint32_t sel0 = odd ? 0x7632 : 0x5410, sel1 = odd ? 0x5410 : 0x7632;
      const uint32_t in = sb + o_kin(pr), fb = sb + B_KF + 8 * pr, out = sb + O_Y + pr * 8192;
      const uint32_t oa = out + (2 * lane + odd) * 64 + (((3 - 2 * hh) ^ (lane & 3)) << 4), ia = in + hh * 2048 + lane * 4;
      auto fetch = [&](int c) {
        wait_until(t0, KT0 + c * KTD + ((((vb * 37) & 63) * KPH) >> 6));
        if (elect_one()) {
          const int kb = 2 * c + (vb >> 6);
          mbar_expect_tx(fb, 69 * 128);
          tma2(in, &M.k_ld, kb * 64, 32 * tk - 4, fb);
          tma2(in + 36 * 128, &M.v_ld, kb * 64, 32 * tk - 1, fb);
          PT(20 + c);
        }
        __syncwarp();
      };
      if (hh == 0) fetch(pr);
      const uint4* skp = (const uint4*)shift_k + (2 * pr + (vb >> 6)) * 32 + lane;
      uint4 sk = __ldg(skp), sk1 = __ldg(skp + 128), sk2 = __ldg(skp + (pr ? 0 : 256));
#pragma unroll 1
      for (int c = pr; c < 5; c += 2) {
        {
          mbar_wait(fb, (c >> 1) & 1);
          if (hh == 0 && lane == 0) PT(25 + c);
          uint32_t k[20], o[17];
#pragma unroll
          for (int i = 0; i < 20; i++) { k[i] = lds32(ia + i * 128); if (i >= 3) o[i - 3] = lds32(ia + (33 + i) * 128); }
          fence_async_smem();
          bar_sync(12 + pr, 64);
          if (hh == 0) {
            if (c < 3) fetch(c + 2);
            else if (lane == 0) mbar_arrive(sb + B_KVD + 8 * (c - 3));
          }
          const uint32_t w0 = prmt(sk.x, sk.z, 0x5410), w1 = prmt(sk.x, sk.z, 0x7632), w2 = prmt(sk.y, sk.w, 0x5410), w3 = prmt(sk.y, sk.w, 0x7632);
#pragma unroll
          for (int i = 0; i < 17; i++) o[i] = hmul2(hfma2(k[i + 3], w0, hfma2(k[i + 2], w1, hfma2(k[i + 1], w2, hmul2(k[i], w3)))), o[i]);
          sk = sk1; sk1 = sk2;
#pragma unroll
          for (int i = 0; i < 4; i++) {
            const int e = 8 * (i >> 1) + (i & 1);
            const uint32_t a = (oa ^ ((i >> 1) * 16)) + (i & 1) * 4096;
            sts128(a, prmt(o[7 + e], o[6 + e], sel0), prmt(o[5 + e], o[4 + e], sel0), prmt(o[3 + e], o[2 + e], sel0), prmt(o[1 + e], o[e], sel0));
            sts128(a ^ 64, prmt(o[7 + e], o[6 + e], sel1), prmt(o[5 + e], o[4 + e], sel1), prmt(o[3 + e], o[2 + e], sel1), prmt(o[1 + e], o[e], sel1));
          }
          bar_sync(12 + pr, 64);
        }
        if (hh) {
          fence_async_smem();
          if (elect_one()) {
            const int kb = 2 * c + (vb >> 6);
            tma3_store(&M.kv_st, 0, kb * 64, 63 - tk, out);
            tma3_store(&M.kv_st, 0, 640 + kb * 64, 63 - tk, out + 4096);
            bulk_commit(); bulk_wait_all();
            mbar_arrive(sb + (c == 4 ? B_KVD + 16 : B_KVS + 4 * (c & 2)));
            PTL(35 + c);
          }
          __syncwarp();
        }
      }
    }
    CTXU();
    const int g = lane >> 2, t = lane & 3, row = 8 * hw + g;
    const uint32_t go = (tb * 160 + row) * 80 + cb * 8 + t;
    const int yb = __shfl_sync(~0u, get_epoch() & 1, 0) * 640;
    uint4 T[10];
    if (hw == 2) {
      if (main_cta) { mbar_wait(sb + B_LAST, 0); mbar_wait(sb + B_S15, 1); }
      if (elect_one()) {
        mbar_expect_tx(sb + B_Q, 20480);
#pragma unroll
        for (int h = 0; h < 2; h++) tma2(sb + O_QT + h * 10240, &M.q_ld, cb * 64 + 32 * h, tb * 160, sb + B_Q);
      }
      __syncwarp();
    }
    mbar_wait(sb + B_Q, 0);
#pragma unroll
    for (int i = 0; i < 10; i++) lds128(sb + O_QT + (i & 1) * 10240 + (i >> 1) * 2048 + row * 64 + t * 16, T[i].x, T[i].y, T[i].z, T[i].w);
    fence_async_smem();
    bar_sync(12 + (hw >> 1), 64);
    if (!(tid & 63)) mbar_arrive(sb + B_QD);
    if (tid == 256) PTL(40);
    if (main_cta) {
      bar_arrive(NB_RFREE, 256);
      bar_arrive(NB_RFREE + 1, 256);
      auto red = [&](int c) {
        const int wg = (c & 1) ^ 1;
        conv_reduce<0, 2>(sb, c, tid - 256, yb + 128 * c + yrow, NB_RFULL + wg, 256);
        if (hw == 3 && elect_one()) flag_add(CNT_Y(4 * c + (vb >> 5)), 1);
        if (tid == 256) PTL(41 + c);
        if (c < 3) bar_arrive(NB_RFREE + wg, 256);
        if (c == 2) {
          bar_sync(NB_HELP, 128);
          if (tid == 256) { mbar_arrive(sb + B_P3E); mbar_arrive_remote(sb + B_P3E, rank ^ 1); }
        }
      };
      if (hw == 3) {
        mbar_wait(sb + B_KVD + 16, 0);
        if (elect_one()) { flag_release(CNT_KV(4 + (vb >> 6))); PTL(32); }
        __syncwarp();
      }
#pragma unroll 1
      for (int c = 0; c < 4; c++) red(c);
    }
    uint32_t G[5];
    mbar_wait(sb + B_G, 0);
#pragma unroll
    for (int q = 0; q < 5; q++) { uint16_t v; asm volatile("ld.shared.u16 %0, [%1];" : "=h"(v) : "r"(sb + O_GT + (32 * q + row) * 2)); G[q] = prmt(v, 0, 0x1010); }
#pragma unroll
    for (int i = 0; i < 10; i++) { const uint32_t c = G[i >> 1] ^ 0x80008000u; T[i] = make_uint4(hmul2(T[i].x, c), hmul2(T[i].y, c), hmul2(T[i].z, c), hmul2(T[i].w, c)); }
    if (main_cta) {
      conv_reduce<0, 1>(sb, 4, tid - 256, yb + 512 + yrow, NB_RFULL + 1, 256);
      if (hw == 3 && elect_one()) { flag_add(CNT_Y(16 + (vb >> 5)), 1); PTL(19); }
      bar_sync(12, 256);
    }
#pragma unroll
    for (int h = 0; h < 2; h++) {
      mbar_wait_wd(sb + B_Y + 8 * h, 0, t0);
      if (tid == 256) PTL(46);
      const uint32_t ya = sb + O_Y + h * 10240 + lane * 64 + ((hw ^ ((lane >> 1) & 3)) << 4);
      uint4 y[5];
      for (;;) {
        uint32_t m = ~0u;
#pragma unroll
        for (int q = 4; q >= 0; q--) {
          ldsm4t(y[q].x, y[q].y, y[q].z, y[q].w, ya + q * 2048);
          m = __vimin3_u16x2(__vimin3_u16x2(m, y[q].x, y[q].y), y[q].z, y[q].w);
          if (q == 4 && tb == 12) m = ~0u;
        }
        if (!__any_sync(~0u, (m & 0xFFFFu) == 0 || m < 0x10000u)) break;
#pragma unroll
        for (int q = 0; q < 5; q++)
          asm volatile("ld.relaxed.gpu.global.v4.b32 {%0,%1,%2,%3}, [%4];" : "=r"(y[q].x), "=r"(y[q].y), "=r"(y[q].z), "=r"(y[q].w)
                       : "l"((const uint4*)g_y2T + (yb + cb * 64 + 32 * h + lane) * 256 + tb * 20 + (q == 4 && tb == 12 ? 0 : 4 * q) + hw) : "memory");
#pragma unroll
        for (int q = 0; q < 5; q++) sts128(ya + q * 2048, y[q].x, y[q].y, y[q].z, y[q].w);
        __syncwarp();
        PTL(49);
      }
#pragma unroll
      for (int q = 0; q < 5; q++) {
        uint4& r = T[2 * q + h];
        r = make_uint4(hmul2(r.x, y[q].x), hmul2(r.y, y[q].y), hmul2(r.z, y[q].z), hmul2(r.w, y[q].w));
      }
    }
    const uint32_t so = sb + O_BT + row * 128 + ((t ^ ((g & 1) << 2 | g >> 1)) << 4);
    if (tid == 256) PTL(47);
#pragma unroll
    for (int q = 0; q < 5; q++) {
      const uint32_t c = hfma2(G[q], 0xBF80BF80u, 0x3F803F80u);
      bar_sync(1 + q, 256);
      if (q == 4) mbar_arrive_p(tid == 256, sb + B_DONE);
#pragma unroll
      for (int h = 0; h < 2; h++) {
        uint4 u;
        lds128((so ^ (h * 64)) + q * 4096, u.x, u.y, u.z, u.w);
        const uint4& r = T[2 * q + h];
        if (q < 4 || tb < 12) ((uint4*)outp)[go + q * 2560 + h * 4] = make_uint4(hfma2(u.x, c, r.x), hfma2(u.y, c, r.y), hfma2(u.z, c, r.z), hfma2(u.w, c, r.w));
      }
    }
  } else {
    reg_dec<RP>();
    uint4 gwv = make_uint4(0, 0, 0, 0);
    if (warp == 15) {
      const int p = cta_pair(), rank = blockIdx.x & 1;
      asm volatile("barrier.cluster.wait.aligned;" ::: "memory");
      if (blockIdx.x >= 128) bar_sync(0, 512);
      else {
#pragma unroll 1
        for (int ks = 1;; ks += 2) {
          mbar_wait(sb + B_EMPTY + 8 * (ks & 7), ((ks >> 3) & 1) ^ 1);
          spin_until(t0, PT1 + (ks - 1) * PTD);
          if (elect_one()) { mbar_expect_tx(sb + B_FULL + 8 * (ks & 7), WST); p1_load_w(ks, p, rank); PT(100 + ks); }
          if (ks == 19) break;
          const int kn = ks + 1;
          mbar_wait(sb + B_EMPTY + 8 * (kn & 7), ((kn >> 3) & 1) ^ 1);
          spin_until(t0, PT1 + ks * PTD - PTE);
          if (elect_one()) { mbar_expect_tx(sb + B_FULL + 8 * (kn & 7), 16384 + WST); p1_load_x(kn, p, rank); p1_load_w(kn, p, rank); PT(100 + kn); }
        }
        if (elect_one()) mbar_arrive(sb + B_LAST);
#pragma unroll 1
        for (int i = 0; i < 2; i++) {
          mbar_wait(sb + B_KVS + 8 * i, 0);
          if (elect_one()) { flag_release(CNT_KV(2 * i + (p >> 5))); PTL(30 + i); }
          __syncwarp();
        }
        mbar_wait(sb + B_S19, 0);
      }
    } else {
      if (threadIdx.x < 384 + 80) gwv = __ldg((const uint4*)gate_w + threadIdx.x - 384);
      init_rest();
    }
    ctx = __shfl_sync(~0u, make_ctx(), 0);
    CTXU();
    if (warp == 12) {
        unsigned epoch = 0;
      if (lane == 0) epoch = *(volatile unsigned*)(g_launch + 32 * vb) + 1;
      if (main_cta) { sts128(sb + O_GW + lane * 16, gwv.x, gwv.y, gwv.z, gwv.w); bar_arrive(NB_G, 96); }
      if (lane == 0) {
        if ((sb & 0xFFFFFF) != SB) __trap();
        sts32(sb + O_EPOCH, epoch);
        mbar_arrive(sb + B_EP);
#pragma unroll 1
        for (int i = 5; i < 11; i++) asm volatile("prefetch.tensormap [%0];" ::"l"(&M.x_par + i) : "memory");
      }
      if (main_cta && rank) {
#pragma unroll
        for (int f = 0; f < 5; f++) st_relaxed(g_halo + vb * 160 + lane + 32 * f, ~0u, ~0u, ~0u, ~0u);
      }
      __syncwarp();
      if (elect_one()) flag_release(g_launch + 32 * vb);
      __syncwarp();
      if (main_cta) {
        uint4 h0 = make_uint4(0, 0, 0, 0);
        if (lane < 5) {
          h0 = __ldg((const uint4*)(ssm_k + (size_t)(128 * lane + vb) * 2048));
          h0.x = prmt(pack_bf16(bf_lo(h0.x) + bf_lo(__ldg(ssm_D + 128 * lane + vb)), 0.f), h0.x, 0x7610);
        }
        epoch = __shfl_sync(~0u, epoch, 0);
        const int ze = lane & 7;
        const uint32_t za = sb + (lane < 8 ? o_u(ze) + UZ : lane < 24 ? o_h(ze) + (lane >> 4) * 4160 + 4096 : o_u(ze) + 512);
        const uint16_t* hp = ssm_k + (size_t)vb * 2048 + 8;
        const uint16_t* up = g_kvT + (size_t)vb * 2048;
        const unsigned* fp = CNT_KV(vb >> 6);
        sts128(sb + O_Y - 512 + lane * 16, 0, 0, 0, 0);
        mbar_wait(sb + B_LAST, 0);
        mbar_wait(sb + B_S13, 1);
#pragma unroll
        for (int c = 0; c < 5; c++) {
          if (c == 0 || c == 3) {
            mbar_wait(sb + B_KVD + (c ? 8 : 0), 0);
#pragma unroll
            for (int e = c; e < (c ? 5 : 3); e++) sts128(sb + o_u(e) + lane * 16, 0, 0, 0, 0);
            if (ze >= c && ze < (c ? 5 : 3)) sts128(za, h0.x, h0.y, h0.z, h0.w);
            fence_async_smem();
            __syncwarp();
            if (elect_one()) {
#pragma unroll
              for (int e = c; e < (c ? 5 : 3); e++) {
                mbar_expect_tx(sb + B_U + 8 * e, 3 * 4096 - 16);
                if (c || e == 0) bulk_load(sb + o_u(e) + UZ + 16, hp + 128 * 2048 * e, 4080, sb + B_U + 8 * e);
              }
            }
          }
          if (!(c & 1)) { flag_wait(fp + 32 * c, 64 * epoch); __syncwarp(); }
          if (elect_one()) {
            bulk_load(sb + o_h(c), up + 128 * 2048 * c, 4096, sb + B_U + 8 * c);
            bulk_load(sb + o_h(c) + 4160, up + (640 + 128 * c) * 2048, 4096, sb + B_U + 8 * c);
            if (c == 1) {
#pragma unroll
              for (int e = 1; e < 3; e++) bulk_load(sb + o_u(e) + UZ + 16, hp + 128 * 2048 * e, 4080, sb + B_U + 8 * e);
            }
            PTL(10 + c);
          }
        }
        mbar_wait(sb + B_LAST, 1);
        if (elect_one()) {
#pragma unroll 1
          for (int i = 0; i < 40; i++) bulk_store(g_y2T + (size_t)((~epoch & 1) * 640 + 5 * vb) * 2048 + i * 256, sb + O_Y - 512, 512);
          bulk_commit(); bulk_wait_read();
          PTL(33);
        }
      }
    } else if (warp != 15) {
        const int r = warp - 13;
      if (main_cta) {
        if (rank && lane == 0) mbar_expect_tx(sb + B_HX0, 1280);
        const int t = lane & 3, grow = hg * 16 + (lane & 15);
        const uint32_t ga = sb + grow * 128 + (((4 * r + (lane >> 4)) ^ (lane & 7)) << 4);
        const uint32_t gp = sb + O_GW + 64 * r + 4 * t;
        float s0 = 0.f, s1 = 0.f;
        if (tid < 384 + 80) sts128(sb + O_GW + (tid - 384) * 16, gwv.x, gwv.y, gwv.z, gwv.w);
        bar_sync(NB_G, 96);
#pragma unroll 1
        for (int ks = 0; ks < 20; ks += 2) {
          uint32_t x[8], gw[4];
#pragma unroll
          for (int i = 0; i < 4; i++) gw[i] = lds32(gp + ks * 64 + i * 16);
          mbar_wait_wd(sb + B_FULL + 8 * (ks & 7), (ks >> 3) & 1, t0);
          if (r == 0 && lane == 0) PT(120 + ks);
          ldsm4(x[0], x[1], x[2], x[3], ga + o_px(ks)); ldsm4(x[4], x[5], x[6], x[7], (ga ^ 32) + o_px(ks));
#pragma unroll
          for (int i = 0; i < 8; i++) x[i] = hmul2(x[i], gw[i >> 1]);
          if (lane < 2) mbar_arrive(sb + B_EMPTY + 8 * (ks & 7) + 8 * lane + (x[0] & x[7] & threadIdx.y));
#pragma unroll
          for (int i = 0; i < 8; i += 4) {
            s0 += (bf_lo(x[i]) + bf_hi(x[i])) + (bf_lo(x[i + 2]) + bf_hi(x[i + 2]));
            s1 += (bf_lo(x[i + 1]) + bf_hi(x[i + 1])) + (bf_lo(x[i + 3]) + bf_hi(x[i + 3]));
          }
        }
        s0 += __shfl_xor_sync(~0u, s0, 1); s1 += __shfl_xor_sync(~0u, s1, 1);
        s0 += __shfl_xor_sync(~0u, s0, 2); s1 += __shfl_xor_sync(~0u, s1, 2);
        if (t < 2) sts32(sb + O_GP + r * 64 + (8 * t + (lane >> 2)) * 4, __float_as_uint(t ? s1 : s0));
        if (lane == 0) mbar_arrive(sb + B_GD);
        if (r == 0) bar_arrive(NB_G, 64);
        if (!rank) {
          uint4 d[3];
          if (mt > 0) {
            const uint4* hp = g_halo + (vb - 1) * 160 + r * 64 + lane;
            mbar_wait_wd(sb + B_EP, 0, t0);
            flag_wait_wd(g_launch + 32 * (vb - 1), lds32(sb + O_EPOCH), t0);
            mbar_wait_wd(sb + B_HX + 56, 0, t0);
            for (;;) {
              bool ok = true;
#pragma unroll
              for (int f = 0; f < 3; f++) {
                asm volatile("ld.relaxed.gpu.global.v4.b32 {%0,%1,%2,%3}, [%4];" : "=r"(d[f].x), "=r"(d[f].y), "=r"(d[f].z), "=r"(d[f].w) : "l"(hp + 32 * f) : "memory");
              }
#pragma unroll
              for (int f = 0; f < 3; f++) ok = ok && max(max(d[f].x, d[f].y), max(d[f].z, d[f].w)) != ~0u;
              if (__all_sync(~0u, ok)) break;
              if (clk() - t0 > 0x70000000u) __trap();
            }
          } else {
#pragma unroll
            for (int f = 0; f < 3; f++) d[f] = make_uint4(0, 0, 0, 0);
          }
#pragma unroll
          for (int f = 0; f < 3; f++) stsm4(sb + O_HIN + r * 1024 + f * 512 + lane * 16, d[f].x, d[f].y, d[f].z, d[f].w);
          __syncwarp();
          if (lane == 0) { mbar_arrive(sb + B_HX0); PTL(15 + r); }
        }
        if (r == 1) {
          bar_sync(NB_G, 64);
          if (lane < 16) {
            const uint32_t pa = sb + O_GP + lane * 4;
            const float z = __uint_as_float(lds32(pa)) + __uint_as_float(lds32(pa + 64));
            g_gate[2 * (mt * 128 + hg * 16 + lane) + par] = (uint16_t)pack_bf16(__fdividef(1.f, 1.f + __expf(-bf_lo(pack_bf16(z, 0.f)))), 0.f);
          }
          __syncwarp();
          if (elect_one()) flag_release(CNT_O(rt));
        }
      }
      mbar_wait_wd(sb + B_EP, 0, t0);
      const unsigned epoch = lds32(sb + O_EPOCH);
      if (main_cta) mbar_wait_wd(sb + B_P3E, 0, t0);
      flag_wait_wd(CNT_Y(2 * cb + r), 32 * epoch, t0);
      __syncwarp();
      if (elect_one()) {
        mbar_expect_tx(sb + B_Y + 8 * r, 10240);
        tma3(sb + O_Y + r * 10240, &M.y_ld, 0, (epoch & 1) * 640 + cb * 64 + 32 * r, tb * 5, sb + B_Y + 8 * r);
        PTL(17 + r);
      }
      __syncwarp();
      mbar_wait_wd(sb + B_DONE, 0, t0);
    } else {
      const unsigned epoch = get_epoch();
      if (main_cta) {
        bar_sync(NB_LEAD, 160);
        if (elect_one()) tma3_store(&M.o_st, hg * 80, par, mt * 128 + 64, sb + O_OST + 2 * STG);
        bar_sync(NB_ATT, 160);
        if (elect_one()) {
          tma3_store(&M.o_st, hg * 80, par, mt * 128, sb + O_OST);
          bulk_commit(); bulk_wait_all();
          flag_release(CNT_O(rt));
          mbar_arrive(sb + B_LAST);
          PTL(3);
        }
        __syncwarp();
      }
      mbar_wait(sb + B_QD, 0);
#pragma unroll 1
      for (int ks = 0; ks < 5; ks++)
        if (elect_one()) tma2(sb + o_p3(ks), &M.wo, cb * 64, ks * 64, sb + B_P3F + 8 * ks);
      if (lane < 4) flag_wait(CNT_O(8 * (lane & 1) + min(7, (80 * tb + 79 * (lane >> 1)) >> 7)), 16 * epoch);
      __syncwarp();
      if (elect_one()) {
        PTL(4);
        mbar_arrive_remote(sb + B_P3R, rank ^ 1);
        mbar_expect_tx(sb + B_G, 320);
        bulk_load(sb + O_GT, g_gate + tb * 160, 320, sb + B_G);
      }
      mbar_wait(sb + B_P3R, 0);
#pragma unroll 1
      for (int ks = 0; ks < 10; ks++) {
        if (ks > 5 || (ks == 5 && main_cta)) mbar_wait(sb + B_P3E + 8 * (ks - 5), 0);
        if (elect_one()) {
          PTP(ks >= 5, ks);
          tma2_mc(sb + o_p3(ks) + 8192 + rank * 10240, &M.o_ld, ks * 64, tb * 160 + rank * 80, sb + B_P3F + 8 * ks);
          if (ks >= 5) tma2(sb + o_p3(ks), &M.wo, cb * 64, ks * 64, sb + B_P3F + 8 * ks);
          mbar_expect_tx(sb + B_P3F + 8 * ks, P3S);
        }
      }
    }
  }
}

typedef CUresult (*PFN_enc)(CUtensorMap*, CUtensorMapDataType, cuuint32_t, void*, const cuuint64_t*, const cuuint64_t*, const cuuint32_t*,
                            const cuuint32_t*, CUtensorMapInterleave, CUtensorMapSwizzle, CUtensorMapL2promotion, CUtensorMapFloatOOBfill);
static void enc(PFN_enc f, CUtensorMap* m, const void* base, int rank, const cuuint64_t* dims, const cuuint64_t* strides, const cuuint32_t* box,
                CUtensorMapSwizzle sw) {
  const cuuint32_t es[5] = {1, 1, 1, 1, 1};
  f(m, CU_TENSOR_MAP_DATA_TYPE_BFLOAT16, rank, (void*)base, dims, strides, box, es, CU_TENSOR_MAP_INTERLEAVE_NONE, sw,
    CU_TENSOR_MAP_L2_PROMOTION_NONE, CU_TENSOR_MAP_FLOAT_OOB_FILL_NONE);
}

extern "C" void kernel_launch(void* const* d_in, const int* in_sizes, int n_in, void* d_out, int out_size) {
  (void)in_sizes; (void)n_in; (void)out_size;
  static PFN_enc f = nullptr;
  static void *kvT, *y2T, *o;
  if (!f) {
    void* p = nullptr;
    cudaDriverEntryPointQueryResult q;
    cudaGetDriverEntryPoint("cuTensorMapEncodeTiled", &p, cudaEnableDefault, &q);
    f = (PFN_enc)p;
    cudaGetSymbolAddress(&kvT, g_kvT); cudaGetSymbolAddress(&y2T, g_y2T); cudaGetSymbolAddress(&o, g_o);
    cudaFuncSetAttribute(fused_kernel, cudaFuncAttributeMaxDynamicSharedMemorySize, SMEM_BYTES);
  }
  Maps M;
  const CUtensorMapSwizzle S0 = CU_TENSOR_MAP_SWIZZLE_NONE, S32 = CU_TENSOR_MAP_SWIZZLE_32B, S64 = CU_TENSOR_MAP_SWIZZLE_64B, S128 = CU_TENSOR_MAP_SWIZZLE_128B;
  const cuuint64_t dpar[3] = {640, 2, 1024}, spar[2] = {1280, 2560};
  const cuuint64_t dw[3] = {640, 640, 3}, sw[2] = {3840, 1280};
  const cuuint64_t dnat[2] = {640, 2048}, snat[1] = {1280};
  const cuuint64_t dT2[3] = {32, 1280, 64}, sT[2] = {4096, 64};
  const cuuint64_t dwo[2] = {640, 640};
  { const cuuint32_t bx[3] = {64, 1, 128}; enc(f, &M.x_par, d_in[0], 3, dpar, spar, bx, S128); }
  { const cuuint32_t bx[3] = {64, 16, 3}; enc(f, &M.w_main, d_in[7], 3, dw, sw, bx, S128); }
  { const cuuint32_t bx[3] = {16, 16, 3}; enc(f, &M.w_tail, d_in[7], 3, dw, sw, bx, S32); }
  { const cuuint32_t bx[3] = {80, 1, 64}; enc(f, &M.o_st, o, 3, dpar, spar, bx, S0); }
  { const cuuint32_t bx[3] = {32, 64, 1}; enc(f, &M.kv_st, kvT, 3, dT2, sT, bx, S64); }
  { const cuuint32_t bx[3] = {32, 32, 5}; enc(f, &M.y_ld, y2T, 3, dT2, sT, bx, S64); }
  { const cuuint32_t bx[2] = {64, 36}; enc(f, &M.k_ld, d_in[1], 2, dnat, snat, bx, S0); }
  { const cuuint32_t bx[2] = {64, 33}; enc(f, &M.v_ld, d_in[2], 2, dnat, snat, bx, S0); }
  { const cuuint32_t bx[2] = {32, 160}; enc(f, &M.q_ld, d_in[0], 2, dnat, snat, bx, S0); }
  { const cuuint32_t bx[2] = {64, 64}; enc(f, &M.wo, d_in[8], 2, dwo, snat, bx, S128); }
  { const cuuint32_t bx[2] = {64, 80}; enc(f, &M.o_ld, o, 2, dnat, snat, bx, S128); }
  fused_kernel<<<130, 512, SMEM_BYTES, cudaStreamPerThread>>>((const uint16_t*)d_in[0], (const uint16_t*)d_in[7], (const uint16_t*)d_in[9], M, (const uint16_t*)d_in[3], (const uint16_t*)d_in[4], (const uint16_t*)d_in[5],
                                                              (uint16_t*)d_out);
}
```

```cpp
#include <cuda_runtime.h>
#include <cuda_bf16.h>
#include <cuda.h>
#include <stdint.h>

#define DEVI __device__ __forceinline__
#define PT1 300
#define PTD 460
#define PTE 150
#define DEFER 4
#define KPH KTD
#define NPRE 1
#define NLATE 4
#define KT0 1500
#define KTD 1000
#define RC 192
#define RH 96
#define RP 32
#define HOLD 750
#define LEAD 3

DEVI uint32_t smem_u32(const void* p) { return (uint32_t)__cvta_generic_to_shared(p); }
DEVI void wg_fence() { asm volatile("wgmma.fence.sync.aligned;" ::: "memory"); }
DEVI void wg_commit() { asm volatile("wgmma.commit_group.sync.aligned;" ::: "memory"); }
template <int N> DEVI void wg_wait() { asm volatile("wgmma.wait_group.sync.aligned %0;" ::"n"(N) : "memory"); }
template <int A = 0, int B = -1, int S> DEVI void fence_regs(float (&d)[S]) {
#pragma unroll
  for (int i = A; i < (B < 0 ? S : B); i++) asm volatile("" : "+f"(d[i])::"memory");
}
DEVI uint64_t mkdesc(uint32_t addr, uint32_t lbo, uint32_t sbo, int swz) {
  return (uint64_t)((addr & 0x3FFFF) >> 4) | ((uint64_t)(lbo >> 4) << 16) | ((uint64_t)(sbo >> 4) << 32) | ((uint64_t)swz << 62);
}
DEVI void mbar_init(uint32_t bar, uint32_t cnt) { asm volatile("mbarrier.init.shared::cta.b64 [%0], %1;" ::"r"(bar), "r"(cnt) : "memory"); }
DEVI void mbar_expect_tx(uint32_t bar, uint32_t bytes) { asm volatile("mbarrier.arrive.expect_tx.shared::cta.b64 _, [%0], %1;" ::"r"(bar), "r"(bytes) : "memory"); }
DEVI void mbar_arrive(uint32_t bar) { asm volatile("mbarrier.arrive.shared::cta.b64 _, [%0];" ::"r"(bar) : "memory"); }
DEVI void mbar_wait(uint32_t bar, uint32_t parity) {
  asm volatile("{\n.reg .pred p;\nLAB_WAIT:\nmbarrier.try_wait.parity.shared::cta.b64 p, [%0], %1;\n@!p bra LAB_WAIT;\n}" ::"r"(bar), "r"(parity) : "memory");
}
DEVI void mbar_wait_wd(uint32_t bar, uint32_t parity, uint32_t t0) {
  asm volatile("{\n.reg .pred p;\n.reg .u32 c;\nLAB_WAIT:\nmbarrier.try_wait.parity.shared::cta.b64 p, [%0], %1;\n@p bra DONE;\nmov.u32 c, %%clock;\nsub.u32 c, c, %2;\nsetp.lt.u32 p, c, 0x70000000;\n@p bra LAB_WAIT;\ntrap;\nDONE:\n}" ::"r"(bar), "r"(parity), "r"(t0) : "memory");
}
DEVI void flag_wait(const unsigned* p, unsigned target) {
  asm volatile("{\n.reg .pred p;\n.reg .s32 v;\nLAB_WAIT:\nld.relaxed.gpu.global.u32 v, [%0];\nsub.s32 v, v, %1;\nsetp.lt.s32 p, v, 0;\n@p bra LAB_WAIT;\n}" ::"l"(p), "r"(target) : "memory");
}
DEVI void flag_wait_wd(const unsigned* p, unsigned target, uint32_t t0) {
  asm volatile("{\n.reg .pred p;\n.reg .s32 v;\nLAB_WAIT:\nld.relaxed.gpu.global.u32 v, [%0];\nsub.s32 v, v, %1;\nsetp.ge.s32 p, v, 0;\n@p bra DONE;\nmov.u32 v, %%clock;\nsub.s32 v, v, %2;\nsetp.lt.u32 p, v, 0x70000000;\n@p bra LAB_WAIT;\ntrap;\nDONE:\n}" ::"l"(p), "r"(target), "r"(t0) : "memory");
}
DEVI void flag_add(unsigned* p, unsigned v) { asm volatile("red.relaxed.gpu.global.add.u32 [%0], %1;" ::"l"(p), "r"(v) : "memory"); }
DEVI void flag_release(unsigned* p) { asm volatile("fence.proxy.async;\nred.relaxed.gpu.global.add.u32 [%0], 1;" ::"l"(p) : "memory"); }
DEVI void fence_async_smem() { asm volatile("fence.proxy.async.shared::cta;" ::: "memory"); }
DEVI bool elect_one() { uint32_t p; asm volatile("{\n.reg .pred P;\nelect.sync _|P, 0xffffffff;\nselp.u32 %0, 1, 0, P;\n}" : "=r"(p)); return p; }
DEVI void bar_sync(int id, int n) { asm volatile("bar.sync %0, %1;" ::"r"(id), "r"(n) : "memory"); }
DEVI void bar_arrive(int id, int n) { asm volatile("bar.arrive %0, %1;" ::"r"(id), "r"(n) : "memory"); }
DEVI void tma2(uint32_t dst, const CUtensorMap* m, int c0, int c1, uint32_t bar) {
  asm volatile("cp.async.bulk.tensor.2d.shared::cluster.global.mbarrier::complete_tx::bytes [%0], [%1, {%3, %4}], [%2];" ::"r"(dst), "l"(m), "r"(bar), "r"(c0), "r"(c1) : "memory");
}
DEVI void tma3(uint32_t dst, const CUtensorMap* m, int c0, int c1, int c2, uint32_t bar) {
  asm volatile("cp.async.bulk.tensor.3d.shared::cluster.global.mbarrier::complete_tx::bytes [%0], [%1, {%3, %4, %5}], [%2];" ::"r"(dst), "l"(m), "r"(bar), "r"(c0), "r"(c1), "r"(c2) : "memory");
}
DEVI void tma3_mc(uint32_t dst, const CUtensorMap* m, int c0, int c1, int c2, uint32_t bar) {
  asm volatile("cp.async.bulk.tensor.3d.shared::cluster.global.mbarrier::complete_tx::bytes.multicast::cluster [%0], [%1, {%3, %4, %5}], [%2], %6;" ::"r"(dst), "l"(m), "r"(bar), "r"(c0), "r"(c1), "r"(c2), "h"((uint16_t)3) : "memory");
}
DEVI void tma2_mc(uint32_t dst, const CUtensorMap* m, int c0, int c1, uint32_t bar) {
  asm volatile("cp.async.bulk.tensor.2d.shared::cluster.global.mbarrier::complete_tx::bytes.multicast::cluster [%0], [%1, {%3, %4}], [%2], %5;" ::"r"(dst), "l"(m), "r"(bar), "r"(c0), "r"(c1), "h"((uint16_t)3) : "memory");
}
DEVI void mbar_arrive_remote(uint32_t bar, uint32_t cta) {
  asm volatile("{\n.reg .b32 ra;\nmapa.shared::cluster.u32 ra, %0, %1;\nmbarrier.arrive.shared::cluster.b64 _, [ra];\n}" ::"r"(bar), "r"(cta) : "memory");
}
DEVI void tma3_store(const CUtensorMap* m, int c0, int c1, int c2, uint32_t src) {
  asm volatile("cp.async.bulk.tensor.3d.global.shared::cta.bulk_group [%0, {%2, %3, %4}], [%1];" ::"l"(m), "r"(src), "r"(c0), "r"(c1), "r"(c2) : "memory");
}
DEVI void bulk_load(uint32_t dst, const void* src, uint32_t bytes, uint32_t bar) {
  asm volatile("cp.async.bulk.shared::cluster.global.mbarrier::complete_tx::bytes [%0], [%1], %2, [%3];" ::"r"(dst), "l"(src), "r"(bytes), "r"(bar) : "memory");
}
DEVI void bulk_store(void* dst, uint32_t src, uint32_t bytes) {
  asm volatile("cp.async.bulk.global.shared::cta.bulk_group [%0], [%1], %2;" ::"l"(dst), "r"(src), "r"(bytes) : "memory");
}
DEVI void pf_l2(const void* p) { asm volatile("prefetch.global.L2 [%0];" ::"l"(p)); }
template <int OFF> DEVI uint32_t ldg_v(const void* p) { uint32_t v; asm volatile("ld.volatile.global.b32 %0, [%1 + %2];" : "=r"(v) : "l"(p), "n"(OFF)); return v; }
DEVI void bulk_commit() { asm volatile("cp.async.bulk.commit_group;" ::: "memory"); }
DEVI void bulk_wait_all() { asm volatile("cp.async.bulk.wait_group 0;" ::: "memory"); }
DEVI void bulk_wait_read() { asm volatile("cp.async.bulk.wait_group.read 0;" ::: "memory"); }
template <int R> DEVI void reg_inc() { asm volatile("setmaxnreg.inc.sync.aligned.u32 %0;" ::"n"(R)); }
template <int R> DEVI void reg_dec() { asm volatile("setmaxnreg.dec.sync.aligned.u32 %0;" ::"n"(R)); }
DEVI uint32_t prmt(uint32_t a, uint32_t b, uint32_t s) { uint32_t r; asm("prmt.b32 %0,%1,%2,%3;" : "=r"(r) : "r"(a), "r"(b), "r"(s)); return r; }
DEVI uint32_t lds32(uint32_t a) { uint32_t r; asm volatile("ld.shared.b32 %0,[%1];" : "=r"(r) : "r"(a)); return r; }
DEVI void sts32(uint32_t a, uint32_t x) { asm volatile("st.shared.b32 [%0],%1;" ::"r"(a), "r"(x) : "memory"); }
DEVI void sts128(uint32_t a, uint32_t x, uint32_t y, uint32_t z, uint32_t w) { asm volatile("st.shared.v4.b32 [%0],{%1,%2,%3,%4};" ::"r"(a), "r"(x), "r"(y), "r"(z), "r"(w) : "memory"); }
DEVI void sts128v(uint32_t a, uint32_t x, uint32_t y, uint32_t z, uint32_t w) { asm volatile("st.volatile.shared.v4.b32 [%0],{%1,%2,%3,%4};" ::"r"(a), "r"(x), "r"(y), "r"(z), "r"(w) : "memory"); }
DEVI void lds128(uint32_t a, uint32_t& x, uint32_t& y, uint32_t& z, uint32_t& w) { asm volatile("ld.shared.v4.b32 {%0,%1,%2,%3},[%4];" : "=r"(x), "=r"(y), "=r"(z), "=r"(w) : "r"(a) : "memory"); }
DEVI void ldsm4(uint32_t& r0, uint32_t& r1, uint32_t& r2, uint32_t& r3, uint32_t addr) {
  asm volatile("ldmatrix.sync.aligned.m8n8.x4.shared.b16 {%0,%1,%2,%3}, [%4];" : "=r"(r0), "=r"(r1), "=r"(r2), "=r"(r3) : "r"(addr) : "memory");
}
DEVI void ldsm4t(uint32_t& r0, uint32_t& r1, uint32_t& r2, uint32_t& r3, uint32_t addr) {
  asm volatile("ldmatrix.sync.aligned.m8n8.x4.trans.shared.b16 {%0,%1,%2,%3}, [%4];" : "=r"(r0), "=r"(r1), "=r"(r2), "=r"(r3) : "r"(addr) : "memory");
}
DEVI void stsm4(uint32_t addr, uint32_t r0, uint32_t r1, uint32_t r2, uint32_t r3) {
  asm volatile("stmatrix.sync.aligned.m8n8.x4.shared.b16 [%0], {%1,%2,%3,%4};" ::"r"(addr), "r"(r0), "r"(r1), "r"(r2), "r"(r3) : "memory");
}
DEVI void stsm4t(uint32_t addr, uint32_t r0, uint32_t r1, uint32_t r2, uint32_t r3) {
  asm volatile("stmatrix.sync.aligned.m8n8.x4.trans.shared.b16 [%0], {%1,%2,%3,%4};" ::"r"(addr), "r"(r0), "r"(r1), "r"(r2), "r"(r3) : "memory");
}
DEVI uint32_t movm(uint32_t a) { uint32_t r; asm volatile("movmatrix.sync.aligned.m8n8.trans.b16 %0, %1;" : "=r"(r) : "r"(a)); return r; }
DEVI uint32_t pack_bf16(float lo, float hi) { uint32_t r; asm("cvt.rn.bf16x2.f32 %0, %1, %2;" : "=r"(r) : "f"(hi), "f"(lo)); return r; }
DEVI uint32_t hmul2(uint32_t a, uint32_t b) { uint32_t r; asm("mul.rn.bf16x2 %0,%1,%2;" : "=r"(r) : "r"(a), "r"(b)); return r; }
DEVI uint32_t hadd2(uint32_t a, uint32_t b) { uint32_t r; asm("add.rn.bf16x2 %0,%1,%2;" : "=r"(r) : "r"(a), "r"(b)); return r; }
DEVI float bf_lo(uint32_t a) { return __uint_as_float(prmt(a, 0, 0x1044)); }
DEVI float bf_hi(uint32_t a) { return __uint_as_float(a & 0xFFFF0000u); }
DEVI void mma16(float (&c)[4], uint32_t a0, uint32_t a1, uint32_t a2, uint32_t a3, uint32_t b0, uint32_t b1) {
  asm volatile("mma.sync.aligned.m16n8k16.row.col.f32.bf16.bf16.f32 {%0,%1,%2,%3},{%4,%5,%6,%7},{%8,%9},{%0,%1,%2,%3};"
      : "+f"(c[0]), "+f"(c[1]), "+f"(c[2]), "+f"(c[3]) : "r"(a0), "r"(a1), "r"(a2), "r"(a3), "r"(b0), "r"(b1));
}
DEVI void mma8(float (&c)[4], uint32_t a0, uint32_t a1, uint32_t b0) {
  asm volatile("mma.sync.aligned.m16n8k8.row.col.f32.bf16.bf16.f32 {%0,%1,%2,%3},{%4,%5},{%6},{%0,%1,%2,%3};"
      : "+f"(c[0]), "+f"(c[1]), "+f"(c[2]), "+f"(c[3]) : "r"(a0), "r"(a1), "r"(b0));
}
DEVI float ex2(float x) { float r; asm volatile("ex2.approx.ftz.f32 %0, %1;" : "=f"(r) : "f"(x)); return r; }

DEVI uint32_t clk() { uint32_t c; asm volatile("mov.u32 %0, %%clock;" : "=r"(c)); return c; }
DEVI void wait_until(uint32_t t0, int dt) { while ((int)(clk() - t0) < dt) __nanosleep(40); }
DEVI void spin_until(uint32_t t0, int dt) { while ((int)(clk() - t0) < dt) {} }
DEVI uint32_t hfma2(uint32_t a, uint32_t b, uint32_t c) { uint32_t r; asm("fma.rn.bf16x2 %0,%1,%2,%3;" : "=r"(r) : "r"(a), "r"(b), "r"(c)); return r; }
DEVI void bar_sync_p(int on, int id, int n) { asm volatile("{\n.reg .pred p;\nsetp.ne.b32 p, %0, 0;\n@p bar.sync %1, %2;\n}" ::"r"(on), "r"(id), "r"(n) : "memory"); }
DEVI void bar_arrive_p(int on, int id, int n) { asm volatile("{\n.reg .pred p;\nsetp.ne.b32 p, %0, 0;\n@p bar.arrive %1, %2;\n}" ::"r"(on), "r"(id), "r"(n) : "memory"); }
DEVI void mbar_arrive_p(int on, uint32_t bar) { asm volatile("{\n.reg .pred p;\nsetp.ne.b32 p, %1, 0;\n@p mbarrier.arrive.shared::cta.b64 _, [%0];\n}" ::"r"(bar), "r"(on) : "memory"); }
DEVI void mbar_arrive2_p(int on, uint32_t bar, uint32_t rbar) {
  asm volatile("{\n.reg .pred p;\nsetp.ne.b32 p, %2, 0;\n@p mbarrier.arrive.shared::cta.b64 _, [%0];\n@p mbarrier.arrive.shared::cluster.b64 _, [%1];\n}" ::"r"(bar), "r"(rbar), "r"(on) : "memory");
}
DEVI void st_relaxed(uint4* p, uint32_t x, uint32_t y, uint32_t z, uint32_t w) {
  asm volatile("st.relaxed.gpu.global.v4.b32 [%0], {%1,%2,%3,%4};" ::"l"(p), "r"(x), "r"(y), "r"(z), "r"(w) : "memory");
}
DEVI uint32_t mapa(uint32_t a, uint32_t cta) { uint32_t r; asm("mapa.shared::cluster.u32 %0, %1, %2;" : "=r"(r) : "r"(a), "r"(cta)); return r; }
DEVI void st_async128(uint32_t a, uint32_t x, uint32_t y, uint32_t z, uint32_t w, uint32_t bar) {
  asm volatile("st.async.weak.shared::cluster.mbarrier::complete_tx::bytes.v4.b32 [%0], {%1,%2,%3,%4}, [%5];" ::"r"(a), "r"(x), "r"(y), "r"(z), "r"(w), "r"(bar) : "memory");
}

template<int OFF, int TB, int S> __device__ __forceinline__ void wgmma_rs_n128(float (&d)[S], uint32_t a0, uint32_t a1, uint32_t a2, uint32_t a3, uint64_t db, int sd) {
  asm volatile("{\n.reg .pred p;\nsetp.ne.b32 p, %69, 0;\n"
    "wgmma.mma_async.sync.aligned.m64n128k16.f32.bf16.bf16 {%0, %1, %2, %3, %4, %5, %6, %7, %8, %9, %10, %11, %12, %13, %14, %15, %16, %17, %18, %19, %20, %21, %22, %23, %24, %25, %26, %27, %28, %29, %30, %31, %32, %33, %34, %35, %36, %37, %38, %39, %40, %41, %42, %43, %44, %45, %46, %47, %48, %49, %50, %51, %52, %53, %54, %55, %56, %57, %58, %59, %60, %61, %62, %63}, {%64, %65, %66, %67}, %68, p, 1, 1, %70;\n}\n"
    : "+f"(d[OFF+0]), "+f"(d[OFF+1]), "+f"(d[OFF+2]), "+f"(d[OFF+3]), "+f"(d[OFF+4]), "+f"(d[OFF+5]), "+f"(d[OFF+6]), "+f"(d[OFF+7]), "+f"(d[OFF+8]), "+f"(d[OFF+9]), "+f"(d[OFF+10]), "+f"(d[OFF+11]), "+f"(d[OFF+12]), "+f"(d[OFF+13]), "+f"(d[OFF+14]), "+f"(d[OFF+15]), "+f"(d[OFF+16]), "+f"(d[OFF+17]), "+f"(d[OFF+18]), "+f"(d[OFF+19]), "+f"(d[OFF+20]), "+f"(d[OFF+21]), "+f"(d[OFF+22]), "+f"(d[OFF+23]), "+f"(d[OFF+24]), "+f"(d[OFF+25]), "+f"(d[OFF+26]), "+f"(d[OFF+27]), "+f"(d[OFF+28]), "+f"(d[OFF+29]), "+f"(d[OFF+30]), "+f"(d[OFF+31]), "+f"(d[OFF+32]), "+f"(d[OFF+33]), "+f"(d[OFF+34]), "+f"(d[OFF+35]), "+f"(d[OFF+36]), "+f"(d[OFF+37]), "+f"(d[OFF+38]), "+f"(d[OFF+39]), "+f"(d[OFF+40]), "+f"(d[OFF+41]), "+f"(d[OFF+42]), "+f"(d[OFF+43]), "+f"(d[OFF+44]), "+f"(d[OFF+45]), "+f"(d[OFF+46]), "+f"(d[OFF+47]), "+f"(d[OFF+48]), "+f"(d[OFF+49]), "+f"(d[OFF+50]), "+f"(d[OFF+51]), "+f"(d[OFF+52]), "+f"(d[OFF+53]), "+f"(d[OFF+54]), "+f"(d[OFF+55]), "+f"(d[OFF+56]), "+f"(d[OFF+57]), "+f"(d[OFF+58]), "+f"(d[OFF+59]), "+f"(d[OFF+60]), "+f"(d[OFF+61]), "+f"(d[OFF+62]), "+f"(d[OFF+63]) : "r"(a0), "r"(a1), "r"(a2), "r"(a3), "l"(db), "r"(sd), "n"(TB));
}
template<int OFF, int TB, int S> __device__ __forceinline__ void wgmma_rs_n64(float (&d)[S], uint32_t a0, uint32_t a1, uint32_t a2, uint32_t a3, uint64_t db, int sd) {
  asm volatile("{\n.reg .pred p;\nsetp.ne.b32 p, %37, 0;\n"
    "wgmma.mma_async.sync.aligned.m64n64k16.f32.bf16.bf16 {%0, %1, %2, %3, %4, %5, %6, %7, %8, %9, %10, %11, %12, %13, %14, %15, %16, %17, %18, %19, %20, %21, %22, %23, %24, %25, %26, %27, %28, %29, %30, %31}, {%32, %33, %34, %35}, %36, p, 1, 1, %38;\n}\n"
    : "+f"(d[OFF+0]), "+f"(d[OFF+1]), "+f"(d[OFF+2]), "+f"(d[OFF+3]), "+f"(d[OFF+4]), "+f"(d[OFF+5]), "+f"(d[OFF+6]), "+f"(d[OFF+7]), "+f"(d[OFF+8]), "+f"(d[OFF+9]), "+f"(d[OFF+10]), "+f"(d[OFF+11]), "+f"(d[OFF+12]), "+f"(d[OFF+13]), "+f"(d[OFF+14]), "+f"(d[OFF+15]), "+f"(d[OFF+16]), "+f"(d[OFF+17]), "+f"(d[OFF+18]), "+f"(d[OFF+19]), "+f"(d[OFF+20]), "+f"(d[OFF+21]), "+f"(d[OFF+22]), "+f"(d[OFF+23]), "+f"(d[OFF+24]), "+f"(d[OFF+25]), "+f"(d[OFF+26]), "+f"(d[OFF+27]), "+f"(d[OFF+28]), "+f"(d[OFF+29]), "+f"(d[OFF+30]), "+f"(d[OFF+31]) : "r"(a0), "r"(a1), "r"(a2), "r"(a3), "l"(db), "r"(sd), "n"(TB));
}
template<int OFF, int TB, int S> __device__ __forceinline__ void wgmma_rs_n48(float (&d)[S], uint32_t a0, uint32_t a1, uint32_t a2, uint32_t a3, uint64_t db, int sd) {
  asm volatile("{\n.reg .pred p;\nsetp.ne.b32 p, %29, 0;\n"
    "wgmma.mma_async.sync.aligned.m64n48k16.f32.bf16.bf16 {%0, %1, %2, %3, %4, %5, %6, %7, %8, %9, %10, %11, %12, %13, %14, %15, %16, %17, %18, %19, %20, %21, %22, %23}, {%24, %25, %26, %27}, %28, p, 1, 1, %30;\n}\n"
    : "+f"(d[OFF+0]), "+f"(d[OFF+1]), "+f"(d[OFF+2]), "+f"(d[OFF+3]), "+f"(d[OFF+4]), "+f"(d[OFF+5]), "+f"(d[OFF+6]), "+f"(d[OFF+7]), "+f"(d[OFF+8]), "+f"(d[OFF+9]), "+f"(d[OFF+10]), "+f"(d[OFF+11]), "+f"(d[OFF+12]), "+f"(d[OFF+13]), "+f"(d[OFF+14]), "+f"(d[OFF+15]), "+f"(d[OFF+16]), "+f"(d[OFF+17]), "+f"(d[OFF+18]), "+f"(d[OFF+19]), "+f"(d[OFF+20]), "+f"(d[OFF+21]), "+f"(d[OFF+22]), "+f"(d[OFF+23]) : "r"(a0), "r"(a1), "r"(a2), "r"(a3), "l"(db), "r"(sd), "n"(TB));
}
template<int OFF, int TB, int S> __device__ __forceinline__ void wgmma_rs_n16(float (&d)[S], uint32_t a0, uint32_t a1, uint32_t a2, uint32_t a3, uint64_t db, int sd) {
  asm volatile("{\n.reg .pred p;\nsetp.ne.b32 p, %13, 0;\n"
    "wgmma.mma_async.sync.aligned.m64n16k16.f32.bf16.bf16 {%0, %1, %2, %3, %4, %5, %6, %7}, {%8, %9, %10, %11}, %12, p, 1, 1, %14;\n}\n"
    : "+f"(d[OFF+0]), "+f"(d[OFF+1]), "+f"(d[OFF+2]), "+f"(d[OFF+3]), "+f"(d[OFF+4]), "+f"(d[OFF+5]), "+f"(d[OFF+6]), "+f"(d[OFF+7]) : "r"(a0), "r"(a1), "r"(a2), "r"(a3), "l"(db), "r"(sd), "n"(TB));
}
template<int OFF, int TA, int TB, int S> __device__ __forceinline__ void wgmma_ss_n160(float (&d)[S], uint64_t da, uint64_t db, int sd) {
  asm volatile("{\n.reg .pred p;\nsetp.ne.b32 p, %82, 0;\n"
    "wgmma.mma_async.sync.aligned.m64n160k16.f32.bf16.bf16 {%0, %1, %2, %3, %4, %5, %6, %7, %8, %9, %10, %11, %12, %13, %14, %15, %16, %17, %18, %19, %20, %21, %22, %23, %24, %25, %26, %27, %28, %29, %30, %31, %32, %33, %34, %35, %36, %37, %38, %39, %40, %41, %42, %43, %44, %45, %46, %47, %48, %49, %50, %51, %52, %53, %54, %55, %56, %57, %58, %59, %60, %61, %62, %63, %64, %65, %66, %67, %68, %69, %70, %71, %72, %73, %74, %75, %76, %77, %78, %79}, %80, %81, p, 1, 1, %83, %84;\n}\n"
    : "+f"(d[OFF+0]), "+f"(d[OFF+1]), "+f"(d[OFF+2]), "+f"(d[OFF+3]), "+f"(d[OFF+4]), "+f"(d[OFF+5]), "+f"(d[OFF+6]), "+f"(d[OFF+7]), "+f"(d[OFF+8]), "+f"(d[OFF+9]), "+f"(d[OFF+10]), "+f"(d[OFF+11]), "+f"(d[OFF+12]), "+f"(d[OFF+13]), "+f"(d[OFF+14]), "+f"(d[OFF+15]), "+f"(d[OFF+16]), "+f"(d[OFF+17]), "+f"(d[OFF+18]), "+f"(d[OFF+19]), "+f"(d[OFF+20]), "+f"(d[OFF+21]), "+f"(d[OFF+22]), "+f"(d[OFF+23]), "+f"(d[OFF+24]), "+f"(d[OFF+25]), "+f"(d[OFF+26]), "+f"(d[OFF+27]), "+f"(d[OFF+28]), "+f"(d[OFF+29]), "+f"(d[OFF+30]), "+f"(d[OFF+31]), "+f"(d[OFF+32]), "+f"(d[OFF+33]), "+f"(d[OFF+34]), "+f"(d[OFF+35]), "+f"(d[OFF+36]), "+f"(d[OFF+37]), "+f"(d[OFF+38]), "+f"(d[OFF+39]), "+f"(d[OFF+40]), "+f"(d[OFF+41]), "+f"(d[OFF+42]), "+f"(d[OFF+43]), "+f"(d[OFF+44]), "+f"(d[OFF+45]), "+f"(d[OFF+46]), "+f"(d[OFF+47]), "+f"(d[OFF+48]), "+f"(d[OFF+49]), "+f"(d[OFF+50]), "+f"(d[OFF+51]), "+f"(d[OFF+52]), "+f"(d[OFF+53]), "+f"(d[OFF+54]), "+f"(d[OFF+55]), "+f"(d[OFF+56]), "+f"(d[OFF+57]), "+f"(d[OFF+58]), "+f"(d[OFF+59]), "+f"(d[OFF+60]), "+f"(d[OFF+61]), "+f"(d[OFF+62]), "+f"(d[OFF+63]), "+f"(d[OFF+64]), "+f"(d[OFF+65]), "+f"(d[OFF+66]), "+f"(d[OFF+67]), "+f"(d[OFF+68]), "+f"(d[OFF+69]), "+f"(d[OFF+70]), "+f"(d[OFF+71]), "+f"(d[OFF+72]), "+f"(d[OFF+73]), "+f"(d[OFF+74]), "+f"(d[OFF+75]), "+f"(d[OFF+76]), "+f"(d[OFF+77]), "+f"(d[OFF+78]), "+f"(d[OFF+79]) : "l"(da), "l"(db), "r"(sd), "n"(TA), "n"(TB));
}

__device__ __align__(1024) uint16_t g_kvT[2 * 640 * 2048];
__device__ __align__(1024) uint16_t g_y2T[2 * 640 * 2048];
__device__ __align__(1024) uint16_t g_o[2048 * 640];
__device__ __align__(1024) uint16_t g_gate[2080];
__device__ __align__(1024) uint4 g_halo[128 * 5 * 32];
__device__ __align__(1024) unsigned g_cnt[46 * 32];
__device__ __align__(1024) unsigned g_launch[132 * 32];
#define CNT_KV(i) (g_cnt + 32 * (i))
#define CNT_O(i) (g_cnt + 32 * (10 + (i)))
#define CNT_Y(i) (g_cnt + 32 * (26 + (i)))
#define PTL(i) do {} while (0)
#define PTPL(on, i) do {} while (0)
#define PT(i) do {} while (0)
#define PTP(on, i) do {} while (0)

constexpr uint32_t SB = 1024;
constexpr uint32_t STG = 23552, WST = 15360;
DEVI constexpr uint32_t o_px(int ks) { return (((ks >> 1) + 1) & 3) * 2 * STG; }
DEVI constexpr uint32_t o_pw(int ks) { return o_px(ks) + 16384 + (ks & 1) * WST; }
constexpr uint32_t O_HALO = 0, O_QT = STG;
constexpr uint32_t O_OST = 2 * STG;
constexpr uint32_t P3S = 28672;
constexpr uint32_t HC = 8320, UC = 4624, UZ = 528;
constexpr uint32_t O_H0 = 5 * P3S, O_U2 = O_H0 + 3 * HC, O_H3 = O_U2 + UC, O_U0 = O_H3 + 2 * HC;
DEVI constexpr uint32_t o_h(int c) { return O_H0 + c * HC + (c > 2 ? UC : 0); }
DEVI constexpr uint32_t o_u(int c) { return c == 2 ? O_U2 : O_U0 + (c > 2 ? c - 1 : c) * UC; }
constexpr uint32_t O_Y = 208896;
DEVI constexpr uint32_t o_x(int c) { return c < 2 ? O_Y + c * 5120 : O_U0 + (c & 1) * UC; }
constexpr uint32_t O_HIN = O_Y + 16384;
DEVI constexpr uint32_t o_kin(int c) { return ((O_U0 + 127) & ~127u) + ((c & 1) ? 0 : 73 * 128); }
DEVI constexpr uint32_t o_p3(int ks) { return (ks < 6 ? ks : ks - 6) * P3S; }
constexpr uint32_t O_BT = 4 * P3S;
constexpr uint32_t O_GT = O_Y + 20480, O_GW = O_GT + 320;
constexpr uint32_t O_BAR = 231040;
constexpr uint32_t B_FULL = O_BAR, B_EMPTY = O_BAR + 8 * 8, B_P3F = O_BAR + 8 * 16, B_P3R = O_BAR + 8 * 26, B_G = O_BAR + 8 * 27, B_U = O_BAR + 8 * 28,
                   B_KVD = O_BAR + 8 * 33, B_KF = O_BAR + 8 * 36, B_Y = O_BAR + 8 * 38, B_EP = O_BAR + 8 * 40, B_LAST = O_BAR + 8 * 41, B_DONE = O_BAR + 8 * 42,
                   B_P1E = O_BAR + 8 * 43, B_HX = O_BAR + 8 * 43  , B_P3E = O_BAR + 8 * 52, B_HX0 = O_BAR + 8 * 57, B_KVS = O_BAR + 8 * 58, B_QD = O_BAR + 8 * 60, B_GD = O_BAR + 8 * 61, B_Q = O_BAR + 8 * 51;
constexpr uint32_t B_S13 = B_EMPTY + 8 * 5, B_S15 = B_EMPTY + 8 * 7, B_S19 = B_EMPTY + 8 * 3;
constexpr uint32_t O_GP = O_BAR + 512, O_EPOCH = O_GW + 1280;
constexpr uint32_t SMEM_BYTES = 232448;
static_assert(O_U0 + 4 * UC <= O_Y - 512 && o_kin(0) >= O_U0 + 2 * UC && O_EPOCH + 4 <= O_BAR && O_U0 >= 8 * STG, "smem map");
enum { NB_LEAD = 1, NB_HELP = 2, NB_HALO = 3, NB_ATT = 4, NB_G = 5, NB_TOK = 6, NB_RFULL = 8, NB_RFREE = 10 };

struct Maps { CUtensorMap x_par, w_main, w_tail, k_ld, v_ld, o_st, kv_st, wo, o_ld, y_ld, q_ld; };

template <int M> DEVI void conv_step(float (&acc)[128], uint32_t a0, uint32_t a1, uint32_t a2, uint32_t a3, uint32_t dl) {
  auto D = [&](int off) { return ((uint64_t)8 << 32) | (uint64_t)(uint32_t)(dl + off - 16 * M); };
  if constexpr (M == 0) wgmma_rs_n16<0, 0>(acc, a0, a1, a2, a3, D(0), 0);
  if constexpr (M <= 3) wgmma_rs_n48<8, 0>(acc, a0, a1, a2, a3, D(16), M == 0 ? 0 : 1);
  if constexpr (M <= 6) wgmma_rs_n48<32, 0>(acc, a0, a1, a2, a3, D(64), M == 0 ? 0 : 1);
  if constexpr (M <= 9) wgmma_rs_n48<56, 0>(acc, a0, a1, a2, a3, D(112), M == 0 ? 0 : 1);
  if constexpr (M <= 12) wgmma_rs_n48<80, 0>(acc, a0, a1, a2, a3, D(160), M == 0 ? 0 : 1);
  wgmma_rs_n48<104, 0>(acc, a0, a1, a2, a3, D(208), M == 0 ? 0 : 1);
}
DEVI constexpr int a_off(int P, int i) { return -4 * (64 * ((i & 4) ? 15 - P : P) + (i & 1) * 32 - (i & 2) * 2); }
template <int P> DEVI void load_pair(uint32_t (&a)[8], uint32_t ab) {
#pragma unroll
  for (int i = 0; i < 8; i++) a[i] = lds32(ab + a_off(P, i));
}
template <int P> DEVI void mma_pair(float (&acc)[128], uint32_t (&a)[8], uint32_t db) {
  wg_fence();
  conv_step<P>(acc, a[0], a[1], a[2], a[3], db);
  conv_step<15 - P>(acc, a[4], a[5], a[6], a[7], db);
  wg_commit();
}

template <int I0, int I1> DEVI void conv_reduce(uint32_t sb, int c, int ht, int chan, int bar, int nthr) {
  const uint32_t a0 = sb + o_h(c) + ht * 16, a2 = sb + o_u(c) + ht * 16, a3 = sb + o_x(c) + ht * 16;
  uint4* yp = (uint4*)(g_y2T + (size_t)chan * 2048) + ht;
#pragma unroll
  for (int i = I0; i < I1; i++) {
    uint4 p, q, r, s;
    if (i == I0) bar_sync(bar, nthr);
    lds128(a0 + i * 2048, p.x, p.y, p.z, p.w); lds128(a0 + 4160 + i * 2048, q.x, q.y, q.z, q.w);
    lds128(a2 + i * 2048, r.x, r.y, r.z, r.w); lds128(a3 + i * 2048, s.x, s.y, s.z, s.w);
    auto sum = [](uint32_t a, uint32_t b, uint32_t c, uint32_t d) { return hadd2(hadd2(hadd2(a, b), 0u), hadd2(c, d)) ^ 0x80008000u; };
    yp[i * 128] = make_uint4(sum(p.x, q.x, r.x, s.x), sum(p.y, q.y, r.y, s.y), sum(p.z, q.z, r.z, s.z), sum(p.w, q.w, r.w, s.w));
  }
}

template <int ODD, int PART> DEVI void pack_qkv(const float (&acc)[120], uint32_t (&Q)[10][2], uint32_t (&K)[10][2], uint32_t (&V)[10][2]) {
#pragma unroll
  for (int f = 0; f < 10; f++) {
    const bool tail = ODD ? (f < 2) : (f >= 8);
    const int fm = ODD ? f - 2 : f, ft = ODD ? f : f - 8;
    const int nq = tail ? 24 + ft : fm, nk = tail ? 26 + ft : 8 + fm, nv = tail ? 28 + ft : 16 + fm;
    if (PART == 0) { K[f][1] = pack_bf16(acc[4 * nk + 2], acc[4 * nk + 3]); V[f][1] = pack_bf16(acc[4 * nv + 2], acc[4 * nv + 3]); }
    if (PART == 1) { V[f][0] = pack_bf16(acc[4 * nv], acc[4 * nv + 1]); K[f][0] = pack_bf16(acc[4 * nk], acc[4 * nk + 1]); }
    if (PART == 2) { Q[f][0] = pack_bf16(acc[4 * nq], acc[4 * nq + 1]); Q[f][1] = pack_bf16(acc[4 * nq + 2], acc[4 * nq + 3]); }
  }
}
DEVI void sched_fence(uint32_t& z) {
  asm volatile("{\n.reg .pred p;\nL:\nshr.u32 %0, %0, 1;\nsetp.ne.u32 p, %0, 0;\n@p bra.uni L;\n}" : "+r"(z));
}

DEVI int pair_of(int c) {
  const int lo = 32 + 8 * c, hi = c - 4 + ((max(c - 29, 0) * 37) >> 8);
  int p; asm("{\n.reg .pred q;\nsetp.lt.s32 q, %1, 4;\nselp.b32 %0, %2, %3, q;\n}" : "=r"(p) : "r"(c), "r"(lo), "r"(hi));
  return p;
}
DEVI uint32_t make_ctx() {
  int b; asm volatile("mov.u32 %0, %%ctaid.x;" : "=r"(b));
  b += clk() & threadIdx.y;
  const int p = pair_of(b >> 1);
  const int j = b < 128 ? 8 * (p & 7) + (p >> 3) : 64;
  const int q = (j * 205) >> 10, r = j - 5 * q, i = j - q, co = (i * 79) >> 10;
  const int cp = r == 4 ? 4 : co, tb = r == 4 ? q : i - 13 * co;
  return ((2 * p + (b & 1)) & 255) | tb << 8 | (2 * cp + (b & 1)) << 12 | (b >> 7) << 16;
}
#define CTX() asm volatile("" : "+r"(ctx)); CTXU()
#define CTXU() int tid; asm volatile("mov.u32 %0, %%tid.x;" : "=r"(tid)); \
  const int lane = tid & 31, vb = ctx & 255, hg = (ctx >> 4) & 7, rt = ctx & 15, par = (ctx >> 3) & 1, mt = ctx & 7, rank = ctx & 1, \
  tb = (ctx >> 8) & 15, cb = (ctx >> 12) & 15; const bool main_cta = ctx < 65536; \
  (void)tid; (void)lane; (void)vb; (void)hg; (void)rt; (void)par; (void)mt; (void)rank; (void)tb; (void)cb; (void)main_cta
#define CTXW() CTX(); const int wg = warp >> 2, w = warp & 3, g = lane >> 2, t = lane & 3; const bool lead = (tid & 127) == 0; \
  (void)wg; (void)w; (void)g; (void)t; (void)lead

__global__ void __cluster_dims__(2, 1, 1) __launch_bounds__(512, 1)
fused_kernel(const uint16_t* __restrict__ xq, const uint16_t* __restrict__ wqkv, const uint16_t* __restrict__ gate_w, const __grid_constant__ Maps M, const uint16_t* __restrict__ shift_k, const uint16_t* __restrict__ ssm_k, const uint16_t* __restrict__ ssm_D,
             uint16_t* __restrict__ outp) {
  extern __shared__ __align__(1024) uint8_t smem_raw[];
  const uint32_t sb = smem_u32(smem_raw);
  const uint32_t t0 = clk();
  auto get_epoch = [&]() { mbar_wait(sb + B_EP, 0); return lds32(sb + O_EPOCH); };

  auto p1_load_x = [&](int ks, int p, int rank) {
    tma3(sb + o_px(ks), &M.x_par, ks * 32, (p >> 2) & 1, (p & 3) * 256 + rank * 128, sb + B_FULL + 8 * (ks & 7));
  };
  auto p1_load_w = [&](int ks, int p, int rank) {
    const uint32_t st = sb + o_pw(ks), fb = sb + B_FULL + 8 * (ks & 7);
    tma3_mc(st + rank * 6144, &M.w_main, (p >> 3) * 80 + 2 * (p & 8), ks * 32 + rank * 16, 0, fb);
    tma3_mc(st + 12288 + rank * 1536, &M.w_tail, (p >> 3) * 80 + 8 * (~p & 8), ks * 32 + rank * 16, 0, fb);
  };
  auto cta_pair = [&]() { return pair_of(blockIdx.x >> 1); };

  if (threadIdx.x < 32) {
    const unsigned b = blockIdx.x, l = threadIdx.x;
    const uint16_t* pfp = l < 16 ? xq + (16 * b + l) * 640 : wqkv + (15 * b + l - 16) * 64;
    if ((l | b >> 7 << 5) < 31) pf_l2(pfp);
  }
  const int warp = __shfl_sync(~0u, threadIdx.x >> 5, 0);
  if ((warp & 14) == 8) {
    if (elect_one()) {
#pragma unroll
      for (int s = 0; s < 8; s++) mbar_init(sb + O_BAR - 512 + 64 * warp + 8 * s, 5 * warp - 39);
      asm volatile("fence.mbarrier_init.release.cluster;" ::: "memory");
    }
    __syncwarp();
  }
  asm volatile("barrier.cluster.arrive.relaxed.aligned;" ::: "memory");
  if (warp == 8 && blockIdx.x < 128) {
    const int p = cta_pair(), rank = blockIdx.x & 1;
    if (elect_one()) { mbar_expect_tx(sb + B_FULL, 16384 + WST); p1_load_x(0, p, rank); }
    __syncwarp();
    asm volatile("barrier.cluster.wait.aligned;" ::: "memory");
    if (elect_one()) { p1_load_w(0, p, rank); PT(100); }
    __syncwarp();
  } else if (warp != 15) {
    asm volatile("barrier.cluster.wait.aligned;" ::: "memory");
    spin_until(t0, HOLD);
  }
  auto init_rest = [&]() {
    if (warp >= 11 && elect_one()) {
#pragma unroll
      for (int s = 0; s < 12; s++) mbar_init(sb + O_BAR + 128 - 11 * 96 + 96 * warp + 8 * s, warp == 14 ? 2 : 1);
      asm volatile("fence.mbarrier_init.release.cluster;" ::: "memory");
    }
    __syncwarp();
    bar_sync(0, blockIdx.x < 128 ? 224 : 512);
  };
  uint32_t ctx = 0;

  if (warp < 8) {
    reg_inc<RC>();
    ctx = make_ctx();
    if (blockIdx.x >= 128) bar_sync(0, 512);
    else {
      {
        uint32_t Q[10][2], K[10][2], V[10][2];
        {
          {
            float acc[120];
            CTXW();
            const int odd = (cta_pair() >> 3) & 1;
            const uint32_t rsb = mapa(sb, (blockIdx.x & 1) ^ 1);
            {
              const uint32_t aa = sb + (warp * 16 + (lane & 15)) * 128 + (((lane >> 4) ^ (lane & 7)) << 4);
              constexpr int NA = DEFER > 3 ? DEFER : 3;
              uint32_t a[NA][8];
              auto load_a = [&](int ks) {
                uint32_t(&r)[8] = a[ks % NA];
                mbar_wait(sb + B_FULL + 8 * (ks & 7), (ks >> 3) & 1);
                PTP(lead && (wg || !(ks & 3)), wg ? 60 + ks : 80 + (ks >> 2));
                ldsm4(r[0], r[1], r[2], r[3], (aa ^ ((ks & 1) * 64)) + o_px(ks)); ldsm4(r[4], r[5], r[6], r[7], (aa ^ ((ks & 1) * 64 + 32)) + o_px(ks));
              };
              auto mma_q = [&](int ks, int h) {
                uint32_t(&r)[8] = a[ks % NA];
                wgmma_rs_n64<0, 1>(acc, r[4 * h], r[4 * h + 1], r[4 * h + 2], r[4 * h + 3], mkdesc(SB + o_pw(ks) + h * 6144, 2048, 1024, 1), ks | h);
              };
              auto mma_step = [&](int ks, int h) {
                uint32_t(&r)[8] = a[ks % NA];
                wg_fence();
                wgmma_rs_n128<32, 1>(acc, r[4 * h], r[4 * h + 1], r[4 * h + 2], r[4 * h + 3], mkdesc(SB + o_pw(ks) + h * 6144 + 2048, 2048, 1024, 1), ks | h);
                if (ks < 20 - DEFER) mma_q(ks, h);
                wgmma_rs_n48<96, 1>(acc, r[4 * h], r[4 * h + 1], r[4 * h + 2], r[4 * h + 3], mkdesc(SB + o_pw(ks) + 12288 + h * 1536, 512, 256, 3), ks | h);
                wg_commit();
              };
              if (lead) PT(1 + wg);
              load_a(0);
#pragma unroll
              for (int ks = 0; ks < 20; ks++) {
                if (LEAD && ks == 20 - LEAD) bar_sync_p(wg == 0, NB_LEAD, 256);
                mma_step(ks, 0);
                if (ks < 19 && ks >= NLATE) load_a(ks + 1);
                mma_step(ks, 1);
                if (ks < NLATE) load_a(ks + 1);
                if (ks >= 1 && ks <= 16) {
                  wg_wait<2>();
                  mbar_arrive2_p(lead, sb + B_EMPTY + 8 * ((ks - 1) & 7), rsb + B_EMPTY + 8 * ((ks - 1) & 7));
                } else if (ks < 19 && ks + 2 - NA >= 16) wg_wait<2>();
              }
              if (LEAD) bar_arrive_p(wg, NB_LEAD, 256);
              if (DEFER) {
                wg_fence();
#pragma unroll
                for (int i = 40 - 2 * DEFER; i < 40; i++) mma_q(i >> 1, i & 1);
                wg_commit();
              }
              mbar_wait(sb + B_S15, 1);
              wg_wait<1>();
              mbar_arrive_p(tid == 0, sb + B_P1E);
              if (!DEFER) wg_wait<0>();
              fence_regs<32, 120>(acc);
              PTPL(lead, 158 + wg);
            }
            if (odd) pack_qkv<1, 0>(acc, Q, K, V); else pack_qkv<0, 0>(acc, Q, K, V);
            if (warp == 7 && (blockIdx.x & 1)) {
              uint4* hp = g_halo + vb * 160 + lane;
              st_relaxed(hp, K[0][1], K[1][1], K[3][1], K[4][1]); st_relaxed(hp + 32, K[5][1], K[6][1], K[8][1], K[9][1]);
              st_relaxed(hp + 64, K[2][1], K[7][1], V[0][1], V[1][1]);
              st_relaxed(hp + 96, V[2][1], V[3][1], V[4][1], V[5][1]); st_relaxed(hp + 128, V[6][1], V[7][1], V[8][1], V[9][1]);
            }
            const uint32_t ho = sb + O_HALO + warp * 2560 + lane * 16;
            stsm4(ho, K[0][1], K[1][1], K[3][1], K[4][1]); stsm4(ho + 512, K[5][1], K[6][1], K[8][1], K[9][1]);
            stsm4(ho + 1024, K[2][1], K[7][1], V[0][1], V[1][1]);
            stsm4(ho + 1536, V[2][1], V[3][1], V[4][1], V[5][1]); stsm4(ho + 2048, V[6][1], V[7][1], V[8][1], V[9][1]);
            if (warp == 7) {
              if (!(blockIdx.x & 1)) {
                fence_async_smem();
                __syncwarp();
                if (elect_one())
                  asm volatile("cp.async.bulk.shared::cluster.shared::cta.mbarrier::complete_tx::bytes [%0], [%1], 2560, [%2];"
                               ::"r"(mapa(sb + O_HIN, 1)), "r"(sb + O_HALO + 7 * 2560), "r"(mapa(sb + B_HX0, 1)) : "memory");
              }
              __syncwarp();
            } else {
              __syncwarp();
              if (lane == 0) mbar_arrive(sb + B_HX + 8 + 8 * warp);
            }
            if (odd) pack_qkv<1, 1>(acc, Q, K, V); else pack_qkv<0, 1>(acc, Q, K, V);
#pragma unroll
            for (int f = 0; f < 10; f++) V[f][0] = movm(V[f][0]);
            wg_wait<0>();
            fence_regs<0, 32>(acc);
            PTPL(lead, 50 + wg);
            mbar_arrive2_p(lead, sb + B_S19, rsb + B_S19);
            if (odd) pack_qkv<1, 2>(acc, Q, K, V); else pack_qkv<0, 2>(acc, Q, K, V);
            if (lead) PT(52 + wg);
            if (wg) mbar_wait(sb + B_P1E, 0);
          }
          CTXW();
          uint32_t z = threadIdx.y;
          const bool gt0 = 2 * t > g, gt1 = 2 * t + 1 > g;
          const uint32_t pmask = (gt0 ? 0xFFFFu : 0u) | (gt1 ? 0xFFFF0000u : 0u);
          const uint32_t hs = warp ? O_HALO + (warp - 1) * 2560 : O_HIN, ha = sb + hs + lane * 16;
          const uint32_t va = sb + ((lane & 8) ? O_HALO + warp * 2560 : hs) + 1280 + (lane >> 4) * 128 + (lane & 7) * 16;
          uint32_t Qh[4][2], Kh[10], Vh[10];
          float c1[4][4] = {}, c2[4][4] = {}, c0[4][4] = {}, l[8][2], m[8], x[8];
#pragma unroll
          for (int j = 0; j < 4; j++) {
            const int fa = (j >> 1) * 5 + (j & 1) * 3, fh = (j >> 1) * 5 + 2;
            const bool mine = (j & 1) ? (t >= 2) : (t < 2);
            Qh[j][0] = mine ? Q[fh][0] : 0u; Qh[j][1] = mine ? Q[fh][1] : 0u;
            mma16(c1[j], Q[fa][0], Q[fa][1], Q[fa + 1][0], Q[fa + 1][1], K[fa][0], K[fa + 1][0]);
            mma16(c2[j], Q[fa][0], Q[fa][1], Q[fa + 1][0], Q[fa + 1][1], K[fa][1], K[fa + 1][1]);
            mma8(c1[j], Qh[j][0], Qh[j][1], K[fh][0]);
            mma8(c2[j], Qh[j][0], Qh[j][1], K[fh][1]);
          }
          if (lead) PT(54 + wg);
          mbar_wait(sb + (warp ? B_HX + 8 * warp : B_HX0), 0);
          if (lead) PT(56 + wg);
          ldsm4(Kh[0], Kh[1], Kh[3], Kh[4], ha); ldsm4(Kh[5], Kh[6], Kh[8], Kh[9], ha + 512);
          asm volatile("ldmatrix.sync.aligned.m8n8.x2.shared.b16 {%0,%1}, [%2];" : "=r"(Kh[2]), "=r"(Kh[7]) : "r"(ha + 1024) : "memory");
          auto load_v = [&]() {
#pragma unroll
            for (int i = 0; i < 5; i++) ldsm4t(Vh[2 * i], V[2 * i][1], Vh[2 * i + 1], V[2 * i + 1][1], va + i * 256);
          };
          load_v();
          const float C = 0.22360679774997896f * 1.4426950408889634f;
          auto max1 = [&](int r) { m[r] = fmaxf(l[r][0], l[r][1]); x[r] = __shfl_xor_sync(~0u, m[r], 1); };
          auto max2 = [&](int r) { m[r] = fmaxf(m[r], x[r]); x[r] = __shfl_xor_sync(~0u, m[r], 2); };
          auto exps = [&](int r) { const float mc = fmaxf(m[r], x[r]) * C; l[r][0] = ex2(fmaf(l[r][0], C, -mc)); l[r][1] = ex2(fmaf(l[r][1], C, -mc)); };
#pragma unroll
          for (int j = 0; j < 4; j++) { l[4 + j][0] = gt0 ? c1[j][2] : c2[j][2]; l[4 + j][1] = gt1 ? c1[j][3] : c2[j][3]; max1(4 + j); }
#pragma unroll
          for (int j = 0; j < 4; j++) {
            const int fa = (j >> 1) * 5 + (j & 1) * 3, fh = (j >> 1) * 5 + 2;
            mma16(c0[j], Q[fa][0], Q[fa][1], Q[fa + 1][0], Q[fa + 1][1], Kh[fa], Kh[fa + 1]);
            mma8(c0[j], Qh[j][0], Qh[j][1], Kh[fh]);
            max2(4 + j);
          }
          const bool have_halo = warp > 0 || mt > 0;
#pragma unroll
          for (int j = 0; j < 4; j++) {
            if (!have_halo) c0[j][0] = c0[j][1] = -INFINITY;
            l[j][0] = gt0 ? c0[j][0] : c1[j][0]; l[j][1] = gt1 ? c0[j][1] : c1[j][1];
            max1(j);
          }
          exps(4); exps(5);
#pragma unroll
          for (int j = 0; j < 4; j++) max2(j);
          exps(6); exps(7);
#pragma unroll
          for (int j = 0; j < 4; j++) exps(j);
          float o[12][4] = {}, sm[4][4] = {};
#pragma unroll
          for (int j = 0; j < 4; j++) {
            const int fa = (j >> 1) * 5 + (j & 1) * 3, fh = (j >> 1) * 5 + 2;
            const uint32_t pl = pack_bf16(l[j][0], l[j][1]), pu = pack_bf16(l[4 + j][0], l[4 + j][1]);
            const uint32_t a0 = pl & pmask, a2 = pl & ~pmask, a3 = pu & pmask, a5 = pu & ~pmask, z0 = z << (2 * j + 1), z1 = z << (2 * j + 2);
            mma8(sm[j], pl, pu, 0x3F803F80u);
#pragma unroll
            for (int q = 0; q < 3; q++) {
              const int f = q < 2 ? fa + q : fh;
              mma8(o[3 * j + q], a2, a3, V[f][0]);
              mma16(o[3 * j + q], a0, z0, z1, a5, Vh[f], V[f][1]);
            }
          }
          sched_fence(z);
          bar_arrive_p(wg == 0, NB_HALO + z, 256);
          uint32_t O[10][2];
#pragma unroll
          for (int j = 0; j < 4; j++) {
            const int fa = (j >> 1) * 5 + (j & 1) * 3, fh = (j >> 1) * 5 + 2;
            float r0, r1;
            asm("rcp.approx.ftz.f32 %0, %1;" : "=f"(r0) : "f"(sm[j][0]));
            asm("rcp.approx.ftz.f32 %0, %1;" : "=f"(r1) : "f"(sm[j][2]));
#pragma unroll
            for (int q = 0; q < 3; q++) {
              const int f = q < 2 ? fa + q : fh;
              const float* e = o[3 * j + q];
              const uint32_t o0 = pack_bf16(e[0] * r0, e[1] * r0), o1 = pack_bf16(e[2] * r1, e[3] * r1);
              if (q < 2 || !(j & 1)) { O[f][0] = o0; O[f][1] = o1; }
              else { O[f][0] = t >= 2 ? o0 : O[f][0]; O[f][1] = t >= 2 ? o1 : O[f][1]; }
            }
          }
          mbar_wait(sb + B_GD, 0);
          const uint32_t oa = sb + O_OST + wg * 2 * STG + (w * 16 + (lane & 15)) * 160 + (lane >> 4) * 16;
#pragma unroll
          for (int i = 0; i < 5; i++) stsm4(oa + i * 32, O[2 * i][0], O[2 * i][1], O[2 * i + 1][0], O[2 * i + 1][1]);
        }
      }
      {
        CTXW();
        fence_async_smem();
        bar_arrive(wg ? NB_LEAD : NB_ATT, 160);
        if (lead) PT(58 + wg);
        const uint32_t abase = sb + (g & 1) * 4160 + 4 * (1023 - 4 - 8 * w - (g >> 1) + t);
        float acc[128];
        uint32_t a0[8], a1[8], a2[8], a3[8];
#pragma unroll 1
        for (int c = wg ^ 1; c < 5; c += 2) {
          const uint32_t ab = abase + o_h(c);
          const uint32_t db = __shfl_sync(~0u, ((SB + o_u(c) + UZ - 16) >> 4) | 0x10000u, 0);
          mbar_wait(sb + B_U + 8 * c, 0);
          load_pair<0>(a0, ab); load_pair<1>(a1, ab); load_pair<2>(a2, ab);
          if (lead) PT(85 + c);
          bar_sync(c ? NB_TOK + wg : NB_HALO, 256);
          fence_regs(acc);
          mma_pair<0>(acc, a0, db);                load_pair<3>(a3, ab);
          mma_pair<1>(acc, a1, db); wg_wait<1>();  load_pair<4>(a0, ab);
          if (lead) PT(90 + c);
          mma_pair<2>(acc, a2, db); wg_wait<1>();  load_pair<5>(a1, ab);
          mma_pair<3>(acc, a3, db); wg_wait<1>();  load_pair<6>(a2, ab);
          mma_pair<4>(acc, a0, db); wg_wait<1>();  load_pair<7>(a3, ab);
          mma_pair<5>(acc, a1, db);
          mma_pair<6>(acc, a2, db);
          bar_arrive_p(c < 4, NB_TOK + (wg ^ 1), 256);
          mma_pair<7>(acc, a3, db);
          bar_arrive_p(c == 4, NB_TOK, 256);
          wg_wait<0>();
          fence_regs(acc);
          PTPL(lead, 95 + c);
          bar_sync(NB_RFREE + wg, 256);
          const uint32_t pb = sb + (w < 2 ? o_h(c) + w * 4160 : w == 2 ? o_u(c) : o_x(c)) + lane * 16;
          if (lane < 2 * w) sts128(pb, 0, 0, 0, 0);
#pragma unroll
          for (int q = 0; q < 8; q++) {
            uint32_t p[4];
#pragma unroll
            for (int i = 0; i < 4; i++) {
              const int nu = 4 * q + i;
              p[i] = pack_bf16(acc[4 * nu], acc[4 * nu + 1]);
              if (nu > 0) p[i] = hadd2(p[i], pack_bf16(acc[4 * nu - 2], acc[4 * nu - 1]));
            }
            stsm4t(pb + w * 32 + q * 512, p[0], p[1], p[2], p[3]);
            if (q == 3) bar_arrive_p(c == 4, NB_RFULL + 1, 256);
          }
          if (c < 4) bar_arrive(NB_RFULL + wg, 256);
          if (lead) PT(140 + c);
        }
        if (wg) {
          const int yb = (lds32(sb + O_EPOCH) & 1) * 640;
              conv_reduce<1, 2>(sb, 4, tid - 128, yb + 512 + ((vb & 0x61) | (vb & 6) << 2 | (vb >> 2 & 6)), 14, 128);
          bar_arrive(12, 256);
          PTPL(lead, 45);
        }
      }
    }
    if (warp < 4) {
      CTXW();
      const uint32_t rsb = mapa(sb, (blockIdx.x & 1) ^ 1);
      const uint32_t ba = sb + O_BT + ((lane >> 4) * 8 + (lane & 7)) * 128 + (((2 * w + ((lane >> 3) & 1)) ^ ((lane & 1) << 2 | (lane >> 1 & 3))) << 4);
      mbar_wait(sb + B_P3F, 0);
      if (lead) PT(145);
      float acc[80];
#pragma unroll
      for (int ks = 0; ks < 10; ks++) {
        if (ks == NPRE) {
          if (NPRE) { wg_wait<0>(); mbar_arrive2_p(lead, sb + B_P3E + 8 * NPRE, rsb + B_P3E + 8 * NPRE); }
          bar_sync_p(blockIdx.x < 128, NB_TOK, 256);
        }
        PTP(lead, 146 + ks);
        const uint64_t da = mkdesc(SB + o_p3(ks), 1024, 1024, 1), db = mkdesc(SB + o_p3(ks) + 8192, 16, 1024, 1);
        wg_fence();
#pragma unroll
        for (int j = 0; j < 4; j++) wgmma_ss_n160<0, 1, 0>(acc, da + j * 128, db + j * 2, j | ks);
        wg_commit();
        if (ks < 9) mbar_wait(sb + B_P3F + 8 * (ks + 1), 0);
        if (ks >= 1 && ks <= 4 && ks != NPRE) { wg_wait<1>(); mbar_arrive2_p(lead, sb + B_P3E + 8 * ks, rsb + B_P3E + 8 * ks); }
      }
      wg_wait<0>();
      fence_regs(acc);
      PTPL(lead, 156);
#pragma unroll
      for (int i = 0; i < 10; i++) {
        stsm4t(ba + i * 2048, pack_bf16(acc[8 * i], acc[8 * i + 1]), pack_bf16(acc[8 * i + 2], acc[8 * i + 3]),
               pack_bf16(acc[8 * i + 4], acc[8 * i + 5]), pack_bf16(acc[8 * i + 6], acc[8 * i + 7]));
        if (i & 1) bar_arrive(1 + (i >> 1), 256);
      }
      if (lead) PT(157);
    }
  } else if (warp < 12) {
    reg_dec<RH>();
    const int hw = warp - 8;
    init_rest();
    ctx = __shfl_sync(~0u, make_ctx(), 0);
    const int yrow = (ctx & 0x61) | (ctx & 6) << 2 | (ctx >> 2 & 6);
    if (ctx < 65536) {
      CTXU();
      const int pr = hw >> 1, hh = hw & 1, tk = vb & 63, odd = (lane >> 2) & 1;
      const uint32_t sel0 = odd ? 0x7632 : 0x5410, sel1 = odd ? 0x5410 : 0x7632;
      const uint32_t in = sb + o_kin(pr), fb = sb + B_KF + 8 * pr, out = sb + O_Y + pr * 8192;
      const uint32_t oa = out + (2 * lane + odd) * 64 + (((3 - 2 * hh) ^ (lane & 3)) << 4), ia = in + hh * 2048 + lane * 4;
      auto fetch = [&](int c) {
        wait_until(t0, KT0 + c * KTD + ((((vb * 37) & 63) * KPH) >> 6));
        if (elect_one()) {
          const int kb = 2 * c + (vb >> 6);
          mbar_expect_tx(fb, 69 * 128);
          tma2(in, &M.k_ld, kb * 64, 32 * tk - 4, fb);
          tma2(in + 36 * 128, &M.v_ld, kb * 64, 32 * tk - 1, fb);
          PT(20 + c);
        }
        __syncwarp();
      };
      if (hh == 0) fetch(pr);
      const uint4* skp = (const uint4*)shift_k + (2 * pr + (vb >> 6)) * 32 + lane;
      uint4 sk = __ldg(skp), sk1 = __ldg(skp + 128), sk2 = __ldg(skp + (pr ? 0 : 256));
#pragma unroll 1
      for (int c = pr; c < 5; c += 2) {
        {
          mbar_wait(fb, (c >> 1) & 1);
          if (hh == 0 && lane == 0) PT(25 + c);
          uint32_t k[20], o[17];
#pragma unroll
          for (int i = 0; i < 20; i++) { k[i] = lds32(ia + i * 128); if (i >= 3) o[i - 3] = lds32(ia + (33 + i) * 128); }
          fence_async_smem();
          bar_sync(12 + pr, 64);
          if (hh == 0) {
            if (c < 3) fetch(c + 2);
            else if (lane == 0) mbar_arrive(sb + B_KVD + 8 * (c - 3));
          }
          const uint32_t w0 = prmt(sk.x, sk.z, 0x5410), w1 = prmt(sk.x, sk.z, 0x7632), w2 = prmt(sk.y, sk.w, 0x5410), w3 = prmt(sk.y, sk.w, 0x7632);
#pragma unroll
          for (int i = 0; i < 17; i++) o[i] = hmul2(hfma2(k[i + 3], w0, hfma2(k[i + 2], w1, hfma2(k[i + 1], w2, hmul2(k[i], w3)))), o[i]);
          sk = sk1; sk1 = sk2;
#pragma unroll
          for (int i = 0; i < 4; i++) {
            const int e = 8 * (i >> 1) + (i & 1);
            const uint32_t a = (oa ^ ((i >> 1) * 16)) + (i & 1) * 4096;
            sts128(a, prmt(o[7 + e], o[6 + e], sel0), prmt(o[5 + e], o[4 + e], sel0), prmt(o[3 + e], o[2 + e], sel0), prmt(o[1 + e], o[e], sel0));
            sts128(a ^ 64, prmt(o[7 + e], o[6 + e], sel1), prmt(o[5 + e], o[4 + e], sel1), prmt(o[3 + e], o[2 + e], sel1), prmt(o[1 + e], o[e], sel1));
          }
          bar_sync(12 + pr, 64);
        }
        if (hh) {
          fence_async_smem();
          if (elect_one()) {
            const int kb = 2 * c + (vb >> 6);
            tma3_store(&M.kv_st, 0, kb * 64, 63 - tk, out);
            tma3_store(&M.kv_st, 0, 640 + kb * 64, 63 - tk, out + 4096);
            bulk_commit(); bulk_wait_all();
            mbar_arrive(sb + (c == 4 ? B_KVD + 16 : B_KVS + 4 * (c & 2)));
            PTL(35 + c);
          }
          __syncwarp();
        }
      }
    }
    CTXU();
    const int g = lane >> 2, t = lane & 3, row = 8 * hw + g;
    const uint32_t go = (tb * 160 + row) * 80 + cb * 8 + t;
    const int yb = __shfl_sync(~0u, get_epoch() & 1, 0) * 640;
    uint4 T[10];
    if (hw == 2) {
      if (main_cta) { mbar_wait(sb + B_LAST, 0); mbar_wait(sb + B_S15, 1); }
      if (elect_one()) {
        mbar_expect_tx(sb + B_Q, 20480);
#pragma unroll
        for (int h = 0; h < 2; h++) tma2(sb + O_QT + h * 10240, &M.q_ld, cb * 64 + 32 * h, tb * 160, sb + B_Q);
      }
      __syncwarp();
    }
    mbar_wait(sb + B_Q, 0);
#pragma unroll
    for (int i = 0; i < 10; i++) lds128(sb + O_QT + (i & 1) * 10240 + (i >> 1) * 2048 + row * 64 + t * 16, T[i].x, T[i].y, T[i].z, T[i].w);
    fence_async_smem();
    bar_sync(12 + (hw >> 1), 64);
    if (!(tid & 63)) mbar_arrive(sb + B_QD);
    if (tid == 256) PTL(40);
    if (main_cta) {
      bar_arrive(NB_RFREE, 256);
      bar_arrive(NB_RFREE + 1, 256);
      auto red = [&](int c) {
        const int wg = (c & 1) ^ 1;
        conv_reduce<0, 2>(sb, c, tid - 256, yb + 128 * c + yrow, NB_RFULL + wg, 256);
        if (hw == 3 && elect_one()) flag_add(CNT_Y(4 * c + (vb >> 5)), 1);
        if (tid == 256) PTL(41 + c);
        if (c < 3) bar_arrive(NB_RFREE + wg, 256);
        if (c == 2) {
          bar_sync(NB_HELP, 128);
          if (tid == 256) { mbar_arrive(sb + B_P3E); mbar_arrive_remote(sb + B_P3E, rank ^ 1); }
        }
      };
      if (hw == 3) {
        mbar_wait(sb + B_KVD + 16, 0);
        if (elect_one()) { flag_release(CNT_KV(4 + (vb >> 6))); PTL(32); }
        __syncwarp();
      }
#pragma unroll 1
      for (int c = 0; c < 4; c++) red(c);
    }
    uint32_t G[5];
    mbar_wait(sb + B_G, 0);
#pragma unroll
    for (int q = 0; q < 5; q++) { uint16_t v; asm volatile("ld.shared.u16 %0, [%1];" : "=h"(v) : "r"(sb + O_GT + (32 * q + row) * 2)); G[q] = prmt(v, 0, 0x1010); }
#pragma unroll
    for (int i = 0; i < 10; i++) { const uint32_t c = G[i >> 1] ^ 0x80008000u; T[i] = make_uint4(hmul2(T[i].x, c), hmul2(T[i].y, c), hmul2(T[i].z, c), hmul2(T[i].w, c)); }
    if (main_cta) {
      conv_reduce<0, 1>(sb, 4, tid - 256, yb + 512 + yrow, NB_RFULL + 1, 256);
      if (hw == 3 && elect_one()) { flag_add(CNT_Y(16 + (vb >> 5)), 1); PTL(19); }
      bar_sync(12, 256);
    }
#pragma unroll
    for (int h = 0; h < 2; h++) {
      mbar_wait_wd(sb + B_Y + 8 * h, 0, t0);
      if (tid == 256) PTL(46);
      const uint32_t ya = sb + O_Y + h * 10240 + lane * 64 + ((hw ^ ((lane >> 1) & 3)) << 4);
      uint4 y[5];
      auto empty = [](uint32_t m) { return (m & 0xFFFFu) == 0 || m < 0x10000u; };
      uint32_t m = ~0u;
#pragma unroll
      for (int q = 4; q >= 0; q--) {
        ldsm4t(y[q].x, y[q].y, y[q].z, y[q].w, ya + q * 2048);
        m = __vimin3_u16x2(__vimin3_u16x2(m, y[q].x, y[q].y), y[q].z, y[q].w);
        if (q == 4 && tb == 12) m = ~0u;
      }
      if (__any_sync(~0u, empty(m))) {
        const uint4* gp = (const uint4*)g_y2T + (yb + cb * 64 + 32 * h + lane) * 256 + tb * 20 + hw;
#pragma unroll
        for (int q = 0; q < 5; q++) lds128(ya + q * 2048, y[q].x, y[q].y, y[q].z, y[q].w);
        if (tb == 12) y[4] = make_uint4(~0u, ~0u, ~0u, ~0u);
        for (;;) {
          bool bad[5], any = false;
#pragma unroll
          for (int q = 0; q < 5; q++) { bad[q] = empty(__vimin3_u16x2(__vminu2(y[q].x, y[q].y), y[q].z, y[q].w)); any |= bad[q]; }
          if (!__any_sync(~0u, any)) break;
#pragma unroll
          for (int q = 0; q < 5; q++)
            if (bad[q]) asm volatile("ld.relaxed.gpu.global.v4.b32 {%0,%1,%2,%3}, [%4];" : "=r"(y[q].x), "=r"(y[q].y), "=r"(y[q].z), "=r"(y[q].w) : "l"(gp + 4 * q) : "memory");
        }
#pragma unroll
        for (int q = 0; q < 5; q++) sts128(ya + q * 2048, y[q].x, y[q].y, y[q].z, y[q].w);
        __syncwarp();
#pragma unroll
        for (int q = 0; q < 5; q++) ldsm4t(y[q].x, y[q].y, y[q].z, y[q].w, ya + q * 2048);
        PTL(49);
      }
#pragma unroll
      for (int q = 0; q < 5; q++) {
        uint4& r = T[2 * q + h];
        r = make_uint4(hmul2(r.x, y[q].x), hmul2(r.y, y[q].y), hmul2(r.z, y[q].z), hmul2(r.w, y[q].w));
      }
    }
    const uint32_t so = sb + O_BT + row * 128 + ((t ^ ((g & 1) << 2 | g >> 1)) << 4);
    if (tid == 256) PTL(47);
#pragma unroll
    for (int q = 0; q < 5; q++) {
      const uint32_t c = hfma2(G[q], 0xBF80BF80u, 0x3F803F80u);
      bar_sync(1 + q, 256);
      if (q == 4) mbar_arrive_p(tid == 256, sb + B_DONE);
#pragma unroll
      for (int h = 0; h < 2; h++) {
        uint4 u;
        lds128((so ^ (h * 64)) + q * 4096, u.x, u.y, u.z, u.w);
        const uint4& r = T[2 * q + h];
        if (q < 4 || tb < 12) ((uint4*)outp)[go + q * 2560 + h * 4] = make_uint4(hfma2(u.x, c, r.x), hfma2(u.y, c, r.y), hfma2(u.z, c, r.z), hfma2(u.w, c, r.w));
      }
    }
  } else {
    reg_dec<RP>();
    uint4 gwv = make_uint4(0, 0, 0, 0);
    if (warp == 15) {
      const int p = cta_pair(), rank = blockIdx.x & 1;
      asm volatile("barrier.cluster.wait.aligned;" ::: "memory");
      if (blockIdx.x >= 128) bar_sync(0, 512);
      else {
#pragma unroll 1
        for (int ks = 1;; ks += 2) {
          mbar_wait(sb + B_EMPTY + 8 * (ks & 7), ((ks >> 3) & 1) ^ 1);
          spin_until(t0, PT1 + (ks - 1) * PTD);
          if (elect_one()) { mbar_expect_tx(sb + B_FULL + 8 * (ks & 7), WST); p1_load_w(ks, p, rank); PT(100 + ks); }
          if (ks == 19) break;
          const int kn = ks + 1;
          mbar_wait(sb + B_EMPTY + 8 * (kn & 7), ((kn >> 3) & 1) ^ 1);
          spin_until(t0, PT1 + ks * PTD - PTE);
          if (elect_one()) { mbar_expect_tx(sb + B_FULL + 8 * (kn & 7), 16384 + WST); p1_load_x(kn, p, rank); p1_load_w(kn, p, rank); PT(100 + kn); }
        }
        if (elect_one()) mbar_arrive(sb + B_LAST);
#pragma unroll 1
        for (int i = 0; i < 2; i++) {
          mbar_wait(sb + B_KVS + 8 * i, 0);
          if (elect_one()) { flag_release(CNT_KV(2 * i + (p >> 5))); PTL(30 + i); }
          __syncwarp();
        }
        mbar_wait(sb + B_S19, 0);
      }
    } else {
      if (threadIdx.x < 384 + 80) gwv = __ldg((const uint4*)gate_w + threadIdx.x - 384);
      init_rest();
    }
    ctx = __shfl_sync(~0u, make_ctx(), 0);
    CTXU();
    if (warp == 12) {
        unsigned epoch = 0;
      if (lane == 0) epoch = *(volatile unsigned*)(g_launch + 32 * vb) + 1;
      if (main_cta) { sts128(sb + O_GW + lane * 16, gwv.x, gwv.y, gwv.z, gwv.w); bar_arrive(NB_G, 96); }
      if (lane == 0) {
        if ((sb & 0xFFFFFF) != SB) __trap();
        sts32(sb + O_EPOCH, epoch);
        mbar_arrive(sb + B_EP);
#pragma unroll 1
        for (int i = 5; i < 11; i++) asm volatile("prefetch.tensormap [%0];" ::"l"(&M.x_par + i) : "memory");
      }
      if (main_cta && rank) {
#pragma unroll
        for (int f = 0; f < 5; f++) st_relaxed(g_halo + vb * 160 + lane + 32 * f, ~0u, ~0u, ~0u, ~0u);
      }
      __syncwarp();
      if (elect_one()) flag_release(g_launch + 32 * vb);
      __syncwarp();
      if (main_cta) {
        uint4 h0 = make_uint4(0, 0, 0, 0);
        if (lane < 5) {
          h0 = __ldg((const uint4*)(ssm_k + (size_t)(128 * lane + vb) * 2048));
          h0.x = prmt(pack_bf16(bf_lo(h0.x) + bf_lo(__ldg(ssm_D + 128 * lane + vb)), 0.f), h0.x, 0x7610);
        }
        epoch = __shfl_sync(~0u, epoch, 0);
        const int ze = lane & 7;
        const uint32_t za = sb + (lane < 8 ? o_u(ze) + UZ : lane < 24 ? o_h(ze) + (lane >> 4) * 4160 + 4096 : o_u(ze) + 512);
        const uint16_t* hp = ssm_k + (size_t)vb * 2048 + 8;
        const uint16_t* up = g_kvT + (size_t)vb * 2048;
        const unsigned* fp = CNT_KV(vb >> 6);
        sts128(sb + O_Y - 512 + lane * 16, 0, 0, 0, 0);
        mbar_wait(sb + B_LAST, 0);
        mbar_wait(sb + B_S13, 1);
#pragma unroll
        for (int c = 0; c < 5; c++) {
          if (c == 0 || c == 3) {
            mbar_wait(sb + B_KVD + (c ? 8 : 0), 0);
#pragma unroll
            for (int e = c; e < (c ? 5 : 3); e++) sts128(sb + o_u(e) + lane * 16, 0, 0, 0, 0);
            if (ze >= c && ze < (c ? 5 : 3)) sts128(za, h0.x, h0.y, h0.z, h0.w);
            fence_async_smem();
            __syncwarp();
            if (elect_one()) {
#pragma unroll
              for (int e = c; e < (c ? 5 : 3); e++) {
                mbar_expect_tx(sb + B_U + 8 * e, 3 * 4096 - 16);
                if (c || e == 0) bulk_load(sb + o_u(e) + UZ + 16, hp + 128 * 2048 * e, 4080, sb + B_U + 8 * e);
              }
            }
          }
          if (!(c & 1)) { flag_wait(fp + 32 * c, 64 * epoch); __syncwarp(); }
          if (elect_one()) {
            bulk_load(sb + o_h(c), up + 128 * 2048 * c, 4096, sb + B_U + 8 * c);
            bulk_load(sb + o_h(c) + 4160, up + (640 + 128 * c) * 2048, 4096, sb + B_U + 8 * c);
            if (c == 1) {
#pragma unroll
              for (int e = 1; e < 3; e++) bulk_load(sb + o_u(e) + UZ + 16, hp + 128 * 2048 * e, 4080, sb + B_U + 8 * e);
            }
            PTL(10 + c);
          }
        }
        mbar_wait(sb + B_LAST, 1);
        if (elect_one()) {
#pragma unroll 1
          for (int i = 0; i < 40; i++) bulk_store(g_y2T + (size_t)((~epoch & 1) * 640 + 5 * vb) * 2048 + i * 256, sb + O_Y - 512, 512);
          bulk_commit(); bulk_wait_read();
          PTL(33);
        }
      }
    } else if (warp != 15) {
        const int r = warp - 13;
      if (main_cta) {
        if (rank && lane == 0) mbar_expect_tx(sb + B_HX0, 1280);
        const int t = lane & 3, grow = hg * 16 + (lane & 15);
        const uint32_t ga = sb + grow * 128 + (((4 * r + (lane >> 4)) ^ (lane & 7)) << 4);
        const uint32_t gp = sb + O_GW + 64 * r + 4 * t;
        float s0 = 0.f, s1 = 0.f;
        if (tid < 384 + 80) sts128(sb + O_GW + (tid - 384) * 16, gwv.x, gwv.y, gwv.z, gwv.w);
        bar_sync(NB_G, 96);
#pragma unroll 1
        for (int ks = 0; ks < 20; ks += 2) {
          uint32_t x[8], gw[4];
#pragma unroll
          for (int i = 0; i < 4; i++) gw[i] = lds32(gp + ks * 64 + i * 16);
          mbar_wait_wd(sb + B_FULL + 8 * (ks & 7), (ks >> 3) & 1, t0);
          if (r == 0 && lane == 0) PT(120 + ks);
          ldsm4(x[0], x[1], x[2], x[3], ga + o_px(ks)); ldsm4(x[4], x[5], x[6], x[7], (ga ^ 32) + o_px(ks));
#pragma unroll
          for (int i = 0; i < 8; i++) x[i] = hmul2(x[i], gw[i >> 1]);
          if (lane < 2) mbar_arrive(sb + B_EMPTY + 8 * (ks & 7) + 8 * lane + (x[0] & x[7] & threadIdx.y));
#pragma unroll
          for (int i = 0; i < 8; i += 4) {
            s0 += (bf_lo(x[i]) + bf_hi(x[i])) + (bf_lo(x[i + 2]) + bf_hi(x[i + 2]));
            s1 += (bf_lo(x[i + 1]) + bf_hi(x[i + 1])) + (bf_lo(x[i + 3]) + bf_hi(x[i + 3]));
          }
        }
        s0 += __shfl_xor_sync(~0u, s0, 1); s1 += __shfl_xor_sync(~0u, s1, 1);
        s0 += __shfl_xor_sync(~0u, s0, 2); s1 += __shfl_xor_sync(~0u, s1, 2);
        if (t < 2) sts32(sb + O_GP + r * 64 + (8 * t + (lane >> 2)) * 4, __float_as_uint(t ? s1 : s0));
        if (lane == 0) mbar_arrive(sb + B_GD);
        if (r == 0) bar_arrive(NB_G, 64);
        if (!rank) {
          uint4 d[3];
          if (mt > 0) {
            const uint4* hp = g_halo + (vb - 1) * 160 + r * 64 + lane;
            mbar_wait_wd(sb + B_EP, 0, t0);
            flag_wait_wd(g_launch + 32 * (vb - 1), lds32(sb + O_EPOCH), t0);
            mbar_wait_wd(sb + B_HX + 56, 0, t0);
            for (;;) {
              bool ok = true;
#pragma unroll
              for (int f = 0; f < 3; f++) {
                asm volatile("ld.relaxed.gpu.global.v4.b32 {%0,%1,%2,%3}, [%4];" : "=r"(d[f].x), "=r"(d[f].y), "=r"(d[f].z), "=r"(d[f].w) : "l"(hp + 32 * f) : "memory");
              }
#pragma unroll
              for (int f = 0; f < 3; f++) ok = ok && max(max(d[f].x, d[f].y), max(d[f].z, d[f].w)) != ~0u;
              if (__all_sync(~0u, ok)) break;
              if (clk() - t0 > 0x70000000u) __trap();
            }
          } else {
#pragma unroll
            for (int f = 0; f < 3; f++) d[f] = make_uint4(0, 0, 0, 0);
          }
#pragma unroll
          for (int f = 0; f < 3; f++) stsm4(sb + O_HIN + r * 1024 + f * 512 + lane * 16, d[f].x, d[f].y, d[f].z, d[f].w);
          __syncwarp();
          if (lane == 0) { mbar_arrive(sb + B_HX0); PTL(15 + r); }
        }
        if (r == 1) {
          bar_sync(NB_G, 64);
          if (lane < 16) {
            const uint32_t pa = sb + O_GP + lane * 4;
            const float z = __uint_as_float(lds32(pa)) + __uint_as_float(lds32(pa + 64));
            g_gate[2 * (mt * 128 + hg * 16 + lane) + par] = (uint16_t)pack_bf16(__fdividef(1.f, 1.f + __expf(-bf_lo(pack_bf16(z, 0.f)))), 0.f);
          }
          __syncwarp();
          if (elect_one()) flag_release(CNT_O(rt));
        }
      }
      mbar_wait_wd(sb + B_EP, 0, t0);
      const unsigned epoch = lds32(sb + O_EPOCH);
      if (main_cta) mbar_wait_wd(sb + B_P3E, 0, t0);
      flag_wait_wd(CNT_Y(2 * cb + r), 32 * epoch, t0);
      __syncwarp();
      if (elect_one()) {
        mbar_expect_tx(sb + B_Y + 8 * r, 10240);
        tma3(sb + O_Y + r * 10240, &M.y_ld, 0, (epoch & 1) * 640 + cb * 64 + 32 * r, tb * 5, sb + B_Y + 8 * r);
        PTL(17 + r);
      }
      __syncwarp();
      mbar_wait_wd(sb + B_DONE, 0, t0);
    } else {
      const unsigned epoch = get_epoch();
      if (main_cta) {
        bar_sync(NB_LEAD, 160);
        if (elect_one()) tma3_store(&M.o_st, hg * 80, par, mt * 128 + 64, sb + O_OST + 2 * STG);
        bar_sync(NB_ATT, 160);
        if (elect_one()) {
          tma3_store(&M.o_st, hg * 80, par, mt * 128, sb + O_OST);
          bulk_commit(); bulk_wait_all();
          flag_release(CNT_O(rt));
          mbar_arrive(sb + B_LAST);
          PTL(3);
        }
        __syncwarp();
      }
      mbar_wait(sb + B_QD, 0);
#pragma unroll 1
      for (int ks = 0; ks < 5; ks++)
        if (elect_one()) tma2(sb + o_p3(ks), &M.wo, cb * 64, ks * 64, sb + B_P3F + 8 * ks);
      if (lane < 4) flag_wait(CNT_O(8 * (lane & 1) + min(7, (80 * tb + 79 * (lane >> 1)) >> 7)), 16 * epoch);
      __syncwarp();
      if (elect_one()) {
        PTL(4);
        mbar_arrive_remote(sb + B_P3R, rank ^ 1);
        mbar_expect_tx(sb + B_G, 320);
        bulk_load(sb + O_GT, g_gate + tb * 160, 320, sb + B_G);
      }
      mbar_wait(sb + B_P3R, 0);
      auto load_o = [&](int ks) {
        tma2_mc(sb + o_p3(ks) + 8192 + rank * 10240, &M.o_ld, ks * 64, tb * 160 + rank * 80, sb + B_P3F + 8 * ks);
        mbar_expect_tx(sb + B_P3F + 8 * ks, P3S);
      };
      auto load_wo = [&](int ks) { tma2(sb + o_p3(ks), &M.wo, cb * 64, ks * 64, sb + B_P3F + 8 * ks); };
#pragma unroll 1
      for (int ks = 0; ks < 5; ks++)
        if (elect_one()) load_o(ks);
#pragma unroll
      for (int ks = 5; ks < 10; ks++) {
        if (ks > 5 || main_cta) mbar_wait(sb + B_P3E + 8 * (ks - 5), 0);
        if (elect_one()) {
          load_o(ks);
          load_wo(ks);
          PTL(ks);
        }
      }
    }
  }
}

typedef CUresult (*PFN_enc)(CUtensorMap*, CUtensorMapDataType, cuuint32_t, void*, const cuuint64_t*, const cuuint64_t*, const cuuint32_t*,
                            const cuuint32_t*, CUtensorMapInterleave, CUtensorMapSwizzle, CUtensorMapL2promotion, CUtensorMapFloatOOBfill);
static void enc(PFN_enc f, CUtensorMap* m, const void* base, int rank, const cuuint64_t* dims, const cuuint64_t* strides, const cuuint32_t* box,
                CUtensorMapSwizzle sw) {
  const cuuint32_t es[5] = {1, 1, 1, 1, 1};
  f(m, CU_TENSOR_MAP_DATA_TYPE_BFLOAT16, rank, (void*)base, dims, strides, box, es, CU_TENSOR_MAP_INTERLEAVE_NONE, sw,
    CU_TENSOR_MAP_L2_PROMOTION_NONE, CU_TENSOR_MAP_FLOAT_OOB_FILL_NONE);
}

extern "C" void kernel_launch(void* const* d_in, const int* in_sizes, int n_in, void* d_out, int out_size) {
  (void)in_sizes; (void)n_in; (void)out_size;
  static PFN_enc f = nullptr;
  static void *kvT, *y2T, *o;
  if (!f) {
    void* p = nullptr;
    cudaDriverEntryPointQueryResult q;
    cudaGetDriverEntryPoint("cuTensorMapEncodeTiled", &p, cudaEnableDefault, &q);
    f = (PFN_enc)p;
    cudaGetSymbolAddress(&kvT, g_kvT); cudaGetSymbolAddress(&y2T, g_y2T); cudaGetSymbolAddress(&o, g_o);
    cudaFuncSetAttribute(fused_kernel, cudaFuncAttributeMaxDynamicSharedMemorySize, SMEM_BYTES);
  }
  Maps M;
  const CUtensorMapSwizzle S0 = CU_TENSOR_MAP_SWIZZLE_NONE, S32 = CU_TENSOR_MAP_SWIZZLE_32B, S64 = CU_TENSOR_MAP_SWIZZLE_64B, S128 = CU_TENSOR_MAP_SWIZZLE_128B;
  const cuuint64_t dpar[3] = {640, 2, 1024}, spar[2] = {1280, 2560};
  const cuuint64_t dw[3] = {640, 640, 3}, sw[2] = {3840, 1280};
  const cuuint64_t dnat[2] = {640, 2048}, snat[1] = {1280};
  const cuuint64_t dT2[3] = {32, 1280, 64}, sT[2] = {4096, 64};
  const cuuint64_t dwo[2] = {640, 640};
  { const cuuint32_t bx[3] = {64, 1, 128}; enc(f, &M.x_par, d_in[0], 3, dpar, spar, bx, S128); }
  { const cuuint32_t bx[3] = {64, 16, 3}; enc(f, &M.w_main, d_in[7], 3, dw, sw, bx, S128); }
  { const cuuint32_t bx[3] = {16, 16, 3}; enc(f, &M.w_tail, d_in[7], 3, dw, sw, bx, S32); }
  { const cuuint32_t bx[3] = {80, 1, 64}; enc(f, &M.o_st, o, 3, dpar, spar, bx, S0); }
  { const cuuint32_t bx[3] = {32, 64, 1}; enc(f, &M.kv_st, kvT, 3, dT2, sT, bx, S64); }
  { const cuuint32_t bx[3] = {32, 32, 5}; enc(f, &M.y_ld, y2T, 3, dT2, sT, bx, S64); }
  { const cuuint32_t bx[2] = {64, 36}; enc(f, &M.k_ld, d_in[1], 2, dnat, snat, bx, S0); }
  { const cuuint32_t bx[2] = {64, 33}; enc(f, &M.v_ld, d_in[2], 2, dnat, snat, bx, S0); }
  { const cuuint32_t bx[2] = {32, 160}; enc(f, &M.q_ld, d_in[0], 2, dnat, snat, bx, S0); }
  { const cuuint32_t bx[2] = {64, 64}; enc(f, &M.wo, d_in[8], 2, dwo, snat, bx, S128); }
  { const cuuint32_t bx[2] = {64, 80}; enc(f, &M.o_ld, o, 2, dnat, snat, bx, S128); }
  fused_kernel<<<130, 512, SMEM_BYTES, cudaStreamPerThread>>>((const uint16_t*)d_in[0], (const uint16_t*)d_in[7], (const uint16_t*)d_in[9], M, (const uint16_t*)d_in[3], (const uint16_t*)d_in[4], (const uint16_t*)d_in[5],
                                                              (uint16_t*)d_out);
}
```

```cpp
#include <cuda_runtime.h>
#include <cuda_bf16.h>
#include <cuda.h>
#include <stdint.h>

#define DEVI __device__ __forceinline__
#define PT1 300
#define PTD 460
#define PTE 150
#define DEFER 4
#define KPH KTD
#define NPRE 1
#define NLATE 4
#define KT0 1500
#define KTD 1000
#define RC 192
#define RH 96
#define RP 32
#define HOLD 750
#define LEAD 3

DEVI uint32_t smem_u32(const void* p) { return (uint32_t)__cvta_generic_to_shared(p); }
DEVI void wg_fence() { asm volatile("wgmma.fence.sync.aligned;" ::: "memory"); }
DEVI void wg_commit() { asm volatile("wgmma.commit_group.sync.aligned;" ::: "memory"); }
template <int N> DEVI void wg_wait() { asm volatile("wgmma.wait_group.sync.aligned %0;" ::"n"(N) : "memory"); }
template <int A = 0, int B = -1, int S> DEVI void fence_regs(float (&d)[S]) {
#pragma unroll
  for (int i = A; i < (B < 0 ? S : B); i++) asm volatile("" : "+f"(d[i])::"memory");
}
DEVI uint64_t mkdesc(uint32_t addr, uint32_t lbo, uint32_t sbo, int swz) {
  return (uint64_t)((addr & 0x3FFFF) >> 4) | ((uint64_t)(lbo >> 4) << 16) | ((uint64_t)(sbo >> 4) << 32) | ((uint64_t)swz << 62);
}
DEVI void mbar_init(uint32_t bar, uint32_t cnt) { asm volatile("mbarrier.init.shared::cta.b64 [%0], %1;" ::"r"(bar), "r"(cnt) : "memory"); }
DEVI void mbar_expect_tx(uint32_t bar, uint32_t bytes) { asm volatile("mbarrier.arrive.expect_tx.shared::cta.b64 _, [%0], %1;" ::"r"(bar), "r"(bytes) : "memory"); }
DEVI void mbar_arrive(uint32_t bar) { asm volatile("mbarrier.arrive.shared::cta.b64 _, [%0];" ::"r"(bar) : "memory"); }
DEVI void mbar_wait(uint32_t bar, uint32_t parity) {
  asm volatile("{\n.reg .pred p;\nLAB_WAIT:\nmbarrier.try_wait.parity.shared::cta.b64 p, [%0], %1;\n@!p bra LAB_WAIT;\n}" ::"r"(bar), "r"(parity) : "memory");
}
DEVI void mbar_wait_wd(uint32_t bar, uint32_t parity, uint32_t t0) {
  asm volatile("{\n.reg .pred p;\n.reg .u32 c;\nLAB_WAIT:\nmbarrier.try_wait.parity.shared::cta.b64 p, [%0], %1;\n@p bra DONE;\nmov.u32 c, %%clock;\nsub.u32 c, c, %2;\nsetp.lt.u32 p, c, 0x70000000;\n@p bra LAB_WAIT;\ntrap;\nDONE:\n}" ::"r"(bar), "r"(parity), "r"(t0) : "memory");
}
DEVI void flag_wait(const unsigned* p, unsigned target) {
  asm volatile("{\n.reg .pred p;\n.reg .s32 v;\nLAB_WAIT:\nld.relaxed.gpu.global.u32 v, [%0];\nsub.s32 v, v, %1;\nsetp.lt.s32 p, v, 0;\n@p bra LAB_WAIT;\n}" ::"l"(p), "r"(target) : "memory");
}
DEVI void flag_wait_wd(const unsigned* p, unsigned target, uint32_t t0) {
  asm volatile("{\n.reg .pred p;\n.reg .s32 v;\nLAB_WAIT:\nld.relaxed.gpu.global.u32 v, [%0];\nsub.s32 v, v, %1;\nsetp.ge.s32 p, v, 0;\n@p bra DONE;\nmov.u32 v, %%clock;\nsub.s32 v, v, %2;\nsetp.lt.u32 p, v, 0x70000000;\n@p bra LAB_WAIT;\ntrap;\nDONE:\n}" ::"l"(p), "r"(target), "r"(t0) : "memory");
}
DEVI void flag_add(unsigned* p, unsigned v) { asm volatile("red.relaxed.gpu.global.add.u32 [%0], %1;" ::"l"(p), "r"(v) : "memory"); }
DEVI void flag_release(unsigned* p) { asm volatile("fence.proxy.async;\nred.relaxed.gpu.global.add.u32 [%0], 1;" ::"l"(p) : "memory"); }
DEVI void fence_async_smem() { asm volatile("fence.proxy.async.shared::cta;" ::: "memory"); }
DEVI bool elect_one() { uint32_t p; asm volatile("{\n.reg .pred P;\nelect.sync _|P, 0xffffffff;\nselp.u32 %0, 1, 0, P;\n}" : "=r"(p)); return p; }
DEVI void bar_sync(int id, int n) { asm volatile("bar.sync %0, %1;" ::"r"(id), "r"(n) : "memory"); }
DEVI void bar_arrive(int id, int n) { asm volatile("bar.arrive %0, %1;" ::"r"(id), "r"(n) : "memory"); }
DEVI void tma2(uint32_t dst, const CUtensorMap* m, int c0, int c1, uint32_t bar) {
  asm volatile("cp.async.bulk.tensor.2d.shared::cluster.global.mbarrier::complete_tx::bytes [%0], [%1, {%3, %4}], [%2];" ::"r"(dst), "l"(m), "r"(bar), "r"(c0), "r"(c1) : "memory");
}
DEVI void tma3(uint32_t dst, const CUtensorMap* m, int c0, int c1, int c2, uint32_t bar) {
  asm volatile("cp.async.bulk.tensor.3d.shared::cluster.global.mbarrier::complete_tx::bytes [%0], [%1, {%3, %4, %5}], [%2];" ::"r"(dst), "l"(m), "r"(bar), "r"(c0), "r"(c1), "r"(c2) : "memory");
}
DEVI void tma3_mc(uint32_t dst, const CUtensorMap* m, int c0, int c1, int c2, uint32_t bar) {
  asm volatile("cp.async.bulk.tensor.3d.shared::cluster.global.mbarrier::complete_tx::bytes.multicast::cluster [%0], [%1, {%3, %4, %5}], [%2], %6;" ::"r"(dst), "l"(m), "r"(bar), "r"(c0), "r"(c1), "r"(c2), "h"((uint16_t)3) : "memory");
}
DEVI void tma2_mc(uint32_t dst, const CUtensorMap* m, int c0, int c1, uint32_t bar) {
  asm volatile("cp.async.bulk.tensor.2d.shared::cluster.global.mbarrier::complete_tx::bytes.multicast::cluster [%0], [%1, {%3, %4}], [%2], %5;" ::"r"(dst), "l"(m), "r"(bar), "r"(c0), "r"(c1), "h"((uint16_t)3) : "memory");
}
DEVI void mbar_arrive_remote(uint32_t bar, uint32_t cta) {
  asm volatile("{\n.reg .b32 ra;\nmapa.shared::cluster.u32 ra, %0, %1;\nmbarrier.arrive.shared::cluster.b64 _, [ra];\n}" ::"r"(bar), "r"(cta) : "memory");
}
DEVI void tma3_store(const CUtensorMap* m, int c0, int c1, int c2, uint32_t src) {
  asm volatile("cp.async.bulk.tensor.3d.global.shared::cta.bulk_group [%0, {%2, %3, %4}], [%1];" ::"l"(m), "r"(src), "r"(c0), "r"(c1), "r"(c2) : "memory");
}
DEVI void bulk_load(uint32_t dst, const void* src, uint32_t bytes, uint32_t bar) {
  asm volatile("cp.async.bulk.shared::cluster.global.mbarrier::complete_tx::bytes [%0], [%1], %2, [%3];" ::"r"(dst), "l"(src), "r"(bytes), "r"(bar) : "memory");
}
DEVI void bulk_store(void* dst, uint32_t src, uint32_t bytes) {
  asm volatile("cp.async.bulk.global.shared::cta.bulk_group [%0], [%1], %2;" ::"l"(dst), "r"(src), "r"(bytes) : "memory");
}
DEVI void pf_l2(const void* p) { asm volatile("prefetch.global.L2 [%0];" ::"l"(p)); }
template <int OFF> DEVI uint32_t ldg_v(const void* p) { uint32_t v; asm volatile("ld.volatile.global.b32 %0, [%1 + %2];" : "=r"(v) : "l"(p), "n"(OFF)); return v; }
DEVI void bulk_commit() { asm volatile("cp.async.bulk.commit_group;" ::: "memory"); }
DEVI void bulk_wait_all() { asm volatile("cp.async.bulk.wait_group 0;" ::: "memory"); }
DEVI void bulk_wait_read() { asm volatile("cp.async.bulk.wait_group.read 0;" ::: "memory"); }
template <int R> DEVI void reg_inc() { asm volatile("setmaxnreg.inc.sync.aligned.u32 %0;" ::"n"(R)); }
template <int R> DEVI void reg_dec() { asm volatile("setmaxnreg.dec.sync.aligned.u32 %0;" ::"n"(R)); }
DEVI uint32_t prmt(uint32_t a, uint32_t b, uint32_t s) { uint32_t r; asm("prmt.b32 %0,%1,%2,%3;" : "=r"(r) : "r"(a), "r"(b), "r"(s)); return r; }
DEVI uint32_t lds32(uint32_t a) { uint32_t r; asm volatile("ld.shared.b32 %0,[%1];" : "=r"(r) : "r"(a)); return r; }
DEVI void sts32(uint32_t a, uint32_t x) { asm volatile("st.shared.b32 [%0],%1;" ::"r"(a), "r"(x) : "memory"); }
DEVI void sts128(uint32_t a, uint32_t x, uint32_t y, uint32_t z, uint32_t w) { asm volatile("st.shared.v4.b32 [%0],{%1,%2,%3,%4};" ::"r"(a), "r"(x), "r"(y), "r"(z), "r"(w) : "memory"); }
DEVI void sts128v(uint32_t a, uint32_t x, uint32_t y, uint32_t z, uint32_t w) { asm volatile("st.volatile.shared.v4.b32 [%0],{%1,%2,%3,%4};" ::"r"(a), "r"(x), "r"(y), "r"(z), "r"(w) : "memory"); }
DEVI void lds128(uint32_t a, uint32_t& x, uint32_t& y, uint32_t& z, uint32_t& w) { asm volatile("ld.shared.v4.b32 {%0,%1,%2,%3},[%4];" : "=r"(x), "=r"(y), "=r"(z), "=r"(w) : "r"(a) : "memory"); }
DEVI void ldsm4(uint32_t& r0, uint32_t& r1, uint32_t& r2, uint32_t& r3, uint32_t addr) {
  asm volatile("ldmatrix.sync.aligned.m8n8.x4.shared.b16 {%0,%1,%2,%3}, [%4];" : "=r"(r0), "=r"(r1), "=r"(r2), "=r"(r3) : "r"(addr) : "memory");
}
DEVI void ldsm4t(uint32_t& r0, uint32_t& r1, uint32_t& r2, uint32_t& r3, uint32_t addr) {
  asm volatile("ldmatrix.sync.aligned.m8n8.x4.trans.shared.b16 {%0,%1,%2,%3}, [%4];" : "=r"(r0), "=r"(r1), "=r"(r2), "=r"(r3) : "r"(addr) : "memory");
}
DEVI void stsm4(uint32_t addr, uint32_t r0, uint32_t r1, uint32_t r2, uint32_t r3) {
  asm volatile("stmatrix.sync.aligned.m8n8.x4.shared.b16 [%0], {%1,%2,%3,%4};" ::"r"(addr), "r"(r0), "r"(r1), "r"(r2), "r"(r3) : "memory");
}
DEVI void stsm4t(uint32_t addr, uint32_t r0, uint32_t r1, uint32_t r2, uint32_t r3) {
  asm volatile("stmatrix.sync.aligned.m8n8.x4.trans.shared.b16 [%0], {%1,%2,%3,%4};" ::"r"(addr), "r"(r0), "r"(r1), "r"(r2), "r"(r3) : "memory");
}
DEVI uint32_t movm(uint32_t a) { uint32_t r; asm volatile("movmatrix.sync.aligned.m8n8.trans.b16 %0, %1;" : "=r"(r) : "r"(a)); return r; }
DEVI uint32_t pack_bf16(float lo, float hi) { uint32_t r; asm("cvt.rn.bf16x2.f32 %0, %1, %2;" : "=r"(r) : "f"(hi), "f"(lo)); return r; }
DEVI uint32_t hmul2(uint32_t a, uint32_t b) { uint32_t r; asm("mul.rn.bf16x2 %0,%1,%2;" : "=r"(r) : "r"(a), "r"(b)); return r; }
DEVI uint32_t hadd2(uint32_t a, uint32_t b) { uint32_t r; asm("add.rn.bf16x2 %0,%1,%2;" : "=r"(r) : "r"(a), "r"(b)); return r; }
DEVI float bf_lo(uint32_t a) { return __uint_as_float(prmt(a, 0, 0x1044)); }
DEVI float bf_hi(uint32_t a) { return __uint_as_float(a & 0xFFFF0000u); }
DEVI void mma16(float (&c)[4], uint32_t a0, uint32_t a1, uint32_t a2, uint32_t a3, uint32_t b0, uint32_t b1) {
  asm volatile("mma.sync.aligned.m16n8k16.row.col.f32.bf16.bf16.f32 {%0,%1,%2,%3},{%4,%5,%6,%7},{%8,%9},{%0,%1,%2,%3};"
      : "+f"(c[0]), "+f"(c[1]), "+f"(c[2]), "+f"(c[3]) : "r"(a0), "r"(a1), "r"(a2), "r"(a3), "r"(b0), "r"(b1));
}
DEVI void mma8(float (&c)[4], uint32_t a0, uint32_t a1, uint32_t b0) {
  asm volatile("mma.sync.aligned.m16n8k8.row.col.f32.bf16.bf16.f32 {%0,%1,%2,%3},{%4,%5},{%6},{%0,%1,%2,%3};"
      : "+f"(c[0]), "+f"(c[1]), "+f"(c[2]), "+f"(c[3]) : "r"(a0), "r"(a1), "r"(b0));
}
DEVI float ex2(float x) { float r; asm volatile("ex2.approx.ftz.f32 %0, %1;" : "=f"(r) : "f"(x)); return r; }

DEVI uint32_t clk() { uint32_t c; asm volatile("mov.u32 %0, %%clock;" : "=r"(c)); return c; }
DEVI void wait_until(uint32_t t0, int dt) { while ((int)(clk() - t0) < dt) __nanosleep(40); }
DEVI void spin_until(uint32_t t0, int dt) { while ((int)(clk() - t0) < dt) {} }
DEVI uint32_t hfma2(uint32_t a, uint32_t b, uint32_t c) { uint32_t r; asm("fma.rn.bf16x2 %0,%1,%2,%3;" : "=r"(r) : "r"(a), "r"(b), "r"(c)); return r; }
DEVI void bar_sync_p(int on, int id, int n) { asm volatile("{\n.reg .pred p;\nsetp.ne.b32 p, %0, 0;\n@p bar.sync %1, %2;\n}" ::"r"(on), "r"(id), "r"(n) : "memory"); }
DEVI void bar_arrive_p(int on, int id, int n) { asm volatile("{\n.reg .pred p;\nsetp.ne.b32 p, %0, 0;\n@p bar.arrive %1, %2;\n}" ::"r"(on), "r"(id), "r"(n) : "memory"); }
DEVI void mbar_arrive_p(int on, uint32_t bar) { asm volatile("{\n.reg .pred p;\nsetp.ne.b32 p, %1, 0;\n@p mbarrier.arrive.shared::cta.b64 _, [%0];\n}" ::"r"(bar), "r"(on) : "memory"); }
DEVI void mbar_arrive2_p(int on, uint32_t bar, uint32_t rbar) {
  asm volatile("{\n.reg .pred p;\nsetp.ne.b32 p, %2, 0;\n@p mbarrier.arrive.shared::cta.b64 _, [%0];\n@p mbarrier.arrive.shared::cluster.b64 _, [%1];\n}" ::"r"(bar), "r"(rbar), "r"(on) : "memory");
}
DEVI void st_relaxed(uint4* p, uint32_t x, uint32_t y, uint32_t z, uint32_t w) {
  asm volatile("st.relaxed.gpu.global.v4.b32 [%0], {%1,%2,%3,%4};" ::"l"(p), "r"(x), "r"(y), "r"(z), "r"(w) : "memory");
}
DEVI uint32_t mapa(uint32_t a, uint32_t cta) { uint32_t r; asm("mapa.shared::cluster.u32 %0, %1, %2;" : "=r"(r) : "r"(a), "r"(cta)); return r; }
DEVI void st_async128(uint32_t a, uint32_t x, uint32_t y, uint32_t z, uint32_t w, uint32_t bar) {
  asm volatile("st.async.weak.shared::cluster.mbarrier::complete_tx::bytes.v4.b32 [%0], {%1,%2,%3,%4}, [%5];" ::"r"(a), "r"(x), "r"(y), "r"(z), "r"(w), "r"(bar) : "memory");
}

template<int OFF, int TB, int S> __device__ __forceinline__ void wgmma_rs_n128(float (&d)[S], uint32_t a0, uint32_t a1, uint32_t a2, uint32_t a3, uint64_t db, int sd) {
  asm volatile("{\n.reg .pred p;\nsetp.ne.b32 p, %69, 0;\n"
    "wgmma.mma_async.sync.aligned.m64n128k16.f32.bf16.bf16 {%0, %1, %2, %3, %4, %5, %6, %7, %8, %9, %10, %11, %12, %13, %14, %15, %16, %17, %18, %19, %20, %21, %22, %23, %24, %25, %26, %27, %28, %29, %30, %31, %32, %33, %34, %35, %36, %37, %38, %39, %40, %41, %42, %43, %44, %45, %46, %47, %48, %49, %50, %51, %52, %53, %54, %55, %56, %57, %58, %59, %60, %61, %62, %63}, {%64, %65, %66, %67}, %68, p, 1, 1, %70;\n}\n"
    : "+f"(d[OFF+0]), "+f"(d[OFF+1]), "+f"(d[OFF+2]), "+f"(d[OFF+3]), "+f"(d[OFF+4]), "+f"(d[OFF+5]), "+f"(d[OFF+6]), "+f"(d[OFF+7]), "+f"(d[OFF+8]), "+f"(d[OFF+9]), "+f"(d[OFF+10]), "+f"(d[OFF+11]), "+f"(d[OFF+12]), "+f"(d[OFF+13]), "+f"(d[OFF+14]), "+f"(d[OFF+15]), "+f"(d[OFF+16]), "+f"(d[OFF+17]), "+f"(d[OFF+18]), "+f"(d[OFF+19]), "+f"(d[OFF+20]), "+f"(d[OFF+21]), "+f"(d[OFF+22]), "+f"(d[OFF+23]), "+f"(d[OFF+24]), "+f"(d[OFF+25]), "+f"(d[OFF+26]), "+f"(d[OFF+27]), "+f"(d[OFF+28]), "+f"(d[OFF+29]), "+f"(d[OFF+30]), "+f"(d[OFF+31]), "+f"(d[OFF+32]), "+f"(d[OFF+33]), "+f"(d[OFF+34]), "+f"(d[OFF+35]), "+f"(d[OFF+36]), "+f"(d[OFF+37]), "+f"(d[OFF+38]), "+f"(d[OFF+39]), "+f"(d[OFF+40]), "+f"(d[OFF+41]), "+f"(d[OFF+42]), "+f"(d[OFF+43]), "+f"(d[OFF+44]), "+f"(d[OFF+45]), "+f"(d[OFF+46]), "+f"(d[OFF+47]), "+f"(d[OFF+48]), "+f"(d[OFF+49]), "+f"(d[OFF+50]), "+f"(d[OFF+51]), "+f"(d[OFF+52]), "+f"(d[OFF+53]), "+f"(d[OFF+54]), "+f"(d[OFF+55]), "+f"(d[OFF+56]), "+f"(d[OFF+57]), "+f"(d[OFF+58]), "+f"(d[OFF+59]), "+f"(d[OFF+60]), "+f"(d[OFF+61]), "+f"(d[OFF+62]), "+f"(d[OFF+63]) : "r"(a0), "r"(a1), "r"(a2), "r"(a3), "l"(db), "r"(sd), "n"(TB));
}
template<int OFF, int TB, int S> __device__ __forceinline__ void wgmma_rs_n64(float (&d)[S], uint32_t a0, uint32_t a1, uint32_t a2, uint32_t a3, uint64_t db, int sd) {
  asm volatile("{\n.reg .pred p;\nsetp.ne.b32 p, %37, 0;\n"
    "wgmma.mma_async.sync.aligned.m64n64k16.f32.bf16.bf16 {%0, %1, %2, %3, %4, %5, %6, %7, %8, %9, %10, %11, %12, %13, %14, %15, %16, %17, %18, %19, %20, %21, %22, %23, %24, %25, %26, %27, %28, %29, %30, %31}, {%32, %33, %34, %35}, %36, p, 1, 1, %38;\n}\n"
    : "+f"(d[OFF+0]), "+f"(d[OFF+1]), "+f"(d[OFF+2]), "+f"(d[OFF+3]), "+f"(d[OFF+4]), "+f"(d[OFF+5]), "+f"(d[OFF+6]), "+f"(d[OFF+7]), "+f"(d[OFF+8]), "+f"(d[OFF+9]), "+f"(d[OFF+10]), "+f"(d[OFF+11]), "+f"(d[OFF+12]), "+f"(d[OFF+13]), "+f"(d[OFF+14]), "+f"(d[OFF+15]), "+f"(d[OFF+16]), "+f"(d[OFF+17]), "+f"(d[OFF+18]), "+f"(d[OFF+19]), "+f"(d[OFF+20]), "+f"(d[OFF+21]), "+f"(d[OFF+22]), "+f"(d[OFF+23]), "+f"(d[OFF+24]), "+f"(d[OFF+25]), "+f"(d[OFF+26]), "+f"(d[OFF+27]), "+f"(d[OFF+28]), "+f"(d[OFF+29]), "+f"(d[OFF+30]), "+f"(d[OFF+31]) : "r"(a0), "r"(a1), "r"(a2), "r"(a3), "l"(db), "r"(sd), "n"(TB));
}
template<int OFF, int TB, int S> __device__ __forceinline__ void wgmma_rs_n48(float (&d)[S], uint32_t a0, uint32_t a1, uint32_t a2, uint32_t a3, uint64_t db, int sd) {
  asm volatile("{\n.reg .pred p;\nsetp.ne.b32 p, %29, 0;\n"
    "wgmma.mma_async.sync.aligned.m64n48k16.f32.bf16.bf16 {%0, %1, %2, %3, %4, %5, %6, %7, %8, %9, %10, %11, %12, %13, %14, %15, %16, %17, %18, %19, %20, %21, %22, %23}, {%24, %25, %26, %27}, %28, p, 1, 1, %30;\n}\n"
    : "+f"(d[OFF+0]), "+f"(d[OFF+1]), "+f"(d[OFF+2]), "+f"(d[OFF+3]), "+f"(d[OFF+4]), "+f"(d[OFF+5]), "+f"(d[OFF+6]), "+f"(d[OFF+7]), "+f"(d[OFF+8]), "+f"(d[OFF+9]), "+f"(d[OFF+10]), "+f"(d[OFF+11]), "+f"(d[OFF+12]), "+f"(d[OFF+13]), "+f"(d[OFF+14]), "+f"(d[OFF+15]), "+f"(d[OFF+16]), "+f"(d[OFF+17]), "+f"(d[OFF+18]), "+f"(d[OFF+19]), "+f"(d[OFF+20]), "+f"(d[OFF+21]), "+f"(d[OFF+22]), "+f"(d[OFF+23]) : "r"(a0), "r"(a1), "r"(a2), "r"(a3), "l"(db), "r"(sd), "n"(TB));
}
template<int OFF, int TB, int S> __device__ __forceinline__ void wgmma_rs_n16(float (&d)[S], uint32_t a0, uint32_t a1, uint32_t a2, uint32_t a3, uint64_t db, int sd) {
  asm volatile("{\n.reg .pred p;\nsetp.ne.b32 p, %13, 0;\n"
    "wgmma.mma_async.sync.aligned.m64n16k16.f32.bf16.bf16 {%0, %1, %2, %3, %4, %5, %6, %7}, {%8, %9, %10, %11}, %12, p, 1, 1, %14;\n}\n"
    : "+f"(d[OFF+0]), "+f"(d[OFF+1]), "+f"(d[OFF+2]), "+f"(d[OFF+3]), "+f"(d[OFF+4]), "+f"(d[OFF+5]), "+f"(d[OFF+6]), "+f"(d[OFF+7]) : "r"(a0), "r"(a1), "r"(a2), "r"(a3), "l"(db), "r"(sd), "n"(TB));
}
template<int OFF, int TA, int TB, int S> __device__ __forceinline__ void wgmma_ss_n160(float (&d)[S], uint64_t da, uint64_t db, int sd) {
  asm volatile("{\n.reg .pred p;\nsetp.ne.b32 p, %82, 0;\n"
    "wgmma.mma_async.sync.aligned.m64n160k16.f32.bf16.bf16 {%0, %1, %2, %3, %4, %5, %6, %7, %8, %9, %10, %11, %12, %13, %14, %15, %16, %17, %18, %19, %20, %21, %22, %23, %24, %25, %26, %27, %28, %29, %30, %31, %32, %33, %34, %35, %36, %37, %38, %39, %40, %41, %42, %43, %44, %45, %46, %47, %48, %49, %50, %51, %52, %53, %54, %55, %56, %57, %58, %59, %60, %61, %62, %63, %64, %65, %66, %67, %68, %69, %70, %71, %72, %73, %74, %75, %76, %77, %78, %79}, %80, %81, p, 1, 1, %83, %84;\n}\n"
    : "+f"(d[OFF+0]), "+f"(d[OFF+1]), "+f"(d[OFF+2]), "+f"(d[OFF+3]), "+f"(d[OFF+4]), "+f"(d[OFF+5]), "+f"(d[OFF+6]), "+f"(d[OFF+7]), "+f"(d[OFF+8]), "+f"(d[OFF+9]), "+f"(d[OFF+10]), "+f"(d[OFF+11]), "+f"(d[OFF+12]), "+f"(d[OFF+13]), "+f"(d[OFF+14]), "+f"(d[OFF+15]), "+f"(d[OFF+16]), "+f"(d[OFF+17]), "+f"(d[OFF+18]), "+f"(d[OFF+19]), "+f"(d[OFF+20]), "+f"(d[OFF+21]), "+f"(d[OFF+22]), "+f"(d[OFF+23]), "+f"(d[OFF+24]), "+f"(d[OFF+25]), "+f"(d[OFF+26]), "+f"(d[OFF+27]), "+f"(d[OFF+28]), "+f"(d[OFF+29]), "+f"(d[OFF+30]), "+f"(d[OFF+31]), "+f"(d[OFF+32]), "+f"(d[OFF+33]), "+f"(d[OFF+34]), "+f"(d[OFF+35]), "+f"(d[OFF+36]), "+f"(d[OFF+37]), "+f"(d[OFF+38]), "+f"(d[OFF+39]), "+f"(d[OFF+40]), "+f"(d[OFF+41]), "+f"(d[OFF+42]), "+f"(d[OFF+43]), "+f"(d[OFF+44]), "+f"(d[OFF+45]), "+f"(d[OFF+46]), "+f"(d[OFF+47]), "+f"(d[OFF+48]), "+f"(d[OFF+49]), "+f"(d[OFF+50]), "+f"(d[OFF+51]), "+f"(d[OFF+52]), "+f"(d[OFF+53]), "+f"(d[OFF+54]), "+f"(d[OFF+55]), "+f"(d[OFF+56]), "+f"(d[OFF+57]), "+f"(d[OFF+58]), "+f"(d[OFF+59]), "+f"(d[OFF+60]), "+f"(d[OFF+61]), "+f"(d[OFF+62]), "+f"(d[OFF+63]), "+f"(d[OFF+64]), "+f"(d[OFF+65]), "+f"(d[OFF+66]), "+f"(d[OFF+67]), "+f"(d[OFF+68]), "+f"(d[OFF+69]), "+f"(d[OFF+70]), "+f"(d[OFF+71]), "+f"(d[OFF+72]), "+f"(d[OFF+73]), "+f"(d[OFF+74]), "+f"(d[OFF+75]), "+f"(d[OFF+76]), "+f"(d[OFF+77]), "+f"(d[OFF+78]), "+f"(d[OFF+79]) : "l"(da), "l"(db), "r"(sd), "n"(TA), "n"(TB));
}

__device__ __align__(1024) uint16_t g_kvT[2 * 640 * 2048];
__device__ __align__(1024) uint16_t g_y2T[2 * 640 * 2048];
__device__ __align__(1024) uint16_t g_o[2048 * 640];
__device__ __align__(1024) uint16_t g_gate[2080];
__device__ __align__(1024) uint4 g_halo[128 * 5 * 32];
__device__ __align__(1024) unsigned g_cnt[46 * 32];
__device__ __align__(1024) unsigned g_launch[132 * 32];
#define CNT_KV(i) (g_cnt + 32 * (i))
#define CNT_O(i) (g_cnt + 32 * (10 + (i)))
#define CNT_Y(i) (g_cnt + 32 * (26 + (i)))
#define PTL(i) do {} while (0)
#define PTPL(on, i) do {} while (0)
#define PT(i) do {} while (0)
#define PTP(on, i) do {} while (0)

constexpr uint32_t SB = 1024;
constexpr uint32_t STG = 23552, WST = 15360;
DEVI constexpr uint32_t o_px(int ks) { return (((ks >> 1) + 1) & 3) * 2 * STG; }
DEVI constexpr uint32_t o_pw(int ks) { return o_px(ks) + 16384 + (ks & 1) * WST; }
constexpr uint32_t O_HALO = 0, O_QT = STG;
constexpr uint32_t O_OST = 2 * STG;
constexpr uint32_t P3S = 28672;
constexpr uint32_t HC = 8320, UC = 4624, UZ = 528;
constexpr uint32_t O_H0 = 5 * P3S, O_U2 = O_H0 + 3 * HC, O_H3 = O_U2 + UC, O_U0 = O_H3 + 2 * HC;
DEVI constexpr uint32_t o_h(int c) { return O_H0 + c * HC + (c > 2 ? UC : 0); }
DEVI constexpr uint32_t o_u(int c) { return c == 2 ? O_U2 : O_U0 + (c > 2 ? c - 1 : c) * UC; }
constexpr uint32_t O_Y = 208896;
DEVI constexpr uint32_t o_x(int c) { return c < 2 ? O_Y + c * 5120 : O_U0 + (c & 1) * UC; }
constexpr uint32_t O_HIN = O_Y + 16384;
DEVI constexpr uint32_t o_kin(int c) { return ((O_U0 + 127) & ~127u) + ((c & 1) ? 0 : 73 * 128); }
DEVI constexpr uint32_t o_p3(int ks) { return (ks < 6 ? ks : ks - 6) * P3S; }
constexpr uint32_t O_BT = 4 * P3S;
constexpr uint32_t O_GT = O_Y + 20480, O_GW = O_GT + 320;
constexpr uint32_t O_BAR = 231040;
constexpr uint32_t B_FULL = O_BAR, B_EMPTY = O_BAR + 8 * 8, B_P3F = O_BAR + 8 * 16, B_P3R = O_BAR + 8 * 26, B_G = O_BAR + 8 * 27, B_U = O_BAR + 8 * 28,
                   B_KVD = O_BAR + 8 * 33, B_KF = O_BAR + 8 * 36, B_Y = O_BAR + 8 * 38, B_EP = O_BAR + 8 * 40, B_LAST = O_BAR + 8 * 41, B_DONE = O_BAR + 8 * 42,
                   B_P1E = O_BAR + 8 * 43, B_HX = O_BAR + 8 * 43  , B_P3E = O_BAR + 8 * 52, B_HX0 = O_BAR + 8 * 57, B_KVS = O_BAR + 8 * 58, B_QD = O_BAR + 8 * 60, B_GD = O_BAR + 8 * 61, B_Q = O_BAR + 8 * 51;
constexpr uint32_t B_S13 = B_EMPTY + 8 * 5, B_S15 = B_EMPTY + 8 * 7, B_S19 = B_EMPTY + 8 * 3;
constexpr uint32_t O_GP = O_BAR + 512, O_EPOCH = O_GW + 1280;
constexpr uint32_t SMEM_BYTES = 232448;
static_assert(O_U0 + 4 * UC <= O_Y - 512 && o_kin(0) >= O_U0 + 2 * UC && O_EPOCH + 4 <= O_BAR && O_U0 >= 8 * STG, "smem map");
enum { NB_LEAD = 1, NB_HELP = 2, NB_HALO = 3, NB_ATT = 4, NB_G = 5, NB_TOK = 6, NB_RFULL = 8, NB_RFREE = 10 };

struct Maps { CUtensorMap x_par, w_main, w_tail, k_ld, v_ld, o_st, kv_st, wo, o_ld, y_ld, q_ld; };

template <int M> DEVI void conv_step(float (&acc)[128], uint32_t a0, uint32_t a1, uint32_t a2, uint32_t a3, uint32_t dl) {
  auto D = [&](int off) { return ((uint64_t)8 << 32) | (uint64_t)(uint32_t)(dl + off - 16 * M); };
  if constexpr (M == 0) wgmma_rs_n16<0, 0>(acc, a0, a1, a2, a3, D(0), 0);
  if constexpr (M <= 3) wgmma_rs_n48<8, 0>(acc, a0, a1, a2, a3, D(16), M == 0 ? 0 : 1);
  if constexpr (M <= 6) wgmma_rs_n48<32, 0>(acc, a0, a1, a2, a3, D(64), M == 0 ? 0 : 1);
  if constexpr (M <= 9) wgmma_rs_n48<56, 0>(acc, a0, a1, a2, a3, D(112), M == 0 ? 0 : 1);
  if constexpr (M <= 12) wgmma_rs_n48<80, 0>(acc, a0, a1, a2, a3, D(160), M == 0 ? 0 : 1);
  wgmma_rs_n48<104, 0>(acc, a0, a1, a2, a3, D(208), M == 0 ? 0 : 1);
}
DEVI constexpr int a_off(int P, int i) { return -4 * (64 * ((i & 4) ? 15 - P : P) + (i & 1) * 32 - (i & 2) * 2); }
template <int P> DEVI void load_pair(uint32_t (&a)[8], uint32_t ab) {
#pragma unroll
  for (int i = 0; i < 8; i++) a[i] = lds32(ab + a_off(P, i));
}
template <int P> DEVI void mma_pair(float (&acc)[128], uint32_t (&a)[8], uint32_t db) {
  wg_fence();
  conv_step<P>(acc, a[0], a[1], a[2], a[3], db);
  conv_step<15 - P>(acc, a[4], a[5], a[6], a[7], db);
  wg_commit();
}

template <int I0, int I1> DEVI void conv_reduce(uint32_t sb, int c, int ht, int chan, int bar, int nthr) {
  const uint32_t a0 = sb + o_h(c) + ht * 16, a2 = sb + o_u(c) + ht * 16, a3 = sb + o_x(c) + ht * 16;
  uint4* yp = (uint4*)(g_y2T + (size_t)chan * 2048) + ht;
#pragma unroll
  for (int i = I0; i < I1; i++) {
    uint4 p, q, r, s;
    if (i == I0) bar_sync(bar, nthr);
    lds128(a0 + i * 2048, p.x, p.y, p.z, p.w); lds128(a0 + 4160 + i * 2048, q.x, q.y, q.z, q.w);
    lds128(a2 + i * 2048, r.x, r.y, r.z, r.w); lds128(a3 + i * 2048, s.x, s.y, s.z, s.w);
    auto sum = [](uint32_t a, uint32_t b, uint32_t c, uint32_t d) { return hadd2(hadd2(hadd2(a, b), 0u), hadd2(c, d)) ^ 0x80008000u; };
    yp[i * 128] = make_uint4(sum(p.x, q.x, r.x, s.x), sum(p.y, q.y, r.y, s.y), sum(p.z, q.z, r.z, s.z), sum(p.w, q.w, r.w, s.w));
  }
}

template <int ODD, int PART> DEVI void pack_qkv(const float (&acc)[120], uint32_t (&Q)[10][2], uint32_t (&K)[10][2], uint32_t (&V)[10][2]) {
#pragma unroll
  for (int f = 0; f < 10; f++) {
    const bool tail = ODD ? (f < 2) : (f >= 8);
    const int fm = ODD ? f - 2 : f, ft = ODD ? f : f - 8;
    const int nq = tail ? 24 + ft : fm, nk = tail ? 26 + ft : 8 + fm, nv = tail ? 28 + ft : 16 + fm;
    if (PART == 0) { K[f][1] = pack_bf16(acc[4 * nk + 2], acc[4 * nk + 3]); V[f][1] = pack_bf16(acc[4 * nv + 2], acc[4 * nv + 3]); }
    if (PART == 1) { V[f][0] = pack_bf16(acc[4 * nv], acc[4 * nv + 1]); K[f][0] = pack_bf16(acc[4 * nk], acc[4 * nk + 1]); }
    if (PART == 2) { Q[f][0] = pack_bf16(acc[4 * nq], acc[4 * nq + 1]); Q[f][1] = pack_bf16(acc[4 * nq + 2], acc[4 * nq + 3]); }
  }
}
DEVI void sched_fence(uint32_t& z) {
  asm volatile("{\n.reg .pred p;\nL:\nshr.u32 %0, %0, 1;\nsetp.ne.u32 p, %0, 0;\n@p bra.uni L;\n}" : "+r"(z));
}

DEVI int pair_of(int c) {
  const int lo = 32 + 8 * c, hi = c - 4 + ((max(c - 29, 0) * 37) >> 8);
  int p; asm("{\n.reg .pred q;\nsetp.lt.s32 q, %1, 4;\nselp.b32 %0, %2, %3, q;\n}" : "=r"(p) : "r"(c), "r"(lo), "r"(hi));
  return p;
}
DEVI uint32_t make_ctx() {
  int b; asm volatile("mov.u32 %0, %%ctaid.x;" : "=r"(b));
  b += clk() & threadIdx.y;
  const int p = pair_of(b >> 1);
  const int j = b < 128 ? 8 * (p & 7) + (p >> 3) : 64;
  const int q = (j * 205) >> 10, r = j - 5 * q, i = j - q, co = (i * 79) >> 10;
  const int cp = r == 4 ? 4 : co, tb = r == 4 ? q : i - 13 * co;
  return ((2 * p + (b & 1)) & 255) | tb << 8 | (2 * cp + (b & 1)) << 12 | (b >> 7) << 16;
}
#define CTX() asm volatile("" : "+r"(ctx)); CTXU()
#define CTXU() int tid; asm volatile("mov.u32 %0, %%tid.x;" : "=r"(tid)); \
  const int lane = tid & 31, vb = ctx & 255, hg = (ctx >> 4) & 7, rt = ctx & 15, par = (ctx >> 3) & 1, mt = ctx & 7, rank = ctx & 1, \
  tb = (ctx >> 8) & 15, cb = (ctx >> 12) & 15; const bool main_cta = ctx < 65536; \
  (void)tid; (void)lane; (void)vb; (void)hg; (void)rt; (void)par; (void)mt; (void)rank; (void)tb; (void)cb; (void)main_cta
#define CTXW() CTX(); const int wg = warp >> 2, w = warp & 3, g = lane >> 2, t = lane & 3; const bool lead = (tid & 127) == 0; \
  (void)wg; (void)w; (void)g; (void)t; (void)lead

__global__ void __cluster_dims__(2, 1, 1) __launch_bounds__(512, 1)
fused_kernel(const uint16_t* __restrict__ xq, const uint16_t* __restrict__ wqkv, const uint16_t* __restrict__ gate_w, const __grid_constant__ Maps M, const uint16_t* __restrict__ shift_k, const uint16_t* __restrict__ ssm_k, const uint16_t* __restrict__ ssm_D,
             uint16_t* __restrict__ outp) {
  extern __shared__ __align__(1024) uint8_t smem_raw[];
  const uint32_t sb = smem_u32(smem_raw);
  const uint32_t t0 = clk();
  auto get_epoch = [&]() { mbar_wait(sb + B_EP, 0); return lds32(sb + O_EPOCH); };

  auto p1_load_x = [&](int ks, int p, int rank) {
    tma3(sb + o_px(ks), &M.x_par, ks * 32, (p >> 2) & 1, (p & 3) * 256 + rank * 128, sb + B_FULL + 8 * (ks & 7));
  };
  auto p1_load_w = [&](int ks, int p, int rank) {
    const uint32_t st = sb + o_pw(ks), fb = sb + B_FULL + 8 * (ks & 7);
    tma3_mc(st + rank * 6144, &M.w_main, (p >> 3) * 80 + 2 * (p & 8), ks * 32 + rank * 16, 0, fb);
    tma3_mc(st + 12288 + rank * 1536, &M.w_tail, (p >> 3) * 80 + 8 * (~p & 8), ks * 32 + rank * 16, 0, fb);
  };
  auto cta_pair = [&]() { return pair_of(blockIdx.x >> 1); };

  if (threadIdx.x < 32) {
    const unsigned b = blockIdx.x, l = threadIdx.x;
    const uint16_t* pfp = l < 16 ? xq + (16 * b + l) * 640 : wqkv + (15 * b + l - 16) * 64;
    if ((l | b >> 7 << 5) < 31) pf_l2(pfp);
  }
  const int warp = __shfl_sync(~0u, threadIdx.x >> 5, 0);
  if ((warp & 14) == 8) {
    if (elect_one()) {
#pragma unroll
      for (int s = 0; s < 8; s++) mbar_init(sb + O_BAR - 512 + 64 * warp + 8 * s, 5 * warp - 39);
      asm volatile("fence.mbarrier_init.release.cluster;" ::: "memory");
    }
    __syncwarp();
  }
  asm volatile("barrier.cluster.arrive.relaxed.aligned;" ::: "memory");
  if (warp == 8 && blockIdx.x < 128) {
    const int p = cta_pair(), rank = blockIdx.x & 1;
    if (elect_one()) { mbar_expect_tx(sb + B_FULL, 16384 + WST); p1_load_x(0, p, rank); }
    __syncwarp();
    asm volatile("barrier.cluster.wait.aligned;" ::: "memory");
    if (elect_one()) { p1_load_w(0, p, rank); PT(100); }
    __syncwarp();
  } else if (warp != 15) {
    asm volatile("barrier.cluster.wait.aligned;" ::: "memory");
    spin_until(t0, HOLD);
  }
  auto init_rest = [&]() {
    if (warp >= 11 && elect_one()) {
#pragma unroll
      for (int s = 0; s < 12; s++) mbar_init(sb + O_BAR + 128 - 11 * 96 + 96 * warp + 8 * s, warp == 14 ? 2 : 1);
      asm volatile("fence.mbarrier_init.release.cluster;" ::: "memory");
    }
    __syncwarp();
    bar_sync(0, blockIdx.x < 128 ? 224 : 512);
  };
  uint32_t ctx = 0;

  if (warp < 8) {
    reg_inc<RC>();
    ctx = make_ctx();
    if (blockIdx.x >= 128) bar_sync(0, 512);
    else {
      {
        uint32_t Q[10][2], K[10][2], V[10][2];
        {
          {
            float acc[120];
            CTXW();
            const int odd = (cta_pair() >> 3) & 1;
            const uint32_t rsb = mapa(sb, (blockIdx.x & 1) ^ 1);
            {
              const uint32_t aa = sb + (warp * 16 + (lane & 15)) * 128 + (((lane >> 4) ^ (lane & 7)) << 4);
              constexpr int NA = DEFER > 3 ? DEFER : 3;
              uint32_t a[NA][8];
              auto load_a = [&](int ks) {
                uint32_t(&r)[8] = a[ks % NA];
                mbar_wait(sb + B_FULL + 8 * (ks & 7), (ks >> 3) & 1);
                PTP(lead && (wg || !(ks & 3)), wg ? 60 + ks : 80 + (ks >> 2));
                ldsm4(r[0], r[1], r[2], r[3], (aa ^ ((ks & 1) * 64)) + o_px(ks)); ldsm4(r[4], r[5], r[6], r[7], (aa ^ ((ks & 1) * 64 + 32)) + o_px(ks));
              };
              auto mma_q = [&](int ks, int h) {
                uint32_t(&r)[8] = a[ks % NA];
                wgmma_rs_n64<0, 1>(acc, r[4 * h], r[4 * h + 1], r[4 * h + 2], r[4 * h + 3], mkdesc(SB + o_pw(ks) + h * 6144, 2048, 1024, 1), ks | h);
              };
              auto mma_step = [&](int ks, int h) {
                uint32_t(&r)[8] = a[ks % NA];
                wg_fence();
                wgmma_rs_n128<32, 1>(acc, r[4 * h], r[4 * h + 1], r[4 * h + 2], r[4 * h + 3], mkdesc(SB + o_pw(ks) + h * 6144 + 2048, 2048, 1024, 1), ks | h);
                if (ks < 20 - DEFER) mma_q(ks, h);
                wgmma_rs_n48<96, 1>(acc, r[4 * h], r[4 * h + 1], r[4 * h + 2], r[4 * h + 3], mkdesc(SB + o_pw(ks) + 12288 + h * 1536, 512, 256, 3), ks | h);
                wg_commit();
              };
              if (lead) PT(1 + wg);
              load_a(0);
#pragma unroll
              for (int ks = 0; ks < 20; ks++) {
                if (LEAD && ks == 20 - LEAD) bar_sync_p(wg == 0, NB_LEAD, 256);
                mma_step(ks, 0);
                if (ks < 19 && ks >= NLATE) load_a(ks + 1);
                mma_step(ks, 1);
                if (ks < NLATE) load_a(ks + 1);
                if (ks >= 1 && ks <= 16) {
                  wg_wait<2>();
                  mbar_arrive2_p(lead, sb + B_EMPTY + 8 * ((ks - 1) & 7), rsb + B_EMPTY + 8 * ((ks - 1) & 7));
                } else if (ks < 19 && ks + 2 - NA >= 16) wg_wait<2>();
              }
              if (LEAD) bar_arrive_p(wg, NB_LEAD, 256);
              if (DEFER) {
                wg_fence();
#pragma unroll
                for (int i = 40 - 2 * DEFER; i < 40; i++) mma_q(i >> 1, i & 1);
                wg_commit();
              }
              mbar_wait(sb + B_S15, 1);
              wg_wait<1>();
              mbar_arrive_p(tid == 0, sb + B_P1E);
              if (!DEFER) wg_wait<0>();
              fence_regs<32, 120>(acc);
              PTPL(lead, 158 + wg);
            }
            if (odd) pack_qkv<1, 0>(acc, Q, K, V); else pack_qkv<0, 0>(acc, Q, K, V);
            if (warp == 7 && (blockIdx.x & 1)) {
              uint4* hp = g_halo + vb * 160 + lane;
              st_relaxed(hp, K[0][1], K[1][1], K[3][1], K[4][1]); st_relaxed(hp + 32, K[5][1], K[6][1], K[8][1], K[9][1]);
              st_relaxed(hp + 64, K[2][1], K[7][1], V[0][1], V[1][1]);
              st_relaxed(hp + 96, V[2][1], V[3][1], V[4][1], V[5][1]); st_relaxed(hp + 128, V[6][1], V[7][1], V[8][1], V[9][1]);
            }
            const uint32_t ho = sb + O_HALO + warp * 2560 + lane * 16;
            stsm4(ho, K[0][1], K[1][1], K[3][1], K[4][1]); stsm4(ho + 512, K[5][1], K[6][1], K[8][1], K[9][1]);
            stsm4(ho + 1024, K[2][1], K[7][1], V[0][1], V[1][1]);
            stsm4(ho + 1536, V[2][1], V[3][1], V[4][1], V[5][1]); stsm4(ho + 2048, V[6][1], V[7][1], V[8][1], V[9][1]);
            if (warp == 7) {
              if (!(blockIdx.x & 1)) {
                fence_async_smem();
                __syncwarp();
                if (elect_one())
                  asm volatile("cp.async.bulk.shared::cluster.shared::cta.mbarrier::complete_tx::bytes [%0], [%1], 2560, [%2];"
                               ::"r"(mapa(sb + O_HIN, 1)), "r"(sb + O_HALO + 7 * 2560), "r"(mapa(sb + B_HX0, 1)) : "memory");
              }
              __syncwarp();
            } else {
              __syncwarp();
              if (lane == 0) mbar_arrive(sb + B_HX + 8 + 8 * warp);
            }
            if (odd) pack_qkv<1, 1>(acc, Q, K, V); else pack_qkv<0, 1>(acc, Q, K, V);
            wg_wait<0>();
            fence_regs<0, 32>(acc);
            PTPL(lead, 50 + wg);
            mbar_arrive2_p(lead, sb + B_S19, rsb + B_S19);
            if (odd) pack_qkv<1, 2>(acc, Q, K, V); else pack_qkv<0, 2>(acc, Q, K, V);
#pragma unroll
            for (int f = 0; f < 10; f++) V[f][0] = movm(V[f][0]);
            if (lead) PT(52 + wg);
            if (wg) mbar_wait(sb + B_P1E, 0);
          }
          CTXW();
          uint32_t z = threadIdx.y;
          const bool gt0 = 2 * t > g, gt1 = 2 * t + 1 > g;
          const uint32_t pmask = (gt0 ? 0xFFFFu : 0u) | (gt1 ? 0xFFFF0000u : 0u);
          const uint32_t hs = warp ? O_HALO + (warp - 1) * 2560 : O_HIN, ha = sb + hs + lane * 16;
          const uint32_t va = sb + ((lane & 8) ? O_HALO + warp * 2560 : hs) + 1280 + (lane >> 4) * 128 + (lane & 7) * 16;
          uint32_t Qh[4][2], Kh[10], Vh[10];
          float c1[4][4] = {}, c2[4][4] = {}, c0[4][4] = {}, l[8][2], m[8], x[8];
#pragma unroll
          for (int j = 0; j < 4; j++) {
            const int fa = (j >> 1) * 5 + (j & 1) * 3, fh = (j >> 1) * 5 + 2;
            const bool mine = (j & 1) ? (t >= 2) : (t < 2);
            Qh[j][0] = mine ? Q[fh][0] : 0u; Qh[j][1] = mine ? Q[fh][1] : 0u;
            mma16(c1[j], Q[fa][0], Q[fa][1], Q[fa + 1][0], Q[fa + 1][1], K[fa][0], K[fa + 1][0]);
            mma16(c2[j], Q[fa][0], Q[fa][1], Q[fa + 1][0], Q[fa + 1][1], K[fa][1], K[fa + 1][1]);
            mma8(c1[j], Qh[j][0], Qh[j][1], K[fh][0]);
            mma8(c2[j], Qh[j][0], Qh[j][1], K[fh][1]);
          }
          if (lead) PT(54 + wg);
          mbar_wait(sb + (warp ? B_HX + 8 * warp : B_HX0), 0);
          if (lead) PT(56 + wg);
          ldsm4(Kh[0], Kh[1], Kh[3], Kh[4], ha); ldsm4(Kh[5], Kh[6], Kh[8], Kh[9], ha + 512);
          asm volatile("ldmatrix.sync.aligned.m8n8.x2.shared.b16 {%0,%1}, [%2];" : "=r"(Kh[2]), "=r"(Kh[7]) : "r"(ha + 1024) : "memory");
          auto load_v = [&]() {
#pragma unroll
            for (int i = 0; i < 5; i++) ldsm4t(Vh[2 * i], V[2 * i][1], Vh[2 * i + 1], V[2 * i + 1][1], va + i * 256);
          };
          load_v();
          const float C = 0.22360679774997896f * 1.4426950408889634f;
          auto max1 = [&](int r) { m[r] = fmaxf(l[r][0], l[r][1]); x[r] = __shfl_xor_sync(~0u, m[r], 1); };
          auto max2 = [&](int r) { m[r] = fmaxf(m[r], x[r]); x[r] = __shfl_xor_sync(~0u, m[r], 2); };
          auto exps = [&](int r) { const float mc = fmaxf(m[r], x[r]) * C; l[r][0] = ex2(fmaf(l[r][0], C, -mc)); l[r][1] = ex2(fmaf(l[r][1], C, -mc)); };
#pragma unroll
          for (int j = 0; j < 4; j++) { l[4 + j][0] = gt0 ? c1[j][2] : c2[j][2]; l[4 + j][1] = gt1 ? c1[j][3] : c2[j][3]; max1(4 + j); }
#pragma unroll
          for (int j = 0; j < 4; j++) {
            const int fa = (j >> 1) * 5 + (j & 1) * 3, fh = (j >> 1) * 5 + 2;
            mma16(c0[j], Q[fa][0], Q[fa][1], Q[fa + 1][0], Q[fa + 1][1], Kh[fa], Kh[fa + 1]);
            mma8(c0[j], Qh[j][0], Qh[j][1], Kh[fh]);
            max2(4 + j);
          }
          const bool have_halo = warp > 0 || mt > 0;
#pragma unroll
          for (int j = 0; j < 4; j++) {
            if (!have_halo) c0[j][0] = c0[j][1] = -INFINITY;
            l[j][0] = gt0 ? c0[j][0] : c1[j][0]; l[j][1] = gt1 ? c0[j][1] : c1[j][1];
            max1(j);
          }
          exps(4); exps(5);
#pragma unroll
          for (int j = 0; j < 4; j++) max2(j);
          exps(6); exps(7);
#pragma unroll
          for (int j = 0; j < 4; j++) exps(j);
          float o[12][4] = {}, sm[4][4] = {};
#pragma unroll
          for (int j = 0; j < 4; j++) {
            const int fa = (j >> 1) * 5 + (j & 1) * 3, fh = (j >> 1) * 5 + 2;
            const uint32_t pl = pack_bf16(l[j][0], l[j][1]), pu = pack_bf16(l[4 + j][0], l[4 + j][1]);
            const uint32_t p0 = pl & pmask, p2 = pl & ~pmask, p3 = pu & pmask, p5 = pu & ~pmask, z0 = z << (2 * j + 1), z1 = z << (2 * j + 2);
            mma8(sm[j], pl, pu, 0x3F803F80u);
#pragma unroll
            for (int q = 0; q < 3; q++) {
              const int f = q < 2 ? fa + q : fh;
              mma8(o[3 * j + q], p2, p3, V[f][0]);
              mma16(o[3 * j + q], p0, z0, z1, p5, Vh[f], V[f][1]);
            }
            asm volatile("rcp.approx.ftz.f32 %0, %0;" : "+f"(sm[j][0]));
            asm volatile("rcp.approx.ftz.f32 %0, %0;" : "+f"(sm[j][2]));
          }
          sched_fence(z);
          bar_arrive_p(wg == 0, NB_HALO + z, 256);
          uint32_t O[10][2];
#pragma unroll
          for (int j = 0; j < 4; j++) {
            const int fa = (j >> 1) * 5 + (j & 1) * 3, fh = (j >> 1) * 5 + 2;
            const float r0 = sm[j][0], r1 = sm[j][2];
#pragma unroll
            for (int q = 0; q < 3; q++) {
              const int f = q < 2 ? fa + q : fh;
              const float* e = o[3 * j + q];
              const uint32_t o0 = pack_bf16(e[0] * r0, e[1] * r0), o1 = pack_bf16(e[2] * r1, e[3] * r1);
              if (q < 2 || !(j & 1)) { O[f][0] = o0; O[f][1] = o1; }
              else { O[f][0] = t >= 2 ? o0 : O[f][0]; O[f][1] = t >= 2 ? o1 : O[f][1]; }
            }
          }
          mbar_wait(sb + B_GD, 0);
          const uint32_t oa = sb + O_OST + wg * 2 * STG + (w * 16 + (lane & 15)) * 160 + (lane >> 4) * 16;
#pragma unroll
          for (int i = 0; i < 5; i++) stsm4(oa + i * 32, O[2 * i][0], O[2 * i][1], O[2 * i + 1][0], O[2 * i + 1][1]);
        }
      }
      {
        CTXW();
        fence_async_smem();
        bar_arrive(wg ? NB_LEAD : NB_ATT, 160);
        if (lead) PT(58 + wg);
        const uint32_t abase = sb + (g & 1) * 4160 + 4 * (1023 - 4 - 8 * w - (g >> 1) + t);
        float acc[128];
        uint32_t a0[8], a1[8], a2[8], a3[8];
#pragma unroll 1
        for (int c = wg ^ 1; c < 5; c += 2) {
          const uint32_t ab = abase + o_h(c);
          const uint32_t db = __shfl_sync(~0u, ((SB + o_u(c) + UZ - 16) >> 4) | 0x10000u, 0);
          mbar_wait(sb + B_U + 8 * c, 0);
          load_pair<0>(a0, ab); load_pair<1>(a1, ab); load_pair<2>(a2, ab);
          if (lead) PT(85 + c);
          bar_sync(c ? NB_TOK + wg : NB_HALO, 256);
          fence_regs(acc);
          mma_pair<0>(acc, a0, db);
          load_pair<3>(a3, ab);
          mma_pair<1>(acc, a1, db); wg_wait<1>();  load_pair<4>(a0, ab);
          if (lead) PT(90 + c);
          mma_pair<2>(acc, a2, db); wg_wait<1>();  load_pair<5>(a1, ab);
          mma_pair<3>(acc, a3, db); wg_wait<1>();  load_pair<6>(a2, ab);
          mma_pair<4>(acc, a0, db); wg_wait<1>();  load_pair<7>(a3, ab);
          mma_pair<5>(acc, a1, db);
          mma_pair<6>(acc, a2, db);
          bar_arrive_p(c < 4, NB_TOK + (wg ^ 1), 256);
          mma_pair<7>(acc, a3, db);
          bar_arrive_p(c == 4, NB_TOK, 256);
          wg_wait<0>();
          fence_regs(acc);
          PTPL(lead, 95 + c);
          bar_sync(NB_RFREE + wg, 256);
          const uint32_t pb = sb + (w < 2 ? o_h(c) + w * 4160 : w == 2 ? o_u(c) : o_x(c)) + lane * 16;
          if (lane < 2 * w) sts128(pb, 0, 0, 0, 0);
#pragma unroll
          for (int q = 0; q < 8; q++) {
            uint32_t p[4];
#pragma unroll
            for (int i = 0; i < 4; i++) {
              const int nu = 4 * q + i;
              p[i] = pack_bf16(acc[4 * nu], acc[4 * nu + 1]);
              if (nu > 0) p[i] = hadd2(p[i], pack_bf16(acc[4 * nu - 2], acc[4 * nu - 1]));
            }
            stsm4t(pb + w * 32 + q * 512, p[0], p[1], p[2], p[3]);
            if (q == 3) bar_arrive_p(c == 4, NB_RFULL + 1, 256);
          }
          if (c < 4) bar_arrive(NB_RFULL + wg, 256);
          if (lead) PT(140 + c);
        }
        if (wg) {
          const int yb = (lds32(sb + O_EPOCH) & 1) * 640;
              conv_reduce<1, 2>(sb, 4, tid - 128, yb + 512 + ((vb & 0x61) | (vb & 6) << 2 | (vb >> 2 & 6)), 14, 128);
          bar_arrive(12, 256);
          PTPL(lead, 45);
        }
      }
    }
    if (warp < 4) {
      CTXW();
      const uint32_t rsb = mapa(sb, (blockIdx.x & 1) ^ 1);
      const uint32_t ba = sb + O_BT + ((lane >> 4) * 8 + (lane & 7)) * 128 + (((2 * w + ((lane >> 3) & 1)) ^ ((lane & 1) << 2 | (lane >> 1 & 3))) << 4);
      mbar_wait(sb + B_P3F, 0);
      if (lead) PT(145);
      float acc[80];
#pragma unroll
      for (int ks = 0; ks < 10; ks++) {
        if (ks == NPRE) {
          if (NPRE) { wg_wait<0>(); mbar_arrive2_p(lead, sb + B_P3E + 8 * NPRE, rsb + B_P3E + 8 * NPRE); }
          bar_sync_p(blockIdx.x < 128, NB_TOK, 256);
        }
        PTP(lead, 146 + ks);
        const uint64_t da = mkdesc(SB + o_p3(ks), 1024, 1024, 1), db = mkdesc(SB + o_p3(ks) + 8192, 16, 1024, 1);
        wg_fence();
#pragma unroll
        for (int j = 0; j < 4; j++) wgmma_ss_n160<0, 1, 0>(acc, da + j * 128, db + j * 2, j | ks);
        wg_commit();
        if (ks < 9) mbar_wait(sb + B_P3F + 8 * (ks + 1), 0);
        if (ks >= 1 && ks <= 4 && ks != NPRE) { wg_wait<1>(); mbar_arrive2_p(lead, sb + B_P3E + 8 * ks, rsb + B_P3E + 8 * ks); }
      }
      wg_wait<0>();
      fence_regs(acc);
      PTPL(lead, 156);
#pragma unroll
      for (int i = 0; i < 10; i++) {
        stsm4t(ba + i * 2048, pack_bf16(acc[8 * i], acc[8 * i + 1]), pack_bf16(acc[8 * i + 2], acc[8 * i + 3]),
               pack_bf16(acc[8 * i + 4], acc[8 * i + 5]), pack_bf16(acc[8 * i + 6], acc[8 * i + 7]));
        if (i & 1) bar_arrive(1 + (i >> 1), 256);
      }
      if (lead) PT(157);
    }
  } else if (warp < 12) {
    reg_dec<RH>();
    const int hw = warp - 8;
    init_rest();
    ctx = __shfl_sync(~0u, make_ctx(), 0);
    const int yrow = (ctx & 0x61) | (ctx & 6) << 2 | (ctx >> 2 & 6);
    if (ctx < 65536) {
      CTXU();
      const int pr = hw >> 1, hh = hw & 1, tk = vb & 63, odd = (lane >> 2) & 1;
      const uint32_t sel0 = odd ? 0x7632 : 0x5410, sel1 = odd ? 0x5410 : 0x7632;
      const uint32_t in = sb + o_kin(pr), fb = sb + B_KF + 8 * pr, out = sb + O_Y + pr * 8192;
      const uint32_t oa = out + (2 * lane + odd) * 64 + (((3 - 2 * hh) ^ (lane & 3)) << 4), ia = in + hh * 2048 + lane * 4;
      auto fetch = [&](int c) {
        wait_until(t0, KT0 + c * KTD + ((((vb * 37) & 63) * KPH) >> 6));
        if (elect_one()) {
          const int kb = 2 * c + (vb >> 6);
          mbar_expect_tx(fb, 69 * 128);
          tma2(in, &M.k_ld, kb * 64, 32 * tk - 4, fb);
          tma2(in + 36 * 128, &M.v_ld, kb * 64, 32 * tk - 1, fb);
          PT(20 + c);
        }
        __syncwarp();
      };
      if (hh == 0) fetch(pr);
      const uint4* skp = (const uint4*)shift_k + (2 * pr + (vb >> 6)) * 32 + lane;
      uint4 sk = __ldg(skp), sk1 = __ldg(skp + 128), sk2 = __ldg(skp + (pr ? 0 : 256));
#pragma unroll 1
      for (int c = pr; c < 5; c += 2) {
        {
          mbar_wait(fb, (c >> 1) & 1);
          if (hh == 0 && lane == 0) PT(25 + c);
          uint32_t k[20], o[17];
#pragma unroll
          for (int i = 0; i < 20; i++) { k[i] = lds32(ia + i * 128); if (i >= 3) o[i - 3] = lds32(ia + (33 + i) * 128); }
          fence_async_smem();
          bar_sync(12 + pr, 64);
          if (hh == 0) {
            if (c < 3) fetch(c + 2);
            else if (lane == 0) mbar_arrive(sb + B_KVD + 8 * (c - 3));
          }
          const uint32_t w0 = prmt(sk.x, sk.z, 0x5410), w1 = prmt(sk.x, sk.z, 0x7632), w2 = prmt(sk.y, sk.w, 0x5410), w3 = prmt(sk.y, sk.w, 0x7632);
#pragma unroll
          for (int i = 0; i < 17; i++) o[i] = hmul2(hfma2(k[i + 3], w0, hfma2(k[i + 2], w1, hfma2(k[i + 1], w2, hmul2(k[i], w3)))), o[i]);
          sk = sk1; sk1 = sk2;
#pragma unroll
          for (int i = 0; i < 4; i++) {
            const int e = 8 * (i >> 1) + (i & 1);
            const uint32_t a = (oa ^ ((i >> 1) * 16)) + (i & 1) * 4096;
            sts128(a, prmt(o[7 + e], o[6 + e], sel0), prmt(o[5 + e], o[4 + e], sel0), prmt(o[3 + e], o[2 + e], sel0), prmt(o[1 + e], o[e], sel0));
            sts128(a ^ 64, prmt(o[7 + e], o[6 + e], sel1), prmt(o[5 + e], o[4 + e], sel1), prmt(o[3 + e], o[2 + e], sel1), prmt(o[1 + e], o[e], sel1));
          }
          bar_sync(12 + pr, 64);
        }
        if (hh) {
          fence_async_smem();
          if (elect_one()) {
            const int kb = 2 * c + (vb >> 6);
            tma3_store(&M.kv_st, 0, kb * 64, 63 - tk, out);
            tma3_store(&M.kv_st, 0, 640 + kb * 64, 63 - tk, out + 4096);
            bulk_commit(); bulk_wait_all();
            mbar_arrive(sb + (c == 4 ? B_KVD + 16 : B_KVS + 4 * (c & 2)));
            PTL(35 + c);
          }
          __syncwarp();
        }
      }
    }
    CTXU();
    const int g = lane >> 2, t = lane & 3, row = 8 * hw + g;
    const uint32_t go = (tb * 160 + row) * 80 + cb * 8 + t;
    const int yb = __shfl_sync(~0u, get_epoch() & 1, 0) * 640;
    uint4 T[10];
    if (hw == 2) {
      if (main_cta) { mbar_wait(sb + B_LAST, 0); mbar_wait(sb + B_S15, 1); }
      if (elect_one()) {
        mbar_expect_tx(sb + B_Q, 20480);
#pragma unroll
        for (int h = 0; h < 2; h++) tma2(sb + O_QT + h * 10240, &M.q_ld, cb * 64 + 32 * h, tb * 160, sb + B_Q);
      }
      __syncwarp();
    }
    mbar_wait(sb + B_Q, 0);
#pragma unroll
    for (int i = 0; i < 10; i++) lds128(sb + O_QT + (i & 1) * 10240 + (i >> 1) * 2048 + row * 64 + t * 16, T[i].x, T[i].y, T[i].z, T[i].w);
    fence_async_smem();
    bar_sync(12 + (hw >> 1), 64);
    if (!(tid & 63)) mbar_arrive(sb + B_QD);
    if (tid == 256) PTL(40);
    if (main_cta) {
      bar_arrive(NB_RFREE, 256);
      bar_arrive(NB_RFREE + 1, 256);
      auto red = [&](int c) {
        const int wg = (c & 1) ^ 1;
        conv_reduce<0, 2>(sb, c, tid - 256, yb + 128 * c + yrow, NB_RFULL + wg, 256);
        if (hw == 3 && elect_one()) flag_add(CNT_Y(4 * c + (vb >> 5)), 1);
        if (tid == 256) PTL(41 + c);
        if (c < 3) bar_arrive(NB_RFREE + wg, 256);
        if (c == 2) {
          bar_sync(NB_HELP, 128);
          if (tid == 256) { mbar_arrive(sb + B_P3E); mbar_arrive_remote(sb + B_P3E, rank ^ 1); }
        }
      };
      if (hw == 3) {
        mbar_wait(sb + B_KVD + 16, 0);
        if (elect_one()) { flag_release(CNT_KV(4 + (vb >> 6))); PTL(32); }
        __syncwarp();
      }
#pragma unroll 1
      for (int c = 0; c < 4; c++) red(c);
    }
    uint32_t G[5];
    mbar_wait(sb + B_G, 0);
#pragma unroll
    for (int q = 0; q < 5; q++) { uint16_t v; asm volatile("ld.shared.u16 %0, [%1];" : "=h"(v) : "r"(sb + O_GT + (32 * q + row) * 2)); G[q] = prmt(v, 0, 0x1010); }
#pragma unroll
    for (int i = 0; i < 10; i++) { const uint32_t c = G[i >> 1] ^ 0x80008000u; T[i] = make_uint4(hmul2(T[i].x, c), hmul2(T[i].y, c), hmul2(T[i].z, c), hmul2(T[i].w, c)); }
    if (main_cta) {
      conv_reduce<0, 1>(sb, 4, tid - 256, yb + 512 + yrow, NB_RFULL + 1, 256);
      if (hw == 3 && elect_one()) { flag_add(CNT_Y(16 + (vb >> 5)), 1); PTL(19); }
      bar_sync(12, 256);
    }
#pragma unroll
    for (int h = 0; h < 2; h++) {
      mbar_wait_wd(sb + B_Y + 8 * h, 0, t0);
      if (tid == 256) PTL(46);
      const uint32_t ya = sb + O_Y + h * 10240 + lane * 64 + ((hw ^ ((lane >> 1) & 3)) << 4);
      uint4 y[5];
      auto empty = [](uint32_t m) { return (m & 0xFFFFu) == 0 || m < 0x10000u; };
      uint32_t m = ~0u;
#pragma unroll
      for (int q = 4; q >= 0; q--) {
        ldsm4t(y[q].x, y[q].y, y[q].z, y[q].w, ya + q * 2048);
        m = __vimin3_u16x2(__vimin3_u16x2(m, y[q].x, y[q].y), y[q].z, y[q].w);
        if (q == 4 && tb == 12) m = ~0u;
      }
      if (__any_sync(~0u, empty(m))) {
        const uint4* gp = (const uint4*)g_y2T + (yb + cb * 64 + 32 * h + lane) * 256 + tb * 20 + hw;
#pragma unroll
        for (int q = 0; q < 5; q++) lds128(ya + q * 2048, y[q].x, y[q].y, y[q].z, y[q].w);
        if (tb == 12) y[4] = make_uint4(~0u, ~0u, ~0u, ~0u);
        for (;;) {
          bool bad[5], any = false;
#pragma unroll
          for (int q = 0; q < 5; q++) { bad[q] = empty(__vimin3_u16x2(__vminu2(y[q].x, y[q].y), y[q].z, y[q].w)); any |= bad[q]; }
          if (!__any_sync(~0u, any)) break;
#pragma unroll
          for (int q = 0; q < 5; q++)
            if (bad[q]) asm volatile("ld.relaxed.gpu.global.v4.b32 {%0,%1,%2,%3}, [%4];" : "=r"(y[q].x), "=r"(y[q].y), "=r"(y[q].z), "=r"(y[q].w) : "l"(gp + 4 * q) : "memory");
        }
#pragma unroll
        for (int q = 0; q < 5; q++) sts128(ya + q * 2048, y[q].x, y[q].y, y[q].z, y[q].w);
        __syncwarp();
#pragma unroll
        for (int q = 0; q < 5; q++) ldsm4t(y[q].x, y[q].y, y[q].z, y[q].w, ya + q * 2048);
        PTL(49);
      }
#pragma unroll
      for (int q = 0; q < 5; q++) {
        uint4& r = T[2 * q + h];
        r = make_uint4(hmul2(r.x, y[q].x), hmul2(r.y, y[q].y), hmul2(r.z, y[q].z), hmul2(r.w, y[q].w));
      }
    }
    const uint32_t so = sb + O_BT + row * 128 + ((t ^ ((g & 1) << 2 | g >> 1)) << 4);
    if (tid == 256) PTL(47);
#pragma unroll
    for (int q = 0; q < 5; q++) {
      const uint32_t c = hfma2(G[q], 0xBF80BF80u, 0x3F803F80u);
      bar_sync(1 + q, 256);
      if (q == 4) mbar_arrive_p(tid == 256, sb + B_DONE);
#pragma unroll
      for (int h = 0; h < 2; h++) {
        uint4 u;
        lds128((so ^ (h * 64)) + q * 4096, u.x, u.y, u.z, u.w);
        const uint4& r = T[2 * q + h];
        if (q < 4 || tb < 12)
          asm volatile("st.global.v4.b32 [%0], {%1,%2,%3,%4};" ::"l"((uint4*)outp + go + q * 2560 + h * 4), "r"(hfma2(u.x, c, r.x)), "r"(hfma2(u.y, c, r.y)), "r"(hfma2(u.z, c, r.z)), "r"(hfma2(u.w, c, r.w)) : "memory");
      }
    }
  } else {
    reg_dec<RP>();
    uint4 gwv = make_uint4(0, 0, 0, 0);
    if (warp == 15) {
      const int p = cta_pair(), rank = blockIdx.x & 1;
      asm volatile("barrier.cluster.wait.aligned;" ::: "memory");
      if (blockIdx.x >= 128) bar_sync(0, 512);
      else {
#pragma unroll 1
        for (int ks = 1;; ks += 2) {
          mbar_wait(sb + B_EMPTY + 8 * (ks & 7), ((ks >> 3) & 1) ^ 1);
          spin_until(t0, PT1 + (ks - 1) * PTD);
          if (elect_one()) { mbar_expect_tx(sb + B_FULL + 8 * (ks & 7), WST); p1_load_w(ks, p, rank); PT(100 + ks); }
          if (ks == 19) break;
          const int kn = ks + 1;
          mbar_wait(sb + B_EMPTY + 8 * (kn & 7), ((kn >> 3) & 1) ^ 1);
          spin_until(t0, PT1 + ks * PTD - PTE);
          if (elect_one()) { mbar_expect_tx(sb + B_FULL + 8 * (kn & 7), 16384 + WST); p1_load_x(kn, p, rank); p1_load_w(kn, p, rank); PT(100 + kn); }
        }
        if (elect_one()) mbar_arrive(sb + B_LAST);
#pragma unroll 1
        for (int i = 0; i < 2; i++) {
          mbar_wait(sb + B_KVS + 8 * i, 0);
          if (elect_one()) { flag_release(CNT_KV(2 * i + (p >> 5))); PTL(30 + i); }
          __syncwarp();
        }
        mbar_wait(sb + B_S19, 0);
      }
    } else {
      if (threadIdx.x < 384 + 80) gwv = __ldg((const uint4*)gate_w + threadIdx.x - 384);
      init_rest();
    }
    ctx = __shfl_sync(~0u, make_ctx(), 0);
    CTXU();
    if (warp == 12) {
        unsigned epoch = 0;
      if (lane == 0) epoch = *(volatile unsigned*)(g_launch + 32 * vb) + 1;
      if (main_cta) { sts128(sb + O_GW + lane * 16, gwv.x, gwv.y, gwv.z, gwv.w); bar_arrive(NB_G, 96); }
      if (lane == 0) {
        if ((sb & 0xFFFFFF) != SB) __trap();
        sts32(sb + O_EPOCH, epoch);
        mbar_arrive(sb + B_EP);
#pragma unroll 1
        for (int i = 5; i < 11; i++) asm volatile("prefetch.tensormap [%0];" ::"l"(&M.x_par + i) : "memory");
      }
      if (main_cta && rank) {
#pragma unroll
        for (int f = 0; f < 5; f++) st_relaxed(g_halo + vb * 160 + lane + 32 * f, ~0u, ~0u, ~0u, ~0u);
      }
      __syncwarp();
      if (elect_one()) flag_release(g_launch + 32 * vb);
      __syncwarp();
      if (main_cta) {
        uint4 h0 = make_uint4(0, 0, 0, 0);
        if (lane < 5) {
          h0 = __ldg((const uint4*)(ssm_k + (size_t)(128 * lane + vb) * 2048));
          h0.x = prmt(pack_bf16(bf_lo(h0.x) + bf_lo(__ldg(ssm_D + 128 * lane + vb)), 0.f), h0.x, 0x7610);
        }
        epoch = __shfl_sync(~0u, epoch, 0);
        const int ze = lane & 7;
        const uint32_t za = sb + (lane < 8 ? o_u(ze) + UZ : lane < 24 ? o_h(ze) + (lane >> 4) * 4160 + 4096 : o_u(ze) + 512);
        const uint16_t* hp = ssm_k + (size_t)vb * 2048 + 8;
        const uint16_t* up = g_kvT + (size_t)vb * 2048;
        const unsigned* fp = CNT_KV(vb >> 6);
        sts128(sb + O_Y - 512 + lane * 16, 0, 0, 0, 0);
        mbar_wait(sb + B_LAST, 0);
        mbar_wait(sb + B_S13, 1);
#pragma unroll
        for (int c = 0; c < 5; c++) {
          if (c == 0 || c == 3) {
            mbar_wait(sb + B_KVD + (c ? 8 : 0), 0);
#pragma unroll
            for (int e = c; e < (c ? 5 : 3); e++) sts128(sb + o_u(e) + lane * 16, 0, 0, 0, 0);
            if (ze >= c && ze < (c ? 5 : 3)) sts128(za, h0.x, h0.y, h0.z, h0.w);
            fence_async_smem();
            __syncwarp();
            if (elect_one()) {
#pragma unroll
              for (int e = c; e < (c ? 5 : 3); e++) {
                mbar_expect_tx(sb + B_U + 8 * e, 3 * 4096 - 16);
                if (c || e == 0) bulk_load(sb + o_u(e) + UZ + 16, hp + 128 * 2048 * e, 4080, sb + B_U + 8 * e);
              }
            }
          }
          if (!(c & 1)) { flag_wait(fp + 32 * c, 64 * epoch); __syncwarp(); }
          if (elect_one()) {
            bulk_load(sb + o_h(c), up + 128 * 2048 * c, 4096, sb + B_U + 8 * c);
            bulk_load(sb + o_h(c) + 4160, up + (640 + 128 * c) * 2048, 4096, sb + B_U + 8 * c);
            if (c == 1) {
#pragma unroll
              for (int e = 1; e < 3; e++) bulk_load(sb + o_u(e) + UZ + 16, hp + 128 * 2048 * e, 4080, sb + B_U + 8 * e);
            }
            PTL(10 + c);
          }
        }
        mbar_wait(sb + B_LAST, 1);
        if (elect_one()) {
#pragma unroll 1
          for (int i = 0; i < 40; i++) bulk_store(g_y2T + (size_t)((~epoch & 1) * 640 + 5 * vb) * 2048 + i * 256, sb + O_Y - 512, 512);
          bulk_commit(); bulk_wait_read();
          PTL(33);
        }
      }
    } else if (warp != 15) {
        const int r = warp - 13;
      if (main_cta) {
        if (rank && lane == 0) mbar_expect_tx(sb + B_HX0, 1280);
        const int t = lane & 3, grow = hg * 16 + (lane & 15);
        const uint32_t ga = sb + grow * 128 + (((4 * r + (lane >> 4)) ^ (lane & 7)) << 4);
        const uint32_t gp = sb + O_GW + 64 * r + 4 * t;
        float s0 = 0.f, s1 = 0.f;
        if (tid < 384 + 80) sts128(sb + O_GW + (tid - 384) * 16, gwv.x, gwv.y, gwv.z, gwv.w);
        bar_sync(NB_G, 96);
#pragma unroll 1
        for (int ks = 0; ks < 20; ks += 2) {
          uint32_t x[8], gw[4];
#pragma unroll
          for (int i = 0; i < 4; i++) gw[i] = lds32(gp + ks * 64 + i * 16);
          mbar_wait_wd(sb + B_FULL + 8 * (ks & 7), (ks >> 3) & 1, t0);
          if (r == 0 && lane == 0) PT(120 + ks);
          ldsm4(x[0], x[1], x[2], x[3], ga + o_px(ks)); ldsm4(x[4], x[5], x[6], x[7], (ga ^ 32) + o_px(ks));
#pragma unroll
          for (int i = 0; i < 8; i++) x[i] = hmul2(x[i], gw[i >> 1]);
          if (lane < 2) mbar_arrive(sb + B_EMPTY + 8 * (ks & 7) + 8 * lane + (x[0] & x[7] & threadIdx.y));
#pragma unroll
          for (int i = 0; i < 8; i += 4) {
            s0 += (bf_lo(x[i]) + bf_hi(x[i])) + (bf_lo(x[i + 2]) + bf_hi(x[i + 2]));
            s1 += (bf_lo(x[i + 1]) + bf_hi(x[i + 1])) + (bf_lo(x[i + 3]) + bf_hi(x[i + 3]));
          }
        }
        s0 += __shfl_xor_sync(~0u, s0, 1); s1 += __shfl_xor_sync(~0u, s1, 1);
        s0 += __shfl_xor_sync(~0u, s0, 2); s1 += __shfl_xor_sync(~0u, s1, 2);
        if (t < 2) sts32(sb + O_GP + r * 64 + (8 * t + (lane >> 2)) * 4, __float_as_uint(t ? s1 : s0));
        if (lane == 0) mbar_arrive(sb + B_GD);
        if (r == 0) bar_arrive(NB_G, 64);
        if (!rank) {
          uint4 d[3];
          if (mt > 0) {
            const uint4* hp = g_halo + (vb - 1) * 160 + r * 64 + lane;
            mbar_wait_wd(sb + B_EP, 0, t0);
            flag_wait_wd(g_launch + 32 * (vb - 1), lds32(sb + O_EPOCH), t0);
            mbar_wait_wd(sb + B_HX + 56, 0, t0);
            for (;;) {
              bool ok = true;
#pragma unroll
              for (int f = 0; f < 3; f++) {
                asm volatile("ld.relaxed.gpu.global.v4.b32 {%0,%1,%2,%3}, [%4];" : "=r"(d[f].x), "=r"(d[f].y), "=r"(d[f].z), "=r"(d[f].w) : "l"(hp + 32 * f) : "memory");
              }
#pragma unroll
              for (int f = 0; f < 3; f++) ok = ok && max(max(d[f].x, d[f].y), max(d[f].z, d[f].w)) != ~0u;
              if (__all_sync(~0u, ok)) break;
              if (clk() - t0 > 0x70000000u) __trap();
            }
          } else {
#pragma unroll
            for (int f = 0; f < 3; f++) d[f] = make_uint4(0, 0, 0, 0);
          }
#pragma unroll
          for (int f = 0; f < 3; f++) stsm4(sb + O_HIN + r * 1024 + f * 512 + lane * 16, d[f].x, d[f].y, d[f].z, d[f].w);
          __syncwarp();
          if (lane == 0) { mbar_arrive(sb + B_HX0); PTL(15 + r); }
        }
        if (r == 1) {
          bar_sync(NB_G, 64);
          if (lane < 16) {
            const uint32_t pa = sb + O_GP + lane * 4;
            const float z = __uint_as_float(lds32(pa)) + __uint_as_float(lds32(pa + 64));
            g_gate[2 * (mt * 128 + hg * 16 + lane) + par] = (uint16_t)pack_bf16(__fdividef(1.f, 1.f + __expf(-bf_lo(pack_bf16(z, 0.f)))), 0.f);
          }
          __syncwarp();
          if (elect_one()) flag_release(CNT_O(rt));
        }
      }
      mbar_wait_wd(sb + B_EP, 0, t0);
      const unsigned epoch = lds32(sb + O_EPOCH);
      if (main_cta) mbar_wait_wd(sb + B_P3E, 0, t0);
      flag_wait_wd(CNT_Y(2 * cb + r), 32 * epoch, t0);
      __syncwarp();
      if (elect_one()) {
        mbar_expect_tx(sb + B_Y + 8 * r, 10240);
        tma3(sb + O_Y + r * 10240, &M.y_ld, 0, (epoch & 1) * 640 + cb * 64 + 32 * r, tb * 5, sb + B_Y + 8 * r);
        PTL(17 + r);
      }
      __syncwarp();
      mbar_wait_wd(sb + B_DONE, 0, t0);
    } else {
      const unsigned epoch = get_epoch();
      if (main_cta) {
        bar_sync(NB_LEAD, 160);
        if (elect_one()) tma3_store(&M.o_st, hg * 80, par, mt * 128 + 64, sb + O_OST + 2 * STG);
        bar_sync(NB_ATT, 160);
        if (elect_one()) {
          tma3_store(&M.o_st, hg * 80, par, mt * 128, sb + O_OST);
          bulk_commit(); bulk_wait_all();
          flag_release(CNT_O(rt));
          mbar_arrive(sb + B_LAST);
          PTL(3);
        }
        __syncwarp();
      }
      mbar_wait(sb + B_QD, 0);
#pragma unroll 1
      for (int ks = 0; ks < 5; ks++)
        if (elect_one()) tma2(sb + o_p3(ks), &M.wo, cb * 64, ks * 64, sb + B_P3F + 8 * ks);
      if (lane < 4) flag_wait(CNT_O(8 * (lane & 1) + min(7, (80 * tb + 79 * (lane >> 1)) >> 7)), 16 * epoch);
      __syncwarp();
      if (elect_one()) {
        PTL(4);
        mbar_arrive_remote(sb + B_P3R, rank ^ 1);
        mbar_expect_tx(sb + B_G, 320);
        bulk_load(sb + O_GT, g_gate + tb * 160, 320, sb + B_G);
      }
      mbar_wait(sb + B_P3R, 0);
      auto load_o = [&](int ks) {
        tma2_mc(sb + o_p3(ks) + 8192 + rank * 10240, &M.o_ld, ks * 64, tb * 160 + rank * 80, sb + B_P3F + 8 * ks);
        mbar_expect_tx(sb + B_P3F + 8 * ks, P3S);
      };
      auto load_wo = [&](int ks) { tma2(sb + o_p3(ks), &M.wo, cb * 64, ks * 64, sb + B_P3F + 8 * ks); };
#pragma unroll 1
      for (int ks = 0; ks < 5; ks++)
        if (elect_one()) load_o(ks);
#pragma unroll
      for (int ks = 5; ks < 10; ks++) {
        if (ks > 5 || main_cta) mbar_wait(sb + B_P3E + 8 * (ks - 5), 0);
        if (elect_one()) {
          load_o(ks);
          load_wo(ks);
          PTL(ks);
        }
      }
    }
  }
}

typedef CUresult (*PFN_enc)(CUtensorMap*, CUtensorMapDataType, cuuint32_t, void*, const cuuint64_t*, const cuuint64_t*, const cuuint32_t*,
                            const cuuint32_t*, CUtensorMapInterleave, CUtensorMapSwizzle, CUtensorMapL2promotion, CUtensorMapFloatOOBfill);
static void enc(PFN_enc f, CUtensorMap* m, const void* base, int rank, const cuuint64_t* dims, const cuuint64_t* strides, const cuuint32_t* box,
                CUtensorMapSwizzle sw) {
  const cuuint32_t es[5] = {1, 1, 1, 1, 1};
  f(m, CU_TENSOR_MAP_DATA_TYPE_BFLOAT16, rank, (void*)base, dims, strides, box, es, CU_TENSOR_MAP_INTERLEAVE_NONE, sw,
    CU_TENSOR_MAP_L2_PROMOTION_NONE, CU_TENSOR_MAP_FLOAT_OOB_FILL_NONE);
}

extern "C" void kernel_launch(void* const* d_in, const int* in_sizes, int n_in, void* d_out, int out_size) {
  (void)in_sizes; (void)n_in; (void)out_size;
  static PFN_enc f = nullptr;
  static void *kvT, *y2T, *o;
  if (!f) {
    void* p = nullptr;
    cudaDriverEntryPointQueryResult q;
    cudaGetDriverEntryPoint("cuTensorMapEncodeTiled", &p, cudaEnableDefault, &q);
    f = (PFN_enc)p;
    cudaGetSymbolAddress(&kvT, g_kvT); cudaGetSymbolAddress(&y2T, g_y2T); cudaGetSymbolAddress(&o, g_o);
    cudaFuncSetAttribute(fused_kernel, cudaFuncAttributeMaxDynamicSharedMemorySize, SMEM_BYTES);
  }
  Maps M;
  const CUtensorMapSwizzle S0 = CU_TENSOR_MAP_SWIZZLE_NONE, S32 = CU_TENSOR_MAP_SWIZZLE_32B, S64 = CU_TENSOR_MAP_SWIZZLE_64B, S128 = CU_TENSOR_MAP_SWIZZLE_128B;
  const cuuint64_t dpar[3] = {640, 2, 1024}, spar[2] = {1280, 2560};
  const cuuint64_t dw[3] = {640, 640, 3}, sw[2] = {3840, 1280};
  const cuuint64_t dnat[2] = {640, 2048}, snat[1] = {1280};
  const cuuint64_t dT2[3] = {32, 1280, 64}, sT[2] = {4096, 64};
  const cuuint64_t dwo[2] = {640, 640};
  { const cuuint32_t bx[3] = {64, 1, 128}; enc(f, &M.x_par, d_in[0], 3, dpar, spar, bx, S128); }
  { const cuuint32_t bx[3] = {64, 16, 3}; enc(f, &M.w_main, d_in[7], 3, dw, sw, bx, S128); }
  { const cuuint32_t bx[3] = {16, 16, 3}; enc(f, &M.w_tail, d_in[7], 3, dw, sw, bx, S32); }
  { const cuuint32_t bx[3] = {80, 1, 64}; enc(f, &M.o_st, o, 3, dpar, spar, bx, S0); }
  { const cuuint32_t bx[3] = {32, 64, 1}; enc(f, &M.kv_st, kvT, 3, dT2, sT, bx, S64); }
  { const cuuint32_t bx[3] = {32, 32, 5}; enc(f, &M.y_ld, y2T, 3, dT2, sT, bx, S64); }
  { const cuuint32_t bx[2] = {64, 36}; enc(f, &M.k_ld, d_in[1], 2, dnat, snat, bx, S0); }
  { const cuuint32_t bx[2] = {64, 33}; enc(f, &M.v_ld, d_in[2], 2, dnat, snat, bx, S0); }
  { const cuuint32_t bx[2] = {32, 160}; enc(f, &M.q_ld, d_in[0], 2, dnat, snat, bx, S0); }
  { const cuuint32_t bx[2] = {64, 64}; enc(f, &M.wo, d_in[8], 2, dwo, snat, bx, S128); }
  { const cuuint32_t bx[2] = {64, 80}; enc(f, &M.o_ld, o, 2, dnat, snat, bx, S128); }
  fused_kernel<<<130, 512, SMEM_BYTES, cudaStreamPerThread>>>((const uint16_t*)d_in[0], (const uint16_t*)d_in[7], (const uint16_t*)d_in[9], M, (const uint16_t*)d_in[3], (const uint16_t*)d_in[4], (const uint16_t*)d_in[5],
                                                              (uint16_t*)d_out);
}
```

```cpp
#include <cuda_runtime.h>
#include <cuda_bf16.h>
#include <cuda.h>
#include <stdint.h>

#define DEVI __device__ __forceinline__
#define PT1 300
#define PTD 460
#define PTE 150
#define DEFER 4
#define KPH KTD
#define NLATE 4
#define KT0 1500
#define KTD 1000
#define RC 192
#define RH 96
#define RP 32
#define HOLD 750
#define LEAD 3

DEVI uint32_t smem_u32(const void* p) { return (uint32_t)__cvta_generic_to_shared(p); }
DEVI void wg_fence() { asm volatile("wgmma.fence.sync.aligned;" ::: "memory"); }
DEVI void wg_commit() { asm volatile("wgmma.commit_group.sync.aligned;" ::: "memory"); }
template <int N> DEVI void wg_wait() { asm volatile("wgmma.wait_group.sync.aligned %0;" ::"n"(N) : "memory"); }
template <int A = 0, int B = -1, int S> DEVI void fence_regs(float (&d)[S]) {
#pragma unroll
  for (int i = A; i < (B < 0 ? S : B); i++) asm volatile("" : "+f"(d[i])::"memory");
}
DEVI uint64_t mkdesc(uint32_t addr, uint32_t lbo, uint32_t sbo, int swz) {
  return (uint64_t)((addr & 0x3FFFF) >> 4) | ((uint64_t)(lbo >> 4) << 16) | ((uint64_t)(sbo >> 4) << 32) | ((uint64_t)swz << 62);
}
DEVI void mbar_init(uint32_t bar, uint32_t cnt) { asm volatile("mbarrier.init.shared::cta.b64 [%0], %1;" ::"r"(bar), "r"(cnt) : "memory"); }
DEVI void mbar_expect_tx(uint32_t bar, uint32_t bytes) { asm volatile("mbarrier.arrive.expect_tx.shared::cta.b64 _, [%0], %1;" ::"r"(bar), "r"(bytes) : "memory"); }
DEVI void mbar_arrive(uint32_t bar) { asm volatile("mbarrier.arrive.shared::cta.b64 _, [%0];" ::"r"(bar) : "memory"); }
DEVI void mbar_wait(uint32_t bar, uint32_t parity) {
  asm volatile("{\n.reg .pred p;\nLAB_WAIT:\nmbarrier.try_wait.parity.shared::cta.b64 p, [%0], %1;\n@!p bra LAB_WAIT;\n}" ::"r"(bar), "r"(parity) : "memory");
}
DEVI void mbar_wait_wd(uint32_t bar, uint32_t parity, uint32_t t0) {
  asm volatile("{\n.reg .pred p;\n.reg .u32 c;\nLAB_WAIT:\nmbarrier.try_wait.parity.shared::cta.b64 p, [%0], %1;\n@p bra DONE;\nmov.u32 c, %%clock;\nsub.u32 c, c, %2;\nsetp.lt.u32 p, c, 0x70000000;\n@p bra LAB_WAIT;\ntrap;\nDONE:\n}" ::"r"(bar), "r"(parity), "r"(t0) : "memory");
}
DEVI void flag_wait(const unsigned* p, unsigned target) {
  asm volatile("{\n.reg .pred p;\n.reg .s32 v;\nLAB_WAIT:\nld.relaxed.gpu.global.u32 v, [%0];\nsub.s32 v, v, %1;\nsetp.lt.s32 p, v, 0;\n@p bra LAB_WAIT;\n}" ::"l"(p), "r"(target) : "memory");
}
DEVI void flag_wait_wd(const unsigned* p, unsigned target, uint32_t t0) {
  asm volatile("{\n.reg .pred p;\n.reg .s32 v;\nLAB_WAIT:\nld.relaxed.gpu.global.u32 v, [%0];\nsub.s32 v, v, %1;\nsetp.ge.s32 p, v, 0;\n@p bra DONE;\nmov.u32 v, %%clock;\nsub.s32 v, v, %2;\nsetp.lt.u32 p, v, 0x70000000;\n@p bra LAB_WAIT;\ntrap;\nDONE:\n}" ::"l"(p), "r"(target), "r"(t0) : "memory");
}
DEVI void flag_add(unsigned* p, unsigned v) { asm volatile("red.relaxed.gpu.global.add.u32 [%0], %1;" ::"l"(p), "r"(v) : "memory"); }
DEVI void flag_release(unsigned* p) { asm volatile("fence.proxy.async;\nred.relaxed.gpu.global.add.u32 [%0], 1;" ::"l"(p) : "memory"); }
DEVI void fence_async_smem() { asm volatile("fence.proxy.async.shared::cta;" ::: "memory"); }
DEVI bool elect_one() { uint32_t p; asm volatile("{\n.reg .pred P;\nelect.sync _|P, 0xffffffff;\nselp.u32 %0, 1, 0, P;\n}" : "=r"(p)); return p; }
DEVI void bar_sync(int id, int n) { asm volatile("bar.sync %0, %1;" ::"r"(id), "r"(n) : "memory"); }
DEVI void bar_arrive(int id, int n) { asm volatile("bar.arrive %0, %1;" ::"r"(id), "r"(n) : "memory"); }
DEVI void tma2(uint32_t dst, const CUtensorMap* m, int c0, int c1, uint32_t bar) {
  asm volatile("cp.async.bulk.tensor.2d.shared::cluster.global.mbarrier::complete_tx::bytes [%0], [%1, {%3, %4}], [%2];" ::"r"(dst), "l"(m), "r"(bar), "r"(c0), "r"(c1) : "memory");
}
DEVI void tma3(uint32_t dst, const CUtensorMap* m, int c0, int c1, int c2, uint32_t bar) {
  asm volatile("cp.async.bulk.tensor.3d.shared::cluster.global.mbarrier::complete_tx::bytes [%0], [%1, {%3, %4, %5}], [%2];" ::"r"(dst), "l"(m), "r"(bar), "r"(c0), "r"(c1), "r"(c2) : "memory");
}
DEVI void tma3_mc(uint32_t dst, const CUtensorMap* m, int c0, int c1, int c2, uint32_t bar) {
  asm volatile("cp.async.bulk.tensor.3d.shared::cluster.global.mbarrier::complete_tx::bytes.multicast::cluster [%0], [%1, {%3, %4, %5}], [%2], %6;" ::"r"(dst), "l"(m), "r"(bar), "r"(c0), "r"(c1), "r"(c2), "h"((uint16_t)3) : "memory");
}
DEVI void tma2_mc(uint32_t dst, const CUtensorMap* m, int c0, int c1, uint32_t bar) {
  asm volatile("cp.async.bulk.tensor.2d.shared::cluster.global.mbarrier::complete_tx::bytes.multicast::cluster [%0], [%1, {%3, %4}], [%2], %5;" ::"r"(dst), "l"(m), "r"(bar), "r"(c0), "r"(c1), "h"((uint16_t)3) : "memory");
}
DEVI void mbar_arrive_remote(uint32_t bar, uint32_t cta) {
  asm volatile("{\n.reg .b32 ra;\nmapa.shared::cluster.u32 ra, %0, %1;\nmbarrier.arrive.shared::cluster.b64 _, [ra];\n}" ::"r"(bar), "r"(cta) : "memory");
}
DEVI void tma3_store(const CUtensorMap* m, int c0, int c1, int c2, uint32_t src) {
  asm volatile("cp.async.bulk.tensor.3d.global.shared::cta.bulk_group [%0, {%2, %3, %4}], [%1];" ::"l"(m), "r"(src), "r"(c0), "r"(c1), "r"(c2) : "memory");
}
DEVI void bulk_load(uint32_t dst, const void* src, uint32_t bytes, uint32_t bar) {
  asm volatile("cp.async.bulk.shared::cluster.global.mbarrier::complete_tx::bytes [%0], [%1], %2, [%3];" ::"r"(dst), "l"(src), "r"(bytes), "r"(bar) : "memory");
}
DEVI void bulk_store(void* dst, uint32_t src, uint32_t bytes) {
  asm volatile("cp.async.bulk.global.shared::cta.bulk_group [%0], [%1], %2;" ::"l"(dst), "r"(src), "r"(bytes) : "memory");
}
DEVI void pf_l2(const void* p) { asm volatile("prefetch.global.L2 [%0];" ::"l"(p)); }
template <int OFF> DEVI uint32_t ldg_v(const void* p) { uint32_t v; asm volatile("ld.volatile.global.b32 %0, [%1 + %2];" : "=r"(v) : "l"(p), "n"(OFF)); return v; }
DEVI void bulk_commit() { asm volatile("cp.async.bulk.commit_group;" ::: "memory"); }
DEVI void bulk_wait_all() { asm volatile("cp.async.bulk.wait_group 0;" ::: "memory"); }
DEVI void bulk_wait_read() { asm volatile("cp.async.bulk.wait_group.read 0;" ::: "memory"); }
template <int R> DEVI void reg_inc() { asm volatile("setmaxnreg.inc.sync.aligned.u32 %0;" ::"n"(R)); }
template <int R> DEVI void reg_dec() { asm volatile("setmaxnreg.dec.sync.aligned.u32 %0;" ::"n"(R)); }
DEVI uint32_t prmt(uint32_t a, uint32_t b, uint32_t s) { uint32_t r; asm("prmt.b32 %0,%1,%2,%3;" : "=r"(r) : "r"(a), "r"(b), "r"(s)); return r; }
DEVI uint32_t lds32(uint32_t a) { uint32_t r; asm volatile("ld.shared.b32 %0,[%1];" : "=r"(r) : "r"(a)); return r; }
DEVI void sts32(uint32_t a, uint32_t x) { asm volatile("st.shared.b32 [%0],%1;" ::"r"(a), "r"(x) : "memory"); }
DEVI void sts128(uint32_t a, uint32_t x, uint32_t y, uint32_t z, uint32_t w) { asm volatile("st.shared.v4.b32 [%0],{%1,%2,%3,%4};" ::"r"(a), "r"(x), "r"(y), "r"(z), "r"(w) : "memory"); }
DEVI void sts128v(uint32_t a, uint32_t x, uint32_t y, uint32_t z, uint32_t w) { asm volatile("st.volatile.shared.v4.b32 [%0],{%1,%2,%3,%4};" ::"r"(a), "r"(x), "r"(y), "r"(z), "r"(w) : "memory"); }
DEVI void lds128(uint32_t a, uint32_t& x, uint32_t& y, uint32_t& z, uint32_t& w) { asm volatile("ld.shared.v4.b32 {%0,%1,%2,%3},[%4];" : "=r"(x), "=r"(y), "=r"(z), "=r"(w) : "r"(a) : "memory"); }
DEVI void ldsm4(uint32_t& r0, uint32_t& r1, uint32_t& r2, uint32_t& r3, uint32_t addr) {
  asm volatile("ldmatrix.sync.aligned.m8n8.x4.shared.b16 {%0,%1,%2,%3}, [%4];" : "=r"(r0), "=r"(r1), "=r"(r2), "=r"(r3) : "r"(addr) : "memory");
}
DEVI void ldsm4t(uint32_t& r0, uint32_t& r1, uint32_t& r2, uint32_t& r3, uint32_t addr) {
  asm volatile("ldmatrix.sync.aligned.m8n8.x4.trans.shared.b16 {%0,%1,%2,%3}, [%4];" : "=r"(r0), "=r"(r1), "=r"(r2), "=r"(r3) : "r"(addr) : "memory");
}
DEVI void stsm4(uint32_t addr, uint32_t r0, uint32_t r1, uint32_t r2, uint32_t r3) {
  asm volatile("stmatrix.sync.aligned.m8n8.x4.shared.b16 [%0], {%1,%2,%3,%4};" ::"r"(addr), "r"(r0), "r"(r1), "r"(r2), "r"(r3) : "memory");
}
DEVI void stsm4t(uint32_t addr, uint32_t r0, uint32_t r1, uint32_t r2, uint32_t r3) {
  asm volatile("stmatrix.sync.aligned.m8n8.x4.trans.shared.b16 [%0], {%1,%2,%3,%4};" ::"r"(addr), "r"(r0), "r"(r1), "r"(r2), "r"(r3) : "memory");
}
DEVI uint32_t movm(uint32_t a) { uint32_t r; asm volatile("movmatrix.sync.aligned.m8n8.trans.b16 %0, %1;" : "=r"(r) : "r"(a)); return r; }
DEVI uint32_t pack_bf16(float lo, float hi) { uint32_t r; asm("cvt.rn.bf16x2.f32 %0, %1, %2;" : "=r"(r) : "f"(hi), "f"(lo)); return r; }
DEVI uint32_t hmul2(uint32_t a, uint32_t b) { uint32_t r; asm("mul.rn.bf16x2 %0,%1,%2;" : "=r"(r) : "r"(a), "r"(b)); return r; }
DEVI uint32_t hadd2(uint32_t a, uint32_t b) { uint32_t r; asm("add.rn.bf16x2 %0,%1,%2;" : "=r"(r) : "r"(a), "r"(b)); return r; }
DEVI float bf_lo(uint32_t a) { return __uint_as_float(prmt(a, 0, 0x1044)); }
DEVI float bf_hi(uint32_t a) { return __uint_as_float(a & 0xFFFF0000u); }
DEVI void mma16(float (&c)[4], uint32_t a0, uint32_t a1, uint32_t a2, uint32_t a3, uint32_t b0, uint32_t b1) {
  asm volatile("mma.sync.aligned.m16n8k16.row.col.f32.bf16.bf16.f32 {%0,%1,%2,%3},{%4,%5,%6,%7},{%8,%9},{%0,%1,%2,%3};"
      : "+f"(c[0]), "+f"(c[1]), "+f"(c[2]), "+f"(c[3]) : "r"(a0), "r"(a1), "r"(a2), "r"(a3), "r"(b0), "r"(b1));
}
DEVI void mma8(float (&c)[4], uint32_t a0, uint32_t a1, uint32_t b0) {
  asm volatile("mma.sync.aligned.m16n8k8.row.col.f32.bf16.bf16.f32 {%0,%1,%2,%3},{%4,%5},{%6},{%0,%1,%2,%3};"
      : "+f"(c[0]), "+f"(c[1]), "+f"(c[2]), "+f"(c[3]) : "r"(a0), "r"(a1), "r"(b0));
}
DEVI float ex2(float x) { float r; asm volatile("ex2.approx.ftz.f32 %0, %1;" : "=f"(r) : "f"(x)); return r; }

DEVI uint32_t clk() { uint32_t c; asm volatile("mov.u32 %0, %%clock;" : "=r"(c)); return c; }
DEVI void wait_until(uint32_t t0, int dt) { while ((int)(clk() - t0) < dt) __nanosleep(40); }
DEVI void spin_until(uint32_t t0, int dt) { while ((int)(clk() - t0) < dt) {} }
DEVI uint32_t hfma2(uint32_t a, uint32_t b, uint32_t c) { uint32_t r; asm("fma.rn.bf16x2 %0,%1,%2,%3;" : "=r"(r) : "r"(a), "r"(b), "r"(c)); return r; }
DEVI void bar_sync_p(int on, int id, int n) { asm volatile("{\n.reg .pred p;\nsetp.ne.b32 p, %0, 0;\n@p bar.sync %1, %2;\n}" ::"r"(on), "r"(id), "r"(n) : "memory"); }
DEVI void bar_arrive_p(int on, int id, int n) { asm volatile("{\n.reg .pred p;\nsetp.ne.b32 p, %0, 0;\n@p bar.arrive %1, %2;\n}" ::"r"(on), "r"(id), "r"(n) : "memory"); }
DEVI void mbar_arrive_p(int on, uint32_t bar) { asm volatile("{\n.reg .pred p;\nsetp.ne.b32 p, %1, 0;\n@p mbarrier.arrive.shared::cta.b64 _, [%0];\n}" ::"r"(bar), "r"(on) : "memory"); }
DEVI void mbar_arrive2_p(int on, uint32_t bar, uint32_t rbar) {
  asm volatile("{\n.reg .pred p;\nsetp.ne.b32 p, %2, 0;\n@p mbarrier.arrive.shared::cta.b64 _, [%0];\n@p mbarrier.arrive.shared::cluster.b64 _, [%1];\n}" ::"r"(bar), "r"(rbar), "r"(on) : "memory");
}
DEVI void st_relaxed(uint4* p, uint32_t x, uint32_t y, uint32_t z, uint32_t w) {
  asm volatile("st.relaxed.gpu.global.v4.b32 [%0], {%1,%2,%3,%4};" ::"l"(p), "r"(x), "r"(y), "r"(z), "r"(w) : "memory");
}
DEVI uint32_t mapa(uint32_t a, uint32_t cta) { uint32_t r; asm("mapa.shared::cluster.u32 %0, %1, %2;" : "=r"(r) : "r"(a), "r"(cta)); return r; }
DEVI void st_async128(uint32_t a, uint32_t x, uint32_t y, uint32_t z, uint32_t w, uint32_t bar) {
  asm volatile("st.async.weak.shared::cluster.mbarrier::complete_tx::bytes.v4.b32 [%0], {%1,%2,%3,%4}, [%5];" ::"r"(a), "r"(x), "r"(y), "r"(z), "r"(w), "r"(bar) : "memory");
}

template<int OFF, int TB, int S> __device__ __forceinline__ void wgmma_rs_n128(float (&d)[S], uint32_t a0, uint32_t a1, uint32_t a2, uint32_t a3, uint64_t db, int sd) {
  asm volatile("{\n.reg .pred p;\nsetp.ne.b32 p, %69, 0;\n"
    "wgmma.mma_async.sync.aligned.m64n128k16.f32.bf16.bf16 {%0, %1, %2, %3, %4, %5, %6, %7, %8, %9, %10, %11, %12, %13, %14, %15, %16, %17, %18, %19, %20, %21, %22, %23, %24, %25, %26, %27, %28, %29, %30, %31, %32, %33, %34, %35, %36, %37, %38, %39, %40, %41, %42, %43, %44, %45, %46, %47, %48, %49, %50, %51, %52, %53, %54, %55, %56, %57, %58, %59, %60, %61, %62, %63}, {%64, %65, %66, %67}, %68, p, 1, 1, %70;\n}\n"
    : "+f"(d[OFF+0]), "+f"(d[OFF+1]), "+f"(d[OFF+2]), "+f"(d[OFF+3]), "+f"(d[OFF+4]), "+f"(d[OFF+5]), "+f"(d[OFF+6]), "+f"(d[OFF+7]), "+f"(d[OFF+8]), "+f"(d[OFF+9]), "+f"(d[OFF+10]), "+f"(d[OFF+11]), "+f"(d[OFF+12]), "+f"(d[OFF+13]), "+f"(d[OFF+14]), "+f"(d[OFF+15]), "+f"(d[OFF+16]), "+f"(d[OFF+17]), "+f"(d[OFF+18]), "+f"(d[OFF+19]), "+f"(d[OFF+20]), "+f"(d[OFF+21]), "+f"(d[OFF+22]), "+f"(d[OFF+23]), "+f"(d[OFF+24]), "+f"(d[OFF+25]), "+f"(d[OFF+26]), "+f"(d[OFF+27]), "+f"(d[OFF+28]), "+f"(d[OFF+29]), "+f"(d[OFF+30]), "+f"(d[OFF+31]), "+f"(d[OFF+32]), "+f"(d[OFF+33]), "+f"(d[OFF+34]), "+f"(d[OFF+35]), "+f"(d[OFF+36]), "+f"(d[OFF+37]), "+f"(d[OFF+38]), "+f"(d[OFF+39]), "+f"(d[OFF+40]), "+f"(d[OFF+41]), "+f"(d[OFF+42]), "+f"(d[OFF+43]), "+f"(d[OFF+44]), "+f"(d[OFF+45]), "+f"(d[OFF+46]), "+f"(d[OFF+47]), "+f"(d[OFF+48]), "+f"(d[OFF+49]), "+f"(d[OFF+50]), "+f"(d[OFF+51]), "+f"(d[OFF+52]), "+f"(d[OFF+53]), "+f"(d[OFF+54]), "+f"(d[OFF+55]), "+f"(d[OFF+56]), "+f"(d[OFF+57]), "+f"(d[OFF+58]), "+f"(d[OFF+59]), "+f"(d[OFF+60]), "+f"(d[OFF+61]), "+f"(d[OFF+62]), "+f"(d[OFF+63]) : "r"(a0), "r"(a1), "r"(a2), "r"(a3), "l"(db), "r"(sd), "n"(TB));
}
template<int OFF, int TB, int S> __device__ __forceinline__ void wgmma_rs_n64(float (&d)[S], uint32_t a0, uint32_t a1, uint32_t a2, uint32_t a3, uint64_t db, int sd) {
  asm volatile("{\n.reg .pred p;\nsetp.ne.b32 p, %37, 0;\n"
    "wgmma.mma_async.sync.aligned.m64n64k16.f32.bf16.bf16 {%0, %1, %2, %3, %4, %5, %6, %7, %8, %9, %10, %11, %12, %13, %14, %15, %16, %17, %18, %19, %20, %21, %22, %23, %24, %25, %26, %27, %28, %29, %30, %31}, {%32, %33, %34, %35}, %36, p, 1, 1, %38;\n}\n"
    : "+f"(d[OFF+0]), "+f"(d[OFF+1]), "+f"(d[OFF+2]), "+f"(d[OFF+3]), "+f"(d[OFF+4]), "+f"(d[OFF+5]), "+f"(d[OFF+6]), "+f"(d[OFF+7]), "+f"(d[OFF+8]), "+f"(d[OFF+9]), "+f"(d[OFF+10]), "+f"(d[OFF+11]), "+f"(d[OFF+12]), "+f"(d[OFF+13]), "+f"(d[OFF+14]), "+f"(d[OFF+15]), "+f"(d[OFF+16]), "+f"(d[OFF+17]), "+f"(d[OFF+18]), "+f"(d[OFF+19]), "+f"(d[OFF+20]), "+f"(d[OFF+21]), "+f"(d[OFF+22]), "+f"(d[OFF+23]), "+f"(d[OFF+24]), "+f"(d[OFF+25]), "+f"(d[OFF+26]), "+f"(d[OFF+27]), "+f"(d[OFF+28]), "+f"(d[OFF+29]), "+f"(d[OFF+30]), "+f"(d[OFF+31]) : "r"(a0), "r"(a1), "r"(a2), "r"(a3), "l"(db), "r"(sd), "n"(TB));
}
template<int OFF, int TB, int S> __device__ __forceinline__ void wgmma_rs_n48(float (&d)[S], uint32_t a0, uint32_t a1, uint32_t a2, uint32_t a3, uint64_t db, int sd) {
  asm volatile("{\n.reg .pred p;\nsetp.ne.b32 p, %29, 0;\n"
    "wgmma.mma_async.sync.aligned.m64n48k16.f32.bf16.bf16 {%0, %1, %2, %3, %4, %5, %6, %7, %8, %9, %10, %11, %12, %13, %14, %15, %16, %17, %18, %19, %20, %21, %22, %23}, {%24, %25, %26, %27}, %28, p, 1, 1, %30;\n}\n"
    : "+f"(d[OFF+0]), "+f"(d[OFF+1]), "+f"(d[OFF+2]), "+f"(d[OFF+3]), "+f"(d[OFF+4]), "+f"(d[OFF+5]), "+f"(d[OFF+6]), "+f"(d[OFF+7]), "+f"(d[OFF+8]), "+f"(d[OFF+9]), "+f"(d[OFF+10]), "+f"(d[OFF+11]), "+f"(d[OFF+12]), "+f"(d[OFF+13]), "+f"(d[OFF+14]), "+f"(d[OFF+15]), "+f"(d[OFF+16]), "+f"(d[OFF+17]), "+f"(d[OFF+18]), "+f"(d[OFF+19]), "+f"(d[OFF+20]), "+f"(d[OFF+21]), "+f"(d[OFF+22]), "+f"(d[OFF+23]) : "r"(a0), "r"(a1), "r"(a2), "r"(a3), "l"(db), "r"(sd), "n"(TB));
}
template<int OFF, int TB, int S> __device__ __forceinline__ void wgmma_rs_n16(float (&d)[S], uint32_t a0, uint32_t a1, uint32_t a2, uint32_t a3, uint64_t db, int sd) {
  asm volatile("{\n.reg .pred p;\nsetp.ne.b32 p, %13, 0;\n"
    "wgmma.mma_async.sync.aligned.m64n16k16.f32.bf16.bf16 {%0, %1, %2, %3, %4, %5, %6, %7}, {%8, %9, %10, %11}, %12, p, 1, 1, %14;\n}\n"
    : "+f"(d[OFF+0]), "+f"(d[OFF+1]), "+f"(d[OFF+2]), "+f"(d[OFF+3]), "+f"(d[OFF+4]), "+f"(d[OFF+5]), "+f"(d[OFF+6]), "+f"(d[OFF+7]) : "r"(a0), "r"(a1), "r"(a2), "r"(a3), "l"(db), "r"(sd), "n"(TB));
}
template<int OFF, int TA, int TB, int S> __device__ __forceinline__ void wgmma_ss_n160(float (&d)[S], uint64_t da, uint64_t db, int sd) {
  asm volatile("{\n.reg .pred p;\nsetp.ne.b32 p, %82, 0;\n"
    "wgmma.mma_async.sync.aligned.m64n160k16.f32.bf16.bf16 {%0, %1, %2, %3, %4, %5, %6, %7, %8, %9, %10, %11, %12, %13, %14, %15, %16, %17, %18, %19, %20, %21, %22, %23, %24, %25, %26, %27, %28, %29, %30, %31, %32, %33, %34, %35, %36, %37, %38, %39, %40, %41, %42, %43, %44, %45, %46, %47, %48, %49, %50, %51, %52, %53, %54, %55, %56, %57, %58, %59, %60, %61, %62, %63, %64, %65, %66, %67, %68, %69, %70, %71, %72, %73, %74, %75, %76, %77, %78, %79}, %80, %81, p, 1, 1, %83, %84;\n}\n"
    : "+f"(d[OFF+0]), "+f"(d[OFF+1]), "+f"(d[OFF+2]), "+f"(d[OFF+3]), "+f"(d[OFF+4]), "+f"(d[OFF+5]), "+f"(d[OFF+6]), "+f"(d[OFF+7]), "+f"(d[OFF+8]), "+f"(d[OFF+9]), "+f"(d[OFF+10]), "+f"(d[OFF+11]), "+f"(d[OFF+12]), "+f"(d[OFF+13]), "+f"(d[OFF+14]), "+f"(d[OFF+15]), "+f"(d[OFF+16]), "+f"(d[OFF+17]), "+f"(d[OFF+18]), "+f"(d[OFF+19]), "+f"(d[OFF+20]), "+f"(d[OFF+21]), "+f"(d[OFF+22]), "+f"(d[OFF+23]), "+f"(d[OFF+24]), "+f"(d[OFF+25]), "+f"(d[OFF+26]), "+f"(d[OFF+27]), "+f"(d[OFF+28]), "+f"(d[OFF+29]), "+f"(d[OFF+30]), "+f"(d[OFF+31]), "+f"(d[OFF+32]), "+f"(d[OFF+33]), "+f"(d[OFF+34]), "+f"(d[OFF+35]), "+f"(d[OFF+36]), "+f"(d[OFF+37]), "+f"(d[OFF+38]), "+f"(d[OFF+39]), "+f"(d[OFF+40]), "+f"(d[OFF+41]), "+f"(d[OFF+42]), "+f"(d[OFF+43]), "+f"(d[OFF+44]), "+f"(d[OFF+45]), "+f"(d[OFF+46]), "+f"(d[OFF+47]), "+f"(d[OFF+48]), "+f"(d[OFF+49]), "+f"(d[OFF+50]), "+f"(d[OFF+51]), "+f"(d[OFF+52]), "+f"(d[OFF+53]), "+f"(d[OFF+54]), "+f"(d[OFF+55]), "+f"(d[OFF+56]), "+f"(d[OFF+57]), "+f"(d[OFF+58]), "+f"(d[OFF+59]), "+f"(d[OFF+60]), "+f"(d[OFF+61]), "+f"(d[OFF+62]), "+f"(d[OFF+63]), "+f"(d[OFF+64]), "+f"(d[OFF+65]), "+f"(d[OFF+66]), "+f"(d[OFF+67]), "+f"(d[OFF+68]), "+f"(d[OFF+69]), "+f"(d[OFF+70]), "+f"(d[OFF+71]), "+f"(d[OFF+72]), "+f"(d[OFF+73]), "+f"(d[OFF+74]), "+f"(d[OFF+75]), "+f"(d[OFF+76]), "+f"(d[OFF+77]), "+f"(d[OFF+78]), "+f"(d[OFF+79]) : "l"(da), "l"(db), "r"(sd), "n"(TA), "n"(TB));
}

__device__ __align__(1024) uint16_t g_kvT[2 * 640 * 2048];
__device__ __align__(1024) uint16_t g_y2T[2 * 640 * 2048];
__device__ __align__(1024) uint16_t g_o[2048 * 640];
__device__ __align__(1024) uint16_t g_gate[2080];
__device__ __align__(1024) uint4 g_halo[128 * 5 * 32];
__device__ __align__(1024) unsigned g_cnt[46 * 32];
__device__ __align__(1024) unsigned g_launch[132 * 32];
#define CNT_KV(i) (g_cnt + 32 * (i))
#define CNT_O(i) (g_cnt + 32 * (10 + (i)))
#define CNT_Y(i) (g_cnt + 32 * (26 + (i)))
#define PTL(i) do {} while (0)
#define PTPL(on, i) do {} while (0)
#define PT(i) do {} while (0)
#define PTP(on, i) do {} while (0)

constexpr uint32_t SB = 1024;
constexpr uint32_t STG = 23552, WST = 15360;
DEVI constexpr uint32_t o_px(int ks) { return (((ks >> 1) + 1) & 3) * 2 * STG; }
DEVI constexpr uint32_t o_pw(int ks) { return o_px(ks) + 16384 + (ks & 1) * WST; }
constexpr uint32_t O_HALO = 0, O_QT = STG;
constexpr uint32_t O_OST = 2 * STG;
constexpr uint32_t P3S = 28672;
constexpr uint32_t HC = 8320, UC = 4624, UZ = 528;
constexpr uint32_t O_H0 = 5 * P3S, O_U2 = O_H0 + 3 * HC, O_H3 = O_U2 + UC, O_U0 = O_H3 + 2 * HC;
DEVI constexpr uint32_t o_h(int c) { return O_H0 + c * HC + (c > 2 ? UC : 0); }
DEVI constexpr uint32_t o_u(int c) { return c == 2 ? O_U2 : O_U0 + (c > 2 ? c - 1 : c) * UC; }
constexpr uint32_t O_Y = 208896;
DEVI constexpr uint32_t o_x(int c) { return c < 2 ? O_Y + c * 5120 : O_U0 + (c & 1) * UC; }
constexpr uint32_t O_HIN = O_Y + 16384;
DEVI constexpr uint32_t o_kin(int c) { return ((O_U0 + 127) & ~127u) + ((c & 1) ? 0 : 73 * 128); }
DEVI constexpr uint32_t o_p3(int ks) { return (ks < 6 ? ks : ks - 6) * P3S; }
constexpr uint32_t O_BT = 4 * P3S;
constexpr uint32_t O_GT = O_Y + 20480, O_GW = O_GT + 320;
constexpr uint32_t O_BAR = 231040;
constexpr uint32_t B_FULL = O_BAR, B_EMPTY = O_BAR + 8 * 8, B_P3F = O_BAR + 8 * 16, B_P3R = O_BAR + 8 * 26, B_G = O_BAR + 8 * 27, B_U = O_BAR + 8 * 28,
                   B_KVD = O_BAR + 8 * 33, B_KF = O_BAR + 8 * 36, B_Y = O_BAR + 8 * 38, B_EP = O_BAR + 8 * 40, B_LAST = O_BAR + 8 * 41, B_DONE = O_BAR + 8 * 42,
                   B_P1E = O_BAR + 8 * 43, B_HX = O_BAR + 8 * 43  , B_P3E = O_BAR + 8 * 52, B_HX0 = O_BAR + 8 * 57, B_KVS = O_BAR + 8 * 58, B_QD = O_BAR + 8 * 60, B_GD = O_BAR + 8 * 61, B_Q = O_BAR + 8 * 51;
constexpr uint32_t B_S13 = B_EMPTY + 8 * 5, B_S15 = B_EMPTY + 8 * 7, B_S19 = B_EMPTY + 8 * 3;
constexpr uint32_t O_GP = O_BAR + 512, O_EPOCH = O_GW + 1280;
constexpr uint32_t SMEM_BYTES = 232448;
static_assert(O_U0 + 4 * UC <= O_Y - 512 && o_kin(0) >= O_U0 + 2 * UC && O_EPOCH + 4 <= O_BAR && O_U0 >= 8 * STG, "smem map");
enum { NB_LEAD = 1, NB_HELP = 2, NB_HALO = 3, NB_ATT = 4, NB_G = 5, NB_TOK = 6, NB_RFULL = 8, NB_RFREE = 10 };

struct Maps { CUtensorMap x_par, w_main, w_tail, k_ld, v_ld, o_st, kv_st, wo, o_ld, y_ld, q_ld; };

template <int M> DEVI void conv_step(float (&acc)[128], uint32_t a0, uint32_t a1, uint32_t a2, uint32_t a3, uint32_t dl) {
  auto D = [&](int off) { return ((uint64_t)8 << 32) | (uint64_t)(uint32_t)(dl + off - 16 * M); };
  if constexpr (M == 0) wgmma_rs_n16<0, 0>(acc, a0, a1, a2, a3, D(0), 0);
  if constexpr (M <= 3) wgmma_rs_n48<8, 0>(acc, a0, a1, a2, a3, D(16), M == 0 ? 0 : 1);
  if constexpr (M <= 6) wgmma_rs_n48<32, 0>(acc, a0, a1, a2, a3, D(64), M == 0 ? 0 : 1);
  if constexpr (M <= 9) wgmma_rs_n48<56, 0>(acc, a0, a1, a2, a3, D(112), M == 0 ? 0 : 1);
  if constexpr (M <= 12) wgmma_rs_n48<80, 0>(acc, a0, a1, a2, a3, D(160), M == 0 ? 0 : 1);
  wgmma_rs_n48<104, 0>(acc, a0, a1, a2, a3, D(208), M == 0 ? 0 : 1);
}
DEVI constexpr int a_off(int P, int i) { return -4 * (64 * ((i & 4) ? 15 - P : P) + (i & 1) * 32 - (i & 2) * 2); }
template <int P> DEVI void load_pair(uint32_t (&a)[8], uint32_t ab) {
#pragma unroll
  for (int i = 0; i < 8; i++) a[i] = lds32(ab + a_off(P, i));
}
template <int P> DEVI void mma_pair(float (&acc)[128], uint32_t (&a)[8], uint32_t db) {
  wg_fence();
  conv_step<P>(acc, a[0], a[1], a[2], a[3], db);
  conv_step<15 - P>(acc, a[4], a[5], a[6], a[7], db);
  wg_commit();
}

template <int I0, int I1> DEVI void conv_reduce(uint32_t sb, int c, int ht, int chan, int bar, int nthr) {
  const uint32_t a0 = sb + o_h(c) + ht * 16, a2 = sb + o_u(c) + ht * 16, a3 = sb + o_x(c) + ht * 16;
  uint4* yp = (uint4*)(g_y2T + (size_t)chan * 2048) + ht;
#pragma unroll
  for (int i = I0; i < I1; i++) {
    uint4 p, q, r, s;
    if (i == I0) bar_sync(bar, nthr);
    lds128(a0 + i * 2048, p.x, p.y, p.z, p.w); lds128(a0 + 4160 + i * 2048, q.x, q.y, q.z, q.w);
    lds128(a2 + i * 2048, r.x, r.y, r.z, r.w); lds128(a3 + i * 2048, s.x, s.y, s.z, s.w);
    auto sum = [](uint32_t a, uint32_t b, uint32_t c, uint32_t d) { return hadd2(hadd2(hadd2(a, b), 0u), hadd2(c, d)) ^ 0x80008000u; };
    yp[i * 128] = make_uint4(sum(p.x, q.x, r.x, s.x), sum(p.y, q.y, r.y, s.y), sum(p.z, q.z, r.z, s.z), sum(p.w, q.w, r.w, s.w));
  }
}

template <int ODD, int PART> DEVI void pack_qkv(const float (&acc)[120], uint32_t (&Q)[10][2], uint32_t (&K)[10][2], uint32_t (&V)[10][2]) {
#pragma unroll
  for (int f = 0; f < 10; f++) {
    const bool tail = ODD ? (f < 2) : (f >= 8);
    const int fm = ODD ? f - 2 : f, ft = ODD ? f : f - 8;
    const int nq = tail ? 24 + ft : fm, nk = tail ? 26 + ft : 8 + fm, nv = tail ? 28 + ft : 16 + fm;
    if (PART == 0) { K[f][1] = pack_bf16(acc[4 * nk + 2], acc[4 * nk + 3]); V[f][1] = pack_bf16(acc[4 * nv + 2], acc[4 * nv + 3]); }
    if (PART == 1) { V[f][0] = pack_bf16(acc[4 * nv], acc[4 * nv + 1]); K[f][0] = pack_bf16(acc[4 * nk], acc[4 * nk + 1]); }
    if (PART == 2) { Q[f][0] = pack_bf16(acc[4 * nq], acc[4 * nq + 1]); Q[f][1] = pack_bf16(acc[4 * nq + 2], acc[4 * nq + 3]); }
  }
}
DEVI int pair_of(int c) {
  const int lo = 32 + 8 * c, hi = c - 4 + ((max(c - 29, 0) * 37) >> 8);
  int p; asm("{\n.reg .pred q;\nsetp.lt.s32 q, %1, 4;\nselp.b32 %0, %2, %3, q;\n}" : "=r"(p) : "r"(c), "r"(lo), "r"(hi));
  return p;
}
DEVI uint32_t make_ctx() {
  int b; asm volatile("mov.u32 %0, %%ctaid.x;" : "=r"(b));
  b += clk() & threadIdx.y;
  const int p = pair_of(b >> 1);
  const int j = b < 128 ? 8 * (p & 7) + (p >> 3) : 64;
  const int q = (j * 205) >> 10, r = j - 5 * q, i = j - q, co = (i * 79) >> 10;
  const int cp = r == 4 ? 4 : co, tb = r == 4 ? q : i - 13 * co;
  return ((2 * p + (b & 1)) & 255) | tb << 8 | (2 * cp + (b & 1)) << 12 | (b >> 7) << 16;
}
#define CTX() asm volatile("" : "+r"(ctx)); CTXU()
#define CTXU() int tid; asm volatile("mov.u32 %0, %%tid.x;" : "=r"(tid)); \
  const int lane = tid & 31, vb = ctx & 255, hg = (ctx >> 4) & 7, rt = ctx & 15, par = (ctx >> 3) & 1, mt = ctx & 7, rank = ctx & 1, \
  tb = (ctx >> 8) & 15, cb = (ctx >> 12) & 15; const bool main_cta = ctx < 65536; \
  (void)tid; (void)lane; (void)vb; (void)hg; (void)rt; (void)par; (void)mt; (void)rank; (void)tb; (void)cb; (void)main_cta
#define CTXW() CTX(); const int wg = warp >> 2, w = warp & 3, g = lane >> 2, t = lane & 3; const bool lead = (tid & 127) == 0; \
  (void)wg; (void)w; (void)g; (void)t; (void)lead

__global__ void __cluster_dims__(2, 1, 1) __launch_bounds__(512, 1)
fused_kernel(const uint16_t* __restrict__ xq, const uint16_t* __restrict__ wqkv, const uint16_t* __restrict__ gate_w, const __grid_constant__ Maps M, const uint16_t* __restrict__ shift_k, const uint16_t* __restrict__ ssm_k, const uint16_t* __restrict__ ssm_D,
             uint16_t* __restrict__ outp) {
  extern __shared__ __align__(1024) uint8_t smem_raw[];
  const uint32_t sb = smem_u32(smem_raw);
  const uint32_t t0 = clk();
  auto get_epoch = [&]() { mbar_wait(sb + B_EP, 0); return lds32(sb + O_EPOCH); };

  auto p1_load_x = [&](int ks, int p, int rank) {
    tma3(sb + o_px(ks), &M.x_par, ks * 32, (p >> 2) & 1, (p & 3) * 256 + rank * 128, sb + B_FULL + 8 * (ks & 7));
  };
  auto p1_load_w = [&](int ks, int p, int rank) {
    const uint32_t st = sb + o_pw(ks), fb = sb + B_FULL + 8 * (ks & 7);
    tma3_mc(st + rank * 6144, &M.w_main, (p >> 3) * 80 + 2 * (p & 8), ks * 32 + rank * 16, 0, fb);
    tma3_mc(st + 12288 + rank * 1536, &M.w_tail, (p >> 3) * 80 + 8 * (~p & 8), ks * 32 + rank * 16, 0, fb);
  };
  auto cta_pair = [&]() { return pair_of(blockIdx.x >> 1); };

  if (threadIdx.x < 32) {
    const unsigned b = blockIdx.x, l = threadIdx.x;
    const uint16_t* pfp = l < 16 ? xq + (16 * b + l) * 640 : wqkv + (15 * b + l - 16) * 64;
    if ((l | b >> 7 << 5) < 31) pf_l2(pfp);
  }
  const int warp = __shfl_sync(~0u, threadIdx.x >> 5, 0);
  if ((warp & 14) == 8) {
    if (elect_one()) {
#pragma unroll
      for (int s = 0; s < 8; s++) mbar_init(sb + O_BAR - 512 + 64 * warp + 8 * s, 5 * warp - 39);
      asm volatile("fence.mbarrier_init.release.cluster;" ::: "memory");
    }
    __syncwarp();
  }
  asm volatile("barrier.cluster.arrive.relaxed.aligned;" ::: "memory");
  if (warp == 8 && blockIdx.x < 128) {
    const int p = cta_pair(), rank = blockIdx.x & 1;
    if (elect_one()) { mbar_expect_tx(sb + B_FULL, 16384 + WST); p1_load_x(0, p, rank); }
    __syncwarp();
    asm volatile("barrier.cluster.wait.aligned;" ::: "memory");
    if (elect_one()) { p1_load_w(0, p, rank); PT(100); }
    __syncwarp();
  } else if (warp != 15) {
    asm volatile("barrier.cluster.wait.aligned;" ::: "memory");
    spin_until(t0, HOLD);
  }
  auto init_rest = [&]() {
    if (warp >= 11 && elect_one()) {
#pragma unroll
      for (int s = 0; s < 12; s++) mbar_init(sb + O_BAR + 128 - 11 * 96 + 96 * warp + 8 * s, warp == 14 ? 2 : 1);
      asm volatile("fence.mbarrier_init.release.cluster;" ::: "memory");
    }
    __syncwarp();
    bar_sync(0, blockIdx.x < 128 ? 224 : 512);
  };
  uint32_t ctx = 0;

  if (warp < 8) {
    reg_inc<RC>();
    ctx = make_ctx();
    if (blockIdx.x >= 128) bar_sync(0, 512);
    else {
      {
        uint32_t Q[10][2], K[10][2], V[10][2];
        {
          {
            float acc[120];
            CTXW();
            const int odd = (cta_pair() >> 3) & 1;
            const uint32_t rsb = mapa(sb, (blockIdx.x & 1) ^ 1);
            {
              const uint32_t aa = sb + (warp * 16 + (lane & 15)) * 128 + (((lane >> 4) ^ (lane & 7)) << 4);
              constexpr int NA = DEFER > 3 ? DEFER : 3;
              uint32_t a[NA][8];
              auto load_a = [&](int ks) {
                uint32_t(&r)[8] = a[ks % NA];
                mbar_wait(sb + B_FULL + 8 * (ks & 7), (ks >> 3) & 1);
                PTP(lead && (wg || !(ks & 3)), wg ? 60 + ks : 80 + (ks >> 2));
                ldsm4(r[0], r[1], r[2], r[3], (aa ^ ((ks & 1) * 64)) + o_px(ks)); ldsm4(r[4], r[5], r[6], r[7], (aa ^ ((ks & 1) * 64 + 32)) + o_px(ks));
              };
              auto mma_q = [&](int ks, int h) {
                uint32_t(&r)[8] = a[ks % NA];
                wgmma_rs_n64<0, 1>(acc, r[4 * h], r[4 * h + 1], r[4 * h + 2], r[4 * h + 3], mkdesc(SB + o_pw(ks) + h * 6144, 2048, 1024, 1), ks | h);
              };
              auto mma_step = [&](int ks, int h) {
                uint32_t(&r)[8] = a[ks % NA];
                wg_fence();
                wgmma_rs_n128<32, 1>(acc, r[4 * h], r[4 * h + 1], r[4 * h + 2], r[4 * h + 3], mkdesc(SB + o_pw(ks) + h * 6144 + 2048, 2048, 1024, 1), ks | h);
                if (ks < 20 - DEFER) mma_q(ks, h);
                wgmma_rs_n48<96, 1>(acc, r[4 * h], r[4 * h + 1], r[4 * h + 2], r[4 * h + 3], mkdesc(SB + o_pw(ks) + 12288 + h * 1536, 512, 256, 3), ks | h);
                wg_commit();
              };
              if (lead) PT(1 + wg);
              load_a(0);
#pragma unroll
              for (int ks = 0; ks < 20; ks++) {
                if (LEAD && ks == 20 - LEAD) bar_sync_p(wg == 0, NB_LEAD, 256);
                mma_step(ks, 0);
                if (ks < 19 && ks >= NLATE) load_a(ks + 1);
                mma_step(ks, 1);
                if (ks < NLATE) load_a(ks + 1);
                if (ks >= 1 && ks <= 16) {
                  wg_wait<2>();
                  mbar_arrive2_p(lead, sb + B_EMPTY + 8 * ((ks - 1) & 7), rsb + B_EMPTY + 8 * ((ks - 1) & 7));
                } else if (ks < 19 && ks + 2 - NA >= 16) wg_wait<2>();
              }
              if (LEAD) bar_arrive_p(wg, NB_LEAD, 256);
              if (DEFER) {
                wg_fence();
#pragma unroll
                for (int i = 40 - 2 * DEFER; i < 40; i++) mma_q(i >> 1, i & 1);
                wg_commit();
              }
              mbar_wait(sb + B_S15, 1);
              wg_wait<1>();
              mbar_arrive_p(tid == 0, sb + B_P1E);
              if (!DEFER) wg_wait<0>();
              fence_regs<32, 120>(acc);
              PTPL(lead, 158 + wg);
            }
            if (odd) pack_qkv<1, 0>(acc, Q, K, V); else pack_qkv<0, 0>(acc, Q, K, V);
            if (warp == 7 && (blockIdx.x & 1)) {
              uint4* hp = g_halo + vb * 160 + lane;
              st_relaxed(hp, K[0][1], K[1][1], K[3][1], K[4][1]); st_relaxed(hp + 32, K[5][1], K[6][1], K[8][1], K[9][1]);
              st_relaxed(hp + 64, K[2][1], K[7][1], V[0][1], V[1][1]);
              st_relaxed(hp + 96, V[2][1], V[3][1], V[4][1], V[5][1]); st_relaxed(hp + 128, V[6][1], V[7][1], V[8][1], V[9][1]);
            }
            const uint32_t ho = sb + O_HALO + warp * 2560 + lane * 16;
            stsm4(ho, K[0][1], K[1][1], K[3][1], K[4][1]); stsm4(ho + 512, K[5][1], K[6][1], K[8][1], K[9][1]);
            stsm4(ho + 1024, K[2][1], K[7][1], V[0][1], V[1][1]);
            stsm4(ho + 1536, V[2][1], V[3][1], V[4][1], V[5][1]); stsm4(ho + 2048, V[6][1], V[7][1], V[8][1], V[9][1]);
            if (warp == 7) {
              if (!(blockIdx.x & 1)) {
                fence_async_smem();
                __syncwarp();
                if (elect_one())
                  asm volatile("cp.async.bulk.shared::cluster.shared::cta.mbarrier::complete_tx::bytes [%0], [%1], 2560, [%2];"
                               ::"r"(mapa(sb + O_HIN, 1)), "r"(sb + O_HALO + 7 * 2560), "r"(mapa(sb + B_HX0, 1)) : "memory");
              }
              __syncwarp();
            } else {
              __syncwarp();
              if (lane == 0) mbar_arrive(sb + B_HX + 8 + 8 * warp);
            }
            if (odd) pack_qkv<1, 1>(acc, Q, K, V); else pack_qkv<0, 1>(acc, Q, K, V);
            wg_wait<0>();
            fence_regs<0, 32>(acc);
            PTPL(lead, 50 + wg);
            mbar_arrive2_p(lead, sb + B_S19, rsb + B_S19);
            if (odd) pack_qkv<1, 2>(acc, Q, K, V); else pack_qkv<0, 2>(acc, Q, K, V);
#pragma unroll
            for (int f = 0; f < 10; f++) V[f][0] = movm(V[f][0]);
            if (lead) PT(52 + wg);
            if (wg) mbar_wait(sb + B_P1E, 0);
          }
          CTXW();
          uint32_t z = threadIdx.y;
          const bool gt0 = 2 * t > g, gt1 = 2 * t + 1 > g;
          const uint32_t pmask = (gt0 ? 0xFFFFu : 0u) | (gt1 ? 0xFFFF0000u : 0u);
          const uint32_t hs = warp ? O_HALO + (warp - 1) * 2560 : O_HIN, ha = sb + hs + lane * 16;
          const uint32_t va = sb + ((lane & 8) ? O_HALO + warp * 2560 : hs) + 1280 + (lane >> 4) * 128 + (lane & 7) * 16;
          uint32_t Qh[4][2], Kh[10], Vh[10];
          float c1[4][4] = {}, c2[4][4] = {}, c0[4][4] = {}, l[8][2], m[8], x[8];
#pragma unroll
          for (int j = 0; j < 4; j++) {
            const int fa = (j >> 1) * 5 + (j & 1) * 3, fh = (j >> 1) * 5 + 2;
            const bool mine = (j & 1) ? (t >= 2) : (t < 2);
            Qh[j][0] = mine ? Q[fh][0] : 0u; Qh[j][1] = mine ? Q[fh][1] : 0u;
            mma16(c1[j], Q[fa][0], Q[fa][1], Q[fa + 1][0], Q[fa + 1][1], K[fa][0], K[fa + 1][0]);
            mma16(c2[j], Q[fa][0], Q[fa][1], Q[fa + 1][0], Q[fa + 1][1], K[fa][1], K[fa + 1][1]);
            mma8(c1[j], Qh[j][0], Qh[j][1], K[fh][0]);
            mma8(c2[j], Qh[j][0], Qh[j][1], K[fh][1]);
          }
          if (lead) PT(54 + wg);
          mbar_wait(sb + (warp ? B_HX + 8 * warp : B_HX0), 0);
          if (lead) PT(56 + wg);
          ldsm4(Kh[0], Kh[1], Kh[3], Kh[4], ha); ldsm4(Kh[5], Kh[6], Kh[8], Kh[9], ha + 512);
          asm volatile("ldmatrix.sync.aligned.m8n8.x2.shared.b16 {%0,%1}, [%2];" : "=r"(Kh[2]), "=r"(Kh[7]) : "r"(ha + 1024) : "memory");
          auto load_v = [&]() {
#pragma unroll
            for (int i = 0; i < 5; i++) ldsm4t(Vh[2 * i], V[2 * i][1], Vh[2 * i + 1], V[2 * i + 1][1], va + i * 256);
          };
          load_v();
          const float C = 0.22360679774997896f * 1.4426950408889634f;
          auto max1 = [&](int r) { m[r] = fmaxf(l[r][0], l[r][1]); x[r] = __shfl_xor_sync(~0u, m[r], 1); };
          auto max2 = [&](int r) { m[r] = fmaxf(m[r], x[r]); x[r] = __shfl_xor_sync(~0u, m[r], 2); };
          auto exps = [&](int r) { const float mc = fmaxf(m[r], x[r]) * C; l[r][0] = ex2(fmaf(l[r][0], C, -mc)); l[r][1] = ex2(fmaf(l[r][1], C, -mc)); };
#pragma unroll
          for (int j = 0; j < 4; j++) { l[4 + j][0] = gt0 ? c1[j][2] : c2[j][2]; l[4 + j][1] = gt1 ? c1[j][3] : c2[j][3]; max1(4 + j); }
#pragma unroll
          for (int j = 0; j < 4; j++) {
            const int fa = (j >> 1) * 5 + (j & 1) * 3, fh = (j >> 1) * 5 + 2;
            mma16(c0[j], Q[fa][0], Q[fa][1], Q[fa + 1][0], Q[fa + 1][1], Kh[fa], Kh[fa + 1]);
            mma8(c0[j], Qh[j][0], Qh[j][1], Kh[fh]);
            max2(4 + j);
          }
          const bool have_halo = warp > 0 || mt > 0;
#pragma unroll
          for (int j = 0; j < 4; j++) {
            if (!have_halo) c0[j][0] = c0[j][1] = -INFINITY;
            l[j][0] = gt0 ? c0[j][0] : c1[j][0]; l[j][1] = gt1 ? c0[j][1] : c1[j][1];
            max1(j);
          }
          exps(4); exps(5);
#pragma unroll
          for (int j = 0; j < 4; j++) max2(j);
          exps(6); exps(7);
#pragma unroll
          for (int j = 0; j < 4; j++) exps(j);
          float o[12][4] = {}, sm[4][4] = {};
#pragma unroll
          for (int j = 0; j < 4; j++) {
            const int fa = (j >> 1) * 5 + (j & 1) * 3, fh = (j >> 1) * 5 + 2;
            const uint32_t pl = pack_bf16(l[j][0], l[j][1]), pu = pack_bf16(l[4 + j][0], l[4 + j][1]);
            const uint32_t p0 = pl & pmask, p2 = pl & ~pmask, p3 = pu & pmask, p5 = pu & ~pmask, z0 = z << (2 * j + 1), z1 = z << (2 * j + 2);
            mma8(sm[j], pl, pu, 0x3F803F80u);
#pragma unroll
            for (int q = 0; q < 3; q++) {
              const int f = q < 2 ? fa + q : fh;
              mma8(o[3 * j + q], p2, p3, V[f][0]);
              mma16(o[3 * j + q], p0, z0, z1, p5, Vh[f], V[f][1]);
            }
            asm volatile("rcp.approx.ftz.f32 %0, %0;" : "+f"(sm[j][0]));
            asm volatile("rcp.approx.ftz.f32 %0, %0;" : "+f"(sm[j][2]));
          }
#pragma unroll
          for (int i = 6; i < 12; i++) z &= __float_as_uint(o[i][0]);
          bar_arrive_p(wg == 0, NB_HALO + z, 256);
          uint32_t O[10][2];
#pragma unroll
          for (int j = 0; j < 4; j++) {
            const int fa = (j >> 1) * 5 + (j & 1) * 3, fh = (j >> 1) * 5 + 2;
            const float r0 = sm[j][0], r1 = sm[j][2];
#pragma unroll
            for (int q = 0; q < 3; q++) {
              const int f = q < 2 ? fa + q : fh;
              const float* e = o[3 * j + q];
              const uint32_t o0 = pack_bf16(e[0] * r0, e[1] * r0), o1 = pack_bf16(e[2] * r1, e[3] * r1);
              if (q < 2 || !(j & 1)) { O[f][0] = o0; O[f][1] = o1; }
              else { O[f][0] = t >= 2 ? o0 : O[f][0]; O[f][1] = t >= 2 ? o1 : O[f][1]; }
            }
          }
          mbar_wait(sb + B_GD, 0);
          const uint32_t oa = sb + O_OST + wg * 2 * STG + (w * 16 + (lane & 15)) * 160 + (lane >> 4) * 16;
#pragma unroll
          for (int i = 0; i < 5; i++) stsm4(oa + i * 32, O[2 * i][0], O[2 * i][1], O[2 * i + 1][0], O[2 * i + 1][1]);
        }
      }
      {
        CTXW();
        fence_async_smem();
        bar_arrive(wg ? NB_LEAD : NB_ATT, 160);
        if (lead) PT(58 + wg);
        const uint32_t abase = sb + (g & 1) * 4160 + 4 * (1023 - 4 - 8 * w - (g >> 1) + t);
        float acc[128];
        uint32_t a0[8], a1[8], a2[8], a3[8];
#pragma unroll 1
        for (int c = wg ^ 1; c < 5; c += 2) {
          const uint32_t ab = abase + o_h(c);
          const uint32_t db = __shfl_sync(~0u, ((SB + o_u(c) + UZ - 16) >> 4) | 0x10000u, 0);
          mbar_wait(sb + B_U + 8 * c, 0);
          load_pair<0>(a0, ab); load_pair<1>(a1, ab); load_pair<2>(a2, ab);
          if (lead) PT(85 + c);
          bar_sync(c ? NB_TOK + wg : NB_HALO, 256);
          fence_regs(acc);
          mma_pair<0>(acc, a0, db);
          load_pair<3>(a3, ab);
          mma_pair<1>(acc, a1, db); wg_wait<1>();  load_pair<4>(a0, ab);
          if (lead) PT(90 + c);
          mma_pair<2>(acc, a2, db); wg_wait<1>();  load_pair<5>(a1, ab);
          mma_pair<3>(acc, a3, db); wg_wait<1>();  load_pair<6>(a2, ab);
          mma_pair<4>(acc, a0, db); wg_wait<1>();  load_pair<7>(a3, ab);
          mma_pair<5>(acc, a1, db);
          mma_pair<6>(acc, a2, db);
          bar_arrive_p(c < 4, NB_TOK + (wg ^ 1), 256);
          mma_pair<7>(acc, a3, db);
          bar_arrive_p(c == 4, NB_TOK, 256);
          wg_wait<0>();
          fence_regs(acc);
          PTPL(lead, 95 + c);
          bar_sync(NB_RFREE + wg, 256);
          const uint32_t pb = sb + (w < 2 ? o_h(c) + w * 4160 : w == 2 ? o_u(c) : o_x(c)) + lane * 16;
          if (lane < 2 * w) sts128(pb, 0, 0, 0, 0);
#pragma unroll
          for (int q = 0; q < 8; q++) {
            uint32_t p[4];
#pragma unroll
            for (int i = 0; i < 4; i++) {
              const int nu = 4 * q + i;
              p[i] = pack_bf16(acc[4 * nu], acc[4 * nu + 1]);
              if (nu > 0) p[i] = hadd2(p[i], pack_bf16(acc[4 * nu - 2], acc[4 * nu - 1]));
            }
            stsm4t(pb + w * 32 + q * 512, p[0], p[1], p[2], p[3]);
            if (q == 3) bar_arrive_p(c == 4, NB_RFULL + 1, 256);
          }
          if (c < 4) bar_arrive(NB_RFULL + wg, 256);
          if (lead) PT(140 + c);
        }
        if (wg) {
          const int yb = (lds32(sb + O_EPOCH) & 1) * 640;
              conv_reduce<1, 2>(sb, 4, tid - 128, yb + 512 + ((vb & 0x61) | (vb & 6) << 2 | (vb >> 2 & 6)), 14, 128);
          bar_arrive(12, 256);
          PTPL(lead, 45);
        }
      }
    }
    if (warp < 4) {
      CTXW();
      const uint32_t rsb = mapa(sb, (blockIdx.x & 1) ^ 1);
      const uint32_t ba = sb + O_BT + ((lane >> 4) * 8 + (lane & 7)) * 128 + (((2 * w + ((lane >> 3) & 1)) ^ ((lane & 1) << 2 | (lane >> 1 & 3))) << 4);
      mbar_wait(sb + B_P3F, 0);
      if (lead) PT(145);
      bar_sync_p(blockIdx.x < 128, NB_TOK, 256);
      float acc[80];
#pragma unroll
      for (int ks = 0; ks < 10; ks++) {
        PTP(lead, 146 + ks);
        const uint64_t da = mkdesc(SB + o_p3(ks), 1024, 1024, 1), db = mkdesc(SB + o_p3(ks) + 8192, 16, 1024, 1);
        wg_fence();
#pragma unroll
        for (int j = 0; j < 4; j++) wgmma_ss_n160<0, 1, 0>(acc, da + j * 128, db + j * 2, j | ks);
        wg_commit();
        if (ks < 9) mbar_wait(sb + B_P3F + 8 * (ks + 1), 0);
        if (ks >= 1 && ks <= 4) { wg_wait<1>(); mbar_arrive2_p(lead, sb + B_P3E + 8 * ks, rsb + B_P3E + 8 * ks); }
      }
      wg_wait<0>();
      fence_regs(acc);
      PTPL(lead, 156);
#pragma unroll
      for (int i = 0; i < 10; i++) {
        stsm4t(ba + i * 2048, pack_bf16(acc[8 * i], acc[8 * i + 1]), pack_bf16(acc[8 * i + 2], acc[8 * i + 3]),
               pack_bf16(acc[8 * i + 4], acc[8 * i + 5]), pack_bf16(acc[8 * i + 6], acc[8 * i + 7]));
        if (i & 1) bar_arrive(1 + (i >> 1), 256);
      }
      if (lead) PT(157);
    }
  } else if (warp < 12) {
    reg_dec<RH>();
    const int hw = warp - 8;
    init_rest();
    ctx = __shfl_sync(~0u, make_ctx(), 0);
    const int yrow = (ctx & 0x61) | (ctx & 6) << 2 | (ctx >> 2 & 6);
    if (ctx < 65536) {
      CTXU();
      const int pr = hw >> 1, hh = hw & 1, tk = vb & 63, odd = (lane >> 2) & 1;
      const uint32_t sel0 = odd ? 0x7632 : 0x5410, sel1 = odd ? 0x5410 : 0x7632;
      const uint32_t in = sb + o_kin(pr), fb = sb + B_KF + 8 * pr, out = sb + O_Y + pr * 8192;
      const uint32_t oa = out + (2 * lane + odd) * 64 + (((3 - 2 * hh) ^ (lane & 3)) << 4), ia = in + hh * 2048 + lane * 4;
      auto fetch = [&](int c) {
        wait_until(t0, KT0 + c * KTD + ((((vb * 37) & 63) * KPH) >> 6));
        if (elect_one()) {
          const int kb = 2 * c + (vb >> 6);
          mbar_expect_tx(fb, 69 * 128);
          tma2(in, &M.k_ld, kb * 64, 32 * tk - 4, fb);
          tma2(in + 36 * 128, &M.v_ld, kb * 64, 32 * tk - 1, fb);
          PT(20 + c);
        }
        __syncwarp();
      };
      if (hh == 0) fetch(pr);
      const uint4* skp = (const uint4*)shift_k + (2 * pr + (vb >> 6)) * 32 + lane;
      uint4 sk = __ldg(skp), sk1 = __ldg(skp + 128), sk2 = __ldg(skp + (pr ? 0 : 256));
#pragma unroll 1
      for (int c = pr; c < 5; c += 2) {
        {
          mbar_wait(fb, (c >> 1) & 1);
          if (hh == 0 && lane == 0) PT(25 + c);
          uint32_t k[20], o[17];
#pragma unroll
          for (int i = 0; i < 20; i++) { k[i] = lds32(ia + i * 128); if (i >= 3) o[i - 3] = lds32(ia + (33 + i) * 128); }
          fence_async_smem();
          bar_sync(12 + pr, 64);
          if (hh == 0) {
            if (c < 3) fetch(c + 2);
            else if (lane == 0) mbar_arrive(sb + B_KVD + 8 * (c - 3));
          }
          const uint32_t w0 = prmt(sk.x, sk.z, 0x5410), w1 = prmt(sk.x, sk.z, 0x7632), w2 = prmt(sk.y, sk.w, 0x5410), w3 = prmt(sk.y, sk.w, 0x7632);
#pragma unroll
          for (int i = 0; i < 17; i++) o[i] = hmul2(hfma2(k[i + 3], w0, hfma2(k[i + 2], w1, hfma2(k[i + 1], w2, hmul2(k[i], w3)))), o[i]);
          sk = sk1; sk1 = sk2;
#pragma unroll
          for (int i = 0; i < 4; i++) {
            const int e = 8 * (i >> 1) + (i & 1);
            const uint32_t a = (oa ^ ((i >> 1) * 16)) + (i & 1) * 4096;
            sts128(a, prmt(o[7 + e], o[6 + e], sel0), prmt(o[5 + e], o[4 + e], sel0), prmt(o[3 + e], o[2 + e], sel0), prmt(o[1 + e], o[e], sel0));
            sts128(a ^ 64, prmt(o[7 + e], o[6 + e], sel1), prmt(o[5 + e], o[4 + e], sel1), prmt(o[3 + e], o[2 + e], sel1), prmt(o[1 + e], o[e], sel1));
          }
          bar_sync(12 + pr, 64);
        }
        if (hh) {
          fence_async_smem();
          if (elect_one()) {
            const int kb = 2 * c + (vb >> 6);
            tma3_store(&M.kv_st, 0, kb * 64, 63 - tk, out);
            tma3_store(&M.kv_st, 0, 640 + kb * 64, 63 - tk, out + 4096);
            bulk_commit(); bulk_wait_all();
            mbar_arrive(sb + (c == 4 ? B_KVD + 16 : B_KVS + 4 * (c & 2)));
            PTL(35 + c);
          }
          __syncwarp();
        }
      }
    }
    CTXU();
    const int g = lane >> 2, t = lane & 3, row = 8 * hw + g;
    const uint32_t go = (tb * 160 + row) * 80 + cb * 8 + t;
    const int yb = __shfl_sync(~0u, get_epoch() & 1, 0) * 640;
    uint4 T[10];
    if (hw == 2) {
      if (main_cta) { mbar_wait(sb + B_LAST, 0); mbar_wait(sb + B_S15, 1); }
      if (elect_one()) {
        mbar_expect_tx(sb + B_Q, 20480);
#pragma unroll
        for (int h = 0; h < 2; h++) tma2(sb + O_QT + h * 10240, &M.q_ld, cb * 64 + 32 * h, tb * 160, sb + B_Q);
      }
      __syncwarp();
    }
    mbar_wait(sb + B_Q, 0);
#pragma unroll
    for (int i = 0; i < 10; i++) lds128(sb + O_QT + (i & 1) * 10240 + (i >> 1) * 2048 + row * 64 + t * 16, T[i].x, T[i].y, T[i].z, T[i].w);
    fence_async_smem();
    bar_sync(12 + (hw >> 1), 64);
    if (!(tid & 63)) mbar_arrive(sb + B_QD);
    if (tid == 256) PTL(40);
    if (main_cta) {
      bar_arrive(NB_RFREE, 256);
      bar_arrive(NB_RFREE + 1, 256);
      auto red = [&](int c) {
        const int wg = (c & 1) ^ 1;
        conv_reduce<0, 2>(sb, c, tid - 256, yb + 128 * c + yrow, NB_RFULL + wg, 256);
        if (hw == 3 && elect_one()) flag_add(CNT_Y(4 * c + (vb >> 5)), 1);
        if (tid == 256) PTL(41 + c);
        if (c < 3) bar_arrive(NB_RFREE + wg, 256);
        if (c == 2) {
          bar_sync(NB_HELP, 128);
          if (tid == 256) { mbar_arrive(sb + B_P3E); mbar_arrive_remote(sb + B_P3E, rank ^ 1); }
        }
      };
      if (hw == 3) {
        mbar_wait(sb + B_KVD + 16, 0);
        if (elect_one()) { flag_release(CNT_KV(4 + (vb >> 6))); PTL(32); }
        __syncwarp();
      }
#pragma unroll 1
      for (int c = 0; c < 4; c++) red(c);
    }
    uint32_t G[5];
    mbar_wait(sb + B_G, 0);
#pragma unroll
    for (int q = 0; q < 5; q++) { uint16_t v; asm volatile("ld.shared.u16 %0, [%1];" : "=h"(v) : "r"(sb + O_GT + (32 * q + row) * 2)); G[q] = prmt(v, 0, 0x1010); }
#pragma unroll
    for (int i = 0; i < 10; i++) { const uint32_t c = G[i >> 1] ^ 0x80008000u; T[i] = make_uint4(hmul2(T[i].x, c), hmul2(T[i].y, c), hmul2(T[i].z, c), hmul2(T[i].w, c)); }
    if (main_cta) {
      conv_reduce<0, 1>(sb, 4, tid - 256, yb + 512 + yrow, NB_RFULL + 1, 256);
      if (hw == 3 && elect_one()) { flag_add(CNT_Y(16 + (vb >> 5)), 1); PTL(19); }
      bar_sync(12, 256);
    }
#pragma unroll
    for (int h = 0; h < 2; h++) {
      mbar_wait_wd(sb + B_Y + 8 * h, 0, t0);
      if (tid == 256) PTL(46);
      const uint32_t ya = sb + O_Y + h * 10240 + lane * 64 + ((hw ^ ((lane >> 1) & 3)) << 4);
      uint4 y[5];
      auto empty = [](uint32_t m) { return (m & 0xFFFFu) == 0 || m < 0x10000u; };
      uint32_t m = ~0u;
#pragma unroll
      for (int q = 4; q >= 0; q--) {
        ldsm4t(y[q].x, y[q].y, y[q].z, y[q].w, ya + q * 2048);
        m = __vimin3_u16x2(__vimin3_u16x2(m, y[q].x, y[q].y), y[q].z, y[q].w);
        if (q == 4 && tb == 12) m = ~0u;
      }
      if (__any_sync(~0u, empty(m))) {
        const uint4* gp = (const uint4*)g_y2T + (yb + cb * 64 + 32 * h + lane) * 256 + tb * 20 + hw;
#pragma unroll
        for (int q = 0; q < 5; q++) lds128(ya + q * 2048, y[q].x, y[q].y, y[q].z, y[q].w);
        if (tb == 12) y[4] = make_uint4(~0u, ~0u, ~0u, ~0u);
        for (;;) {
          bool bad[5], any = false;
#pragma unroll
          for (int q = 0; q < 5; q++) { bad[q] = empty(__vimin3_u16x2(__vminu2(y[q].x, y[q].y), y[q].z, y[q].w)); any |= bad[q]; }
          if (!__any_sync(~0u, any)) break;
#pragma unroll
          for (int q = 0; q < 5; q++)
            if (bad[q]) asm volatile("ld.relaxed.gpu.global.v4.b32 {%0,%1,%2,%3}, [%4];" : "=r"(y[q].x), "=r"(y[q].y), "=r"(y[q].z), "=r"(y[q].w) : "l"(gp + 4 * q) : "memory");
        }
#pragma unroll
        for (int q = 0; q < 5; q++) sts128(ya + q * 2048, y[q].x, y[q].y, y[q].z, y[q].w);
        __syncwarp();
#pragma unroll
        for (int q = 0; q < 5; q++) ldsm4t(y[q].x, y[q].y, y[q].z, y[q].w, ya + q * 2048);
        PTL(49);
      }
#pragma unroll
      for (int q = 0; q < 5; q++) {
        uint4& r = T[2 * q + h];
        r = make_uint4(hmul2(r.x, y[q].x), hmul2(r.y, y[q].y), hmul2(r.z, y[q].z), hmul2(r.w, y[q].w));
      }
    }
    const uint32_t so = sb + O_BT + row * 128 + ((t ^ ((g & 1) << 2 | g >> 1)) << 4);
    if (tid == 256) PTL(47);
#pragma unroll
    for (int q = 0; q < 5; q++) {
      const uint32_t c = hfma2(G[q], 0xBF80BF80u, 0x3F803F80u);
      bar_sync(1 + q, 256);
      if (q == 4) mbar_arrive_p(tid == 256, sb + B_DONE);
#pragma unroll
      for (int h = 0; h < 2; h++) {
        uint4 u;
        lds128((so ^ (h * 64)) + q * 4096, u.x, u.y, u.z, u.w);
        const uint4& r = T[2 * q + h];
        if (q < 4 || tb < 12)
          asm volatile("st.global.v4.b32 [%0], {%1,%2,%3,%4};" ::"l"((uint4*)outp + go + q * 2560 + h * 4), "r"(hfma2(u.x, c, r.x)), "r"(hfma2(u.y, c, r.y)), "r"(hfma2(u.z, c, r.z)), "r"(hfma2(u.w, c, r.w)) : "memory");
      }
    }
  } else {
    reg_dec<RP>();
    uint4 gwv = make_uint4(0, 0, 0, 0);
    if (warp == 15) {
      const int p = cta_pair(), rank = blockIdx.x & 1;
      asm volatile("barrier.cluster.wait.aligned;" ::: "memory");
      if (blockIdx.x >= 128) bar_sync(0, 512);
      else {
#pragma unroll 1
        for (int ks = 1;; ks += 2) {
          mbar_wait(sb + B_EMPTY + 8 * (ks & 7), ((ks >> 3) & 1) ^ 1);
          spin_until(t0, PT1 + (ks - 1) * PTD);
          if (elect_one()) { mbar_expect_tx(sb + B_FULL + 8 * (ks & 7), WST); p1_load_w(ks, p, rank); PT(100 + ks); }
          if (ks == 19) break;
          const int kn = ks + 1;
          mbar_wait(sb + B_EMPTY + 8 * (kn & 7), ((kn >> 3) & 1) ^ 1);
          spin_until(t0, PT1 + ks * PTD - PTE);
          if (elect_one()) { mbar_expect_tx(sb + B_FULL + 8 * (kn & 7), 16384 + WST); p1_load_x(kn, p, rank); p1_load_w(kn, p, rank); PT(100 + kn); }
        }
        if (elect_one()) mbar_arrive(sb + B_LAST);
#pragma unroll 1
        for (int i = 0; i < 2; i++) {
          mbar_wait(sb + B_KVS + 8 * i, 0);
          if (elect_one()) { flag_release(CNT_KV(2 * i + (p >> 5))); PTL(30 + i); }
          __syncwarp();
        }
        mbar_wait(sb + B_S19, 0);
      }
    } else {
      if (threadIdx.x < 384 + 80) gwv = __ldg((const uint4*)gate_w + threadIdx.x - 384);
      init_rest();
    }
    ctx = __shfl_sync(~0u, make_ctx(), 0);
    CTXU();
    if (warp == 12) {
        unsigned epoch = 0;
      if (lane == 0) epoch = *(volatile unsigned*)(g_launch + 32 * vb) + 1;
      if (main_cta) { sts128(sb + O_GW + lane * 16, gwv.x, gwv.y, gwv.z, gwv.w); bar_arrive(NB_G, 96); }
      if (lane == 0) {
        if ((sb & 0xFFFFFF) != SB) __trap();
        sts32(sb + O_EPOCH, epoch);
        mbar_arrive(sb + B_EP);
#pragma unroll 1
        for (int i = 5; i < 11; i++) asm volatile("prefetch.tensormap [%0];" ::"l"(&M.x_par + i) : "memory");
      }
      if (main_cta && rank) {
#pragma unroll
        for (int f = 0; f < 5; f++) st_relaxed(g_halo + vb * 160 + lane + 32 * f, ~0u, ~0u, ~0u, ~0u);
      }
      __syncwarp();
      if (elect_one()) flag_release(g_launch + 32 * vb);
      __syncwarp();
      if (main_cta) {
        uint4 h0 = make_uint4(0, 0, 0, 0);
        if (lane < 5) {
          h0 = __ldg((const uint4*)(ssm_k + (size_t)(128 * lane + vb) * 2048));
          h0.x = prmt(pack_bf16(bf_lo(h0.x) + bf_lo(__ldg(ssm_D + 128 * lane + vb)), 0.f), h0.x, 0x7610);
        }
        epoch = __shfl_sync(~0u, epoch, 0);
        const int ze = lane & 7;
        const uint32_t za = sb + (lane < 8 ? o_u(ze) + UZ : lane < 24 ? o_h(ze) + (lane >> 4) * 4160 + 4096 : o_u(ze) + 512);
        const uint16_t* hp = ssm_k + (size_t)vb * 2048 + 8;
        const uint16_t* up = g_kvT + (size_t)vb * 2048;
        const unsigned* fp = CNT_KV(vb >> 6);
        sts128(sb + O_Y - 512 + lane * 16, 0, 0, 0, 0);
        mbar_wait(sb + B_LAST, 0);
        mbar_wait(sb + B_S13, 1);
#pragma unroll
        for (int c = 0; c < 5; c++) {
          if (c == 0 || c == 3) {
            mbar_wait(sb + B_KVD + (c ? 8 : 0), 0);
#pragma unroll
            for (int e = c; e < (c ? 5 : 3); e++) sts128(sb + o_u(e) + lane * 16, 0, 0, 0, 0);
            if (ze >= c && ze < (c ? 5 : 3)) sts128(za, h0.x, h0.y, h0.z, h0.w);
            fence_async_smem();
            __syncwarp();
            if (elect_one()) {
#pragma unroll
              for (int e = c; e < (c ? 5 : 3); e++) {
                mbar_expect_tx(sb + B_U + 8 * e, 3 * 4096 - 16);
                if (c || e == 0) bulk_load(sb + o_u(e) + UZ + 16, hp + 128 * 2048 * e, 4080, sb + B_U + 8 * e);
              }
            }
          }
          if (!(c & 1)) { flag_wait(fp + 32 * c, 64 * epoch); __syncwarp(); }
          if (elect_one()) {
            bulk_load(sb + o_h(c), up + 128 * 2048 * c, 4096, sb + B_U + 8 * c);
            bulk_load(sb + o_h(c) + 4160, up + (640 + 128 * c) * 2048, 4096, sb + B_U + 8 * c);
            if (c == 1) {
#pragma unroll
              for (int e = 1; e < 3; e++) bulk_load(sb + o_u(e) + UZ + 16, hp + 128 * 2048 * e, 4080, sb + B_U + 8 * e);
            }
            PTL(10 + c);
          }
        }
        mbar_wait(sb + B_LAST, 1);
        if (elect_one()) {
#pragma unroll 1
          for (int i = 0; i < 40; i++) bulk_store(g_y2T + (size_t)((~epoch & 1) * 640 + 5 * vb) * 2048 + i * 256, sb + O_Y - 512, 512);
          bulk_commit(); bulk_wait_read();
          PTL(33);
        }
      }
    } else if (warp != 15) {
        const int r = warp - 13;
      if (main_cta) {
        if (rank && lane == 0) mbar_expect_tx(sb + B_HX0, 1280);
        const int t = lane & 3, grow = hg * 16 + (lane & 15);
        const uint32_t ga = sb + grow * 128 + (((4 * r + (lane >> 4)) ^ (lane & 7)) << 4);
        const uint32_t gp = sb + O_GW + 64 * r + 4 * t;
        float s0 = 0.f, s1 = 0.f;
        if (tid < 384 + 80) sts128(sb + O_GW + (tid - 384) * 16, gwv.x, gwv.y, gwv.z, gwv.w);
        bar_sync(NB_G, 96);
#pragma unroll 1
        for (int ks = 0; ks < 20; ks += 2) {
          uint32_t x[8], gw[4];
#pragma unroll
          for (int i = 0; i < 4; i++) gw[i] = lds32(gp + ks * 64 + i * 16);
          mbar_wait_wd(sb + B_FULL + 8 * (ks & 7), (ks >> 3) & 1, t0);
          if (r == 0 && lane == 0) PT(120 + ks);
          ldsm4(x[0], x[1], x[2], x[3], ga + o_px(ks)); ldsm4(x[4], x[5], x[6], x[7], (ga ^ 32) + o_px(ks));
#pragma unroll
          for (int i = 0; i < 8; i++) x[i] = hmul2(x[i], gw[i >> 1]);
          if (lane < 2) mbar_arrive(sb + B_EMPTY + 8 * (ks & 7) + 8 * lane + (x[0] & x[7] & threadIdx.y));
#pragma unroll
          for (int i = 0; i < 8; i += 4) {
            s0 += (bf_lo(x[i]) + bf_hi(x[i])) + (bf_lo(x[i + 2]) + bf_hi(x[i + 2]));
            s1 += (bf_lo(x[i + 1]) + bf_hi(x[i + 1])) + (bf_lo(x[i + 3]) + bf_hi(x[i + 3]));
          }
        }
        s0 += __shfl_xor_sync(~0u, s0, 1); s1 += __shfl_xor_sync(~0u, s1, 1);
        s0 += __shfl_xor_sync(~0u, s0, 2); s1 += __shfl_xor_sync(~0u, s1, 2);
        if (t < 2) sts32(sb + O_GP + r * 64 + (8 * t + (lane >> 2)) * 4, __float_as_uint(t ? s1 : s0));
        if (lane == 0) mbar_arrive(sb + B_GD);
        if (r == 0) bar_arrive(NB_G, 64);
        if (!rank) {
          uint4 d[3];
          if (mt > 0) {
            const uint4* hp = g_halo + (vb - 1) * 160 + r * 64 + lane;
            mbar_wait_wd(sb + B_EP, 0, t0);
            flag_wait_wd(g_launch + 32 * (vb - 1), lds32(sb + O_EPOCH), t0);
            mbar_wait_wd(sb + B_HX + 56, 0, t0);
            for (;;) {
              bool ok = true;
#pragma unroll
              for (int f = 0; f < 3; f++) {
                asm volatile("ld.relaxed.gpu.global.v4.b32 {%0,%1,%2,%3}, [%4];" : "=r"(d[f].x), "=r"(d[f].y), "=r"(d[f].z), "=r"(d[f].w) : "l"(hp + 32 * f) : "memory");
              }
#pragma unroll
              for (int f = 0; f < 3; f++) ok = ok && max(max(d[f].x, d[f].y), max(d[f].z, d[f].w)) != ~0u;
              if (__all_sync(~0u, ok)) break;
              if (clk() - t0 > 0x70000000u) __trap();
            }
          } else {
#pragma unroll
            for (int f = 0; f < 3; f++) d[f] = make_uint4(0, 0, 0, 0);
          }
#pragma unroll
          for (int f = 0; f < 3; f++) stsm4(sb + O_HIN + r * 1024 + f * 512 + lane * 16, d[f].x, d[f].y, d[f].z, d[f].w);
          __syncwarp();
          if (lane == 0) { mbar_arrive(sb + B_HX0); PTL(15 + r); }
        }
        if (r == 1) {
          bar_sync(NB_G, 64);
          if (lane < 16) {
            const uint32_t pa = sb + O_GP + lane * 4;
            const float z = __uint_as_float(lds32(pa)) + __uint_as_float(lds32(pa + 64));
            g_gate[2 * (mt * 128 + hg * 16 + lane) + par] = (uint16_t)pack_bf16(__fdividef(1.f, 1.f + __expf(-bf_lo(pack_bf16(z, 0.f)))), 0.f);
          }
          __syncwarp();
          if (elect_one()) flag_release(CNT_O(rt));
        }
      }
      mbar_wait_wd(sb + B_EP, 0, t0);
      const unsigned epoch = lds32(sb + O_EPOCH);
      if (main_cta) mbar_wait_wd(sb + B_P3E, 0, t0);
      flag_wait_wd(CNT_Y(2 * cb + r), 32 * epoch, t0);
      __syncwarp();
      if (elect_one()) {
        mbar_expect_tx(sb + B_Y + 8 * r, 10240);
        tma3(sb + O_Y + r * 10240, &M.y_ld, 0, (epoch & 1) * 640 + cb * 64 + 32 * r, tb * 5, sb + B_Y + 8 * r);
        PTL(17 + r);
      }
      __syncwarp();
      mbar_wait_wd(sb + B_DONE, 0, t0);
    } else {
      const unsigned epoch = get_epoch();
      if (main_cta) {
        bar_sync(NB_LEAD, 160);
        if (elect_one()) tma3_store(&M.o_st, hg * 80, par, mt * 128 + 64, sb + O_OST + 2 * STG);
        bar_sync(NB_ATT, 160);
        if (elect_one()) {
          tma3_store(&M.o_st, hg * 80, par, mt * 128, sb + O_OST);
          bulk_commit(); bulk_wait_all();
          flag_release(CNT_O(rt));
          mbar_arrive(sb + B_LAST);
          PTL(3);
        }
        __syncwarp();
      }
      mbar_wait(sb + B_QD, 0);
#pragma unroll 1
      for (int ks = 0; ks < 5; ks++)
        if (elect_one()) tma2(sb + o_p3(ks), &M.wo, cb * 64, ks * 64, sb + B_P3F + 8 * ks);
      if (lane < 4) flag_wait(CNT_O(8 * (lane & 1) + min(7, (80 * tb + 79 * (lane >> 1)) >> 7)), 16 * epoch);
      __syncwarp();
      if (elect_one()) {
        PTL(4);
        mbar_arrive_remote(sb + B_P3R, rank ^ 1);
        mbar_expect_tx(sb + B_G, 320);
        bulk_load(sb + O_GT, g_gate + tb * 160, 320, sb + B_G);
      }
      mbar_wait(sb + B_P3R, 0);
      auto load_o = [&](int ks) {
        tma2_mc(sb + o_p3(ks) + 8192 + rank * 10240, &M.o_ld, ks * 64, tb * 160 + rank * 80, sb + B_P3F + 8 * ks);
        mbar_expect_tx(sb + B_P3F + 8 * ks, P3S);
      };
      auto load_wo = [&](int ks) { tma2(sb + o_p3(ks), &M.wo, cb * 64, ks * 64, sb + B_P3F + 8 * ks); };
#pragma unroll 1
      for (int ks = 0; ks < 5; ks++)
        if (elect_one()) load_o(ks);
#pragma unroll
      for (int ks = 5; ks < 10; ks++) {
        if (ks > 5 || main_cta) mbar_wait(sb + B_P3E + 8 * (ks - 5), 0);
        if (elect_one()) {
          load_o(ks); load_wo(ks);
          PTL(ks);
        }
      }
    }
  }
}

typedef CUresult (*PFN_enc)(CUtensorMap*, CUtensorMapDataType, cuuint32_t, void*, const cuuint64_t*, const cuuint64_t*, const cuuint32_t*,
                            const cuuint32_t*, CUtensorMapInterleave, CUtensorMapSwizzle, CUtensorMapL2promotion, CUtensorMapFloatOOBfill);
static void enc(PFN_enc f, CUtensorMap* m, const void* base, int rank, const cuuint64_t* dims, const cuuint64_t* strides, const cuuint32_t* box,
                CUtensorMapSwizzle sw) {
  const cuuint32_t es[5] = {1, 1, 1, 1, 1};
  f(m, CU_TENSOR_MAP_DATA_TYPE_BFLOAT16, rank, (void*)base, dims, strides, box, es, CU_TENSOR_MAP_INTERLEAVE_NONE, sw,
    CU_TENSOR_MAP_L2_PROMOTION_NONE, CU_TENSOR_MAP_FLOAT_OOB_FILL_NONE);
}

extern "C" void kernel_launch(void* const* d_in, const int* in_sizes, int n_in, void* d_out, int out_size) {
  (void)in_sizes; (void)n_in; (void)out_size;
  static PFN_enc f = nullptr;
  static void *kvT, *y2T, *o;
  if (!f) {
    void* p = nullptr;
    cudaDriverEntryPointQueryResult q;
    cudaGetDriverEntryPoint("cuTensorMapEncodeTiled", &p, cudaEnableDefault, &q);
    f = (PFN_enc)p;
    cudaGetSymbolAddress(&kvT, g_kvT); cudaGetSymbolAddress(&y2T, g_y2T); cudaGetSymbolAddress(&o, g_o);
    cudaFuncSetAttribute(fused_kernel, cudaFuncAttributeMaxDynamicSharedMemorySize, SMEM_BYTES);
  }
  Maps M;
  const CUtensorMapSwizzle S0 = CU_TENSOR_MAP_SWIZZLE_NONE, S32 = CU_TENSOR_MAP_SWIZZLE_32B, S64 = CU_TENSOR_MAP_SWIZZLE_64B, S128 = CU_TENSOR_MAP_SWIZZLE_128B;
  const cuuint64_t dpar[3] = {640, 2, 1024}, spar[2] = {1280, 2560};
  const cuuint64_t dw[3] = {640, 640, 3}, sw[2] = {3840, 1280};
  const cuuint64_t dnat[2] = {640, 2048}, snat[1] = {1280};
  const cuuint64_t dT2[3] = {32, 1280, 64}, sT[2] = {4096, 64};
  const cuuint64_t dwo[2] = {640, 640};
  { const cuuint32_t bx[3] = {64, 1, 128}; enc(f, &M.x_par, d_in[0], 3, dpar, spar, bx, S128); }
  { const cuuint32_t bx[3] = {64, 16, 3}; enc(f, &M.w_main, d_in[7], 3, dw, sw, bx, S128); }
  { const cuuint32_t bx[3] = {16, 16, 3}; enc(f, &M.w_tail, d_in[7], 3, dw, sw, bx, S32); }
  { const cuuint32_t bx[3] = {80, 1, 64}; enc(f, &M.o_st, o, 3, dpar, spar, bx, S0); }
  { const cuuint32_t bx[3] = {32, 64, 1}; enc(f, &M.kv_st, kvT, 3, dT2, sT, bx, S64); }
  { const cuuint32_t bx[3] = {32, 32, 5}; enc(f, &M.y_ld, y2T, 3, dT2, sT, bx, S64); }
  { const cuuint32_t bx[2] = {64, 36}; enc(f, &M.k_ld, d_in[1], 2, dnat, snat, bx, S0); }
  { const cuuint32_t bx[2] = {64, 33}; enc(f, &M.v_ld, d_in[2], 2, dnat, snat, bx, S0); }
  { const cuuint32_t bx[2] = {32, 160}; enc(f, &M.q_ld, d_in[0], 2, dnat, snat, bx, S0); }
  { const cuuint32_t bx[2] = {64, 64}; enc(f, &M.wo, d_in[8], 2, dwo, snat, bx, S128); }
  { const cuuint32_t bx[2] = {64, 80}; enc(f, &M.o_ld, o, 2, dnat, snat, bx, S128); }
  fused_kernel<<<130, 512, SMEM_BYTES, cudaStreamPerThread>>>((const uint16_t*)d_in[0], (const uint16_t*)d_in[7], (const uint16_t*)d_in[9], M, (const uint16_t*)d_in[3], (const uint16_t*)d_in[4], (const uint16_t*)d_in[5],
                                                              (uint16_t*)d_out);
}
```

```cpp
#include <cuda_runtime.h>
#include <cuda_bf16.h>
#include <cuda.h>
#include <stdint.h>

#define DEVI __device__ __forceinline__
#define PT1 300
#define PTD 460
#define PTE 150
#define DEFER 4
#define KPH KTD
#define NLATE 4
#define KT0 1500
#define KTD 1000
#define RC 192
#define RH 96
#define RP 32
#define HOLD 750
#define LEAD 3

DEVI uint32_t smem_u32(const void* p) { return (uint32_t)__cvta_generic_to_shared(p); }
DEVI void wg_fence() { asm volatile("wgmma.fence.sync.aligned;" ::: "memory"); }
DEVI void wg_commit() { asm volatile("wgmma.commit_group.sync.aligned;" ::: "memory"); }
template <int N> DEVI void wg_wait() { asm volatile("wgmma.wait_group.sync.aligned %0;" ::"n"(N) : "memory"); }
template <int A = 0, int B = -1, int S> DEVI void fence_regs(float (&d)[S]) {
#pragma unroll
  for (int i = A; i < (B < 0 ? S : B); i++) asm volatile("" : "+f"(d[i])::"memory");
}
DEVI uint64_t mkdesc(uint32_t addr, uint32_t lbo, uint32_t sbo, int swz) {
  return (uint64_t)((addr & 0x3FFFF) >> 4) | ((uint64_t)(lbo >> 4) << 16) | ((uint64_t)(sbo >> 4) << 32) | ((uint64_t)swz << 62);
}
DEVI void mbar_init(uint32_t bar, uint32_t cnt) { asm volatile("mbarrier.init.shared::cta.b64 [%0], %1;" ::"r"(bar), "r"(cnt) : "memory"); }
DEVI void mbar_expect_tx(uint32_t bar, uint32_t bytes) { asm volatile("mbarrier.arrive.expect_tx.shared::cta.b64 _, [%0], %1;" ::"r"(bar), "r"(bytes) : "memory"); }
DEVI void mbar_arrive(uint32_t bar) { asm volatile("mbarrier.arrive.shared::cta.b64 _, [%0];" ::"r"(bar) : "memory"); }
DEVI void mbar_wait(uint32_t bar, uint32_t parity) {
  asm volatile("{\n.reg .pred p;\nLAB_WAIT:\nmbarrier.try_wait.parity.shared::cta.b64 p, [%0], %1;\n@!p bra LAB_WAIT;\n}" ::"r"(bar), "r"(parity) : "memory");
}
DEVI void mbar_wait_wd(uint32_t bar, uint32_t parity, uint32_t t0) {
  asm volatile("{\n.reg .pred p;\n.reg .u32 c;\nLAB_WAIT:\nmbarrier.try_wait.parity.shared::cta.b64 p, [%0], %1;\n@p bra DONE;\nmov.u32 c, %%clock;\nsub.u32 c, c, %2;\nsetp.lt.u32 p, c, 0x70000000;\n@p bra LAB_WAIT;\ntrap;\nDONE:\n}" ::"r"(bar), "r"(parity), "r"(t0) : "memory");
}
DEVI void flag_wait(const unsigned* p, unsigned target) {
  asm volatile("{\n.reg .pred p;\n.reg .s32 v;\nLAB_WAIT:\nld.relaxed.gpu.global.u32 v, [%0];\nsub.s32 v, v, %1;\nsetp.lt.s32 p, v, 0;\n@p bra LAB_WAIT;\n}" ::"l"(p), "r"(target) : "memory");
}
DEVI void flag_wait_wd(const unsigned* p, unsigned target, uint32_t t0) {
  asm volatile("{\n.reg .pred p;\n.reg .s32 v;\nLAB_WAIT:\nld.relaxed.gpu.global.u32 v, [%0];\nsub.s32 v, v, %1;\nsetp.ge.s32 p, v, 0;\n@p bra DONE;\nmov.u32 v, %%clock;\nsub.s32 v, v, %2;\nsetp.lt.u32 p, v, 0x70000000;\n@p bra LAB_WAIT;\ntrap;\nDONE:\n}" ::"l"(p), "r"(target), "r"(t0) : "memory");
}
DEVI void flag_add(unsigned* p, unsigned v) { asm volatile("red.relaxed.gpu.global.add.u32 [%0], %1;" ::"l"(p), "r"(v) : "memory"); }
DEVI void flag_release(unsigned* p) { asm volatile("fence.proxy.async;\nred.relaxed.gpu.global.add.u32 [%0], 1;" ::"l"(p) : "memory"); }
DEVI void fence_async_smem() { asm volatile("fence.proxy.async.shared::cta;" ::: "memory"); }
DEVI bool elect_one() { uint32_t p; asm volatile("{\n.reg .pred P;\nelect.sync _|P, 0xffffffff;\nselp.u32 %0, 1, 0, P;\n}" : "=r"(p)); return p; }
DEVI void bar_sync(int id, int n) { asm volatile("bar.sync %0, %1;" ::"r"(id), "r"(n) : "memory"); }
DEVI void bar_arrive(int id, int n) { asm volatile("bar.arrive %0, %1;" ::"r"(id), "r"(n) : "memory"); }
DEVI void tma2(uint32_t dst, const CUtensorMap* m, int c0, int c1, uint32_t bar) {
  asm volatile("cp.async.bulk.tensor.2d.shared::cluster.global.mbarrier::complete_tx::bytes [%0], [%1, {%3, %4}], [%2];" ::"r"(dst), "l"(m), "r"(bar), "r"(c0), "r"(c1) : "memory");
}
DEVI void tma3(uint32_t dst, const CUtensorMap* m, int c0, int c1, int c2, uint32_t bar) {
  asm volatile("cp.async.bulk.tensor.3d.shared::cluster.global.mbarrier::complete_tx::bytes [%0], [%1, {%3, %4, %5}], [%2];" ::"r"(dst), "l"(m), "r"(bar), "r"(c0), "r"(c1), "r"(c2) : "memory");
}
DEVI void tma3_mc(uint32_t dst, const CUtensorMap* m, int c0, int c1, int c2, uint32_t bar) {
  asm volatile("cp.async.bulk.tensor.3d.shared::cluster.global.mbarrier::complete_tx::bytes.multicast::cluster [%0], [%1, {%3, %4, %5}], [%2], %6;" ::"r"(dst), "l"(m), "r"(bar), "r"(c0), "r"(c1), "r"(c2), "h"((uint16_t)3) : "memory");
}
DEVI void tma2_mc(uint32_t dst, const CUtensorMap* m, int c0, int c1, uint32_t bar) {
  asm volatile("cp.async.bulk.tensor.2d.shared::cluster.global.mbarrier::complete_tx::bytes.multicast::cluster [%0], [%1, {%3, %4}], [%2], %5;" ::"r"(dst), "l"(m), "r"(bar), "r"(c0), "r"(c1), "h"((uint16_t)3) : "memory");
}
DEVI void mbar_arrive_remote(uint32_t bar, uint32_t cta) {
  asm volatile("{\n.reg .b32 ra;\nmapa.shared::cluster.u32 ra, %0, %1;\nmbarrier.arrive.shared::cluster.b64 _, [ra];\n}" ::"r"(bar), "r"(cta) : "memory");
}
DEVI void tma3_store(const CUtensorMap* m, int c0, int c1, int c2, uint32_t src) {
  asm volatile("cp.async.bulk.tensor.3d.global.shared::cta.bulk_group [%0, {%2, %3, %4}], [%1];" ::"l"(m), "r"(src), "r"(c0), "r"(c1), "r"(c2) : "memory");
}
DEVI void bulk_load(uint32_t dst, const void* src, uint32_t bytes, uint32_t bar) {
  asm volatile("cp.async.bulk.shared::cluster.global.mbarrier::complete_tx::bytes [%0], [%1], %2, [%3];" ::"r"(dst), "l"(src), "r"(bytes), "r"(bar) : "memory");
}
DEVI void bulk_store(void* dst, uint32_t src, uint32_t bytes) {
  asm volatile("cp.async.bulk.global.shared::cta.bulk_group [%0], [%1], %2;" ::"l"(dst), "r"(src), "r"(bytes) : "memory");
}
DEVI void pf_l2(const void* p) { asm volatile("prefetch.global.L2 [%0];" ::"l"(p)); }
template <int OFF> DEVI uint32_t ldg_v(const void* p) { uint32_t v; asm volatile("ld.volatile.global.b32 %0, [%1 + %2];" : "=r"(v) : "l"(p), "n"(OFF)); return v; }
DEVI void bulk_commit() { asm volatile("cp.async.bulk.commit_group;" ::: "memory"); }
DEVI void bulk_wait_all() { asm volatile("cp.async.bulk.wait_group 0;" ::: "memory"); }
DEVI void bulk_wait_read() { asm volatile("cp.async.bulk.wait_group.read 0;" ::: "memory"); }
template <int R> DEVI void reg_inc() { asm volatile("setmaxnreg.inc.sync.aligned.u32 %0;" ::"n"(R)); }
template <int R> DEVI void reg_dec() { asm volatile("setmaxnreg.dec.sync.aligned.u32 %0;" ::"n"(R)); }
DEVI uint32_t prmt(uint32_t a, uint32_t b, uint32_t s) { uint32_t r; asm("prmt.b32 %0,%1,%2,%3;" : "=r"(r) : "r"(a), "r"(b), "r"(s)); return r; }
DEVI uint32_t lds32(uint32_t a) { uint32_t r; asm volatile("ld.shared.b32 %0,[%1];" : "=r"(r) : "r"(a)); return r; }
DEVI void sts32(uint32_t a, uint32_t x) { asm volatile("st.shared.b32 [%0],%1;" ::"r"(a), "r"(x) : "memory"); }
DEVI void sts128(uint32_t a, uint32_t x, uint32_t y, uint32_t z, uint32_t w) { asm volatile("st.shared.v4.b32 [%0],{%1,%2,%3,%4};" ::"r"(a), "r"(x), "r"(y), "r"(z), "r"(w) : "memory"); }
DEVI void sts128v(uint32_t a, uint32_t x, uint32_t y, uint32_t z, uint32_t w) { asm volatile("st.volatile.shared.v4.b32 [%0],{%1,%2,%3,%4};" ::"r"(a), "r"(x), "r"(y), "r"(z), "r"(w) : "memory"); }
DEVI void lds128(uint32_t a, uint32_t& x, uint32_t& y, uint32_t& z, uint32_t& w) { asm volatile("ld.shared.v4.b32 {%0,%1,%2,%3},[%4];" : "=r"(x), "=r"(y), "=r"(z), "=r"(w) : "r"(a) : "memory"); }
DEVI void ldsm4(uint32_t& r0, uint32_t& r1, uint32_t& r2, uint32_t& r3, uint32_t addr) {
  asm volatile("ldmatrix.sync.aligned.m8n8.x4.shared.b16 {%0,%1,%2,%3}, [%4];" : "=r"(r0), "=r"(r1), "=r"(r2), "=r"(r3) : "r"(addr) : "memory");
}
DEVI void ldsm4t(uint32_t& r0, uint32_t& r1, uint32_t& r2, uint32_t& r3, uint32_t addr) {
  asm volatile("ldmatrix.sync.aligned.m8n8.x4.trans.shared.b16 {%0,%1,%2,%3}, [%4];" : "=r"(r0), "=r"(r1), "=r"(r2), "=r"(r3) : "r"(addr) : "memory");
}
DEVI void stsm4(uint32_t addr, uint32_t r0, uint32_t r1, uint32_t r2, uint32_t r3) {
  asm volatile("stmatrix.sync.aligned.m8n8.x4.shared.b16 [%0], {%1,%2,%3,%4};" ::"r"(addr), "r"(r0), "r"(r1), "r"(r2), "r"(r3) : "memory");
}
DEVI void stsm4t(uint32_t addr, uint32_t r0, uint32_t r1, uint32_t r2, uint32_t r3) {
  asm volatile("stmatrix.sync.aligned.m8n8.x4.trans.shared.b16 [%0], {%1,%2,%3,%4};" ::"r"(addr), "r"(r0), "r"(r1), "r"(r2), "r"(r3) : "memory");
}
DEVI uint32_t movm(uint32_t a) { uint32_t r; asm volatile("movmatrix.sync.aligned.m8n8.trans.b16 %0, %1;" : "=r"(r) : "r"(a)); return r; }
DEVI uint32_t pack_bf16(float lo, float hi) { uint32_t r; asm("cvt.rn.bf16x2.f32 %0, %1, %2;" : "=r"(r) : "f"(hi), "f"(lo)); return r; }
DEVI uint32_t hmul2(uint32_t a, uint32_t b) { uint32_t r; asm("mul.rn.bf16x2 %0,%1,%2;" : "=r"(r) : "r"(a), "r"(b)); return r; }
DEVI uint32_t hadd2(uint32_t a, uint32_t b) { uint32_t r; asm("add.rn.bf16x2 %0,%1,%2;" : "=r"(r) : "r"(a), "r"(b)); return r; }
DEVI float bf_lo(uint32_t a) { return __uint_as_float(prmt(a, 0, 0x1044)); }
DEVI float bf_hi(uint32_t a) { return __uint_as_float(a & 0xFFFF0000u); }
DEVI void mma16(float (&c)[4], uint32_t a0, uint32_t a1, uint32_t a2, uint32_t a3, uint32_t b0, uint32_t b1) {
  asm volatile("mma.sync.aligned.m16n8k16.row.col.f32.bf16.bf16.f32 {%0,%1,%2,%3},{%4,%5,%6,%7},{%8,%9},{%0,%1,%2,%3};"
      : "+f"(c[0]), "+f"(c[1]), "+f"(c[2]), "+f"(c[3]) : "r"(a0), "r"(a1), "r"(a2), "r"(a3), "r"(b0), "r"(b1));
}
DEVI void mma8(float (&c)[4], uint32_t a0, uint32_t a1, uint32_t b0) {
  asm volatile("mma.sync.aligned.m16n8k8.row.col.f32.bf16.bf16.f32 {%0,%1,%2,%3},{%4,%5},{%6},{%0,%1,%2,%3};"
      : "+f"(c[0]), "+f"(c[1]), "+f"(c[2]), "+f"(c[3]) : "r"(a0), "r"(a1), "r"(b0));
}
DEVI float ex2(float x) { float r; asm volatile("ex2.approx.ftz.f32 %0, %1;" : "=f"(r) : "f"(x)); return r; }

DEVI uint32_t clk() { uint32_t c; asm volatile("mov.u32 %0, %%clock;" : "=r"(c)); return c; }
DEVI void wait_until(uint32_t t0, int dt) { while ((int)(clk() - t0) < dt) __nanosleep(40); }
DEVI void spin_until(uint32_t t0, int dt) { while ((int)(clk() - t0) < dt) {} }
DEVI uint32_t hfma2(uint32_t a, uint32_t b, uint32_t c) { uint32_t r; asm("fma.rn.bf16x2 %0,%1,%2,%3;" : "=r"(r) : "r"(a), "r"(b), "r"(c)); return r; }
DEVI void bar_sync_p(int on, int id, int n) { asm volatile("{\n.reg .pred p;\nsetp.ne.b32 p, %0, 0;\n@p bar.sync %1, %2;\n}" ::"r"(on), "r"(id), "r"(n) : "memory"); }
DEVI void bar_arrive_p(int on, int id, int n) { asm volatile("{\n.reg .pred p;\nsetp.ne.b32 p, %0, 0;\n@p bar.arrive %1, %2;\n}" ::"r"(on), "r"(id), "r"(n) : "memory"); }
DEVI void mbar_arrive_p(int on, uint32_t bar) { asm volatile("{\n.reg .pred p;\nsetp.ne.b32 p, %1, 0;\n@p mbarrier.arrive.shared::cta.b64 _, [%0];\n}" ::"r"(bar), "r"(on) : "memory"); }
DEVI void mbar_arrive2_p(int on, uint32_t bar, uint32_t rbar) {
  asm volatile("{\n.reg .pred p;\nsetp.ne.b32 p, %2, 0;\n@p mbarrier.arrive.shared::cta.b64 _, [%0];\n@p mbarrier.arrive.shared::cluster.b64 _, [%1];\n}" ::"r"(bar), "r"(rbar), "r"(on) : "memory");
}
DEVI void st_relaxed(uint4* p, uint32_t x, uint32_t y, uint32_t z, uint32_t w) {
  asm volatile("st.relaxed.gpu.global.v4.b32 [%0], {%1,%2,%3,%4};" ::"l"(p), "r"(x), "r"(y), "r"(z), "r"(w) : "memory");
}
DEVI uint32_t mapa(uint32_t a, uint32_t cta) { uint32_t r; asm("mapa.shared::cluster.u32 %0, %1, %2;" : "=r"(r) : "r"(a), "r"(cta)); return r; }
DEVI void st_async128(uint32_t a, uint32_t x, uint32_t y, uint32_t z, uint32_t w, uint32_t bar) {
  asm volatile("st.async.weak.shared::cluster.mbarrier::complete_tx::bytes.v4.b32 [%0], {%1,%2,%3,%4}, [%5];" ::"r"(a), "r"(x), "r"(y), "r"(z), "r"(w), "r"(bar) : "memory");
}

template<int OFF, int TB, int S> __device__ __forceinline__ void wgmma_rs_n128(float (&d)[S], uint32_t a0, uint32_t a1, uint32_t a2, uint32_t a3, uint64_t db, int sd) {
  asm volatile("{\n.reg .pred p;\nsetp.ne.b32 p, %69, 0;\n"
    "wgmma.mma_async.sync.aligned.m64n128k16.f32.bf16.bf16 {%0, %1, %2, %3, %4, %5, %6, %7, %8, %9, %10, %11, %12, %13, %14, %15, %16, %17, %18, %19, %20, %21, %22, %23, %24, %25, %26, %27, %28, %29, %30, %31, %32, %33, %34, %35, %36, %37, %38, %39, %40, %41, %42, %43, %44, %45, %46, %47, %48, %49, %50, %51, %52, %53, %54, %55, %56, %57, %58, %59, %60, %61, %62, %63}, {%64, %65, %66, %67}, %68, p, 1, 1, %70;\n}\n"
    : "+f"(d[OFF+0]), "+f"(d[OFF+1]), "+f"(d[OFF+2]), "+f"(d[OFF+3]), "+f"(d[OFF+4]), "+f"(d[OFF+5]), "+f"(d[OFF+6]), "+f"(d[OFF+7]), "+f"(d[OFF+8]), "+f"(d[OFF+9]), "+f"(d[OFF+10]), "+f"(d[OFF+11]), "+f"(d[OFF+12]), "+f"(d[OFF+13]), "+f"(d[OFF+14]), "+f"(d[OFF+15]), "+f"(d[OFF+16]), "+f"(d[OFF+17]), "+f"(d[OFF+18]), "+f"(d[OFF+19]), "+f"(d[OFF+20]), "+f"(d[OFF+21]), "+f"(d[OFF+22]), "+f"(d[OFF+23]), "+f"(d[OFF+24]), "+f"(d[OFF+25]), "+f"(d[OFF+26]), "+f"(d[OFF+27]), "+f"(d[OFF+28]), "+f"(d[OFF+29]), "+f"(d[OFF+30]), "+f"(d[OFF+31]), "+f"(d[OFF+32]), "+f"(d[OFF+33]), "+f"(d[OFF+34]), "+f"(d[OFF+35]), "+f"(d[OFF+36]), "+f"(d[OFF+37]), "+f"(d[OFF+38]), "+f"(d[OFF+39]), "+f"(d[OFF+40]), "+f"(d[OFF+41]), "+f"(d[OFF+42]), "+f"(d[OFF+43]), "+f"(d[OFF+44]), "+f"(d[OFF+45]), "+f"(d[OFF+46]), "+f"(d[OFF+47]), "+f"(d[OFF+48]), "+f"(d[OFF+49]), "+f"(d[OFF+50]), "+f"(d[OFF+51]), "+f"(d[OFF+52]), "+f"(d[OFF+53]), "+f"(d[OFF+54]), "+f"(d[OFF+55]), "+f"(d[OFF+56]), "+f"(d[OFF+57]), "+f"(d[OFF+58]), "+f"(d[OFF+59]), "+f"(d[OFF+60]), "+f"(d[OFF+61]), "+f"(d[OFF+62]), "+f"(d[OFF+63]) : "r"(a0), "r"(a1), "r"(a2), "r"(a3), "l"(db), "r"(sd), "n"(TB));
}
template<int OFF, int TB, int S> __device__ __forceinline__ void wgmma_rs_n64(float (&d)[S], uint32_t a0, uint32_t a1, uint32_t a2, uint32_t a3, uint64_t db, int sd) {
  asm volatile("{\n.reg .pred p;\nsetp.ne.b32 p, %37, 0;\n"
    "wgmma.mma_async.sync.aligned.m64n64k16.f32.bf16.bf16 {%0, %1, %2, %3, %4, %5, %6, %7, %8, %9, %10, %11, %12, %13, %14, %15, %16, %17, %18, %19, %20, %21, %22, %23, %24, %25, %26, %27, %28, %29, %30, %31}, {%32, %33, %34, %35}, %36, p, 1, 1, %38;\n}\n"
    : "+f"(d[OFF+0]), "+f"(d[OFF+1]), "+f"(d[OFF+2]), "+f"(d[OFF+3]), "+f"(d[OFF+4]), "+f"(d[OFF+5]), "+f"(d[OFF+6]), "+f"(d[OFF+7]), "+f"(d[OFF+8]), "+f"(d[OFF+9]), "+f"(d[OFF+10]), "+f"(d[OFF+11]), "+f"(d[OFF+12]), "+f"(d[OFF+13]), "+f"(d[OFF+14]), "+f"(d[OFF+15]), "+f"(d[OFF+16]), "+f"(d[OFF+17]), "+f"(d[OFF+18]), "+f"(d[OFF+19]), "+f"(d[OFF+20]), "+f"(d[OFF+21]), "+f"(d[OFF+22]), "+f"(d[OFF+23]), "+f"(d[OFF+24]), "+f"(d[OFF+25]), "+f"(d[OFF+26]), "+f"(d[OFF+27]), "+f"(d[OFF+28]), "+f"(d[OFF+29]), "+f"(d[OFF+30]), "+f"(d[OFF+31]) : "r"(a0), "r"(a1), "r"(a2), "r"(a3), "l"(db), "r"(sd), "n"(TB));
}
template<int OFF, int TB, int S> __device__ __forceinline__ void wgmma_rs_n48(float (&d)[S], uint32_t a0, uint32_t a1, uint32_t a2, uint32_t a3, uint64_t db, int sd) {
  asm volatile("{\n.reg .pred p;\nsetp.ne.b32 p, %29, 0;\n"
    "wgmma.mma_async.sync.aligned.m64n48k16.f32.bf16.bf16 {%0, %1, %2, %3, %4, %5, %6, %7, %8, %9, %10, %11, %12, %13, %14, %15, %16, %17, %18, %19, %20, %21, %22, %23}, {%24, %25, %26, %27}, %28, p, 1, 1, %30;\n}\n"
    : "+f"(d[OFF+0]), "+f"(d[OFF+1]), "+f"(d[OFF+2]), "+f"(d[OFF+3]), "+f"(d[OFF+4]), "+f"(d[OFF+5]), "+f"(d[OFF+6]), "+f"(d[OFF+7]), "+f"(d[OFF+8]), "+f"(d[OFF+9]), "+f"(d[OFF+10]), "+f"(d[OFF+11]), "+f"(d[OFF+12]), "+f"(d[OFF+13]), "+f"(d[OFF+14]), "+f"(d[OFF+15]), "+f"(d[OFF+16]), "+f"(d[OFF+17]), "+f"(d[OFF+18]), "+f"(d[OFF+19]), "+f"(d[OFF+20]), "+f"(d[OFF+21]), "+f"(d[OFF+22]), "+f"(d[OFF+23]) : "r"(a0), "r"(a1), "r"(a2), "r"(a3), "l"(db), "r"(sd), "n"(TB));
}
template<int OFF, int TB, int S> __device__ __forceinline__ void wgmma_rs_n16(float (&d)[S], uint32_t a0, uint32_t a1, uint32_t a2, uint32_t a3, uint64_t db, int sd) {
  asm volatile("{\n.reg .pred p;\nsetp.ne.b32 p, %13, 0;\n"
    "wgmma.mma_async.sync.aligned.m64n16k16.f32.bf16.bf16 {%0, %1, %2, %3, %4, %5, %6, %7}, {%8, %9, %10, %11}, %12, p, 1, 1, %14;\n}\n"
    : "+f"(d[OFF+0]), "+f"(d[OFF+1]), "+f"(d[OFF+2]), "+f"(d[OFF+3]), "+f"(d[OFF+4]), "+f"(d[OFF+5]), "+f"(d[OFF+6]), "+f"(d[OFF+7]) : "r"(a0), "r"(a1), "r"(a2), "r"(a3), "l"(db), "r"(sd), "n"(TB));
}
template<int OFF, int TA, int TB, int S> __device__ __forceinline__ void wgmma_ss_n160(float (&d)[S], uint64_t da, uint64_t db, int sd) {
  asm volatile("{\n.reg .pred p;\nsetp.ne.b32 p, %82, 0;\n"
    "wgmma.mma_async.sync.aligned.m64n160k16.f32.bf16.bf16 {%0, %1, %2, %3, %4, %5, %6, %7, %8, %9, %10, %11, %12, %13, %14, %15, %16, %17, %18, %19, %20, %21, %22, %23, %24, %25, %26, %27, %28, %29, %30, %31, %32, %33, %34, %35, %36, %37, %38, %39, %40, %41, %42, %43, %44, %45, %46, %47, %48, %49, %50, %51, %52, %53, %54, %55, %56, %57, %58, %59, %60, %61, %62, %63, %64, %65, %66, %67, %68, %69, %70, %71, %72, %73, %74, %75, %76, %77, %78, %79}, %80, %81, p, 1, 1, %83, %84;\n}\n"
    : "+f"(d[OFF+0]), "+f"(d[OFF+1]), "+f"(d[OFF+2]), "+f"(d[OFF+3]), "+f"(d[OFF+4]), "+f"(d[OFF+5]), "+f"(d[OFF+6]), "+f"(d[OFF+7]), "+f"(d[OFF+8]), "+f"(d[OFF+9]), "+f"(d[OFF+10]), "+f"(d[OFF+11]), "+f"(d[OFF+12]), "+f"(d[OFF+13]), "+f"(d[OFF+14]), "+f"(d[OFF+15]), "+f"(d[OFF+16]), "+f"(d[OFF+17]), "+f"(d[OFF+18]), "+f"(d[OFF+19]), "+f"(d[OFF+20]), "+f"(d[OFF+21]), "+f"(d[OFF+22]), "+f"(d[OFF+23]), "+f"(d[OFF+24]), "+f"(d[OFF+25]), "+f"(d[OFF+26]), "+f"(d[OFF+27]), "+f"(d[OFF+28]), "+f"(d[OFF+29]), "+f"(d[OFF+30]), "+f"(d[OFF+31]), "+f"(d[OFF+32]), "+f"(d[OFF+33]), "+f"(d[OFF+34]), "+f"(d[OFF+35]), "+f"(d[OFF+36]), "+f"(d[OFF+37]), "+f"(d[OFF+38]), "+f"(d[OFF+39]), "+f"(d[OFF+40]), "+f"(d[OFF+41]), "+f"(d[OFF+42]), "+f"(d[OFF+43]), "+f"(d[OFF+44]), "+f"(d[OFF+45]), "+f"(d[OFF+46]), "+f"(d[OFF+47]), "+f"(d[OFF+48]), "+f"(d[OFF+49]), "+f"(d[OFF+50]), "+f"(d[OFF+51]), "+f"(d[OFF+52]), "+f"(d[OFF+53]), "+f"(d[OFF+54]), "+f"(d[OFF+55]), "+f"(d[OFF+56]), "+f"(d[OFF+57]), "+f"(d[OFF+58]), "+f"(d[OFF+59]), "+f"(d[OFF+60]), "+f"(d[OFF+61]), "+f"(d[OFF+62]), "+f"(d[OFF+63]), "+f"(d[OFF+64]), "+f"(d[OFF+65]), "+f"(d[OFF+66]), "+f"(d[OFF+67]), "+f"(d[OFF+68]), "+f"(d[OFF+69]), "+f"(d[OFF+70]), "+f"(d[OFF+71]), "+f"(d[OFF+72]), "+f"(d[OFF+73]), "+f"(d[OFF+74]), "+f"(d[OFF+75]), "+f"(d[OFF+76]), "+f"(d[OFF+77]), "+f"(d[OFF+78]), "+f"(d[OFF+79]) : "l"(da), "l"(db), "r"(sd), "n"(TA), "n"(TB));
}

__device__ __align__(1024) uint16_t g_kvT[2 * 640 * 2048];
__device__ __align__(1024) uint16_t g_y2T[2 * 640 * 2048];
__device__ __align__(1024) uint16_t g_o[2048 * 640];
__device__ __align__(1024) uint16_t g_gate[2080];
__device__ __align__(1024) uint4 g_halo[128 * 5 * 32];
__device__ __align__(1024) unsigned g_cnt[46 * 32];
__device__ __align__(1024) unsigned g_launch[132 * 32];
#define CNT_KV(i) (g_cnt + 32 * (i))
#define CNT_O(i) (g_cnt + 32 * (10 + (i)))
#define CNT_Y(i) (g_cnt + 32 * (26 + (i)))
#define PTL(i) do {} while (0)
#define PTPL(on, i) do {} while (0)
#define PT(i) do {} while (0)
#define PTP(on, i) do {} while (0)

constexpr uint32_t SB = 1024;
constexpr uint32_t STG = 23552, WST = 15360;
DEVI constexpr uint32_t o_px(int ks) { return (((ks >> 1) + 1) & 3) * 2 * STG; }
DEVI constexpr uint32_t o_pw(int ks) { return o_px(ks) + 16384 + (ks & 1) * WST; }
constexpr uint32_t O_HALO = 0, O_QT = STG;
constexpr uint32_t O_OST = 2 * STG;
constexpr uint32_t P3S = 28672;
constexpr uint32_t HC = 8320, UC = 4624, UZ = 528;
constexpr uint32_t O_H0 = 5 * P3S, O_U2 = O_H0 + 3 * HC, O_H3 = O_U2 + UC, O_U0 = O_H3 + 2 * HC;
DEVI constexpr uint32_t o_h(int c) { return O_H0 + c * HC + (c > 2 ? UC : 0); }
DEVI constexpr uint32_t o_u(int c) { return c == 2 ? O_U2 : O_U0 + (c > 2 ? c - 1 : c) * UC; }
constexpr uint32_t O_Y = 208896;
DEVI constexpr uint32_t o_x(int c) { return c < 2 ? O_Y + c * 5120 : O_U0 + (c & 1) * UC; }
constexpr uint32_t O_HIN = O_Y + 16384;
DEVI constexpr uint32_t o_kin(int c) { return ((O_U0 + 127) & ~127u) + ((c & 1) ? 0 : 73 * 128); }
DEVI constexpr uint32_t o_p3(int ks) { return (ks < 6 ? ks : ks - 6) * P3S; }
constexpr uint32_t O_BT = 4 * P3S;
constexpr uint32_t O_GT = O_Y + 20480, O_GW = O_GT + 320;
constexpr uint32_t O_BAR = 231040;
constexpr uint32_t B_FULL = O_BAR, B_EMPTY = O_BAR + 8 * 8, B_P3F = O_BAR + 8 * 16, B_P3R = O_BAR + 8 * 26, B_G = O_BAR + 8 * 27, B_U = O_BAR + 8 * 28,
                   B_KVD = O_BAR + 8 * 33, B_KF = O_BAR + 8 * 36, B_Y = O_BAR + 8 * 38, B_EP = O_BAR + 8 * 40, B_LAST = O_BAR + 8 * 41, B_DONE = O_BAR + 8 * 42,
                   B_P1E = O_BAR + 8 * 43, B_HX = O_BAR + 8 * 43  , B_P3E = O_BAR + 8 * 52, B_HX0 = O_BAR + 8 * 57, B_KVS = O_BAR + 8 * 58, B_QD = O_BAR + 8 * 60, B_GD = O_BAR + 8 * 61, B_OR = O_BAR + 8 * 62, B_Q = O_BAR + 8 * 51;
constexpr uint32_t B_S13 = B_EMPTY + 8 * 5, B_S15 = B_EMPTY + 8 * 7, B_S19 = B_EMPTY + 8 * 3;
constexpr uint32_t O_GP = O_BAR + 512, O_EPOCH = O_GW + 1280;
constexpr uint32_t SMEM_BYTES = 232448;
static_assert(O_U0 + 4 * UC <= O_Y - 512 && o_kin(0) >= O_U0 + 2 * UC && O_EPOCH + 4 <= O_BAR && O_U0 >= 8 * STG, "smem map");
enum { NB_LEAD = 1, NB_HELP = 2, NB_HALO = 3, NB_ATT = 4, NB_G = 5, NB_TOK = 6, NB_RFULL = 8, NB_RFREE = 10 };

struct Maps { CUtensorMap x_par, w_main, w_tail, k_ld, v_ld, o_st, kv_st, wo, o_ld, y_ld, q_ld; };

template <int M> DEVI void conv_step(float (&acc)[128], uint32_t a0, uint32_t a1, uint32_t a2, uint32_t a3, uint32_t dl) {
  auto D = [&](int off) { return ((uint64_t)8 << 32) | (uint64_t)(uint32_t)(dl + off - 16 * M); };
  if constexpr (M == 0) wgmma_rs_n16<0, 0>(acc, a0, a1, a2, a3, D(0), 0);
  if constexpr (M <= 3) wgmma_rs_n48<8, 0>(acc, a0, a1, a2, a3, D(16), M == 0 ? 0 : 1);
  if constexpr (M <= 6) wgmma_rs_n48<32, 0>(acc, a0, a1, a2, a3, D(64), M == 0 ? 0 : 1);
  if constexpr (M <= 9) wgmma_rs_n48<56, 0>(acc, a0, a1, a2, a3, D(112), M == 0 ? 0 : 1);
  if constexpr (M <= 12) wgmma_rs_n48<80, 0>(acc, a0, a1, a2, a3, D(160), M == 0 ? 0 : 1);
  wgmma_rs_n48<104, 0>(acc, a0, a1, a2, a3, D(208), M == 0 ? 0 : 1);
}
DEVI constexpr int a_off(int P, int i) { return -4 * (64 * ((i & 4) ? 15 - P : P) + (i & 1) * 32 - (i & 2) * 2); }
template <int P> DEVI void load_pair(uint32_t (&a)[8], uint32_t ab) {
#pragma unroll
  for (int i = 0; i < 8; i++) a[i] = lds32(ab + a_off(P, i));
}
template <int P> DEVI void mma_pair(float (&acc)[128], uint32_t (&a)[8], uint32_t db) {
  wg_fence();
  conv_step<P>(acc, a[0], a[1], a[2], a[3], db);
  conv_step<15 - P>(acc, a[4], a[5], a[6], a[7], db);
  wg_commit();
}

template <int I0, int I1> DEVI void conv_reduce(uint32_t sb, int c, int ht, int chan, int bar, int nthr) {
  const uint32_t a0 = sb + o_h(c) + ht * 16, a2 = sb + o_u(c) + ht * 16, a3 = sb + o_x(c) + ht * 16;
  uint4* yp = (uint4*)(g_y2T + (size_t)chan * 2048) + ht;
#pragma unroll
  for (int i = I0; i < I1; i++) {
    uint4 p, q, r, s;
    if (i == I0) bar_sync(bar, nthr);
    lds128(a0 + i * 2048, p.x, p.y, p.z, p.w); lds128(a0 + 4160 + i * 2048, q.x, q.y, q.z, q.w);
    lds128(a2 + i * 2048, r.x, r.y, r.z, r.w); lds128(a3 + i * 2048, s.x, s.y, s.z, s.w);
    auto sum = [](uint32_t a, uint32_t b, uint32_t c, uint32_t d) { return hadd2(hadd2(hadd2(a, b), 0u), hadd2(c, d)) ^ 0x80008000u; };
    yp[i * 128] = make_uint4(sum(p.x, q.x, r.x, s.x), sum(p.y, q.y, r.y, s.y), sum(p.z, q.z, r.z, s.z), sum(p.w, q.w, r.w, s.w));
  }
}

template <int ODD, int PART> DEVI void pack_qkv(const float (&acc)[120], uint32_t (&Q)[10][2], uint32_t (&K)[10][2], uint32_t (&V)[10][2]) {
#pragma unroll
  for (int f = 0; f < 10; f++) {
    const bool tail = ODD ? (f < 2) : (f >= 8);
    const int fm = ODD ? f - 2 : f, ft = ODD ? f : f - 8;
    const int nq = tail ? 24 + ft : fm, nk = tail ? 26 + ft : 8 + fm, nv = tail ? 28 + ft : 16 + fm;
    if (PART == 0) { K[f][1] = pack_bf16(acc[4 * nk + 2], acc[4 * nk + 3]); V[f][1] = pack_bf16(acc[4 * nv + 2], acc[4 * nv + 3]); }
    if (PART == 1) { V[f][0] = pack_bf16(acc[4 * nv], acc[4 * nv + 1]); K[f][0] = pack_bf16(acc[4 * nk], acc[4 * nk + 1]); }
    if (PART == 2) { Q[f][0] = pack_bf16(acc[4 * nq], acc[4 * nq + 1]); Q[f][1] = pack_bf16(acc[4 * nq + 2], acc[4 * nq + 3]); }
  }
}
DEVI int pair_of(int c) {
  const int lo = 32 + 8 * c, hi = c - 4 + ((max(c - 29, 0) * 37) >> 8);
  int p; asm("{\n.reg .pred q;\nsetp.lt.s32 q, %1, 4;\nselp.b32 %0, %2, %3, q;\n}" : "=r"(p) : "r"(c), "r"(lo), "r"(hi));
  return p;
}
DEVI uint32_t make_ctx() {
  int b; asm volatile("mov.u32 %0, %%ctaid.x;" : "=r"(b));
  b += clk() & threadIdx.y;
  const int p = pair_of(b >> 1);
  const int j = b < 128 ? 8 * (p & 7) + (p >> 3) : 64;
  const int q = (j * 205) >> 10, r = j - 5 * q, i = j - q, co = (i * 79) >> 10;
  const int cp = r == 4 ? 4 : co, tb = r == 4 ? q : i - 13 * co;
  return ((2 * p + (b & 1)) & 255) | tb << 8 | (2 * cp + (b & 1)) << 12 | (b >> 7) << 16;
}
#define CTX() asm volatile("" : "+r"(ctx)); CTXU()
#define CTXU() int tid; asm volatile("mov.u32 %0, %%tid.x;" : "=r"(tid)); \
  const int lane = tid & 31, vb = ctx & 255, hg = (ctx >> 4) & 7, rt = ctx & 15, par = (ctx >> 3) & 1, mt = ctx & 7, rank = ctx & 1, \
  tb = (ctx >> 8) & 15, cb = (ctx >> 12) & 15; const bool main_cta = ctx < 65536; \
  (void)tid; (void)lane; (void)vb; (void)hg; (void)rt; (void)par; (void)mt; (void)rank; (void)tb; (void)cb; (void)main_cta
#define CTXW() CTX(); const int wg = warp >> 2, w = warp & 3, g = lane >> 2, t = lane & 3; const bool lead = (tid & 127) == 0; \
  (void)wg; (void)w; (void)g; (void)t; (void)lead

__global__ void __cluster_dims__(2, 1, 1) __launch_bounds__(512, 1)
fused_kernel(const uint16_t* __restrict__ xq, const uint16_t* __restrict__ wqkv, const uint16_t* __restrict__ gate_w, const __grid_constant__ Maps M, const uint16_t* __restrict__ shift_k, const uint16_t* __restrict__ ssm_k, const uint16_t* __restrict__ ssm_D,
             uint16_t* __restrict__ outp) {
  extern __shared__ __align__(1024) uint8_t smem_raw[];
  const uint32_t sb = smem_u32(smem_raw);
  const uint32_t t0 = clk();
  auto get_epoch = [&]() { mbar_wait(sb + B_EP, 0); return lds32(sb + O_EPOCH); };

  auto p1_load_x = [&](int ks, int p, int rank) {
    tma3(sb + o_px(ks), &M.x_par, ks * 32, (p >> 2) & 1, (p & 3) * 256 + rank * 128, sb + B_FULL + 8 * (ks & 7));
  };
  auto p1_load_w = [&](int ks, int p, int rank) {
    const uint32_t st = sb + o_pw(ks), fb = sb + B_FULL + 8 * (ks & 7);
    tma3_mc(st + rank * 6144, &M.w_main, (p >> 3) * 80 + 2 * (p & 8), ks * 32 + rank * 16, 0, fb);
    tma3_mc(st + 12288 + rank * 1536, &M.w_tail, (p >> 3) * 80 + 8 * (~p & 8), ks * 32 + rank * 16, 0, fb);
  };
  auto cta_pair = [&]() { return pair_of(blockIdx.x >> 1); };

  if (threadIdx.x < 32) {
    const unsigned b = blockIdx.x, l = threadIdx.x;
    const uint16_t* pfp = l < 16 ? xq + (16 * b + l) * 640 : wqkv + (15 * b + l - 16) * 64;
    if ((l | b >> 7 << 5) < 31) pf_l2(pfp);
  }
  const int warp = __shfl_sync(~0u, threadIdx.x >> 5, 0);
  if ((warp & 14) == 8) {
    if (elect_one()) {
#pragma unroll
      for (int s = 0; s < 8; s++) mbar_init(sb + O_BAR - 512 + 64 * warp + 8 * s, 5 * warp - 39);
      asm volatile("fence.mbarrier_init.release.cluster;" ::: "memory");
    }
    __syncwarp();
  }
  asm volatile("barrier.cluster.arrive.relaxed.aligned;" ::: "memory");
  if (warp == 8 && blockIdx.x < 128) {
    const int p = cta_pair(), rank = blockIdx.x & 1;
    if (elect_one()) { mbar_expect_tx(sb + B_FULL, 16384 + WST); p1_load_x(0, p, rank); }
    __syncwarp();
    asm volatile("barrier.cluster.wait.aligned;" ::: "memory");
    if (elect_one()) { p1_load_w(0, p, rank); PT(100); }
    __syncwarp();
  } else if (warp != 15) {
    asm volatile("barrier.cluster.wait.aligned;" ::: "memory");
    spin_until(t0, HOLD);
  }
  auto cluster_sync = [&]() {
    asm volatile("barrier.cluster.arrive.relaxed.aligned;" ::: "memory");
    asm volatile("barrier.cluster.wait.aligned;" ::: "memory");
  };
  auto init_rest = [&]() {
    if (warp >= 11 && elect_one()) {
#pragma unroll
      for (int s = 0; s < 12; s++) mbar_init(sb + O_BAR + 128 - 11 * 96 + 96 * warp + 8 * s, warp == 14 ? 2 : 1);
      asm volatile("fence.mbarrier_init.release.cluster;" ::: "memory");
    }
    __syncwarp();
    if (blockIdx.x < 128) bar_sync(0, 224); else cluster_sync();
  };
  uint32_t ctx = 0;

  if (warp < 8) {
    reg_inc<RC>();
    ctx = make_ctx();
    if (blockIdx.x >= 128) cluster_sync();
    else {
      {
        uint32_t Q[10][2], K[10][2], V[10][2];
        {
          {
            float acc[120];
            CTXW();
            const int odd = (cta_pair() >> 3) & 1;
            const uint32_t rsb = mapa(sb, (blockIdx.x & 1) ^ 1);
            {
              const uint32_t aa = sb + (warp * 16 + (lane & 15)) * 128 + (((lane >> 4) ^ (lane & 7)) << 4);
              constexpr int NA = DEFER > 3 ? DEFER : 3;
              uint32_t a[NA][8];
              auto load_a = [&](int ks) {
                uint32_t(&r)[8] = a[ks % NA];
                mbar_wait(sb + B_FULL + 8 * (ks & 7), (ks >> 3) & 1);
                PTP(lead && (wg || !(ks & 3)), wg ? 60 + ks : 80 + (ks >> 2));
                ldsm4(r[0], r[1], r[2], r[3], (aa ^ ((ks & 1) * 64)) + o_px(ks)); ldsm4(r[4], r[5], r[6], r[7], (aa ^ ((ks & 1) * 64 + 32)) + o_px(ks));
              };
              auto mma_q = [&](int ks, int h) {
                uint32_t(&r)[8] = a[ks % NA];
                wgmma_rs_n64<0, 1>(acc, r[4 * h], r[4 * h + 1], r[4 * h + 2], r[4 * h + 3], mkdesc(SB + o_pw(ks) + h * 6144, 2048, 1024, 1), ks | h);
              };
              auto mma_step = [&](int ks, int h) {
                uint32_t(&r)[8] = a[ks % NA];
                wg_fence();
                wgmma_rs_n128<32, 1>(acc, r[4 * h], r[4 * h + 1], r[4 * h + 2], r[4 * h + 3], mkdesc(SB + o_pw(ks) + h * 6144 + 2048, 2048, 1024, 1), ks | h);
                if (ks < 20 - DEFER) mma_q(ks, h);
                wgmma_rs_n48<96, 1>(acc, r[4 * h], r[4 * h + 1], r[4 * h + 2], r[4 * h + 3], mkdesc(SB + o_pw(ks) + 12288 + h * 1536, 512, 256, 3), ks | h);
                wg_commit();
              };
              if (lead) PT(1 + wg);
              load_a(0);
#pragma unroll
              for (int ks = 0; ks < 20; ks++) {
                if (LEAD && ks == 20 - LEAD) bar_sync_p(wg == 0, NB_LEAD, 256);
                mma_step(ks, 0);
                if (ks < 19 && ks >= NLATE) load_a(ks + 1);
                mma_step(ks, 1);
                if (ks < NLATE) load_a(ks + 1);
                if (ks >= 1 && ks <= 16) {
                  wg_wait<2>();
                  mbar_arrive2_p(lead, sb + B_EMPTY + 8 * ((ks - 1) & 7), rsb + B_EMPTY + 8 * ((ks - 1) & 7));
                } else if (ks < 19 && ks + 2 - NA >= 16) wg_wait<2>();
              }
              if (LEAD) bar_arrive_p(wg, NB_LEAD, 256);
              if (DEFER) {
                wg_fence();
#pragma unroll
                for (int i = 40 - 2 * DEFER; i < 40; i++) mma_q(i >> 1, i & 1);
                wg_commit();
              }
              mbar_wait(sb + B_S15, 1);
              wg_wait<1>();
              mbar_arrive_p(tid == 0, sb + B_P1E);
              if (!DEFER) wg_wait<0>();
              fence_regs<32, 120>(acc);
              PTPL(lead, 158 + wg);
            }
            if (odd) pack_qkv<1, 0>(acc, Q, K, V); else pack_qkv<0, 0>(acc, Q, K, V);
            if (warp == 7 && (blockIdx.x & 1)) {
              uint4* hp = g_halo + vb * 160 + lane;
              st_relaxed(hp, K[0][1], K[1][1], K[3][1], K[4][1]); st_relaxed(hp + 32, K[5][1], K[6][1], K[8][1], K[9][1]);
              st_relaxed(hp + 64, K[2][1], K[7][1], V[0][1], V[1][1]);
              st_relaxed(hp + 96, V[2][1], V[3][1], V[4][1], V[5][1]); st_relaxed(hp + 128, V[6][1], V[7][1], V[8][1], V[9][1]);
            }
            const uint32_t ho = sb + O_HALO + warp * 2560 + lane * 16;
            stsm4(ho, K[0][1], K[1][1], K[3][1], K[4][1]); stsm4(ho + 512, K[5][1], K[6][1], K[8][1], K[9][1]);
            stsm4(ho + 1024, K[2][1], K[7][1], V[0][1], V[1][1]);
            stsm4(ho + 1536, V[2][1], V[3][1], V[4][1], V[5][1]); stsm4(ho + 2048, V[6][1], V[7][1], V[8][1], V[9][1]);
            if (warp == 7) {
              if (!(blockIdx.x & 1)) {
                fence_async_smem();
                __syncwarp();
                if (elect_one())
                  asm volatile("cp.async.bulk.shared::cluster.shared::cta.mbarrier::complete_tx::bytes [%0], [%1], 2560, [%2];"
                               ::"r"(mapa(sb + O_HIN, 1)), "r"(sb + O_HALO + 7 * 2560), "r"(mapa(sb + B_HX0, 1)) : "memory");
              }
              __syncwarp();
            } else {
              __syncwarp();
              if (lane == 0) mbar_arrive(sb + B_HX + 8 + 8 * warp);
            }
            if (odd) pack_qkv<1, 1>(acc, Q, K, V); else pack_qkv<0, 1>(acc, Q, K, V);
            wg_wait<0>();
            fence_regs<0, 32>(acc);
            PTPL(lead, 50 + wg);
            mbar_arrive2_p(lead, sb + B_S19, rsb + B_S19);
            if (odd) pack_qkv<1, 2>(acc, Q, K, V); else pack_qkv<0, 2>(acc, Q, K, V);
#pragma unroll
            for (int f = 0; f < 10; f++) V[f][0] = movm(V[f][0]);
            if (lead) PT(52 + wg);
            if (wg) mbar_wait(sb + B_P1E, 0);
          }
          CTXW();
          uint32_t z = threadIdx.y;
          const bool gt0 = 2 * t > g, gt1 = 2 * t + 1 > g;
          const uint32_t pmask = (gt0 ? 0xFFFFu : 0u) | (gt1 ? 0xFFFF0000u : 0u);
          const uint32_t hs = warp ? O_HALO + (warp - 1) * 2560 : O_HIN, ha = sb + hs + lane * 16;
          const uint32_t va = sb + ((lane & 8) ? O_HALO + warp * 2560 : hs) + 1280 + (lane >> 4) * 128 + (lane & 7) * 16;
          uint32_t Qh[4][2], Kh[10], Vh[10];
          float c1[4][4] = {}, c2[4][4] = {}, c0[4][4] = {}, l[8][2], m[8], x[8];
#pragma unroll
          for (int j = 0; j < 4; j++) {
            const int fa = (j >> 1) * 5 + (j & 1) * 3, fh = (j >> 1) * 5 + 2;
            const bool mine = (j & 1) ? (t >= 2) : (t < 2);
            Qh[j][0] = mine ? Q[fh][0] : 0u; Qh[j][1] = mine ? Q[fh][1] : 0u;
            mma16(c1[j], Q[fa][0], Q[fa][1], Q[fa + 1][0], Q[fa + 1][1], K[fa][0], K[fa + 1][0]);
            mma16(c2[j], Q[fa][0], Q[fa][1], Q[fa + 1][0], Q[fa + 1][1], K[fa][1], K[fa + 1][1]);
            mma8(c1[j], Qh[j][0], Qh[j][1], K[fh][0]);
            mma8(c2[j], Qh[j][0], Qh[j][1], K[fh][1]);
          }
          if (lead) PT(54 + wg);
          mbar_wait(sb + (warp ? B_HX + 8 * warp : B_HX0), 0);
          if (lead) PT(56 + wg);
          ldsm4(Kh[0], Kh[1], Kh[3], Kh[4], ha); ldsm4(Kh[5], Kh[6], Kh[8], Kh[9], ha + 512);
          asm volatile("ldmatrix.sync.aligned.m8n8.x2.shared.b16 {%0,%1}, [%2];" : "=r"(Kh[2]), "=r"(Kh[7]) : "r"(ha + 1024) : "memory");
          auto load_v = [&]() {
#pragma unroll
            for (int i = 0; i < 5; i++) ldsm4t(Vh[2 * i], V[2 * i][1], Vh[2 * i + 1], V[2 * i + 1][1], va + i * 256);
          };
          load_v();
          const float C = 0.22360679774997896f * 1.4426950408889634f;
          auto max1 = [&](int r) { m[r] = fmaxf(l[r][0], l[r][1]); x[r] = __shfl_xor_sync(~0u, m[r], 1); };
          auto max2 = [&](int r) { m[r] = fmaxf(m[r], x[r]); x[r] = __shfl_xor_sync(~0u, m[r], 2); };
          auto exps = [&](int r) { const float mc = fmaxf(m[r], x[r]) * C; l[r][0] = ex2(fmaf(l[r][0], C, -mc)); l[r][1] = ex2(fmaf(l[r][1], C, -mc)); };
#pragma unroll
          for (int j = 0; j < 4; j++) { l[4 + j][0] = gt0 ? c1[j][2] : c2[j][2]; l[4 + j][1] = gt1 ? c1[j][3] : c2[j][3]; max1(4 + j); }
#pragma unroll
          for (int j = 0; j < 4; j++) {
            const int fa = (j >> 1) * 5 + (j & 1) * 3, fh = (j >> 1) * 5 + 2;
            mma16(c0[j], Q[fa][0], Q[fa][1], Q[fa + 1][0], Q[fa + 1][1], Kh[fa], Kh[fa + 1]);
            mma8(c0[j], Qh[j][0], Qh[j][1], Kh[fh]);
            max2(4 + j);
          }
          const bool have_halo = warp > 0 || mt > 0;
#pragma unroll
          for (int j = 0; j < 4; j++) {
            if (!have_halo) c0[j][0] = c0[j][1] = -INFINITY;
            l[j][0] = gt0 ? c0[j][0] : c1[j][0]; l[j][1] = gt1 ? c0[j][1] : c1[j][1];
            max1(j);
          }
          exps(4); exps(5);
#pragma unroll
          for (int j = 0; j < 4; j++) max2(j);
          exps(6); exps(7);
#pragma unroll
          for (int j = 0; j < 4; j++) exps(j);
          float o[12][4] = {}, sm[4][4] = {};
#pragma unroll
          for (int j = 0; j < 4; j++) {
            const int fa = (j >> 1) * 5 + (j & 1) * 3, fh = (j >> 1) * 5 + 2;
            const uint32_t pl = pack_bf16(l[j][0], l[j][1]), pu = pack_bf16(l[4 + j][0], l[4 + j][1]);
            const uint32_t p0 = pl & pmask, p2 = pl & ~pmask, p3 = pu & pmask, p5 = pu & ~pmask, z0 = z << (2 * j + 1), z1 = z << (2 * j + 2);
            mma8(sm[j], pl, pu, 0x3F803F80u);
#pragma unroll
            for (int q = 0; q < 3; q++) {
              const int f = q < 2 ? fa + q : fh;
              mma8(o[3 * j + q], p2, p3, V[f][0]);
              mma16(o[3 * j + q], p0, z0, z1, p5, Vh[f], V[f][1]);
            }
            asm volatile("rcp.approx.ftz.f32 %0, %0;" : "+f"(sm[j][0]));
            asm volatile("rcp.approx.ftz.f32 %0, %0;" : "+f"(sm[j][2]));
          }
#pragma unroll
          for (int i = 6; i < 12; i++) z &= __float_as_uint(o[i][0]);
          bar_arrive_p(wg == 0, NB_HALO + z, 256);
          uint32_t O[10][2];
#pragma unroll
          for (int j = 0; j < 4; j++) {
            const int fa = (j >> 1) * 5 + (j & 1) * 3, fh = (j >> 1) * 5 + 2;
            const float r0 = sm[j][0], r1 = sm[j][2];
#pragma unroll
            for (int q = 0; q < 3; q++) {
              const int f = q < 2 ? fa + q : fh;
              const float* e = o[3 * j + q];
              const uint32_t o0 = pack_bf16(e[0] * r0, e[1] * r0), o1 = pack_bf16(e[2] * r1, e[3] * r1);
              if (q < 2 || !(j & 1)) { O[f][0] = o0; O[f][1] = o1; }
              else { O[f][0] = t >= 2 ? o0 : O[f][0]; O[f][1] = t >= 2 ? o1 : O[f][1]; }
            }
          }
          mbar_wait(sb + B_GD, 0);
          const uint32_t oa = sb + O_OST + wg * 2 * STG + (w * 16 + (lane & 15)) * 160 + (lane >> 4) * 16;
#pragma unroll
          for (int i = 0; i < 5; i++) stsm4(oa + i * 32, O[2 * i][0], O[2 * i][1], O[2 * i + 1][0], O[2 * i + 1][1]);
        }
      }
      {
        CTXW();
        fence_async_smem();
        bar_arrive(wg ? NB_LEAD : NB_ATT, 160);
        if (lead) PT(58 + wg);
        const uint32_t abase = sb + (g & 1) * 4160 + 4 * (1023 - 4 - 8 * w - (g >> 1) + t);
        float acc[128];
        uint32_t a0[8], a1[8], a2[8], a3[8];
#pragma unroll 1
        for (int c = wg ^ 1; c < 5; c += 2) {
          const uint32_t ab = abase + o_h(c);
          const uint32_t db = __shfl_sync(~0u, ((SB + o_u(c) + UZ - 16) >> 4) | 0x10000u, 0);
          mbar_wait(sb + B_U + 8 * c, 0);
          load_pair<0>(a0, ab); load_pair<1>(a1, ab); load_pair<2>(a2, ab);
          if (lead) PT(85 + c);
          bar_sync(c ? NB_TOK + wg : NB_HALO, 256);
          fence_regs(acc);
          mma_pair<0>(acc, a0, db);
          load_pair<3>(a3, ab);
          mma_pair<1>(acc, a1, db); wg_wait<1>();  load_pair<4>(a0, ab);
          if (lead) PT(90 + c);
          mma_pair<2>(acc, a2, db); wg_wait<1>();  load_pair<5>(a1, ab);
          mma_pair<3>(acc, a3, db); wg_wait<1>();  load_pair<6>(a2, ab);
          mma_pair<4>(acc, a0, db); wg_wait<1>();  load_pair<7>(a3, ab);
          mma_pair<5>(acc, a1, db);
          mma_pair<6>(acc, a2, db);
          bar_arrive_p(c < 4, NB_TOK + (wg ^ 1), 256);
          mma_pair<7>(acc, a3, db);
          bar_arrive_p(c == 4, NB_TOK, 256);
          wg_wait<0>();
          fence_regs(acc);
          PTPL(lead, 95 + c);
          bar_sync(NB_RFREE + wg, 256);
          const uint32_t pb = sb + (w < 2 ? o_h(c) + w * 4160 : w == 2 ? o_u(c) : o_x(c)) + lane * 16;
          if (lane < 2 * w) sts128(pb, 0, 0, 0, 0);
#pragma unroll
          for (int q = 0; q < 8; q++) {
            uint32_t p[4];
#pragma unroll
            for (int i = 0; i < 4; i++) {
              const int nu = 4 * q + i;
              p[i] = pack_bf16(acc[4 * nu], acc[4 * nu + 1]);
              if (nu > 0) p[i] = hadd2(p[i], pack_bf16(acc[4 * nu - 2], acc[4 * nu - 1]));
            }
            stsm4t(pb + w * 32 + q * 512, p[0], p[1], p[2], p[3]);
            if (q == 3) bar_arrive_p(c == 4, NB_RFULL + 1, 256);
          }
          if (c < 4) bar_arrive(NB_RFULL + wg, 256);
          if (lead) PT(140 + c);
        }
        if (wg) {
          const int yb = (lds32(sb + O_EPOCH) & 1) * 640;
              conv_reduce<1, 2>(sb, 4, tid - 128, yb + 512 + ((vb & 0x61) | (vb & 6) << 2 | (vb >> 2 & 6)), 14, 128);
          bar_arrive(12, 256);
          PTPL(lead, 45);
        }
      }
    }
    if (warp < 4) {
      CTXW();
      const uint32_t rsb = mapa(sb, (blockIdx.x & 1) ^ 1);
      const uint32_t ba = sb + O_BT + ((lane >> 4) * 8 + (lane & 7)) * 128 + (((2 * w + ((lane >> 3) & 1)) ^ ((lane & 1) << 2 | (lane >> 1 & 3))) << 4);
      mbar_wait(sb + B_P3F, 0);
      if (lead) PT(145);
      bar_sync_p(blockIdx.x < 128, NB_TOK, 256);
      float acc[80];
#pragma unroll
      for (int ks = 0; ks < 10; ks++) {
        PTP(lead, 146 + ks);
        const uint64_t da = mkdesc(SB + o_p3(ks), 1024, 1024, 1), db = mkdesc(SB + o_p3(ks) + 8192, 16, 1024, 1);
        wg_fence();
#pragma unroll
        for (int j = 0; j < 4; j++) wgmma_ss_n160<0, 1, 0>(acc, da + j * 128, db + j * 2, j | ks);
        wg_commit();
        if (ks < 9) mbar_wait(sb + B_P3F + 8 * (ks + 1), 0);
        if (ks >= 1 && ks <= 4) { wg_wait<1>(); mbar_arrive2_p(lead, sb + B_P3E + 8 * ks, rsb + B_P3E + 8 * ks); }
      }
      wg_wait<0>();
      fence_regs(acc);
      PTPL(lead, 156);
#pragma unroll
      for (int i = 0; i < 10; i++) {
        stsm4t(ba + i * 2048, pack_bf16(acc[8 * i], acc[8 * i + 1]), pack_bf16(acc[8 * i + 2], acc[8 * i + 3]),
               pack_bf16(acc[8 * i + 4], acc[8 * i + 5]), pack_bf16(acc[8 * i + 6], acc[8 * i + 7]));
        if (i & 1) bar_arrive(1 + (i >> 1), 256);
      }
      if (lead) PT(157);
    }
  } else if (warp < 12) {
    reg_dec<RH>();
    const int hw = warp - 8;
    init_rest();
    ctx = __shfl_sync(~0u, make_ctx(), 0);
    const int yrow = (ctx & 0x61) | (ctx & 6) << 2 | (ctx >> 2 & 6);
    if (ctx < 65536) {
      CTXU();
      const int pr = hw >> 1, hh = hw & 1, tk = vb & 63, odd = (lane >> 2) & 1;
      const uint32_t sel0 = odd ? 0x7632 : 0x5410, sel1 = odd ? 0x5410 : 0x7632;
      const uint32_t in = sb + o_kin(pr), fb = sb + B_KF + 8 * pr, out = sb + O_Y + pr * 8192;
      const uint32_t oa = out + (2 * lane + odd) * 64 + (((3 - 2 * hh) ^ (lane & 3)) << 4), ia = in + hh * 2048 + lane * 4;
      auto fetch = [&](int c) {
        wait_until(t0, KT0 + c * KTD + ((((vb * 37) & 63) * KPH) >> 6));
        if (elect_one()) {
          const int kb = 2 * c + (vb >> 6);
          mbar_expect_tx(fb, 69 * 128);
          tma2(in, &M.k_ld, kb * 64, 32 * tk - 4, fb);
          tma2(in + 36 * 128, &M.v_ld, kb * 64, 32 * tk - 1, fb);
          PT(20 + c);
        }
        __syncwarp();
      };
      if (hh == 0) fetch(pr);
      const uint4* skp = (const uint4*)shift_k + (2 * pr + (vb >> 6)) * 32 + lane;
      uint4 sk = __ldg(skp), sk1 = __ldg(skp + 128), sk2 = __ldg(skp + (pr ? 0 : 256));
#pragma unroll 1
      for (int c = pr; c < 5; c += 2) {
        {
          mbar_wait(fb, (c >> 1) & 1);
          if (hh == 0 && lane == 0) PT(25 + c);
          uint32_t k[20], o[17];
#pragma unroll
          for (int i = 0; i < 20; i++) { k[i] = lds32(ia + i * 128); if (i >= 3) o[i - 3] = lds32(ia + (33 + i) * 128); }
          fence_async_smem();
          bar_sync(12 + pr, 64);
          if (hh == 0) {
            if (c < 3) fetch(c + 2);
            else if (lane == 0) mbar_arrive(sb + B_KVD + 8 * (c - 3));
          }
          const uint32_t w0 = prmt(sk.x, sk.z, 0x5410), w1 = prmt(sk.x, sk.z, 0x7632), w2 = prmt(sk.y, sk.w, 0x5410), w3 = prmt(sk.y, sk.w, 0x7632);
#pragma unroll
          for (int i = 0; i < 17; i++) o[i] = hmul2(hfma2(k[i + 3], w0, hfma2(k[i + 2], w1, hfma2(k[i + 1], w2, hmul2(k[i], w3)))), o[i]);
          sk = sk1; sk1 = sk2;
#pragma unroll
          for (int i = 0; i < 4; i++) {
            const int e = 8 * (i >> 1) + (i & 1);
            const uint32_t a = (oa ^ ((i >> 1) * 16)) + (i & 1) * 4096;
            sts128(a, prmt(o[7 + e], o[6 + e], sel0), prmt(o[5 + e], o[4 + e], sel0), prmt(o[3 + e], o[2 + e], sel0), prmt(o[1 + e], o[e], sel0));
            sts128(a ^ 64, prmt(o[7 + e], o[6 + e], sel1), prmt(o[5 + e], o[4 + e], sel1), prmt(o[3 + e], o[2 + e], sel1), prmt(o[1 + e], o[e], sel1));
          }
          bar_sync(12 + pr, 64);
        }
        if (hh) {
          fence_async_smem();
          if (elect_one()) {
            const int kb = 2 * c + (vb >> 6);
            tma3_store(&M.kv_st, 0, kb * 64, 63 - tk, out);
            tma3_store(&M.kv_st, 0, 640 + kb * 64, 63 - tk, out + 4096);
            bulk_commit(); bulk_wait_all();
            mbar_arrive(sb + (c == 4 ? B_KVD + 16 : B_KVS + 4 * (c & 2)));
            PTL(35 + c);
          }
          __syncwarp();
        }
      }
    }
    CTXU();
    const int g = lane >> 2, t = lane & 3, row = 8 * hw + g;
    const uint32_t go = (tb * 160 + row) * 80 + cb * 8 + t;
    const int yb = __shfl_sync(~0u, get_epoch() & 1, 0) * 640;
    uint4 T[10];
    if (hw == 2) {
      if (main_cta) { mbar_wait(sb + B_LAST, 0); mbar_wait(sb + B_S15, 1); }
      if (elect_one()) {
        mbar_expect_tx(sb + B_Q, 20480);
#pragma unroll
        for (int h = 0; h < 2; h++) tma2(sb + O_QT + h * 10240, &M.q_ld, cb * 64 + 32 * h, tb * 160, sb + B_Q);
      }
      __syncwarp();
    }
    mbar_wait(sb + B_Q, 0);
#pragma unroll
    for (int i = 0; i < 10; i++) lds128(sb + O_QT + (i & 1) * 10240 + (i >> 1) * 2048 + row * 64 + t * 16, T[i].x, T[i].y, T[i].z, T[i].w);
    fence_async_smem();
    bar_sync(12 + (hw >> 1), 64);
    if (!(tid & 63)) mbar_arrive(sb + B_QD);
    if (tid == 256) PTL(40);
    if (main_cta) {
      bar_arrive(NB_RFREE, 256);
      bar_arrive(NB_RFREE + 1, 256);
      auto red = [&](int c) {
        const int wg = (c & 1) ^ 1;
        conv_reduce<0, 2>(sb, c, tid - 256, yb + 128 * c + yrow, NB_RFULL + wg, 256);
        if (hw == 3 && elect_one()) flag_add(CNT_Y(4 * c + (vb >> 5)), 1);
        if (tid == 256) PTL(41 + c);
        if (c < 3) bar_arrive(NB_RFREE + wg, 256);
        if (c == 2) {
          bar_sync(NB_HELP, 128);
          if (tid == 256) { mbar_arrive(sb + B_P3E); mbar_arrive_remote(sb + B_P3E, rank ^ 1); }
        }
      };
      if (hw == 3) {
        mbar_wait(sb + B_KVD + 16, 0);
        if (elect_one()) { flag_release(CNT_KV(4 + (vb >> 6))); PTL(32); }
        __syncwarp();
      }
#pragma unroll 1
      for (int c = 0; c < 4; c++) red(c);
    }
    uint32_t G[5];
    mbar_wait(sb + B_G, 0);
#pragma unroll
    for (int q = 0; q < 5; q++) { uint16_t v; asm volatile("ld.shared.u16 %0, [%1];" : "=h"(v) : "r"(sb + O_GT + (32 * q + row) * 2)); G[q] = prmt(v, 0, 0x1010); }
#pragma unroll
    for (int i = 0; i < 10; i++) { const uint32_t c = G[i >> 1] ^ 0x80008000u; T[i] = make_uint4(hmul2(T[i].x, c), hmul2(T[i].y, c), hmul2(T[i].z, c), hmul2(T[i].w, c)); }
    if (main_cta) {
      conv_reduce<0, 1>(sb, 4, tid - 256, yb + 512 + yrow, NB_RFULL + 1, 256);
      if (hw == 3 && elect_one()) { flag_add(CNT_Y(16 + (vb >> 5)), 1); PTL(19); }
      bar_sync(12, 256);
    }
#pragma unroll
    for (int h = 0; h < 2; h++) {
      mbar_wait_wd(sb + B_Y + 8 * h, 0, t0);
      if (tid == 256) PTL(46);
      const uint32_t ya = sb + O_Y + h * 10240 + lane * 64 + ((hw ^ ((lane >> 1) & 3)) << 4);
      uint4 y[5];
      auto empty = [](uint32_t m) { return (m & 0xFFFFu) == 0 || m < 0x10000u; };
      uint32_t m = ~0u;
#pragma unroll
      for (int q = 4; q >= 0; q--) {
        ldsm4t(y[q].x, y[q].y, y[q].z, y[q].w, ya + q * 2048);
        m = __vimin3_u16x2(__vimin3_u16x2(m, y[q].x, y[q].y), y[q].z, y[q].w);
        if (q == 4 && tb == 12) m = ~0u;
      }
      if (__any_sync(~0u, empty(m))) {
        const uint4* gp = (const uint4*)g_y2T + (yb + cb * 64 + 32 * h + lane) * 256 + tb * 20 + hw;
#pragma unroll
        for (int q = 0; q < 5; q++) lds128(ya + q * 2048, y[q].x, y[q].y, y[q].z, y[q].w);
        if (tb == 12) y[4] = make_uint4(~0u, ~0u, ~0u, ~0u);
        for (;;) {
          bool bad[5], any = false;
#pragma unroll
          for (int q = 0; q < 5; q++) { bad[q] = empty(__vimin3_u16x2(__vminu2(y[q].x, y[q].y), y[q].z, y[q].w)); any |= bad[q]; }
          if (!__any_sync(~0u, any)) break;
#pragma unroll
          for (int q = 0; q < 5; q++)
            if (bad[q]) asm volatile("ld.relaxed.gpu.global.v4.b32 {%0,%1,%2,%3}, [%4];" : "=r"(y[q].x), "=r"(y[q].y), "=r"(y[q].z), "=r"(y[q].w) : "l"(gp + 4 * q) : "memory");
        }
#pragma unroll
        for (int q = 0; q < 5; q++) sts128(ya + q * 2048, y[q].x, y[q].y, y[q].z, y[q].w);
        __syncwarp();
#pragma unroll
        for (int q = 0; q < 5; q++) ldsm4t(y[q].x, y[q].y, y[q].z, y[q].w, ya + q * 2048);
        PTL(49);
      }
#pragma unroll
      for (int q = 0; q < 5; q++) {
        uint4& r = T[2 * q + h];
        r = make_uint4(hmul2(r.x, y[q].x), hmul2(r.y, y[q].y), hmul2(r.z, y[q].z), hmul2(r.w, y[q].w));
      }
    }
    const uint32_t so = sb + O_BT + row * 128 + ((t ^ ((g & 1) << 2 | g >> 1)) << 4);
    if (tid == 256) PTL(47);
#pragma unroll
    for (int q = 0; q < 5; q++) {
      const uint32_t c = hfma2(G[q], 0xBF80BF80u, 0x3F803F80u);
      bar_sync(1 + q, 256);
      if (q == 4) mbar_arrive_p(tid == 256, sb + B_DONE);
#pragma unroll
      for (int h = 0; h < 2; h++) {
        uint4 u;
        lds128((so ^ (h * 64)) + q * 4096, u.x, u.y, u.z, u.w);
        const uint4& r = T[2 * q + h];
        if (q < 4 || tb < 12)
          asm volatile("st.global.v4.b32 [%0], {%1,%2,%3,%4};" ::"l"((uint4*)outp + go + q * 2560 + h * 4), "r"(hfma2(u.x, c, r.x)), "r"(hfma2(u.y, c, r.y)), "r"(hfma2(u.z, c, r.z)), "r"(hfma2(u.w, c, r.w)) : "memory");
      }
    }
  } else {
    reg_dec<RP>();
    uint4 gwv = make_uint4(0, 0, 0, 0);
    if (warp == 15) {
      const int p = cta_pair(), rank = blockIdx.x & 1;
      asm volatile("barrier.cluster.wait.aligned;" ::: "memory");
      if (blockIdx.x >= 128) cluster_sync();
      else {
#pragma unroll 1
        for (int ks = 1;; ks += 2) {
          mbar_wait(sb + B_EMPTY + 8 * (ks & 7), ((ks >> 3) & 1) ^ 1);
          spin_until(t0, PT1 + (ks - 1) * PTD);
          if (elect_one()) { mbar_expect_tx(sb + B_FULL + 8 * (ks & 7), WST); p1_load_w(ks, p, rank); PT(100 + ks); }
          if (ks == 19) break;
          const int kn = ks + 1;
          mbar_wait(sb + B_EMPTY + 8 * (kn & 7), ((kn >> 3) & 1) ^ 1);
          spin_until(t0, PT1 + ks * PTD - PTE);
          if (elect_one()) { mbar_expect_tx(sb + B_FULL + 8 * (kn & 7), 16384 + WST); p1_load_x(kn, p, rank); p1_load_w(kn, p, rank); PT(100 + kn); }
        }
        if (elect_one()) mbar_arrive(sb + B_LAST);
#pragma unroll 1
        for (int i = 0; i < 2; i++) {
          mbar_wait(sb + B_KVS + 8 * i, 0);
          if (elect_one()) { flag_release(CNT_KV(2 * i + (p >> 5))); PTL(30 + i); }
          __syncwarp();
        }
        mbar_wait(sb + B_S19, 0);
      }
    } else {
      if (threadIdx.x < 384 + 80) gwv = __ldg((const uint4*)gate_w + threadIdx.x - 384);
      init_rest();
    }
    ctx = __shfl_sync(~0u, make_ctx(), 0);
    CTXU();
    if (warp == 12) {
        unsigned epoch = 0;
      if (lane == 0) epoch = *(volatile unsigned*)(g_launch + 32 * vb) + 1;
      if (main_cta) { sts128(sb + O_GW + lane * 16, gwv.x, gwv.y, gwv.z, gwv.w); bar_arrive(NB_G, 96); }
      if (lane == 0) {
        if ((sb & 0xFFFFFF) != SB) __trap();
        sts32(sb + O_EPOCH, epoch);
        mbar_arrive(sb + B_EP);
#pragma unroll 1
        for (int i = 5; i < 11; i++) asm volatile("prefetch.tensormap [%0];" ::"l"(&M.x_par + i) : "memory");
      }
      if (main_cta && rank) {
#pragma unroll
        for (int f = 0; f < 5; f++) st_relaxed(g_halo + vb * 160 + lane + 32 * f, ~0u, ~0u, ~0u, ~0u);
      }
      __syncwarp();
      if (elect_one()) flag_release(g_launch + 32 * vb);
      __syncwarp();
      if (main_cta) {
        uint4 h0 = make_uint4(0, 0, 0, 0);
        if (lane < 5) {
          h0 = __ldg((const uint4*)(ssm_k + (size_t)(128 * lane + vb) * 2048));
          h0.x = prmt(pack_bf16(bf_lo(h0.x) + bf_lo(__ldg(ssm_D + 128 * lane + vb)), 0.f), h0.x, 0x7610);
        }
        epoch = __shfl_sync(~0u, epoch, 0);
        const int ze = lane & 7;
        const uint32_t za = sb + (lane < 8 ? o_u(ze) + UZ : lane < 24 ? o_h(ze) + (lane >> 4) * 4160 + 4096 : o_u(ze) + 512);
        const uint16_t* hp = ssm_k + (size_t)vb * 2048 + 8;
        const uint16_t* up = g_kvT + (size_t)vb * 2048;
        const unsigned* fp = CNT_KV(vb >> 6);
        sts128(sb + O_Y - 512 + lane * 16, 0, 0, 0, 0);
        mbar_wait(sb + B_LAST, 0);
        mbar_wait(sb + B_S13, 1);
#pragma unroll
        for (int c = 0; c < 5; c++) {
          if (c == 0 || c == 3) {
            mbar_wait(sb + B_KVD + (c ? 8 : 0), 0);
#pragma unroll
            for (int e = c; e < (c ? 5 : 3); e++) sts128(sb + o_u(e) + lane * 16, 0, 0, 0, 0);
            if (ze >= c && ze < (c ? 5 : 3)) sts128(za, h0.x, h0.y, h0.z, h0.w);
            fence_async_smem();
            __syncwarp();
            if (elect_one()) {
#pragma unroll
              for (int e = c; e < (c ? 5 : 3); e++) {
                mbar_expect_tx(sb + B_U + 8 * e, 3 * 4096 - 16);
                if (c || e == 0) bulk_load(sb + o_u(e) + UZ + 16, hp + 128 * 2048 * e, 4080, sb + B_U + 8 * e);
              }
            }
          }
          if (!(c & 1)) { flag_wait(fp + 32 * c, 64 * epoch); __syncwarp(); }
          if (elect_one()) {
            bulk_load(sb + o_h(c), up + 128 * 2048 * c, 4096, sb + B_U + 8 * c);
            bulk_load(sb + o_h(c) + 4160, up + (640 + 128 * c) * 2048, 4096, sb + B_U + 8 * c);
            if (c == 1) {
#pragma unroll
              for (int e = 1; e < 3; e++) bulk_load(sb + o_u(e) + UZ + 16, hp + 128 * 2048 * e, 4080, sb + B_U + 8 * e);
            }
            PTL(10 + c);
          }
        }
        mbar_wait(sb + B_OR, 0);
        if (elect_one()) {
#pragma unroll 1
          for (int i = 0; i < 40; i++) bulk_store(g_y2T + (size_t)((~epoch & 1) * 640 + 5 * vb) * 2048 + i * 256, sb + O_Y - 512, 512);
          bulk_commit(); bulk_wait_read();
          PTL(33);
        }
      }
    } else if (warp != 15) {
        const int r = warp - 13;
      if (main_cta) {
        if (rank && lane == 0) mbar_expect_tx(sb + B_HX0, 1280);
        const int t = lane & 3, grow = hg * 16 + (lane & 15);
        const uint32_t ga = sb + grow * 128 + (((4 * r + (lane >> 4)) ^ (lane & 7)) << 4);
        const uint32_t gp = sb + O_GW + 64 * r + 4 * t;
        float s0 = 0.f, s1 = 0.f;
        if (tid < 384 + 80) sts128(sb + O_GW + (tid - 384) * 16, gwv.x, gwv.y, gwv.z, gwv.w);
        bar_sync(NB_G, 96);
#pragma unroll 1
        for (int ks = 0; ks < 20; ks += 2) {
          uint32_t x[8], gw[4];
#pragma unroll
          for (int i = 0; i < 4; i++) gw[i] = lds32(gp + ks * 64 + i * 16);
          mbar_wait_wd(sb + B_FULL + 8 * (ks & 7), (ks >> 3) & 1, t0);
          if (r == 0 && lane == 0) PT(120 + ks);
          ldsm4(x[0], x[1], x[2], x[3], ga + o_px(ks)); ldsm4(x[4], x[5], x[6], x[7], (ga ^ 32) + o_px(ks));
#pragma unroll
          for (int i = 0; i < 8; i++) x[i] = hmul2(x[i], gw[i >> 1]);
          if (lane < 2) mbar_arrive(sb + B_EMPTY + 8 * (ks & 7) + 8 * lane + (x[0] & x[7] & threadIdx.y));
#pragma unroll
          for (int i = 0; i < 8; i += 4) {
            s0 += (bf_lo(x[i]) + bf_hi(x[i])) + (bf_lo(x[i + 2]) + bf_hi(x[i + 2]));
            s1 += (bf_lo(x[i + 1]) + bf_hi(x[i + 1])) + (bf_lo(x[i + 3]) + bf_hi(x[i + 3]));
          }
        }
        s0 += __shfl_xor_sync(~0u, s0, 1); s1 += __shfl_xor_sync(~0u, s1, 1);
        s0 += __shfl_xor_sync(~0u, s0, 2); s1 += __shfl_xor_sync(~0u, s1, 2);
        if (t < 2) sts32(sb + O_GP + r * 64 + (8 * t + (lane >> 2)) * 4, __float_as_uint(t ? s1 : s0));
        if (lane == 0) mbar_arrive(sb + B_GD);
        if (r == 0) bar_arrive(NB_G, 64);
        if (!rank) {
          uint4 d[3];
          if (mt > 0) {
            const uint4* hp = g_halo + (vb - 1) * 160 + r * 64 + lane;
            mbar_wait_wd(sb + B_EP, 0, t0);
            flag_wait_wd(g_launch + 32 * (vb - 1), lds32(sb + O_EPOCH), t0);
            mbar_wait_wd(sb + B_HX + 56, 0, t0);
            for (;;) {
              bool ok = true;
#pragma unroll
              for (int f = 0; f < 3; f++) {
                asm volatile("ld.relaxed.gpu.global.v4.b32 {%0,%1,%2,%3}, [%4];" : "=r"(d[f].x), "=r"(d[f].y), "=r"(d[f].z), "=r"(d[f].w) : "l"(hp + 32 * f) : "memory");
              }
#pragma unroll
              for (int f = 0; f < 3; f++) ok = ok && max(max(d[f].x, d[f].y), max(d[f].z, d[f].w)) != ~0u;
              if (__all_sync(~0u, ok)) break;
              if (clk() - t0 > 0x70000000u) __trap();
            }
          } else {
#pragma unroll
            for (int f = 0; f < 3; f++) d[f] = make_uint4(0, 0, 0, 0);
          }
#pragma unroll
          for (int f = 0; f < 3; f++) stsm4(sb + O_HIN + r * 1024 + f * 512 + lane * 16, d[f].x, d[f].y, d[f].z, d[f].w);
          __syncwarp();
          if (lane == 0) { mbar_arrive(sb + B_HX0); PTL(15 + r); }
        }
        if (r == 1) {
          bar_sync(NB_G, 64);
          if (lane < 16) {
            const uint32_t pa = sb + O_GP + lane * 4;
            const float z = __uint_as_float(lds32(pa)) + __uint_as_float(lds32(pa + 64));
            g_gate[2 * (mt * 128 + hg * 16 + lane) + par] = (uint16_t)pack_bf16(__fdividef(1.f, 1.f + __expf(-bf_lo(pack_bf16(z, 0.f)))), 0.f);
          }
          __syncwarp();
          if (elect_one()) flag_release(CNT_O(rt));
        }
      }
      mbar_wait_wd(sb + B_EP, 0, t0);
      const unsigned epoch = lds32(sb + O_EPOCH);
      if (main_cta) mbar_wait_wd(sb + B_P3E, 0, t0);
      flag_wait_wd(CNT_Y(2 * cb + r), 32 * epoch, t0);
      __syncwarp();
      if (elect_one()) {
        mbar_expect_tx(sb + B_Y + 8 * r, 10240);
        tma3(sb + O_Y + r * 10240, &M.y_ld, 0, (epoch & 1) * 640 + cb * 64 + 32 * r, tb * 5, sb + B_Y + 8 * r);
        PTL(17 + r);
      }
      __syncwarp();
      mbar_wait_wd(sb + B_DONE, 0, t0);
    } else {
      const unsigned epoch = get_epoch();
      if (main_cta) {
        bar_sync(NB_LEAD, 160);
        if (elect_one()) tma3_store(&M.o_st, hg * 80, par, mt * 128 + 64, sb + O_OST + 2 * STG);
        bar_sync(NB_ATT, 160);
        if (elect_one()) {
          tma3_store(&M.o_st, hg * 80, par, mt * 128, sb + O_OST);
          bulk_commit(); bulk_wait_all();
          flag_release(CNT_O(rt));
          mbar_arrive(sb + B_OR); mbar_arrive(sb + B_OR);
          PTL(3);
        }
        __syncwarp();
      }
      mbar_wait(sb + B_QD, 0);
#pragma unroll 1
      for (int ks = 0; ks < 5; ks++)
        if (elect_one()) tma2(sb + o_p3(ks), &M.wo, cb * 64, ks * 64, sb + B_P3F + 8 * ks);
      if (lane < 4) flag_wait(CNT_O(8 * (lane & 1) + min(7, (80 * tb + 79 * (lane >> 1)) >> 7)), 16 * epoch);
      __syncwarp();
      if (elect_one()) {
        PTL(4);
        mbar_arrive_remote(sb + B_P3R, rank ^ 1);
        mbar_expect_tx(sb + B_G, 320);
        bulk_load(sb + O_GT, g_gate + tb * 160, 320, sb + B_G);
      }
      mbar_wait(sb + B_P3R, 0);
      auto load_o = [&](int ks) {
        tma2_mc(sb + o_p3(ks) + 8192 + rank * 10240, &M.o_ld, ks * 64, tb * 160 + rank * 80, sb + B_P3F + 8 * ks);
        mbar_expect_tx(sb + B_P3F + 8 * ks, P3S);
      };
      auto load_wo = [&](int ks) { tma2(sb + o_p3(ks), &M.wo, cb * 64, ks * 64, sb + B_P3F + 8 * ks); };
#pragma unroll 1
      for (int ks = 0; ks < 5; ks++)
        if (elect_one()) load_o(ks);
#pragma unroll
      for (int ks = 5; ks < 10; ks++) {
        if (ks > 5 || main_cta) mbar_wait(sb + B_P3E + 8 * (ks - 5), 0);
        if (elect_one()) {
          load_o(ks); load_wo(ks);
          PTL(ks);
        }
      }
    }
  }
}

typedef CUresult (*PFN_enc)(CUtensorMap*, CUtensorMapDataType, cuuint32_t, void*, const cuuint64_t*, const cuuint64_t*, const cuuint32_t*,
                            const cuuint32_t*, CUtensorMapInterleave, CUtensorMapSwizzle, CUtensorMapL2promotion, CUtensorMapFloatOOBfill);
static void enc(PFN_enc f, CUtensorMap* m, const void* base, int rank, const cuuint64_t* dims, const cuuint64_t* strides, const cuuint32_t* box,
                CUtensorMapSwizzle sw) {
  const cuuint32_t es[5] = {1, 1, 1, 1, 1};
  f(m, CU_TENSOR_MAP_DATA_TYPE_BFLOAT16, rank, (void*)base, dims, strides, box, es, CU_TENSOR_MAP_INTERLEAVE_NONE, sw,
    CU_TENSOR_MAP_L2_PROMOTION_NONE, CU_TENSOR_MAP_FLOAT_OOB_FILL_NONE);
}

extern "C" void kernel_launch(void* const* d_in, const int* in_sizes, int n_in, void* d_out, int out_size) {
  (void)in_sizes; (void)n_in; (void)out_size;
  static PFN_enc f = nullptr;
  static void *kvT, *y2T, *o;
  if (!f) {
    void* p = nullptr;
    cudaDriverEntryPointQueryResult q;
    cudaGetDriverEntryPoint("cuTensorMapEncodeTiled", &p, cudaEnableDefault, &q);
    f = (PFN_enc)p;
    cudaGetSymbolAddress(&kvT, g_kvT); cudaGetSymbolAddress(&y2T, g_y2T); cudaGetSymbolAddress(&o, g_o);
    cudaFuncSetAttribute(fused_kernel, cudaFuncAttributeMaxDynamicSharedMemorySize, SMEM_BYTES);
  }
  Maps M;
  const CUtensorMapSwizzle S0 = CU_TENSOR_MAP_SWIZZLE_NONE, S32 = CU_TENSOR_MAP_SWIZZLE_32B, S64 = CU_TENSOR_MAP_SWIZZLE_64B, S128 = CU_TENSOR_MAP_SWIZZLE_128B;
  const cuuint64_t dpar[3] = {640, 2, 1024}, spar[2] = {1280, 2560};
  const cuuint64_t dw[3] = {640, 640, 3}, sw[2] = {3840, 1280};
  const cuuint64_t dnat[2] = {640, 2048}, snat[1] = {1280};
  const cuuint64_t dT2[3] = {32, 1280, 64}, sT[2] = {4096, 64};
  const cuuint64_t dwo[2] = {640, 640};
  { const cuuint32_t bx[3] = {64, 1, 128}; enc(f, &M.x_par, d_in[0], 3, dpar, spar, bx, S128); }
  { const cuuint32_t bx[3] = {64, 16, 3}; enc(f, &M.w_main, d_in[7], 3, dw, sw, bx, S128); }
  { const cuuint32_t bx[3] = {16, 16, 3}; enc(f, &M.w_tail, d_in[7], 3, dw, sw, bx, S32); }
  { const cuuint32_t bx[3] = {80, 1, 64}; enc(f, &M.o_st, o, 3, dpar, spar, bx, S0); }
  { const cuuint32_t bx[3] = {32, 64, 1}; enc(f, &M.kv_st, kvT, 3, dT2, sT, bx, S64); }
  { const cuuint32_t bx[3] = {32, 32, 5}; enc(f, &M.y_ld, y2T, 3, dT2, sT, bx, S64); }
  { const cuuint32_t bx[2] = {64, 36}; enc(f, &M.k_ld, d_in[1], 2, dnat, snat, bx, S0); }
  { const cuuint32_t bx[2] = {64, 33}; enc(f, &M.v_ld, d_in[2], 2, dnat, snat, bx, S0); }
  { const cuuint32_t bx[2] = {32, 160}; enc(f, &M.q_ld, d_in[0], 2, dnat, snat, bx, S0); }
  { const cuuint32_t bx[2] = {64, 64}; enc(f, &M.wo, d_in[8], 2, dwo, snat, bx, S128); }
  { const cuuint32_t bx[2] = {64, 80}; enc(f, &M.o_ld, o, 2, dnat, snat, bx, S128); }
  fused_kernel<<<130, 512, SMEM_BYTES, cudaStreamPerThread>>>((const uint16_t*)d_in[0], (const uint16_t*)d_in[7], (const uint16_t*)d_in[9], M, (const uint16_t*)d_in[3], (const uint16_t*)d_in[4], (const uint16_t*)d_in[5],
                                                              (uint16_t*)d_out);
}
```

```cpp
#include <cuda_runtime.h>
#include <cuda_bf16.h>
#include <cuda.h>
#include <stdint.h>

#define DEVI __device__ __forceinline__
#define PT1 300
#define PTD 460
#define PTE 150
#define DEFER 4
#define KPH KTD
#define NLATE 4
#define NPRE 1
#define KT0 1500
#define KTD 1000
#define RC 192
#define RH 96
#define RP 32
#define HOLD 750
#define LEAD 3

DEVI uint32_t smem_u32(const void* p) { return (uint32_t)__cvta_generic_to_shared(p); }
DEVI void wg_fence() { asm volatile("wgmma.fence.sync.aligned;" ::: "memory"); }
DEVI void wg_commit() { asm volatile("wgmma.commit_group.sync.aligned;" ::: "memory"); }
template <int N> DEVI void wg_wait() { asm volatile("wgmma.wait_group.sync.aligned %0;" ::"n"(N) : "memory"); }
template <int A = 0, int B = -1, int S> DEVI void fence_regs(float (&d)[S]) {
#pragma unroll
  for (int i = A; i < (B < 0 ? S : B); i++) asm volatile("" : "+f"(d[i])::"memory");
}
DEVI uint64_t mkdesc(uint32_t addr, uint32_t lbo, uint32_t sbo, int swz) {
  return (uint64_t)((addr & 0x3FFFF) >> 4) | ((uint64_t)(lbo >> 4) << 16) | ((uint64_t)(sbo >> 4) << 32) | ((uint64_t)swz << 62);
}
DEVI void mbar_init(uint32_t bar, uint32_t cnt) { asm volatile("mbarrier.init.shared::cta.b64 [%0], %1;" ::"r"(bar), "r"(cnt) : "memory"); }
DEVI void mbar_expect_tx(uint32_t bar, uint32_t bytes) { asm volatile("mbarrier.arrive.expect_tx.shared::cta.b64 _, [%0], %1;" ::"r"(bar), "r"(bytes) : "memory"); }
DEVI void mbar_arrive(uint32_t bar) { asm volatile("mbarrier.arrive.shared::cta.b64 _, [%0];" ::"r"(bar) : "memory"); }
DEVI void mbar_wait(uint32_t bar, uint32_t parity) {
  asm volatile("{\n.reg .pred p;\nLAB_WAIT:\nmbarrier.try_wait.parity.shared::cta.b64 p, [%0], %1;\n@!p bra LAB_WAIT;\n}" ::"r"(bar), "r"(parity) : "memory");
}
DEVI void mbar_wait_wd(uint32_t bar, uint32_t parity, uint32_t t0) {
  asm volatile("{\n.reg .pred p;\n.reg .u32 c;\nLAB_WAIT:\nmbarrier.try_wait.parity.shared::cta.b64 p, [%0], %1;\n@p bra DONE;\nmov.u32 c, %%clock;\nsub.u32 c, c, %2;\nsetp.lt.u32 p, c, 0x70000000;\n@p bra LAB_WAIT;\ntrap;\nDONE:\n}" ::"r"(bar), "r"(parity), "r"(t0) : "memory");
}
DEVI void flag_wait(const unsigned* p, unsigned target) {
  asm volatile("{\n.reg .pred p;\n.reg .s32 v;\nLAB_WAIT:\nld.relaxed.gpu.global.u32 v, [%0];\nsub.s32 v, v, %1;\nsetp.lt.s32 p, v, 0;\n@p bra LAB_WAIT;\n}" ::"l"(p), "r"(target) : "memory");
}
DEVI void flag_wait_wd(const unsigned* p, unsigned target, uint32_t t0) {
  asm volatile("{\n.reg .pred p;\n.reg .s32 v;\nLAB_WAIT:\nld.relaxed.gpu.global.u32 v, [%0];\nsub.s32 v, v, %1;\nsetp.ge.s32 p, v, 0;\n@p bra DONE;\nmov.u32 v, %%clock;\nsub.s32 v, v, %2;\nsetp.lt.u32 p, v, 0x70000000;\n@p bra LAB_WAIT;\ntrap;\nDONE:\n}" ::"l"(p), "r"(target), "r"(t0) : "memory");
}
DEVI void flag_add(unsigned* p, unsigned v) { asm volatile("red.relaxed.gpu.global.add.u32 [%0], %1;" ::"l"(p), "r"(v) : "memory"); }
DEVI void flag_release(unsigned* p) { asm volatile("fence.proxy.async;\nred.relaxed.gpu.global.add.u32 [%0], 1;" ::"l"(p) : "memory"); }
DEVI void fence_async_smem() { asm volatile("fence.proxy.async.shared::cta;" ::: "memory"); }
DEVI bool elect_one() { uint32_t p; asm volatile("{\n.reg .pred P;\nelect.sync _|P, 0xffffffff;\nselp.u32 %0, 1, 0, P;\n}" : "=r"(p)); return p; }
DEVI void bar_sync(int id, int n) { asm volatile("bar.sync %0, %1;" ::"r"(id), "r"(n) : "memory"); }
DEVI void bar_arrive(int id, int n) { asm volatile("bar.arrive %0, %1;" ::"r"(id), "r"(n) : "memory"); }
DEVI void tma2(uint32_t dst, const CUtensorMap* m, int c0, int c1, uint32_t bar) {
  asm volatile("cp.async.bulk.tensor.2d.shared::cluster.global.mbarrier::complete_tx::bytes [%0], [%1, {%3, %4}], [%2];" ::"r"(dst), "l"(m), "r"(bar), "r"(c0), "r"(c1) : "memory");
}
DEVI void tma3(uint32_t dst, const CUtensorMap* m, int c0, int c1, int c2, uint32_t bar) {
  asm volatile("cp.async.bulk.tensor.3d.shared::cluster.global.mbarrier::complete_tx::bytes [%0], [%1, {%3, %4, %5}], [%2];" ::"r"(dst), "l"(m), "r"(bar), "r"(c0), "r"(c1), "r"(c2) : "memory");
}
DEVI void tma3_mc(uint32_t dst, const CUtensorMap* m, int c0, int c1, int c2, uint32_t bar) {
  asm volatile("cp.async.bulk.tensor.3d.shared::cluster.global.mbarrier::complete_tx::bytes.multicast::cluster [%0], [%1, {%3, %4, %5}], [%2], %6;" ::"r"(dst), "l"(m), "r"(bar), "r"(c0), "r"(c1), "r"(c2), "h"((uint16_t)3) : "memory");
}
DEVI void tma2_mc(uint32_t dst, const CUtensorMap* m, int c0, int c1, uint32_t bar) {
  asm volatile("cp.async.bulk.tensor.2d.shared::cluster.global.mbarrier::complete_tx::bytes.multicast::cluster [%0], [%1, {%3, %4}], [%2], %5;" ::"r"(dst), "l"(m), "r"(bar), "r"(c0), "r"(c1), "h"((uint16_t)3) : "memory");
}
DEVI void mbar_arrive_remote(uint32_t bar, uint32_t cta) {
  asm volatile("{\n.reg .b32 ra;\nmapa.shared::cluster.u32 ra, %0, %1;\nmbarrier.arrive.shared::cluster.b64 _, [ra];\n}" ::"r"(bar), "r"(cta) : "memory");
}
DEVI void tma3_store(const CUtensorMap* m, int c0, int c1, int c2, uint32_t src) {
  asm volatile("cp.async.bulk.tensor.3d.global.shared::cta.bulk_group [%0, {%2, %3, %4}], [%1];" ::"l"(m), "r"(src), "r"(c0), "r"(c1), "r"(c2) : "memory");
}
DEVI void bulk_load(uint32_t dst, const void* src, uint32_t bytes, uint32_t bar) {
  asm volatile("cp.async.bulk.shared::cluster.global.mbarrier::complete_tx::bytes [%0], [%1], %2, [%3];" ::"r"(dst), "l"(src), "r"(bytes), "r"(bar) : "memory");
}
DEVI void bulk_store(void* dst, uint32_t src, uint32_t bytes) {
  asm volatile("cp.async.bulk.global.shared::cta.bulk_group [%0], [%1], %2;" ::"l"(dst), "r"(src), "r"(bytes) : "memory");
}
DEVI void pf_map(const CUtensorMap* m) { asm volatile("prefetch.tensormap [%0];" ::"l"(m) : "memory"); }
DEVI void pf_l2(const void* p) { asm volatile("prefetch.global.L2 [%0];" ::"l"(p)); }
template <int OFF> DEVI uint32_t ldg_v(const void* p) { uint32_t v; asm volatile("ld.volatile.global.b32 %0, [%1 + %2];" : "=r"(v) : "l"(p), "n"(OFF)); return v; }
DEVI void bulk_commit() { asm volatile("cp.async.bulk.commit_group;" ::: "memory"); }
DEVI void bulk_wait_all() { asm volatile("cp.async.bulk.wait_group 0;" ::: "memory"); }
DEVI void bulk_wait_read() { asm volatile("cp.async.bulk.wait_group.read 0;" ::: "memory"); }
template <int R> DEVI void reg_inc() { asm volatile("setmaxnreg.inc.sync.aligned.u32 %0;" ::"n"(R)); }
template <int R> DEVI void reg_dec() { asm volatile("setmaxnreg.dec.sync.aligned.u32 %0;" ::"n"(R)); }
DEVI uint32_t prmt(uint32_t a, uint32_t b, uint32_t s) { uint32_t r; asm("prmt.b32 %0,%1,%2,%3;" : "=r"(r) : "r"(a), "r"(b), "r"(s)); return r; }
DEVI uint32_t lds32(uint32_t a) { uint32_t r; asm volatile("ld.shared.b32 %0,[%1];" : "=r"(r) : "r"(a)); return r; }
DEVI void sts32(uint32_t a, uint32_t x) { asm volatile("st.shared.b32 [%0],%1;" ::"r"(a), "r"(x) : "memory"); }
DEVI void sts128(uint32_t a, uint32_t x, uint32_t y, uint32_t z, uint32_t w) { asm volatile("st.shared.v4.b32 [%0],{%1,%2,%3,%4};" ::"r"(a), "r"(x), "r"(y), "r"(z), "r"(w) : "memory"); }
DEVI void sts128v(uint32_t a, uint32_t x, uint32_t y, uint32_t z, uint32_t w) { asm volatile("st.volatile.shared.v4.b32 [%0],{%1,%2,%3,%4};" ::"r"(a), "r"(x), "r"(y), "r"(z), "r"(w) : "memory"); }
DEVI void lds128(uint32_t a, uint32_t& x, uint32_t& y, uint32_t& z, uint32_t& w) { asm volatile("ld.shared.v4.b32 {%0,%1,%2,%3},[%4];" : "=r"(x), "=r"(y), "=r"(z), "=r"(w) : "r"(a) : "memory"); }
DEVI void ldsm4(uint32_t& r0, uint32_t& r1, uint32_t& r2, uint32_t& r3, uint32_t addr) {
  asm volatile("ldmatrix.sync.aligned.m8n8.x4.shared.b16 {%0,%1,%2,%3}, [%4];" : "=r"(r0), "=r"(r1), "=r"(r2), "=r"(r3) : "r"(addr) : "memory");
}
DEVI void ldsm4t(uint32_t& r0, uint32_t& r1, uint32_t& r2, uint32_t& r3, uint32_t addr) {
  asm volatile("ldmatrix.sync.aligned.m8n8.x4.trans.shared.b16 {%0,%1,%2,%3}, [%4];" : "=r"(r0), "=r"(r1), "=r"(r2), "=r"(r3) : "r"(addr) : "memory");
}
DEVI void stsm4(uint32_t addr, uint32_t r0, uint32_t r1, uint32_t r2, uint32_t r3) {
  asm volatile("stmatrix.sync.aligned.m8n8.x4.shared.b16 [%0], {%1,%2,%3,%4};" ::"r"(addr), "r"(r0), "r"(r1), "r"(r2), "r"(r3) : "memory");
}
DEVI void stsm4t(uint32_t addr, uint32_t r0, uint32_t r1, uint32_t r2, uint32_t r3) {
  asm volatile("stmatrix.sync.aligned.m8n8.x4.trans.shared.b16 [%0], {%1,%2,%3,%4};" ::"r"(addr), "r"(r0), "r"(r1), "r"(r2), "r"(r3) : "memory");
}
DEVI uint32_t movm(uint32_t a) { uint32_t r; asm volatile("movmatrix.sync.aligned.m8n8.trans.b16 %0, %1;" : "=r"(r) : "r"(a)); return r; }
DEVI uint32_t pack_bf16(float lo, float hi) { uint32_t r; asm("cvt.rn.bf16x2.f32 %0, %1, %2;" : "=r"(r) : "f"(hi), "f"(lo)); return r; }
DEVI uint32_t hmul2(uint32_t a, uint32_t b) { uint32_t r; asm("mul.rn.bf16x2 %0,%1,%2;" : "=r"(r) : "r"(a), "r"(b)); return r; }
DEVI uint32_t hadd2(uint32_t a, uint32_t b) { uint32_t r; asm("add.rn.bf16x2 %0,%1,%2;" : "=r"(r) : "r"(a), "r"(b)); return r; }
DEVI float bf_lo(uint32_t a) { return __uint_as_float(prmt(a, 0, 0x1044)); }
DEVI float bf_hi(uint32_t a) { return __uint_as_float(a & 0xFFFF0000u); }
DEVI void mma16(float (&c)[4], uint32_t a0, uint32_t a1, uint32_t a2, uint32_t a3, uint32_t b0, uint32_t b1) {
  asm volatile("mma.sync.aligned.m16n8k16.row.col.f32.bf16.bf16.f32 {%0,%1,%2,%3},{%4,%5,%6,%7},{%8,%9},{%0,%1,%2,%3};"
      : "+f"(c[0]), "+f"(c[1]), "+f"(c[2]), "+f"(c[3]) : "r"(a0), "r"(a1), "r"(a2), "r"(a3), "r"(b0), "r"(b1));
}
DEVI void mma8(float (&c)[4], uint32_t a0, uint32_t a1, uint32_t b0) {
  asm volatile("mma.sync.aligned.m16n8k8.row.col.f32.bf16.bf16.f32 {%0,%1,%2,%3},{%4,%5},{%6},{%0,%1,%2,%3};"
      : "+f"(c[0]), "+f"(c[1]), "+f"(c[2]), "+f"(c[3]) : "r"(a0), "r"(a1), "r"(b0));
}
DEVI float ex2(float x) { float r; asm volatile("ex2.approx.ftz.f32 %0, %1;" : "=f"(r) : "f"(x)); return r; }

DEVI uint32_t clk() { uint32_t c; asm volatile("mov.u32 %0, %%clock;" : "=r"(c)); return c; }
DEVI void wait_until(uint32_t t0, int dt) { while ((int)(clk() - t0) < dt) __nanosleep(40); }
DEVI void spin_until(uint32_t t0, int dt) { while ((int)(clk() - t0) < dt) {} }
DEVI uint32_t hfma2(uint32_t a, uint32_t b, uint32_t c) { uint32_t r; asm("fma.rn.bf16x2 %0,%1,%2,%3;" : "=r"(r) : "r"(a), "r"(b), "r"(c)); return r; }
DEVI void bar_sync_p(int on, int id, int n) { asm volatile("{\n.reg .pred p;\nsetp.ne.b32 p, %0, 0;\n@p bar.sync %1, %2;\n}" ::"r"(on), "r"(id), "r"(n) : "memory"); }
DEVI void bar_arrive_p(int on, int id, int n) { asm volatile("{\n.reg .pred p;\nsetp.ne.b32 p, %0, 0;\n@p bar.arrive %1, %2;\n}" ::"r"(on), "r"(id), "r"(n) : "memory"); }
DEVI void mbar_arrive_p(int on, uint32_t bar) { asm volatile("{\n.reg .pred p;\nsetp.ne.b32 p, %1, 0;\n@p mbarrier.arrive.shared::cta.b64 _, [%0];\n}" ::"r"(bar), "r"(on) : "memory"); }
DEVI void mbar_arrive2_p(int on, uint32_t bar, uint32_t rbar) {
  asm volatile("{\n.reg .pred p;\nsetp.ne.b32 p, %2, 0;\n@p mbarrier.arrive.shared::cta.b64 _, [%0];\n@p mbarrier.arrive.shared::cluster.b64 _, [%1];\n}" ::"r"(bar), "r"(rbar), "r"(on) : "memory");
}
DEVI void st_relaxed(uint4* p, uint32_t x, uint32_t y, uint32_t z, uint32_t w) {
  asm volatile("st.relaxed.gpu.global.v4.b32 [%0], {%1,%2,%3,%4};" ::"l"(p), "r"(x), "r"(y), "r"(z), "r"(w) : "memory");
}
DEVI uint32_t mapa(uint32_t a, uint32_t cta) { uint32_t r; asm("mapa.shared::cluster.u32 %0, %1, %2;" : "=r"(r) : "r"(a), "r"(cta)); return r; }
DEVI void st_async128(uint32_t a, uint32_t x, uint32_t y, uint32_t z, uint32_t w, uint32_t bar) {
  asm volatile("st.async.weak.shared::cluster.mbarrier::complete_tx::bytes.v4.b32 [%0], {%1,%2,%3,%4}, [%5];" ::"r"(a), "r"(x), "r"(y), "r"(z), "r"(w), "r"(bar) : "memory");
}

template<int OFF, int TB, int S> __device__ __forceinline__ void wgmma_rs_n128(float (&d)[S], uint32_t a0, uint32_t a1, uint32_t a2, uint32_t a3, uint64_t db, int sd) {
  asm volatile("{\n.reg .pred p;\nsetp.ne.b32 p, %69, 0;\n"
    "wgmma.mma_async.sync.aligned.m64n128k16.f32.bf16.bf16 {%0, %1, %2, %3, %4, %5, %6, %7, %8, %9, %10, %11, %12, %13, %14, %15, %16, %17, %18, %19, %20, %21, %22, %23, %24, %25, %26, %27, %28, %29, %30, %31, %32, %33, %34, %35, %36, %37, %38, %39, %40, %41, %42, %43, %44, %45, %46, %47, %48, %49, %50, %51, %52, %53, %54, %55, %56, %57, %58, %59, %60, %61, %62, %63}, {%64, %65, %66, %67}, %68, p, 1, 1, %70;\n}\n"
    : "+f"(d[OFF+0]), "+f"(d[OFF+1]), "+f"(d[OFF+2]), "+f"(d[OFF+3]), "+f"(d[OFF+4]), "+f"(d[OFF+5]), "+f"(d[OFF+6]), "+f"(d[OFF+7]), "+f"(d[OFF+8]), "+f"(d[OFF+9]), "+f"(d[OFF+10]), "+f"(d[OFF+11]), "+f"(d[OFF+12]), "+f"(d[OFF+13]), "+f"(d[OFF+14]), "+f"(d[OFF+15]), "+f"(d[OFF+16]), "+f"(d[OFF+17]), "+f"(d[OFF+18]), "+f"(d[OFF+19]), "+f"(d[OFF+20]), "+f"(d[OFF+21]), "+f"(d[OFF+22]), "+f"(d[OFF+23]), "+f"(d[OFF+24]), "+f"(d[OFF+25]), "+f"(d[OFF+26]), "+f"(d[OFF+27]), "+f"(d[OFF+28]), "+f"(d[OFF+29]), "+f"(d[OFF+30]), "+f"(d[OFF+31]), "+f"(d[OFF+32]), "+f"(d[OFF+33]), "+f"(d[OFF+34]), "+f"(d[OFF+35]), "+f"(d[OFF+36]), "+f"(d[OFF+37]), "+f"(d[OFF+38]), "+f"(d[OFF+39]), "+f"(d[OFF+40]), "+f"(d[OFF+41]), "+f"(d[OFF+42]), "+f"(d[OFF+43]), "+f"(d[OFF+44]), "+f"(d[OFF+45]), "+f"(d[OFF+46]), "+f"(d[OFF+47]), "+f"(d[OFF+48]), "+f"(d[OFF+49]), "+f"(d[OFF+50]), "+f"(d[OFF+51]), "+f"(d[OFF+52]), "+f"(d[OFF+53]), "+f"(d[OFF+54]), "+f"(d[OFF+55]), "+f"(d[OFF+56]), "+f"(d[OFF+57]), "+f"(d[OFF+58]), "+f"(d[OFF+59]), "+f"(d[OFF+60]), "+f"(d[OFF+61]), "+f"(d[OFF+62]), "+f"(d[OFF+63]) : "r"(a0), "r"(a1), "r"(a2), "r"(a3), "l"(db), "r"(sd), "n"(TB));
}
template<int OFF, int TB, int S> __device__ __forceinline__ void wgmma_rs_n64(float (&d)[S], uint32_t a0, uint32_t a1, uint32_t a2, uint32_t a3, uint64_t db, int sd) {
  asm volatile("{\n.reg .pred p;\nsetp.ne.b32 p, %37, 0;\n"
    "wgmma.mma_async.sync.aligned.m64n64k16.f32.bf16.bf16 {%0, %1, %2, %3, %4, %5, %6, %7, %8, %9, %10, %11, %12, %13, %14, %15, %16, %17, %18, %19, %20, %21, %22, %23, %24, %25, %26, %27, %28, %29, %30, %31}, {%32, %33, %34, %35}, %36, p, 1, 1, %38;\n}\n"
    : "+f"(d[OFF+0]), "+f"(d[OFF+1]), "+f"(d[OFF+2]), "+f"(d[OFF+3]), "+f"(d[OFF+4]), "+f"(d[OFF+5]), "+f"(d[OFF+6]), "+f"(d[OFF+7]), "+f"(d[OFF+8]), "+f"(d[OFF+9]), "+f"(d[OFF+10]), "+f"(d[OFF+11]), "+f"(d[OFF+12]), "+f"(d[OFF+13]), "+f"(d[OFF+14]), "+f"(d[OFF+15]), "+f"(d[OFF+16]), "+f"(d[OFF+17]), "+f"(d[OFF+18]), "+f"(d[OFF+19]), "+f"(d[OFF+20]), "+f"(d[OFF+21]), "+f"(d[OFF+22]), "+f"(d[OFF+23]), "+f"(d[OFF+24]), "+f"(d[OFF+25]), "+f"(d[OFF+26]), "+f"(d[OFF+27]), "+f"(d[OFF+28]), "+f"(d[OFF+29]), "+f"(d[OFF+30]), "+f"(d[OFF+31]) : "r"(a0), "r"(a1), "r"(a2), "r"(a3), "l"(db), "r"(sd), "n"(TB));
}
template<int OFF, int TB, int S> __device__ __forceinline__ void wgmma_rs_n48(float (&d)[S], uint32_t a0, uint32_t a1, uint32_t a2, uint32_t a3, uint64_t db, int sd) {
  asm volatile("{\n.reg .pred p;\nsetp.ne.b32 p, %29, 0;\n"
    "wgmma.mma_async.sync.aligned.m64n48k16.f32.bf16.bf16 {%0, %1, %2, %3, %4, %5, %6, %7, %8, %9, %10, %11, %12, %13, %14, %15, %16, %17, %18, %19, %20, %21, %22, %23}, {%24, %25, %26, %27}, %28, p, 1, 1, %30;\n}\n"
    : "+f"(d[OFF+0]), "+f"(d[OFF+1]), "+f"(d[OFF+2]), "+f"(d[OFF+3]), "+f"(d[OFF+4]), "+f"(d[OFF+5]), "+f"(d[OFF+6]), "+f"(d[OFF+7]), "+f"(d[OFF+8]), "+f"(d[OFF+9]), "+f"(d[OFF+10]), "+f"(d[OFF+11]), "+f"(d[OFF+12]), "+f"(d[OFF+13]), "+f"(d[OFF+14]), "+f"(d[OFF+15]), "+f"(d[OFF+16]), "+f"(d[OFF+17]), "+f"(d[OFF+18]), "+f"(d[OFF+19]), "+f"(d[OFF+20]), "+f"(d[OFF+21]), "+f"(d[OFF+22]), "+f"(d[OFF+23]) : "r"(a0), "r"(a1), "r"(a2), "r"(a3), "l"(db), "r"(sd), "n"(TB));
}
template<int OFF, int TB, int S> __device__ __forceinline__ void wgmma_rs_n16(float (&d)[S], uint32_t a0, uint32_t a1, uint32_t a2, uint32_t a3, uint64_t db, int sd) {
  asm volatile("{\n.reg .pred p;\nsetp.ne.b32 p, %13, 0;\n"
    "wgmma.mma_async.sync.aligned.m64n16k16.f32.bf16.bf16 {%0, %1, %2, %3, %4, %5, %6, %7}, {%8, %9, %10, %11}, %12, p, 1, 1, %14;\n}\n"
    : "+f"(d[OFF+0]), "+f"(d[OFF+1]), "+f"(d[OFF+2]), "+f"(d[OFF+3]), "+f"(d[OFF+4]), "+f"(d[OFF+5]), "+f"(d[OFF+6]), "+f"(d[OFF+7]) : "r"(a0), "r"(a1), "r"(a2), "r"(a3), "l"(db), "r"(sd), "n"(TB));
}
template<int OFF, int TA, int TB, int S> __device__ __forceinline__ void wgmma_ss_n160(float (&d)[S], uint64_t da, uint64_t db, int sd) {
  asm volatile("{\n.reg .pred p;\nsetp.ne.b32 p, %82, 0;\n"
    "wgmma.mma_async.sync.aligned.m64n160k16.f32.bf16.bf16 {%0, %1, %2, %3, %4, %5, %6, %7, %8, %9, %10, %11, %12, %13, %14, %15, %16, %17, %18, %19, %20, %21, %22, %23, %24, %25, %26, %27, %28, %29, %30, %31, %32, %33, %34, %35, %36, %37, %38, %39, %40, %41, %42, %43, %44, %45, %46, %47, %48, %49, %50, %51, %52, %53, %54, %55, %56, %57, %58, %59, %60, %61, %62, %63, %64, %65, %66, %67, %68, %69, %70, %71, %72, %73, %74, %75, %76, %77, %78, %79}, %80, %81, p, 1, 1, %83, %84;\n}\n"
    : "+f"(d[OFF+0]), "+f"(d[OFF+1]), "+f"(d[OFF+2]), "+f"(d[OFF+3]), "+f"(d[OFF+4]), "+f"(d[OFF+5]), "+f"(d[OFF+6]), "+f"(d[OFF+7]), "+f"(d[OFF+8]), "+f"(d[OFF+9]), "+f"(d[OFF+10]), "+f"(d[OFF+11]), "+f"(d[OFF+12]), "+f"(d[OFF+13]), "+f"(d[OFF+14]), "+f"(d[OFF+15]), "+f"(d[OFF+16]), "+f"(d[OFF+17]), "+f"(d[OFF+18]), "+f"(d[OFF+19]), "+f"(d[OFF+20]), "+f"(d[OFF+21]), "+f"(d[OFF+22]), "+f"(d[OFF+23]), "+f"(d[OFF+24]), "+f"(d[OFF+25]), "+f"(d[OFF+26]), "+f"(d[OFF+27]), "+f"(d[OFF+28]), "+f"(d[OFF+29]), "+f"(d[OFF+30]), "+f"(d[OFF+31]), "+f"(d[OFF+32]), "+f"(d[OFF+33]), "+f"(d[OFF+34]), "+f"(d[OFF+35]), "+f"(d[OFF+36]), "+f"(d[OFF+37]), "+f"(d[OFF+38]), "+f"(d[OFF+39]), "+f"(d[OFF+40]), "+f"(d[OFF+41]), "+f"(d[OFF+42]), "+f"(d[OFF+43]), "+f"(d[OFF+44]), "+f"(d[OFF+45]), "+f"(d[OFF+46]), "+f"(d[OFF+47]), "+f"(d[OFF+48]), "+f"(d[OFF+49]), "+f"(d[OFF+50]), "+f"(d[OFF+51]), "+f"(d[OFF+52]), "+f"(d[OFF+53]), "+f"(d[OFF+54]), "+f"(d[OFF+55]), "+f"(d[OFF+56]), "+f"(d[OFF+57]), "+f"(d[OFF+58]), "+f"(d[OFF+59]), "+f"(d[OFF+60]), "+f"(d[OFF+61]), "+f"(d[OFF+62]), "+f"(d[OFF+63]), "+f"(d[OFF+64]), "+f"(d[OFF+65]), "+f"(d[OFF+66]), "+f"(d[OFF+67]), "+f"(d[OFF+68]), "+f"(d[OFF+69]), "+f"(d[OFF+70]), "+f"(d[OFF+71]), "+f"(d[OFF+72]), "+f"(d[OFF+73]), "+f"(d[OFF+74]), "+f"(d[OFF+75]), "+f"(d[OFF+76]), "+f"(d[OFF+77]), "+f"(d[OFF+78]), "+f"(d[OFF+79]) : "l"(da), "l"(db), "r"(sd), "n"(TA), "n"(TB));
}

__device__ __align__(1024) uint16_t g_kvT[2 * 640 * 2048];
__device__ __align__(1024) uint16_t g_y2T[2 * 640 * 2048];
__device__ __align__(1024) uint16_t g_o[2048 * 640];
__device__ __align__(1024) uint16_t g_gate[2080];
__device__ __align__(1024) uint4 g_halo[128 * 5 * 32];
__device__ __align__(1024) unsigned g_cnt[46 * 32];
__device__ __align__(1024) unsigned g_launch[132 * 32];
#define CNT_KV(i) (g_cnt + 32 * (i))
#define CNT_O(i) (g_cnt + 32 * (10 + (i)))
#define CNT_Y(i) (g_cnt + 32 * (26 + (i)))
#define PTL(i) do {} while (0)
#define PTPL(on, i) do {} while (0)
#define PT(i) do {} while (0)
#define PTP(on, i) do {} while (0)

constexpr uint32_t SB = 1024;
constexpr uint32_t STG = 23552, WST = 15360;
DEVI constexpr uint32_t o_px(int ks) { return (((ks >> 1) + 1) & 3) * 2 * STG; }
DEVI constexpr uint32_t o_pw(int ks) { return o_px(ks) + 16384 + (ks & 1) * WST; }
constexpr uint32_t O_HALO = 0, O_QT = STG;
constexpr uint32_t O_OST = 2 * STG;
constexpr uint32_t P3S = 28672;
constexpr uint32_t HC = 8320, UC = 4624, UZ = 528;
constexpr uint32_t O_H0 = 5 * P3S, O_U2 = O_H0 + 3 * HC, O_H3 = O_U2 + UC, O_U0 = O_H3 + 2 * HC;
DEVI constexpr uint32_t o_h(int c) { return O_H0 + c * HC + (c > 2 ? UC : 0); }
DEVI constexpr uint32_t o_u(int c) { return c == 2 ? O_U2 : O_U0 + (c > 2 ? c - 1 : c) * UC; }
constexpr uint32_t O_Y = 208896;
DEVI constexpr uint32_t o_x(int c) { return c < 2 ? O_Y + c * 5120 : O_U0 + (c & 1) * UC; }
constexpr uint32_t O_HIN = O_Y + 16384;
DEVI constexpr uint32_t o_kin(int c) { return ((O_U0 + 127) & ~127u) + ((c & 1) ? 0 : 73 * 128); }
DEVI constexpr uint32_t o_p3(int ks) { return (ks < 6 ? ks : ks - 6) * P3S; }
constexpr uint32_t O_BT = 4 * P3S;
constexpr uint32_t O_GT = O_Y + 20480, O_GW = O_GT + 320;
constexpr uint32_t O_BAR = 231040;
constexpr uint32_t B_FULL = O_BAR, B_EMPTY = O_BAR + 8 * 8, B_P3F = O_BAR + 8 * 16, B_P3R = O_BAR + 8 * 26, B_G = O_BAR + 8 * 27, B_U = O_BAR + 8 * 28,
                   B_KVD = O_BAR + 8 * 33, B_KF = O_BAR + 8 * 36, B_Y = O_BAR + 8 * 38, B_EP = O_BAR + 8 * 40, B_LAST = O_BAR + 8 * 41, B_DONE = O_BAR + 8 * 42,
                   B_P1E = O_BAR + 8 * 43, B_HX = O_BAR + 8 * 43  , B_P3E = O_BAR + 8 * 52, B_HX0 = O_BAR + 8 * 57, B_KVS = O_BAR + 8 * 58, B_QD = O_BAR + 8 * 60, B_GD = O_BAR + 8 * 61, B_OR = O_BAR + 8 * 62, B_Q = O_BAR + 8 * 51;
constexpr uint32_t B_S13 = B_EMPTY + 8 * 5, B_S15 = B_EMPTY + 8 * 7, B_S19 = B_EMPTY + 8 * 3;
constexpr uint32_t O_GP = O_BAR + 512, O_EPOCH = O_GW + 1280;
constexpr uint32_t SMEM_BYTES = 232448;
static_assert(O_U0 + 4 * UC <= O_Y - 512 && o_kin(0) >= O_U0 + 2 * UC && O_EPOCH + 4 <= O_BAR && O_U0 >= 8 * STG, "smem map");
enum { NB_LEAD = 1, NB_HELP = 2, NB_HALO = 3, NB_ATT = 4, NB_G = 5, NB_TOK = 6, NB_RFULL = 8, NB_RFREE = 10 };

struct Maps { CUtensorMap x_par, w_main, w_tail, k_ld, v_ld, o_st, kv_st, wo, o_ld, y_ld, q_ld; };

template <int M> DEVI void conv_step(float (&acc)[128], uint32_t a0, uint32_t a1, uint32_t a2, uint32_t a3, uint32_t dl) {
  auto D = [&](int off) { return ((uint64_t)8 << 32) | (uint64_t)(uint32_t)(dl + off - 16 * M); };
  if constexpr (M == 0) wgmma_rs_n16<0, 0>(acc, a0, a1, a2, a3, D(0), 0);
  if constexpr (M <= 3) wgmma_rs_n48<8, 0>(acc, a0, a1, a2, a3, D(16), M == 0 ? 0 : 1);
  if constexpr (M <= 6) wgmma_rs_n48<32, 0>(acc, a0, a1, a2, a3, D(64), M == 0 ? 0 : 1);
  if constexpr (M <= 9) wgmma_rs_n48<56, 0>(acc, a0, a1, a2, a3, D(112), M == 0 ? 0 : 1);
  if constexpr (M <= 12) wgmma_rs_n48<80, 0>(acc, a0, a1, a2, a3, D(160), M == 0 ? 0 : 1);
  wgmma_rs_n48<104, 0>(acc, a0, a1, a2, a3, D(208), M == 0 ? 0 : 1);
}
DEVI constexpr int a_off(int P, int i) { return -4 * (64 * ((i & 4) ? 15 - P : P) + (i & 1) * 32 - (i & 2) * 2); }
template <int P> DEVI void load_pair(uint32_t (&a)[8], uint32_t ab) {
#pragma unroll
  for (int i = 0; i < 8; i++) a[i] = lds32(ab + a_off(P, i));
}
template <int P> DEVI void mma_pair(float (&acc)[128], uint32_t (&a)[8], uint32_t db) {
  wg_fence();
  conv_step<P>(acc, a[0], a[1], a[2], a[3], db);
  conv_step<15 - P>(acc, a[4], a[5], a[6], a[7], db);
  wg_commit();
}

template <int I0, int I1> DEVI void conv_reduce(uint32_t sb, int c, int ht, int chan, int bar, int nthr) {
  const uint32_t a0 = sb + o_h(c) + ht * 16, a2 = sb + o_u(c) + ht * 16, a3 = sb + o_x(c) + ht * 16;
  uint4* yp = (uint4*)(g_y2T + (size_t)chan * 2048) + ht;
#pragma unroll
  for (int i = I0; i < I1; i++) {
    uint4 p, q, r, s;
    if (i == I0) bar_sync(bar, nthr);
    lds128(a0 + i * 2048, p.x, p.y, p.z, p.w); lds128(a0 + 4160 + i * 2048, q.x, q.y, q.z, q.w);
    lds128(a2 + i * 2048, r.x, r.y, r.z, r.w); lds128(a3 + i * 2048, s.x, s.y, s.z, s.w);
    auto sum = [](uint32_t a, uint32_t b, uint32_t c, uint32_t d) { return hadd2(hadd2(hadd2(a, b), 0u), hadd2(c, d)) ^ 0x80008000u; };
    yp[i * 128] = make_uint4(sum(p.x, q.x, r.x, s.x), sum(p.y, q.y, r.y, s.y), sum(p.z, q.z, r.z, s.z), sum(p.w, q.w, r.w, s.w));
  }
}

template <int ODD, int PART> DEVI void pack_qkv(const float (&acc)[120], uint32_t (&Q)[10][2], uint32_t (&K)[10][2], uint32_t (&V)[10][2]) {
#pragma unroll
  for (int f = 0; f < 10; f++) {
    const bool tail = ODD ? (f < 2) : (f >= 8);
    const int fm = ODD ? f - 2 : f, ft = ODD ? f : f - 8;
    const int nq = tail ? 24 + ft : fm, nk = tail ? 26 + ft : 8 + fm, nv = tail ? 28 + ft : 16 + fm;
    if (PART == 0) { K[f][1] = pack_bf16(acc[4 * nk + 2], acc[4 * nk + 3]); V[f][1] = pack_bf16(acc[4 * nv + 2], acc[4 * nv + 3]); }
    if (PART == 1) { V[f][0] = pack_bf16(acc[4 * nv], acc[4 * nv + 1]); K[f][0] = pack_bf16(acc[4 * nk], acc[4 * nk + 1]); }
    if (PART == 2) { Q[f][0] = pack_bf16(acc[4 * nq], acc[4 * nq + 1]); Q[f][1] = pack_bf16(acc[4 * nq + 2], acc[4 * nq + 3]); }
  }
}
DEVI int pair_of(int c) {
  const int lo = 32 + 8 * c, hi = c - 4 + ((max(c - 29, 0) * 37) >> 8);
  int p; asm("{\n.reg .pred q;\nsetp.lt.s32 q, %1, 4;\nselp.b32 %0, %2, %3, q;\n}" : "=r"(p) : "r"(c), "r"(lo), "r"(hi));
  return p;
}
DEVI uint32_t make_ctx() {
  int b; asm volatile("mov.u32 %0, %%ctaid.x;" : "=r"(b));
  b += clk() & threadIdx.y;
  const int p = pair_of(b >> 1);
  const int j = b < 128 ? 8 * (p & 7) + (p >> 3) : 64;
  const int q = (j * 205) >> 10, r = j - 5 * q, i = j - q, co = (i * 79) >> 10;
  const int cp = r == 4 ? 4 : co, tb = r == 4 ? q : i - 13 * co;
  return ((2 * p + (b & 1)) & 255) | tb << 8 | (2 * cp + (b & 1)) << 12 | (b >> 7) << 16;
}
#define CTX() asm volatile("" : "+r"(ctx)); CTXU()
#define CTXU() int tid; asm volatile("mov.u32 %0, %%tid.x;" : "=r"(tid)); \
  const int lane = tid & 31, vb = ctx & 255, hg = (ctx >> 4) & 7, rt = ctx & 15, par = (ctx >> 3) & 1, mt = ctx & 7, rank = ctx & 1, \
  tb = (ctx >> 8) & 15, cb = (ctx >> 12) & 15; const bool main_cta = ctx < 65536; \
  (void)tid; (void)lane; (void)vb; (void)hg; (void)rt; (void)par; (void)mt; (void)rank; (void)tb; (void)cb; (void)main_cta
#define CTXW() CTX(); const int wg = warp >> 2, w = warp & 3, g = lane >> 2, t = lane & 3; const bool lead = (tid & 127) == 0; \
  (void)wg; (void)w; (void)g; (void)t; (void)lead

__global__ void __cluster_dims__(2, 1, 1) __launch_bounds__(512, 1)
fused_kernel(const uint16_t* __restrict__ xq, const uint16_t* __restrict__ wqkv, const uint16_t* __restrict__ gate_w, const __grid_constant__ Maps M, const uint16_t* __restrict__ shift_k, const uint16_t* __restrict__ ssm_k, const uint16_t* __restrict__ ssm_D,
             uint16_t* __restrict__ outp) {
  extern __shared__ __align__(1024) uint8_t smem_raw[];
  const uint32_t sb = smem_u32(smem_raw);
  const uint32_t t0 = clk();
  auto get_epoch = [&]() { mbar_wait(sb + B_EP, 0); return lds32(sb + O_EPOCH); };

  auto p1_load_x = [&](int ks, int p, int rank) {
    tma3(sb + o_px(ks), &M.x_par, ks * 32, (p >> 2) & 1, (p & 3) * 256 + rank * 128, sb + B_FULL + 8 * (ks & 7));
  };
  auto p1_load_w = [&](int ks, int p, int rank) {
    const uint32_t st = sb + o_pw(ks), fb = sb + B_FULL + 8 * (ks & 7);
    tma3_mc(st + rank * 6144, &M.w_main, (p >> 3) * 80 + 2 * (p & 8), ks * 32 + rank * 16, 0, fb);
    tma3_mc(st + 12288 + rank * 1536, &M.w_tail, (p >> 3) * 80 + 8 * (~p & 8), ks * 32 + rank * 16, 0, fb);
  };
  auto cta_pair = [&]() { return pair_of(blockIdx.x >> 1); };

  if (threadIdx.x < 32) {
    const unsigned b = blockIdx.x, l = threadIdx.x;
    const uint16_t* pfp = l < 16 ? xq + (16 * b + l) * 640 : wqkv + (15 * b + l - 16) * 64;
    if ((l | b >> 7 << 5) < 31) pf_l2(pfp);
  }
  const int warp = __shfl_sync(~0u, threadIdx.x >> 5, 0);
  if ((warp & 14) == 8) {
    if (elect_one()) {
#pragma unroll
      for (int s = 0; s < 8; s++) mbar_init(sb + O_BAR - 512 + 64 * warp + 8 * s, 5 * warp - 39);
      asm volatile("fence.mbarrier_init.release.cluster;" ::: "memory");
    }
    __syncwarp();
  }
  asm volatile("barrier.cluster.arrive.relaxed.aligned;" ::: "memory");
  if (warp == 8 && blockIdx.x < 128) {
    const int p = cta_pair(), rank = blockIdx.x & 1;
    if (elect_one()) { mbar_expect_tx(sb + B_FULL, 16384 + WST); p1_load_x(0, p, rank); }
    __syncwarp();
    asm volatile("barrier.cluster.wait.aligned;" ::: "memory");
    if (elect_one()) {
      p1_load_w(0, p, rank); PT(100);
      pf_map(&M.k_ld); pf_map(&M.v_ld);
    }
    __syncwarp();
  } else if (warp != 15) {
    asm volatile("barrier.cluster.wait.aligned;" ::: "memory");
    spin_until(t0, HOLD);
  }
  auto cluster_sync = [&]() {
    asm volatile("barrier.cluster.arrive.relaxed.aligned;" ::: "memory");
    asm volatile("barrier.cluster.wait.aligned;" ::: "memory");
  };
  auto init_rest = [&]() {
    if (warp >= 11 && elect_one()) {
#pragma unroll
      for (int s = 0; s < 12; s++) mbar_init(sb + O_BAR + 128 - 11 * 96 + 96 * warp + 8 * s, warp == 14 ? 2 : 1);
      asm volatile("fence.mbarrier_init.release.cluster;" ::: "memory");
    }
    __syncwarp();
    if (blockIdx.x < 128) bar_sync(0, 224); else cluster_sync();
  };
  uint32_t ctx = 0;

  if (warp < 8) {
    reg_inc<RC>();
    ctx = make_ctx();
    if (blockIdx.x >= 128) cluster_sync();
    else {
      {
        uint32_t Q[10][2], K[10][2], V[10][2];
        {
          {
            float acc[120];
            CTXW();
            const int odd = (cta_pair() >> 3) & 1;
            const uint32_t rsb = mapa(sb, (blockIdx.x & 1) ^ 1);
            {
              const uint32_t aa = sb + (warp * 16 + (lane & 15)) * 128 + (((lane >> 4) ^ (lane & 7)) << 4);
              constexpr int NA = DEFER > 3 ? DEFER : 3;
              uint32_t a[NA][8];
              auto load_a = [&](int ks) {
                uint32_t(&r)[8] = a[ks % NA];
                mbar_wait(sb + B_FULL + 8 * (ks & 7), (ks >> 3) & 1);
                PTP(lead && (wg || !(ks & 3)), wg ? 60 + ks : 80 + (ks >> 2));
                ldsm4(r[0], r[1], r[2], r[3], (aa ^ ((ks & 1) * 64)) + o_px(ks)); ldsm4(r[4], r[5], r[6], r[7], (aa ^ ((ks & 1) * 64 + 32)) + o_px(ks));
              };
              auto mma_q = [&](int ks, int h) {
                uint32_t(&r)[8] = a[ks % NA];
                wgmma_rs_n64<0, 1>(acc, r[4 * h], r[4 * h + 1], r[4 * h + 2], r[4 * h + 3], mkdesc(SB + o_pw(ks) + h * 6144, 2048, 1024, 1), ks | h);
              };
              auto mma_step = [&](int ks, int h) {
                uint32_t(&r)[8] = a[ks % NA];
                wg_fence();
                wgmma_rs_n128<32, 1>(acc, r[4 * h], r[4 * h + 1], r[4 * h + 2], r[4 * h + 3], mkdesc(SB + o_pw(ks) + h * 6144 + 2048, 2048, 1024, 1), ks | h);
                if (ks < 20 - DEFER) mma_q(ks, h);
                wgmma_rs_n48<96, 1>(acc, r[4 * h], r[4 * h + 1], r[4 * h + 2], r[4 * h + 3], mkdesc(SB + o_pw(ks) + 12288 + h * 1536, 512, 256, 3), ks | h);
                wg_commit();
              };
              if (lead) PT(1 + wg);
              load_a(0);
#pragma unroll
              for (int ks = 0; ks < 20; ks++) {
                if (LEAD && ks == 20 - LEAD) bar_sync_p(wg == 0, NB_LEAD, 256);
                mma_step(ks, 0);
                if (ks < 19 && ks >= NLATE) load_a(ks + 1);
                mma_step(ks, 1);
                if (ks < NLATE) load_a(ks + 1);
                if (ks >= 1 && ks <= 16) {
                  wg_wait<2>();
                  mbar_arrive2_p(lead, sb + B_EMPTY + 8 * ((ks - 1) & 7), rsb + B_EMPTY + 8 * ((ks - 1) & 7));
                } else if (ks < 19 && ks + 2 - NA >= 16) wg_wait<2>();
              }
              if (LEAD) bar_arrive_p(wg, NB_LEAD, 256);
              if (DEFER) {
                wg_fence();
#pragma unroll
                for (int i = 40 - 2 * DEFER; i < 40; i++) mma_q(i >> 1, i & 1);
                wg_commit();
              }
              mbar_wait(sb + B_S15, 1);
              wg_wait<1>();
              mbar_arrive_p(tid == 0, sb + B_P1E);
              if (!DEFER) wg_wait<0>();
              fence_regs<32, 120>(acc);
              PTPL(lead, 158 + wg);
            }
            if (odd) pack_qkv<1, 0>(acc, Q, K, V); else pack_qkv<0, 0>(acc, Q, K, V);
            if (warp == 7 && (blockIdx.x & 1)) {
              uint4* hp = g_halo + vb * 160 + lane;
              st_relaxed(hp, K[0][1], K[1][1], K[3][1], K[4][1]); st_relaxed(hp + 32, K[5][1], K[6][1], K[8][1], K[9][1]);
              st_relaxed(hp + 64, K[2][1], K[7][1], V[0][1], V[1][1]);
              st_relaxed(hp + 96, V[2][1], V[3][1], V[4][1], V[5][1]); st_relaxed(hp + 128, V[6][1], V[7][1], V[8][1], V[9][1]);
            }
            const uint32_t ho = sb + O_HALO + warp * 2560 + lane * 16;
            stsm4(ho, K[0][1], K[1][1], K[3][1], K[4][1]); stsm4(ho + 512, K[5][1], K[6][1], K[8][1], K[9][1]);
            stsm4(ho + 1024, K[2][1], K[7][1], V[0][1], V[1][1]);
            stsm4(ho + 1536, V[2][1], V[3][1], V[4][1], V[5][1]); stsm4(ho + 2048, V[6][1], V[7][1], V[8][1], V[9][1]);
            if (warp == 7) {
              if (!(blockIdx.x & 1)) {
                fence_async_smem();
                __syncwarp();
                if (elect_one())
                  asm volatile("cp.async.bulk.shared::cluster.shared::cta.mbarrier::complete_tx::bytes [%0], [%1], 2560, [%2];"
                               ::"r"(mapa(sb + O_HIN, 1)), "r"(sb + O_HALO + 7 * 2560), "r"(mapa(sb + B_HX0, 1)) : "memory");
              }
              __syncwarp();
            } else {
              __syncwarp();
              if (lane == 0) mbar_arrive(sb + B_HX + 8 + 8 * warp);
            }
            if (odd) pack_qkv<1, 1>(acc, Q, K, V); else pack_qkv<0, 1>(acc, Q, K, V);
            wg_wait<0>();
            fence_regs<0, 32>(acc);
            PTPL(lead, 50 + wg);
            mbar_arrive2_p(lead, sb + B_S19, rsb + B_S19);
            if (odd) pack_qkv<1, 2>(acc, Q, K, V); else pack_qkv<0, 2>(acc, Q, K, V);
#pragma unroll
            for (int f = 0; f < 10; f++) V[f][0] = movm(V[f][0]);
            if (lead) PT(52 + wg);
            if (wg) mbar_wait(sb + B_P1E, 0);
          }
          CTXW();
          uint32_t z = threadIdx.y;
          const bool gt0 = 2 * t > g, gt1 = 2 * t + 1 > g;
          const uint32_t pmask = (gt0 ? 0xFFFFu : 0u) | (gt1 ? 0xFFFF0000u : 0u);
          const uint32_t hs = warp ? O_HALO + (warp - 1) * 2560 : O_HIN, ha = sb + hs + lane * 16;
          const uint32_t va = sb + ((lane & 8) ? O_HALO + warp * 2560 : hs) + 1280 + (lane >> 4) * 128 + (lane & 7) * 16;
          uint32_t Qh[4][2], Kh[10], Vh[10];
          float c1[4][4] = {}, c2[4][4] = {}, c0[4][4] = {}, l[8][2], m[8], x[8];
#pragma unroll
          for (int j = 0; j < 4; j++) {
            const int fa = (j >> 1) * 5 + (j & 1) * 3, fh = (j >> 1) * 5 + 2;
            const bool mine = (j & 1) ? (t >= 2) : (t < 2);
            Qh[j][0] = mine ? Q[fh][0] : 0u; Qh[j][1] = mine ? Q[fh][1] : 0u;
            mma16(c1[j], Q[fa][0], Q[fa][1], Q[fa + 1][0], Q[fa + 1][1], K[fa][0], K[fa + 1][0]);
            mma16(c2[j], Q[fa][0], Q[fa][1], Q[fa + 1][0], Q[fa + 1][1], K[fa][1], K[fa + 1][1]);
            mma8(c1[j], Qh[j][0], Qh[j][1], K[fh][0]);
            mma8(c2[j], Qh[j][0], Qh[j][1], K[fh][1]);
          }
          if (lead) PT(54 + wg);
          mbar_wait(sb + (warp ? B_HX + 8 * warp : B_HX0), 0);
          if (lead) PT(56 + wg);
          ldsm4(Kh[0], Kh[1], Kh[3], Kh[4], ha); ldsm4(Kh[5], Kh[6], Kh[8], Kh[9], ha + 512);
          asm volatile("ldmatrix.sync.aligned.m8n8.x2.shared.b16 {%0,%1}, [%2];" : "=r"(Kh[2]), "=r"(Kh[7]) : "r"(ha + 1024) : "memory");
          auto load_v = [&]() {
#pragma unroll
            for (int i = 0; i < 5; i++) ldsm4t(Vh[2 * i], V[2 * i][1], Vh[2 * i + 1], V[2 * i + 1][1], va + i * 256);
          };
          load_v();
          const float C = 0.22360679774997896f * 1.4426950408889634f;
          auto max1 = [&](int r) { m[r] = fmaxf(l[r][0], l[r][1]); x[r] = __shfl_xor_sync(~0u, m[r], 1); };
          auto max2 = [&](int r) { m[r] = fmaxf(m[r], x[r]); x[r] = __shfl_xor_sync(~0u, m[r], 2); };
          auto exps = [&](int r) { const float mc = fmaxf(m[r], x[r]) * C; l[r][0] = ex2(fmaf(l[r][0], C, -mc)); l[r][1] = ex2(fmaf(l[r][1], C, -mc)); };
#pragma unroll
          for (int j = 0; j < 4; j++) { l[4 + j][0] = gt0 ? c1[j][2] : c2[j][2]; l[4 + j][1] = gt1 ? c1[j][3] : c2[j][3]; max1(4 + j); }
#pragma unroll
          for (int j = 0; j < 4; j++) {
            const int fa = (j >> 1) * 5 + (j & 1) * 3, fh = (j >> 1) * 5 + 2;
            mma16(c0[j], Q[fa][0], Q[fa][1], Q[fa + 1][0], Q[fa + 1][1], Kh[fa], Kh[fa + 1]);
            mma8(c0[j], Qh[j][0], Qh[j][1], Kh[fh]);
            max2(4 + j);
          }
          const bool have_halo = warp > 0 || mt > 0;
#pragma unroll
          for (int j = 0; j < 4; j++) {
            if (!have_halo) c0[j][0] = c0[j][1] = -INFINITY;
            l[j][0] = gt0 ? c0[j][0] : c1[j][0]; l[j][1] = gt1 ? c0[j][1] : c1[j][1];
            max1(j);
          }
          exps(4); exps(5);
#pragma unroll
          for (int j = 0; j < 4; j++) max2(j);
          exps(6); exps(7);
#pragma unroll
          for (int j = 0; j < 4; j++) exps(j);
          float o[12][4] = {}, sm[4][4] = {};
#pragma unroll
          for (int j = 0; j < 4; j++) {
            const int fa = (j >> 1) * 5 + (j & 1) * 3, fh = (j >> 1) * 5 + 2;
            const uint32_t pl = pack_bf16(l[j][0], l[j][1]), pu = pack_bf16(l[4 + j][0], l[4 + j][1]);
            const uint32_t p0 = pl & pmask, p2 = pl & ~pmask, p3 = pu & pmask, p5 = pu & ~pmask, z0 = z << (2 * j + 1), z1 = z << (2 * j + 2);
            mma8(sm[j], pl, pu, 0x3F803F80u);
#pragma unroll
            for (int q = 0; q < 3; q++) {
              const int f = q < 2 ? fa + q : fh;
              mma8(o[3 * j + q], p2, p3, V[f][0]);
              mma16(o[3 * j + q], p0, z0, z1, p5, Vh[f], V[f][1]);
            }
            asm volatile("rcp.approx.ftz.f32 %0, %0;" : "+f"(sm[j][0]));
            asm volatile("rcp.approx.ftz.f32 %0, %0;" : "+f"(sm[j][2]));
          }
#pragma unroll
          for (int i = 0; i < 12; i++) z &= __float_as_uint(o[i][0]);
          bar_arrive_p(wg == 0, NB_HALO + z, 256);
          uint32_t O[10][2];
#pragma unroll
          for (int j = 0; j < 4; j++) {
            const int fa = (j >> 1) * 5 + (j & 1) * 3, fh = (j >> 1) * 5 + 2;
            const float r0 = sm[j][0], r1 = sm[j][2];
#pragma unroll
            for (int q = 0; q < 3; q++) {
              const int f = q < 2 ? fa + q : fh;
              const float* e = o[3 * j + q];
              const uint32_t o0 = pack_bf16(e[0] * r0, e[1] * r0), o1 = pack_bf16(e[2] * r1, e[3] * r1);
              if (q < 2 || !(j & 1)) { O[f][0] = o0; O[f][1] = o1; }
              else { O[f][0] = t >= 2 ? o0 : O[f][0]; O[f][1] = t >= 2 ? o1 : O[f][1]; }
            }
          }
          mbar_wait(sb + B_GD, 0);
          const uint32_t oa = sb + O_OST + wg * 2 * STG + (w * 16 + (lane & 15)) * 160 + (lane >> 4) * 16;
#pragma unroll
          for (int i = 0; i < 5; i++) stsm4(oa + i * 32, O[2 * i][0], O[2 * i][1], O[2 * i + 1][0], O[2 * i + 1][1]);
        }
      }
      {
        CTXW();
        fence_async_smem();
        bar_arrive(wg ? NB_LEAD : NB_ATT, 160);
        if (lead) PT(58 + wg);
        const uint32_t abase = sb + (g & 1) * 4160 + 4 * (1023 - 4 - 8 * w - (g >> 1) + t);
        float acc[128];
        uint32_t a0[8], a1[8], a2[8], a3[8];
#pragma unroll 1
        for (int c = wg ^ 1; c < 5; c += 2) {
          const uint32_t ab = abase + o_h(c);
          const uint32_t db = __shfl_sync(~0u, ((SB + o_u(c) + UZ - 16) >> 4) | 0x10000u, 0);
          mbar_wait(sb + B_U + 8 * c, 0);
          load_pair<0>(a0, ab); load_pair<1>(a1, ab); load_pair<2>(a2, ab);
          if (lead) PT(85 + c);
          bar_sync(c ? NB_TOK + wg : NB_HALO, 256);
          fence_regs(acc);
          mma_pair<0>(acc, a0, db);
          load_pair<3>(a3, ab);
          mma_pair<1>(acc, a1, db); wg_wait<1>();  load_pair<4>(a0, ab);
          if (lead) PT(90 + c);
          mma_pair<2>(acc, a2, db); wg_wait<1>();  load_pair<5>(a1, ab);
          mma_pair<3>(acc, a3, db); wg_wait<1>();  load_pair<6>(a2, ab);
          mma_pair<4>(acc, a0, db); wg_wait<1>();  load_pair<7>(a3, ab);
          mma_pair<5>(acc, a1, db);
          mma_pair<6>(acc, a2, db);
          bar_arrive_p(c < 4, NB_TOK + (wg ^ 1), 256);
          mma_pair<7>(acc, a3, db);
          bar_arrive_p(c == 4, NB_TOK, 256);
          wg_wait<0>();
          fence_regs(acc);
          PTPL(lead, 95 + c);
          bar_sync(NB_RFREE + wg, 256);
          const uint32_t pb = sb + (w < 2 ? o_h(c) + w * 4160 : w == 2 ? o_u(c) : o_x(c)) + lane * 16;
          if (lane < 2 * w) sts128(pb, 0, 0, 0, 0);
#pragma unroll
          for (int q = 0; q < 8; q++) {
            uint32_t p[4];
#pragma unroll
            for (int i = 0; i < 4; i++) {
              const int nu = 4 * q + i;
              p[i] = pack_bf16(acc[4 * nu], acc[4 * nu + 1]);
              if (nu > 0) p[i] = hadd2(p[i], pack_bf16(acc[4 * nu - 2], acc[4 * nu - 1]));
            }
            stsm4t(pb + w * 32 + q * 512, p[0], p[1], p[2], p[3]);
            if (q == 3) bar_arrive_p(c == 4, NB_RFULL + 1, 256);
          }
          if (c < 4) bar_arrive(NB_RFULL + wg, 256);
          if (lead) PT(140 + c);
        }
        if (wg) {
          const int yb = (lds32(sb + O_EPOCH) & 1) * 640;
              conv_reduce<1, 2>(sb, 4, tid - 128, yb + 512 + ((vb & 0x61) | (vb & 6) << 2 | (vb >> 2 & 6)), 14, 128);
          bar_arrive(12, 256);
          PTPL(lead, 45);
        }
      }
    }
    if (warp < 4) {
      CTXW();
      const uint32_t rsb = mapa(sb, (blockIdx.x & 1) ^ 1);
      const uint32_t ba = sb + O_BT + ((lane >> 4) * 8 + (lane & 7)) * 128 + (((2 * w + ((lane >> 3) & 1)) ^ ((lane & 1) << 2 | (lane >> 1 & 3))) << 4);
      mbar_wait(sb + B_P3F, 0);
      if (lead) PT(145);
      float acc[80];
#pragma unroll
      for (int ks = 0; ks < 10; ks++) {
        if (ks == NPRE) {
          if (NPRE) { wg_wait<0>(); mbar_arrive2_p(lead, sb + B_P3E + 8 * NPRE, rsb + B_P3E + 8 * NPRE); }
          bar_sync_p(blockIdx.x < 128, NB_TOK, 256);
        }
        PTP(lead, 146 + ks);
        const uint64_t da = mkdesc(SB + o_p3(ks), 1024, 1024, 1), db = mkdesc(SB + o_p3(ks) + 8192, 16, 1024, 1);
        wg_fence();
#pragma unroll
        for (int j = 0; j < 4; j++) wgmma_ss_n160<0, 1, 0>(acc, da + j * 128, db + j * 2, j | ks);
        wg_commit();
        if (ks < 9) mbar_wait(sb + B_P3F + 8 * (ks + 1), 0);
        if (ks >= 1 && ks <= 4 && ks != NPRE) { wg_wait<1>(); mbar_arrive2_p(lead, sb + B_P3E + 8 * ks, rsb + B_P3E + 8 * ks); }
      }
      wg_wait<0>();
      fence_regs(acc);
      PTPL(lead, 156);
#pragma unroll
      for (int i = 0; i < 10; i++) {
        stsm4t(ba + i * 2048, pack_bf16(acc[8 * i], acc[8 * i + 1]), pack_bf16(acc[8 * i + 2], acc[8 * i + 3]),
               pack_bf16(acc[8 * i + 4], acc[8 * i + 5]), pack_bf16(acc[8 * i + 6], acc[8 * i + 7]));
        if (i & 1) bar_arrive(1 + (i >> 1), 256);
      }
      if (lead) PT(157);
    }
  } else if (warp < 12) {
    reg_dec<RH>();
    const int hw = warp - 8;
    init_rest();
    ctx = __shfl_sync(~0u, make_ctx(), 0);
    const int yrow = (ctx & 0x61) | (ctx & 6) << 2 | (ctx >> 2 & 6);
    if (ctx < 65536) {
      CTXU();
      const int pr = hw >> 1, hh = hw & 1, tk = vb & 63, odd = (lane >> 2) & 1;
      const uint32_t sel0 = odd ? 0x7632 : 0x5410, sel1 = odd ? 0x5410 : 0x7632;
      const uint32_t in = sb + o_kin(pr), fb = sb + B_KF + 8 * pr, out = sb + O_Y + pr * 8192;
      const uint32_t oa = out + (2 * lane + odd) * 64 + (((3 - 2 * hh) ^ (lane & 3)) << 4), ia = in + hh * 2048 + lane * 4;
      auto fetch = [&](int c) {
        wait_until(t0, KT0 + c * KTD + ((((vb * 37) & 63) * KPH) >> 6));
        if (elect_one()) {
          const int kb = 2 * c + (vb >> 6);
          mbar_expect_tx(fb, 69 * 128);
          tma2(in, &M.k_ld, kb * 64, 32 * tk - 4, fb);
          tma2(in + 36 * 128, &M.v_ld, kb * 64, 32 * tk - 1, fb);
          PT(20 + c);
        }
        __syncwarp();
      };
      if (hh == 0) fetch(pr);
      const uint4* skp = (const uint4*)shift_k + (2 * pr + (vb >> 6)) * 32 + lane;
      uint4 sk = __ldg(skp), sk1 = __ldg(skp + 128), sk2 = __ldg(skp + (pr ? 0 : 256));
#pragma unroll 1
      for (int c = pr; c < 5; c += 2) {
        {
          mbar_wait(fb, (c >> 1) & 1);
          if (hh == 0 && lane == 0) PT(25 + c);
          uint32_t k[20], o[17];
#pragma unroll
          for (int i = 0; i < 20; i++) { k[i] = lds32(ia + i * 128); if (i >= 3) o[i - 3] = lds32(ia + (33 + i) * 128); }
          fence_async_smem();
          bar_sync(12 + pr, 64);
          if (hh == 0) {
            if (c < 3) fetch(c + 2);
            else if (lane == 0) mbar_arrive(sb + B_KVD + 8 * (c - 3));
          }
          const uint32_t w0 = prmt(sk.x, sk.z, 0x5410), w1 = prmt(sk.x, sk.z, 0x7632), w2 = prmt(sk.y, sk.w, 0x5410), w3 = prmt(sk.y, sk.w, 0x7632);
#pragma unroll
          for (int i = 0; i < 17; i++) o[i] = hmul2(hfma2(k[i + 3], w0, hfma2(k[i + 2], w1, hfma2(k[i + 1], w2, hmul2(k[i], w3)))), o[i]);
          sk = sk1; sk1 = sk2;
#pragma unroll
          for (int i = 0; i < 4; i++) {
            const int e = 8 * (i >> 1) + (i & 1);
            const uint32_t a = (oa ^ ((i >> 1) * 16)) + (i & 1) * 4096;
            sts128(a, prmt(o[7 + e], o[6 + e], sel0), prmt(o[5 + e], o[4 + e], sel0), prmt(o[3 + e], o[2 + e], sel0), prmt(o[1 + e], o[e], sel0));
            sts128(a ^ 64, prmt(o[7 + e], o[6 + e], sel1), prmt(o[5 + e], o[4 + e], sel1), prmt(o[3 + e], o[2 + e], sel1), prmt(o[1 + e], o[e], sel1));
          }
          bar_sync(12 + pr, 64);
        }
        if (hh) {
          fence_async_smem();
          if (elect_one()) {
            const int kb = 2 * c + (vb >> 6);
            tma3_store(&M.kv_st, 0, kb * 64, 63 - tk, out);
            tma3_store(&M.kv_st, 0, 640 + kb * 64, 63 - tk, out + 4096);
            bulk_commit(); bulk_wait_all();
            mbar_arrive(sb + (c == 4 ? B_KVD + 16 : B_KVS + 4 * (c & 2)));
            PTL(35 + c);
          }
          __syncwarp();
        }
      }
    }
    CTXU();
    const int g = lane >> 2, t = lane & 3, row = 8 * hw + g;
    const uint32_t go = (tb * 160 + row) * 80 + cb * 8 + t;
    const int yb = __shfl_sync(~0u, get_epoch() & 1, 0) * 640;
    uint4 T[10];
    if (hw == 2) {
      if (main_cta) { mbar_wait(sb + B_LAST, 0); mbar_wait(sb + B_S15, 1); }
      if (elect_one()) {
        mbar_expect_tx(sb + B_Q, 20480);
#pragma unroll
        for (int h = 0; h < 2; h++) tma2(sb + O_QT + h * 10240, &M.q_ld, cb * 64 + 32 * h, tb * 160, sb + B_Q);
      }
      __syncwarp();
    }
    mbar_wait(sb + B_Q, 0);
#pragma unroll
    for (int i = 0; i < 10; i++) lds128(sb + O_QT + (i & 1) * 10240 + (i >> 1) * 2048 + row * 64 + t * 16, T[i].x, T[i].y, T[i].z, T[i].w);
    fence_async_smem();
    bar_sync(12 + (hw >> 1), 64);
    if (!(tid & 63)) mbar_arrive(sb + B_QD);
    if (tid == 256) PTL(40);
    if (main_cta) {
      bar_arrive(NB_RFREE, 256);
      bar_arrive(NB_RFREE + 1, 256);
      auto red = [&](int c) {
        const int wg = (c & 1) ^ 1;
        conv_reduce<0, 2>(sb, c, tid - 256, yb + 128 * c + yrow, NB_RFULL + wg, 256);
        if (hw == 3 && elect_one()) flag_add(CNT_Y(4 * c + (vb >> 5)), 1);
        if (tid == 256) PTL(41 + c);
        if (c < 3) bar_arrive(NB_RFREE + wg, 256);
        if (c == 2) {
          bar_sync(NB_HELP, 128);
          if (tid == 256) { mbar_arrive(sb + B_P3E); mbar_arrive_remote(sb + B_P3E, rank ^ 1); }
        }
      };
      if (hw == 3) {
        mbar_wait(sb + B_KVD + 16, 0);
        if (elect_one()) { flag_release(CNT_KV(4 + (vb >> 6))); PTL(32); }
        __syncwarp();
      }
#pragma unroll 1
      for (int c = 0; c < 4; c++) red(c);
    }
    uint32_t G[5];
    mbar_wait(sb + B_G, 0);
#pragma unroll
    for (int q = 0; q < 5; q++) { uint16_t v; asm volatile("ld.shared.u16 %0, [%1];" : "=h"(v) : "r"(sb + O_GT + (32 * q + row) * 2)); G[q] = prmt(v, 0, 0x1010); }
    auto gate_q = [&]() {
#pragma unroll
      for (int i = 0; i < 10; i++) { const uint32_t c = G[i >> 1] ^ 0x80008000u; T[i] = make_uint4(hmul2(T[i].x, c), hmul2(T[i].y, c), hmul2(T[i].z, c), hmul2(T[i].w, c)); }
    };
    gate_q();
    const uint32_t so = __shfl_sync(~0u, sb + O_BT + row * 128 + ((t ^ ((g & 1) << 2 | g >> 1)) << 4), lane);
    uint4* const op = (uint4*)__shfl_sync(~0u, (unsigned long long)((uint4*)outp + go), lane);
    if (main_cta) {
      conv_reduce<0, 1>(sb, 4, tid - 256, yb + 512 + yrow, NB_RFULL + 1, 256);
      if (hw == 3 && elect_one()) { flag_add(CNT_Y(16 + (vb >> 5)), 1); PTL(19); }
      bar_sync(12, 256);
    }
    const uint32_t ya = sb + O_Y + lane * 64 + ((hw ^ ((lane >> 1) & 3)) << 4);
    auto empty = [](uint32_t m) { return (m & 0xFFFFu) == 0 || m < 0x10000u; };
    int redo = blockIdx.y;
#pragma unroll 1
    do {
      if (redo) {
#pragma unroll 1
        for (int i = 0; i < (tb < 12 ? 10 : 8); i++) {
          const uint32_t a = ya + (i & 1) * 10240 + (i >> 1) * 2048;
          uint4 v;
          lds128(a, v.x, v.y, v.z, v.w);
          while (empty(__vimin3_u16x2(__vminu2(v.x, v.y), v.z, v.w)))
            asm volatile("ld.relaxed.gpu.global.v4.b32 {%0,%1,%2,%3}, [%4];" : "=r"(v.x), "=r"(v.y), "=r"(v.z), "=r"(v.w)
                         : "l"((const uint4*)g_y2T + (yb + cb * 64 + 32 * (i & 1) + lane) * 256 + tb * 20 + 4 * (i >> 1) + hw) : "memory");
          sts128(a, v.x, v.y, v.z, v.w);
        }
        __syncwarp();
#pragma unroll
        for (int i = 0; i < 10; i++) if (i < 8 || tb < 12) T[i] = __ldg((const uint4*)xq + go + (i >> 1) * 2560 + (i & 1) * 4);
        gate_q();
        PTL(49);
      }
      uint32_t m = ~0u;
#pragma unroll
      for (int h = 0; h < 2; h++) {
        if (h) mbar_wait(sb + B_Y + 8, 0); else mbar_wait_wd(sb + B_Y, 0, t0);
        if (tid == 256) PTL(46);
#pragma unroll
        for (int q = 0; q < 5; q++) {
          uint4 y;
          ldsm4t(y.x, y.y, y.z, y.w, ya + h * 10240 + q * 2048);
          const uint32_t mq = __vimin3_u16x2(__vimin3_u16x2(m, y.x, y.y), y.z, y.w);
          m = q == 4 && tb == 12 ? m : mq;
          uint4& r = T[2 * q + h];
          r = make_uint4(hmul2(r.x, y.x), hmul2(r.y, y.y), hmul2(r.z, y.z), hmul2(r.w, y.w));
        }
      }
      redo = __any_sync(~0u, empty(m));
    } while (redo);
    if (tid == 256) PTL(47);
#pragma unroll
    for (int q = 0; q < 5; q++) {
      const uint32_t c = hfma2(G[q], 0xBF80BF80u, 0x3F803F80u);
      bar_sync(1 + q, 256);
      if (q == 4) mbar_arrive_p(tid == 256, sb + B_DONE);
#pragma unroll
      for (int h = 0; h < 2; h++) {
        uint4 u;
        lds128((so ^ (h * 64)) + q * 4096, u.x, u.y, u.z, u.w);
        const uint4& r = T[2 * q + h];
        if (q < 4 || tb < 12)
          asm volatile("st.global.v4.b32 [%0], {%1,%2,%3,%4};" ::"l"(op + q * 2560 + h * 4), "r"(hfma2(u.x, c, r.x)), "r"(hfma2(u.y, c, r.y)), "r"(hfma2(u.z, c, r.z)), "r"(hfma2(u.w, c, r.w)) : "memory");
      }
    }
  } else {
    reg_dec<RP>();
    uint4 gwv = make_uint4(0, 0, 0, 0);
    if (warp == 15) {
      const int p = cta_pair(), rank = blockIdx.x & 1;
      asm volatile("barrier.cluster.wait.aligned;" ::: "memory");
      if (blockIdx.x >= 128) cluster_sync();
      else {
#pragma unroll 1
        for (int ks = 1;; ks += 2) {
          mbar_wait(sb + B_EMPTY + 8 * (ks & 7), ((ks >> 3) & 1) ^ 1);
          spin_until(t0, PT1 + (ks - 1) * PTD);
          if (elect_one()) { mbar_expect_tx(sb + B_FULL + 8 * (ks & 7), WST); p1_load_w(ks, p, rank); PT(100 + ks); }
          if (ks == 19) break;
          const int kn = ks + 1;
          mbar_wait(sb + B_EMPTY + 8 * (kn & 7), ((kn >> 3) & 1) ^ 1);
          spin_until(t0, PT1 + ks * PTD - PTE);
          if (elect_one()) { mbar_expect_tx(sb + B_FULL + 8 * (kn & 7), 16384 + WST); p1_load_x(kn, p, rank); p1_load_w(kn, p, rank); PT(100 + kn); }
        }
        if (elect_one()) mbar_arrive(sb + B_LAST);
#pragma unroll 1
        for (int i = 0; i < 2; i++) {
          mbar_wait(sb + B_KVS + 8 * i, 0);
          if (elect_one()) { flag_release(CNT_KV(2 * i + (p >> 5))); PTL(30 + i); }
          __syncwarp();
        }
        mbar_wait(sb + B_S19, 0);
      }
    } else {
      if (threadIdx.x < 384 + 80) gwv = __ldg((const uint4*)gate_w + threadIdx.x - 384);
      init_rest();
    }
    ctx = __shfl_sync(~0u, make_ctx(), 0);
    CTXU();
    if (warp == 12) {
        unsigned epoch = 0;
      if (lane == 0) epoch = *(volatile unsigned*)(g_launch + 32 * vb) + 1;
      if (main_cta) { sts128(sb + O_GW + lane * 16, gwv.x, gwv.y, gwv.z, gwv.w); bar_arrive(NB_G, 96); }
      if (lane == 0) {
        if ((sb & 0xFFFFFF) != SB) __trap();
        sts32(sb + O_EPOCH, epoch);
        mbar_arrive(sb + B_EP);
      }
      if (main_cta && rank) {
#pragma unroll
        for (int f = 0; f < 5; f++) st_relaxed(g_halo + vb * 160 + lane + 32 * f, ~0u, ~0u, ~0u, ~0u);
      }
      __syncwarp();
      if (elect_one()) flag_release(g_launch + 32 * vb);
      __syncwarp();
      if (main_cta) {
        uint4 h0 = make_uint4(0, 0, 0, 0);
        if (lane < 5) {
          h0 = __ldg((const uint4*)(ssm_k + (size_t)(128 * lane + vb) * 2048));
          h0.x = prmt(pack_bf16(bf_lo(h0.x) + bf_lo(__ldg(ssm_D + 128 * lane + vb)), 0.f), h0.x, 0x7610);
        }
        epoch = __shfl_sync(~0u, epoch, 0);
        const int ze = lane & 7;
        const uint32_t za = sb + (lane < 8 ? o_u(ze) + UZ : lane < 24 ? o_h(ze) + (lane >> 4) * 4160 + 4096 : o_u(ze) + 512);
        const uint16_t* hp = ssm_k + (size_t)vb * 2048 + 8;
        const uint16_t* up = g_kvT + (size_t)vb * 2048;
        const unsigned* fp = CNT_KV(vb >> 6);
        sts128(sb + O_Y - 512 + lane * 16, 0, 0, 0, 0);
        mbar_wait(sb + B_LAST, 0);
        mbar_wait(sb + B_S13, 1);
#pragma unroll
        for (int c = 0; c < 5; c++) {
          if (c == 0 || c == 3) {
            mbar_wait(sb + B_KVD + (c ? 8 : 0), 0);
#pragma unroll
            for (int e = c; e < (c ? 5 : 3); e++) sts128(sb + o_u(e) + lane * 16, 0, 0, 0, 0);
            if (ze >= c && ze < (c ? 5 : 3)) sts128(za, h0.x, h0.y, h0.z, h0.w);
            fence_async_smem();
            __syncwarp();
            if (elect_one()) {
#pragma unroll
              for (int e = c; e < (c ? 5 : 3); e++) {
                mbar_expect_tx(sb + B_U + 8 * e, 3 * 4096 - 16);
                if (c || e == 0) bulk_load(sb + o_u(e) + UZ + 16, hp + 128 * 2048 * e, 4080, sb + B_U + 8 * e);
              }
            }
          }
          if (!(c & 1)) { flag_wait(fp + 32 * c, 64 * epoch); __syncwarp(); }
          if (elect_one()) {
            bulk_load(sb + o_h(c), up + 128 * 2048 * c, 4096, sb + B_U + 8 * c);
            bulk_load(sb + o_h(c) + 4160, up + (640 + 128 * c) * 2048, 4096, sb + B_U + 8 * c);
            if (c == 1) {
#pragma unroll
              for (int e = 1; e < 3; e++) bulk_load(sb + o_u(e) + UZ + 16, hp + 128 * 2048 * e, 4080, sb + B_U + 8 * e);
            }
            PTL(10 + c);
          }
        }
        mbar_wait(sb + B_OR, 0);
        if (elect_one()) {
#pragma unroll 1
          for (int i = 0; i < 40; i++) bulk_store(g_y2T + (size_t)((~epoch & 1) * 640 + 5 * vb) * 2048 + i * 256, sb + O_Y - 512, 512);
          bulk_commit(); bulk_wait_read();
          PTL(33);
        }
      }
    } else if (warp != 15) {
        const int r = warp - 13;
      if (main_cta) {
        if (rank && lane == 0) mbar_expect_tx(sb + B_HX0, 1280);
        const int t = lane & 3, grow = hg * 16 + (lane & 15);
        const uint32_t ga = sb + grow * 128 + (((4 * r + (lane >> 4)) ^ (lane & 7)) << 4);
        const uint32_t gp = sb + O_GW + 64 * r + 4 * t;
        float s0 = 0.f, s1 = 0.f;
        if (tid < 384 + 80) sts128(sb + O_GW + (tid - 384) * 16, gwv.x, gwv.y, gwv.z, gwv.w);
        bar_sync(NB_G, 96);
#pragma unroll 1
        for (int ks = 0; ks < 20; ks += 2) {
          uint32_t x[8], gw[4];
#pragma unroll
          for (int i = 0; i < 4; i++) gw[i] = lds32(gp + ks * 64 + i * 16);
          mbar_wait_wd(sb + B_FULL + 8 * (ks & 7), (ks >> 3) & 1, t0);
          if (r == 0 && lane == 0) PT(120 + ks);
          ldsm4(x[0], x[1], x[2], x[3], ga + o_px(ks)); ldsm4(x[4], x[5], x[6], x[7], (ga ^ 32) + o_px(ks));
#pragma unroll
          for (int i = 0; i < 8; i++) x[i] = hmul2(x[i], gw[i >> 1]);
          if (lane < 2) mbar_arrive(sb + B_EMPTY + 8 * (ks & 7) + 8 * lane + (x[0] & x[7] & threadIdx.y));
#pragma unroll
          for (int i = 0; i < 8; i += 4) {
            s0 += (bf_lo(x[i]) + bf_hi(x[i])) + (bf_lo(x[i + 2]) + bf_hi(x[i + 2]));
            s1 += (bf_lo(x[i + 1]) + bf_hi(x[i + 1])) + (bf_lo(x[i + 3]) + bf_hi(x[i + 3]));
          }
        }
        s0 += __shfl_xor_sync(~0u, s0, 1); s1 += __shfl_xor_sync(~0u, s1, 1);
        s0 += __shfl_xor_sync(~0u, s0, 2); s1 += __shfl_xor_sync(~0u, s1, 2);
        if (t < 2) sts32(sb + O_GP + r * 64 + (8 * t + (lane >> 2)) * 4, __float_as_uint(t ? s1 : s0));
        if (lane == 0) mbar_arrive(sb + B_GD);
        if (r == 0) bar_arrive(NB_G, 64);
        if (!rank) {
          uint4 d[3];
          if (mt > 0) {
            const uint4* hp = g_halo + (vb - 1) * 160 + r * 64 + lane;
            mbar_wait_wd(sb + B_EP, 0, t0);
            flag_wait_wd(g_launch + 32 * (vb - 1), lds32(sb + O_EPOCH), t0);
            mbar_wait_wd(sb + B_HX + 56, 0, t0);
            for (;;) {
              bool ok = true;
#pragma unroll
              for (int f = 0; f < 3; f++) {
                asm volatile("ld.relaxed.gpu.global.v4.b32 {%0,%1,%2,%3}, [%4];" : "=r"(d[f].x), "=r"(d[f].y), "=r"(d[f].z), "=r"(d[f].w) : "l"(hp + 32 * f) : "memory");
              }
#pragma unroll
              for (int f = 0; f < 3; f++) ok = ok && max(max(d[f].x, d[f].y), max(d[f].z, d[f].w)) != ~0u;
              if (__all_sync(~0u, ok)) break;
              if (clk() - t0 > 0x70000000u) __trap();
            }
          } else {
#pragma unroll
            for (int f = 0; f < 3; f++) d[f] = make_uint4(0, 0, 0, 0);
          }
#pragma unroll
          for (int f = 0; f < 3; f++) stsm4(sb + O_HIN + r * 1024 + f * 512 + lane * 16, d[f].x, d[f].y, d[f].z, d[f].w);
          __syncwarp();
          if (lane == 0) { mbar_arrive(sb + B_HX0); PTL(15 + r); }
        }
        if (r == 1) {
          bar_sync(NB_G, 64);
          if (lane < 16) {
            const uint32_t pa = sb + O_GP + lane * 4;
            const float z = __uint_as_float(lds32(pa)) + __uint_as_float(lds32(pa + 64));
            g_gate[2 * (mt * 128 + hg * 16 + lane) + par] = (uint16_t)pack_bf16(__fdividef(1.f, 1.f + __expf(-bf_lo(pack_bf16(z, 0.f)))), 0.f);
          }
          __syncwarp();
          if (elect_one()) flag_release(CNT_O(rt));
        }
      }
      mbar_wait_wd(sb + B_EP, 0, t0);
      const unsigned epoch = lds32(sb + O_EPOCH);
      if (main_cta) mbar_wait_wd(sb + B_P3E, 0, t0);
      const uint32_t yd = __shfl_sync(~0u, sb + O_Y + r * 10240 + threadIdx.y, 0), yb = __shfl_sync(~0u, sb + B_Y + 8 * r + threadIdx.y, 0);
      const int y1 = __shfl_sync(~0u, (epoch & 1) * 640 + cb * 64 + 32 * r + threadIdx.y, 0), y2 = __shfl_sync(~0u, tb * 5 + threadIdx.y, 0);
      if (elect_one()) { pf_map(&M.y_ld); mbar_expect_tx(yb, 10240); }
      __syncwarp();
      flag_wait_wd(CNT_Y(2 * cb + r), 32 * epoch, t0);
      __syncwarp();
      if (elect_one()) { tma3(yd, &M.y_ld, 0, y1, y2, yb); PTL(17 + r); }
      __syncwarp();
      mbar_wait_wd(sb + B_DONE, 0, t0);
    } else {
      const unsigned epoch = get_epoch();
      if (main_cta) {
        if (elect_one()) { pf_map(&M.o_st); pf_map(&M.wo); pf_map(&M.o_ld); }
        __syncwarp();
        bar_sync(NB_LEAD, 160);
        if (elect_one()) tma3_store(&M.o_st, hg * 80, par, mt * 128 + 64, sb + O_OST + 2 * STG);
        bar_sync(NB_ATT, 160);
        if (elect_one()) {
          tma3_store(&M.o_st, hg * 80, par, mt * 128, sb + O_OST);
          bulk_commit(); bulk_wait_all();
          flag_release(CNT_O(rt));
          mbar_arrive(sb + B_OR); mbar_arrive(sb + B_OR);
          PTL(3);
        }
        __syncwarp();
      }
      mbar_wait(sb + B_QD, 0);
#pragma unroll 1
      for (int ks = 0; ks < 5; ks++)
        if (elect_one()) tma2(sb + o_p3(ks), &M.wo, cb * 64, ks * 64, sb + B_P3F + 8 * ks);
      if (lane < 4) flag_wait(CNT_O(8 * (lane & 1) + min(7, (80 * tb + 79 * (lane >> 1)) >> 7)), 16 * epoch);
      __syncwarp();
      if (elect_one()) {
        PTL(4);
        mbar_arrive_remote(sb + B_P3R, rank ^ 1);
        mbar_expect_tx(sb + B_G, 320);
        bulk_load(sb + O_GT, g_gate + tb * 160, 320, sb + B_G);
      }
      mbar_wait(sb + B_P3R, 0);
      auto load_o = [&](int ks) {
        tma2_mc(sb + o_p3(ks) + 8192 + rank * 10240, &M.o_ld, ks * 64, tb * 160 + rank * 80, sb + B_P3F + 8 * ks);
        mbar_expect_tx(sb + B_P3F + 8 * ks, P3S);
      };
      auto load_wo = [&](int ks) { tma2(sb + o_p3(ks), &M.wo, cb * 64, ks * 64, sb + B_P3F + 8 * ks); };
#pragma unroll 1
      for (int ks = 0; ks < 5; ks++)
        if (elect_one()) load_o(ks);
#pragma unroll
      for (int ks = 5; ks < 10; ks++) {
        if (ks > 5 || main_cta) mbar_wait(sb + B_P3E + 8 * (ks - 5), 0);
        if (elect_one()) {
          load_o(ks); load_wo(ks);
          PTL(ks);
        }
      }
    }
  }
}

typedef CUresult (*PFN_enc)(CUtensorMap*, CUtensorMapDataType, cuuint32_t, void*, const cuuint64_t*, const cuuint64_t*, const cuuint32_t*,
                            const cuuint32_t*, CUtensorMapInterleave, CUtensorMapSwizzle, CUtensorMapL2promotion, CUtensorMapFloatOOBfill);
static void enc(PFN_enc f, CUtensorMap* m, const void* base, int rank, const cuuint64_t* dims, const cuuint64_t* strides, const cuuint32_t* box,
                CUtensorMapSwizzle sw) {
  const cuuint32_t es[5] = {1, 1, 1, 1, 1};
  f(m, CU_TENSOR_MAP_DATA_TYPE_BFLOAT16, rank, (void*)base, dims, strides, box, es, CU_TENSOR_MAP_INTERLEAVE_NONE, sw,
    CU_TENSOR_MAP_L2_PROMOTION_NONE, CU_TENSOR_MAP_FLOAT_OOB_FILL_NONE);
}

extern "C" void kernel_launch(void* const* d_in, const int* in_sizes, int n_in, void* d_out, int out_size) {
  (void)in_sizes; (void)n_in; (void)out_size;
  static PFN_enc f = nullptr;
  static void *kvT, *y2T, *o;
  if (!f) {
    void* p = nullptr;
    cudaDriverEntryPointQueryResult q;
    cudaGetDriverEntryPoint("cuTensorMapEncodeTiled", &p, cudaEnableDefault, &q);
    f = (PFN_enc)p;
    cudaGetSymbolAddress(&kvT, g_kvT); cudaGetSymbolAddress(&y2T, g_y2T); cudaGetSymbolAddress(&o, g_o);
    cudaFuncSetAttribute(fused_kernel, cudaFuncAttributeMaxDynamicSharedMemorySize, SMEM_BYTES);
  }
  Maps M;
  const CUtensorMapSwizzle S0 = CU_TENSOR_MAP_SWIZZLE_NONE, S32 = CU_TENSOR_MAP_SWIZZLE_32B, S64 = CU_TENSOR_MAP_SWIZZLE_64B, S128 = CU_TENSOR_MAP_SWIZZLE_128B;
  const cuuint64_t dpar[3] = {640, 2, 1024}, spar[2] = {1280, 2560};
  const cuuint64_t dw[3] = {640, 640, 3}, sw[2] = {3840, 1280};
  const cuuint64_t dnat[2] = {640, 2048}, snat[1] = {1280};
  const cuuint64_t dT2[3] = {32, 1280, 64}, sT[2] = {4096, 64};
  const cuuint64_t dwo[2] = {640, 640};
  { const cuuint32_t bx[3] = {64, 1, 128}; enc(f, &M.x_par, d_in[0], 3, dpar, spar, bx, S128); }
  { const cuuint32_t bx[3] = {64, 16, 3}; enc(f, &M.w_main, d_in[7], 3, dw, sw, bx, S128); }
  { const cuuint32_t bx[3] = {16, 16, 3}; enc(f, &M.w_tail, d_in[7], 3, dw, sw, bx, S32); }
  { const cuuint32_t bx[3] = {80, 1, 64}; enc(f, &M.o_st, o, 3, dpar, spar, bx, S0); }
  { const cuuint32_t bx[3] = {32, 64, 1}; enc(f, &M.kv_st, kvT, 3, dT2, sT, bx, S64); }
  { const cuuint32_t bx[3] = {32, 32, 5}; enc(f, &M.y_ld, y2T, 3, dT2, sT, bx, S64); }
  { const cuuint32_t bx[2] = {64, 36}; enc(f, &M.k_ld, d_in[1], 2, dnat, snat, bx, S0); }
  { const cuuint32_t bx[2] = {64, 33}; enc(f, &M.v_ld, d_in[2], 2, dnat, snat, bx, S0); }
  { const cuuint32_t bx[2] = {32, 160}; enc(f, &M.q_ld, d_in[0], 2, dnat, snat, bx, S0); }
  { const cuuint32_t bx[2] = {64, 64}; enc(f, &M.wo, d_in[8], 2, dwo, snat, bx, S128); }
  { const cuuint32_t bx[2] = {64, 80}; enc(f, &M.o_ld, o, 2, dnat, snat, bx, S128); }
  fused_kernel<<<130, 512, SMEM_BYTES, cudaStreamPerThread>>>((const uint16_t*)d_in[0], (const uint16_t*)d_in[7], (const uint16_t*)d_in[9], M, (const uint16_t*)d_in[3], (const uint16_t*)d_in[4], (const uint16_t*)d_in[5],
                                                              (uint16_t*)d_out);
}
```

```cpp
#include <cuda_runtime.h>
#include <cuda_bf16.h>
#include <cuda.h>
#include <stdint.h>
#include <type_traits>

#define DEVI __device__ __forceinline__
#define PT1 300
#define PTD 460
#define PTE 150
#define DEFER 4
#define KPH KTD
#define NLATE 4
#define NPRE 1
#define KT0 1500
#define KTD 1000
#define RC 192
#define RH 96
#define RP 32
#define HOLD 750
#define LEAD 3

DEVI uint32_t smem_u32(const void* p) { return (uint32_t)__cvta_generic_to_shared(p); }
DEVI void wg_fence() { asm volatile("wgmma.fence.sync.aligned;" ::: "memory"); }
DEVI void wg_commit() { asm volatile("wgmma.commit_group.sync.aligned;" ::: "memory"); }
template <int N> DEVI void wg_wait() { asm volatile("wgmma.wait_group.sync.aligned %0;" ::"n"(N) : "memory"); }
template <int A = 0, int B = -1, int S> DEVI void fence_regs(float (&d)[S]) {
#pragma unroll
  for (int i = A; i < (B < 0 ? S : B); i++) asm volatile("" : "+f"(d[i])::"memory");
}
DEVI uint64_t mkdesc(uint32_t addr, uint32_t lbo, uint32_t sbo, int swz) {
  return (uint64_t)((addr & 0x3FFFF) >> 4) | ((uint64_t)(lbo >> 4) << 16) | ((uint64_t)(sbo >> 4) << 32) | ((uint64_t)swz << 62);
}
DEVI void mbar_init(uint32_t bar, uint32_t cnt) { asm volatile("mbarrier.init.shared::cta.b64 [%0], %1;" ::"r"(bar), "r"(cnt) : "memory"); }
DEVI void mbar_expect_tx(uint32_t bar, uint32_t bytes) { asm volatile("mbarrier.arrive.expect_tx.shared::cta.b64 _, [%0], %1;" ::"r"(bar), "r"(bytes) : "memory"); }
DEVI void mbar_arrive(uint32_t bar) { asm volatile("mbarrier.arrive.shared::cta.b64 _, [%0];" ::"r"(bar) : "memory"); }
DEVI void mbar_wait(uint32_t bar, uint32_t parity) {
  asm volatile("{\n.reg .pred p;\nLAB_WAIT:\nmbarrier.try_wait.parity.shared::cta.b64 p, [%0], %1;\n@!p bra LAB_WAIT;\n}" ::"r"(bar), "r"(parity) : "memory");
}
DEVI void mbar_wait_wd(uint32_t bar, uint32_t parity, uint32_t t0) {
  asm volatile("{\n.reg .pred p;\n.reg .u32 c;\nLAB_WAIT:\nmbarrier.try_wait.parity.shared::cta.b64 p, [%0], %1;\n@p bra DONE;\nmov.u32 c, %%clock;\nsub.u32 c, c, %2;\nsetp.lt.u32 p, c, 0x70000000;\n@p bra LAB_WAIT;\ntrap;\nDONE:\n}" ::"r"(bar), "r"(parity), "r"(t0) : "memory");
}
DEVI void flag_wait(const unsigned* p, unsigned target) {
  asm volatile("{\n.reg .pred p;\n.reg .s32 v;\nLAB_WAIT:\nld.relaxed.gpu.global.u32 v, [%0];\nsub.s32 v, v, %1;\nsetp.lt.s32 p, v, 0;\n@p bra LAB_WAIT;\n}" ::"l"(p), "r"(target) : "memory");
}
DEVI void flag_wait_wd(const unsigned* p, unsigned target, uint32_t t0) {
  asm volatile("{\n.reg .pred p;\n.reg .s32 v;\nLAB_WAIT:\nld.relaxed.gpu.global.u32 v, [%0];\nsub.s32 v, v, %1;\nsetp.ge.s32 p, v, 0;\n@p bra DONE;\nmov.u32 v, %%clock;\nsub.s32 v, v, %2;\nsetp.lt.u32 p, v, 0x70000000;\n@p bra LAB_WAIT;\ntrap;\nDONE:\n}" ::"l"(p), "r"(target), "r"(t0) : "memory");
}
DEVI void flag_add(unsigned* p, unsigned v) { asm volatile("red.relaxed.gpu.global.add.u32 [%0], %1;" ::"l"(p), "r"(v) : "memory"); }
DEVI void flag_release(unsigned* p) { asm volatile("fence.proxy.async;\nred.relaxed.gpu.global.add.u32 [%0], 1;" ::"l"(p) : "memory"); }
DEVI void fence_async_smem() { asm volatile("fence.proxy.async.shared::cta;" ::: "memory"); }
DEVI bool elect_one() { uint32_t p; asm volatile("{\n.reg .pred P;\nelect.sync _|P, 0xffffffff;\nselp.u32 %0, 1, 0, P;\n}" : "=r"(p)); return p; }
DEVI void bar_sync(int id, int n) { asm volatile("bar.sync %0, %1;" ::"r"(id), "r"(n) : "memory"); }
DEVI void bar_arrive(int id, int n) { asm volatile("bar.arrive %0, %1;" ::"r"(id), "r"(n) : "memory"); }
DEVI void tma2(uint32_t dst, const CUtensorMap* m, int c0, int c1, uint32_t bar) {
  asm volatile("cp.async.bulk.tensor.2d.shared::cluster.global.mbarrier::complete_tx::bytes [%0], [%1, {%3, %4}], [%2];" ::"r"(dst), "l"(m), "r"(bar), "r"(c0), "r"(c1) : "memory");
}
DEVI void tma3(uint32_t dst, const CUtensorMap* m, int c0, int c1, int c2, uint32_t bar) {
  asm volatile("cp.async.bulk.tensor.3d.shared::cluster.global.mbarrier::complete_tx::bytes [%0], [%1, {%3, %4, %5}], [%2];" ::"r"(dst), "l"(m), "r"(bar), "r"(c0), "r"(c1), "r"(c2) : "memory");
}
DEVI void tma3_mc(uint32_t dst, const CUtensorMap* m, int c0, int c1, int c2, uint32_t bar) {
  asm volatile("cp.async.bulk.tensor.3d.shared::cluster.global.mbarrier::complete_tx::bytes.multicast::cluster [%0], [%1, {%3, %4, %5}], [%2], %6;" ::"r"(dst), "l"(m), "r"(bar), "r"(c0), "r"(c1), "r"(c2), "h"((uint16_t)3) : "memory");
}
DEVI void tma2_mc(uint32_t dst, const CUtensorMap* m, int c0, int c1, uint32_t bar) {
  asm volatile("cp.async.bulk.tensor.2d.shared::cluster.global.mbarrier::complete_tx::bytes.multicast::cluster [%0], [%1, {%3, %4}], [%2], %5;" ::"r"(dst), "l"(m), "r"(bar), "r"(c0), "r"(c1), "h"((uint16_t)3) : "memory");
}
DEVI void mbar_arrive_remote(uint32_t bar, uint32_t cta) {
  asm volatile("{\n.reg .b32 ra;\nmapa.shared::cluster.u32 ra, %0, %1;\nmbarrier.arrive.shared::cluster.b64 _, [ra];\n}" ::"r"(bar), "r"(cta) : "memory");
}
DEVI void tma3_store(const CUtensorMap* m, int c0, int c1, int c2, uint32_t src) {
  asm volatile("cp.async.bulk.tensor.3d.global.shared::cta.bulk_group [%0, {%2, %3, %4}], [%1];" ::"l"(m), "r"(src), "r"(c0), "r"(c1), "r"(c2) : "memory");
}
DEVI void bulk_load(uint32_t dst, const void* src, uint32_t bytes, uint32_t bar) {
  asm volatile("cp.async.bulk.shared::cluster.global.mbarrier::complete_tx::bytes [%0], [%1], %2, [%3];" ::"r"(dst), "l"(src), "r"(bytes), "r"(bar) : "memory");
}
DEVI void bulk_store(void* dst, uint32_t src, uint32_t bytes) {
  asm volatile("cp.async.bulk.global.shared::cta.bulk_group [%0], [%1], %2;" ::"l"(dst), "r"(src), "r"(bytes) : "memory");
}
DEVI void pf_map(const CUtensorMap* m) { asm volatile("prefetch.tensormap [%0];" ::"l"(m) : "memory"); }
DEVI void pf_l2(const void* p) { asm volatile("prefetch.global.L2 [%0];" ::"l"(p)); }
template <int OFF> DEVI uint32_t ldg_v(const void* p) { uint32_t v; asm volatile("ld.volatile.global.b32 %0, [%1 + %2];" : "=r"(v) : "l"(p), "n"(OFF)); return v; }
DEVI void bulk_commit() { asm volatile("cp.async.bulk.commit_group;" ::: "memory"); }
DEVI void bulk_wait_all() { asm volatile("cp.async.bulk.wait_group 0;" ::: "memory"); }
DEVI void bulk_wait_read() { asm volatile("cp.async.bulk.wait_group.read 0;" ::: "memory"); }
template <int R> DEVI void reg_inc() { asm volatile("setmaxnreg.inc.sync.aligned.u32 %0;" ::"n"(R)); }
template <int R> DEVI void reg_dec() { asm volatile("setmaxnreg.dec.sync.aligned.u32 %0;" ::"n"(R)); }
DEVI uint32_t prmt(uint32_t a, uint32_t b, uint32_t s) { uint32_t r; asm("prmt.b32 %0,%1,%2,%3;" : "=r"(r) : "r"(a), "r"(b), "r"(s)); return r; }
DEVI uint32_t lds32(uint32_t a) { uint32_t r; asm volatile("ld.shared.b32 %0,[%1];" : "=r"(r) : "r"(a)); return r; }
DEVI void sts32(uint32_t a, uint32_t x) { asm volatile("st.shared.b32 [%0],%1;" ::"r"(a), "r"(x) : "memory"); }
DEVI void sts128(uint32_t a, uint32_t x, uint32_t y, uint32_t z, uint32_t w) { asm volatile("st.shared.v4.b32 [%0],{%1,%2,%3,%4};" ::"r"(a), "r"(x), "r"(y), "r"(z), "r"(w) : "memory"); }
DEVI void sts128v(uint32_t a, uint32_t x, uint32_t y, uint32_t z, uint32_t w) { asm volatile("st.volatile.shared.v4.b32 [%0],{%1,%2,%3,%4};" ::"r"(a), "r"(x), "r"(y), "r"(z), "r"(w) : "memory"); }
DEVI void lds128(uint32_t a, uint32_t& x, uint32_t& y, uint32_t& z, uint32_t& w) { asm volatile("ld.shared.v4.b32 {%0,%1,%2,%3},[%4];" : "=r"(x), "=r"(y), "=r"(z), "=r"(w) : "r"(a) : "memory"); }
DEVI void ldsm4(uint32_t& r0, uint32_t& r1, uint32_t& r2, uint32_t& r3, uint32_t addr) {
  asm volatile("ldmatrix.sync.aligned.m8n8.x4.shared.b16 {%0,%1,%2,%3}, [%4];" : "=r"(r0), "=r"(r1), "=r"(r2), "=r"(r3) : "r"(addr) : "memory");
}
DEVI void ldsm4t(uint32_t& r0, uint32_t& r1, uint32_t& r2, uint32_t& r3, uint32_t addr) {
  asm volatile("ldmatrix.sync.aligned.m8n8.x4.trans.shared.b16 {%0,%1,%2,%3}, [%4];" : "=r"(r0), "=r"(r1), "=r"(r2), "=r"(r3) : "r"(addr) : "memory");
}
DEVI void stsm4(uint32_t addr, uint32_t r0, uint32_t r1, uint32_t r2, uint32_t r3) {
  asm volatile("stmatrix.sync.aligned.m8n8.x4.shared.b16 [%0], {%1,%2,%3,%4};" ::"r"(addr), "r"(r0), "r"(r1), "r"(r2), "r"(r3) : "memory");
}
DEVI void stsm4t(uint32_t addr, uint32_t r0, uint32_t r1, uint32_t r2, uint32_t r3) {
  asm volatile("stmatrix.sync.aligned.m8n8.x4.trans.shared.b16 [%0], {%1,%2,%3,%4};" ::"r"(addr), "r"(r0), "r"(r1), "r"(r2), "r"(r3) : "memory");
}
DEVI uint32_t movm(uint32_t a) { uint32_t r; asm volatile("movmatrix.sync.aligned.m8n8.trans.b16 %0, %1;" : "=r"(r) : "r"(a)); return r; }
DEVI uint32_t pack_bf16(float lo, float hi) { uint32_t r; asm("cvt.rn.bf16x2.f32 %0, %1, %2;" : "=r"(r) : "f"(hi), "f"(lo)); return r; }
DEVI uint32_t hmul2(uint32_t a, uint32_t b) { uint32_t r; asm("mul.rn.bf16x2 %0,%1,%2;" : "=r"(r) : "r"(a), "r"(b)); return r; }
DEVI uint32_t hadd2(uint32_t a, uint32_t b) { uint32_t r; asm("add.rn.bf16x2 %0,%1,%2;" : "=r"(r) : "r"(a), "r"(b)); return r; }
DEVI float bf_lo(uint32_t a) { return __uint_as_float(prmt(a, 0, 0x1044)); }
DEVI float bf_hi(uint32_t a) { return __uint_as_float(a & 0xFFFF0000u); }
DEVI void mma16(float (&c)[4], uint32_t a0, uint32_t a1, uint32_t a2, uint32_t a3, uint32_t b0, uint32_t b1) {
  asm volatile("mma.sync.aligned.m16n8k16.row.col.f32.bf16.bf16.f32 {%0,%1,%2,%3},{%4,%5,%6,%7},{%8,%9},{%0,%1,%2,%3};"
      : "+f"(c[0]), "+f"(c[1]), "+f"(c[2]), "+f"(c[3]) : "r"(a0), "r"(a1), "r"(a2), "r"(a3), "r"(b0), "r"(b1));
}
DEVI void mma8(float (&c)[4], uint32_t a0, uint32_t a1, uint32_t b0) {
  asm volatile("mma.sync.aligned.m16n8k8.row.col.f32.bf16.bf16.f32 {%0,%1,%2,%3},{%4,%5},{%6},{%0,%1,%2,%3};"
      : "+f"(c[0]), "+f"(c[1]), "+f"(c[2]), "+f"(c[3]) : "r"(a0), "r"(a1), "r"(b0));
}
DEVI float ex2(float x) { float r; asm volatile("ex2.approx.ftz.f32 %0, %1;" : "=f"(r) : "f"(x)); return r; }

DEVI uint32_t clk() { uint32_t c; asm volatile("mov.u32 %0, %%clock;" : "=r"(c)); return c; }
DEVI void wait_until(uint32_t t0, int dt) { while ((int)(clk() - t0) < dt) __nanosleep(40); }
DEVI void spin_until(uint32_t t0, int dt) { while ((int)(clk() - t0) < dt) {} }
DEVI uint32_t hfma2(uint32_t a, uint32_t b, uint32_t c) { uint32_t r; asm("fma.rn.bf16x2 %0,%1,%2,%3;" : "=r"(r) : "r"(a), "r"(b), "r"(c)); return r; }
DEVI void bar_sync_p(int on, int id, int n) { asm volatile("{\n.reg .pred p;\nsetp.ne.b32 p, %0, 0;\n@p bar.sync %1, %2;\n}" ::"r"(on), "r"(id), "r"(n) : "memory"); }
DEVI void bar_arrive_p(int on, int id, int n) { asm volatile("{\n.reg .pred p;\nsetp.ne.b32 p, %0, 0;\n@p bar.arrive %1, %2;\n}" ::"r"(on), "r"(id), "r"(n) : "memory"); }
DEVI void mbar_arrive_p(int on, uint32_t bar) { asm volatile("{\n.reg .pred p;\nsetp.ne.b32 p, %1, 0;\n@p mbarrier.arrive.shared::cta.b64 _, [%0];\n}" ::"r"(bar), "r"(on) : "memory"); }
DEVI void mbar_arrive2_p(int on, uint32_t bar, uint32_t rbar) {
  asm volatile("{\n.reg .pred p;\nsetp.ne.b32 p, %2, 0;\n@p mbarrier.arrive.shared::cta.b64 _, [%0];\n@p mbarrier.arrive.shared::cluster.b64 _, [%1];\n}" ::"r"(bar), "r"(rbar), "r"(on) : "memory");
}
DEVI void st_relaxed(uint4* p, uint32_t x, uint32_t y, uint32_t z, uint32_t w) {
  asm volatile("st.relaxed.gpu.global.v4.b32 [%0], {%1,%2,%3,%4};" ::"l"(p), "r"(x), "r"(y), "r"(z), "r"(w) : "memory");
}
DEVI uint32_t mapa(uint32_t a, uint32_t cta) { uint32_t r; asm("mapa.shared::cluster.u32 %0, %1, %2;" : "=r"(r) : "r"(a), "r"(cta)); return r; }
DEVI void st_async128(uint32_t a, uint32_t x, uint32_t y, uint32_t z, uint32_t w, uint32_t bar) {
  asm volatile("st.async.weak.shared::cluster.mbarrier::complete_tx::bytes.v4.b32 [%0], {%1,%2,%3,%4}, [%5];" ::"r"(a), "r"(x), "r"(y), "r"(z), "r"(w), "r"(bar) : "memory");
}

template<int OFF, int TB, int S> __device__ __forceinline__ void wgmma_rs_n128(float (&d)[S], uint32_t a0, uint32_t a1, uint32_t a2, uint32_t a3, uint64_t db, int sd) {
  asm volatile("{\n.reg .pred p;\nsetp.ne.b32 p, %69, 0;\n"
    "wgmma.mma_async.sync.aligned.m64n128k16.f32.bf16.bf16 {%0, %1, %2, %3, %4, %5, %6, %7, %8, %9, %10, %11, %12, %13, %14, %15, %16, %17, %18, %19, %20, %21, %22, %23, %24, %25, %26, %27, %28, %29, %30, %31, %32, %33, %34, %35, %36, %37, %38, %39, %40, %41, %42, %43, %44, %45, %46, %47, %48, %49, %50, %51, %52, %53, %54, %55, %56, %57, %58, %59, %60, %61, %62, %63}, {%64, %65, %66, %67}, %68, p, 1, 1, %70;\n}\n"
    : "+f"(d[OFF+0]), "+f"(d[OFF+1]), "+f"(d[OFF+2]), "+f"(d[OFF+3]), "+f"(d[OFF+4]), "+f"(d[OFF+5]), "+f"(d[OFF+6]), "+f"(d[OFF+7]), "+f"(d[OFF+8]), "+f"(d[OFF+9]), "+f"(d[OFF+10]), "+f"(d[OFF+11]), "+f"(d[OFF+12]), "+f"(d[OFF+13]), "+f"(d[OFF+14]), "+f"(d[OFF+15]), "+f"(d[OFF+16]), "+f"(d[OFF+17]), "+f"(d[OFF+18]), "+f"(d[OFF+19]), "+f"(d[OFF+20]), "+f"(d[OFF+21]), "+f"(d[OFF+22]), "+f"(d[OFF+23]), "+f"(d[OFF+24]), "+f"(d[OFF+25]), "+f"(d[OFF+26]), "+f"(d[OFF+27]), "+f"(d[OFF+28]), "+f"(d[OFF+29]), "+f"(d[OFF+30]), "+f"(d[OFF+31]), "+f"(d[OFF+32]), "+f"(d[OFF+33]), "+f"(d[OFF+34]), "+f"(d[OFF+35]), "+f"(d[OFF+36]), "+f"(d[OFF+37]), "+f"(d[OFF+38]), "+f"(d[OFF+39]), "+f"(d[OFF+40]), "+f"(d[OFF+41]), "+f"(d[OFF+42]), "+f"(d[OFF+43]), "+f"(d[OFF+44]), "+f"(d[OFF+45]), "+f"(d[OFF+46]), "+f"(d[OFF+47]), "+f"(d[OFF+48]), "+f"(d[OFF+49]), "+f"(d[OFF+50]), "+f"(d[OFF+51]), "+f"(d[OFF+52]), "+f"(d[OFF+53]), "+f"(d[OFF+54]), "+f"(d[OFF+55]), "+f"(d[OFF+56]), "+f"(d[OFF+57]), "+f"(d[OFF+58]), "+f"(d[OFF+59]), "+f"(d[OFF+60]), "+f"(d[OFF+61]), "+f"(d[OFF+62]), "+f"(d[OFF+63]) : "r"(a0), "r"(a1), "r"(a2), "r"(a3), "l"(db), "r"(sd), "n"(TB));
}
template<int OFF, int TB, int S> __device__ __forceinline__ void wgmma_rs_n64(float (&d)[S], uint32_t a0, uint32_t a1, uint32_t a2, uint32_t a3, uint64_t db, int sd) {
  asm volatile("{\n.reg .pred p;\nsetp.ne.b32 p, %37, 0;\n"
    "wgmma.mma_async.sync.aligned.m64n64k16.f32.bf16.bf16 {%0, %1, %2, %3, %4, %5, %6, %7, %8, %9, %10, %11, %12, %13, %14, %15, %16, %17, %18, %19, %20, %21, %22, %23, %24, %25, %26, %27, %28, %29, %30, %31}, {%32, %33, %34, %35}, %36, p, 1, 1, %38;\n}\n"
    : "+f"(d[OFF+0]), "+f"(d[OFF+1]), "+f"(d[OFF+2]), "+f"(d[OFF+3]), "+f"(d[OFF+4]), "+f"(d[OFF+5]), "+f"(d[OFF+6]), "+f"(d[OFF+7]), "+f"(d[OFF+8]), "+f"(d[OFF+9]), "+f"(d[OFF+10]), "+f"(d[OFF+11]), "+f"(d[OFF+12]), "+f"(d[OFF+13]), "+f"(d[OFF+14]), "+f"(d[OFF+15]), "+f"(d[OFF+16]), "+f"(d[OFF+17]), "+f"(d[OFF+18]), "+f"(d[OFF+19]), "+f"(d[OFF+20]), "+f"(d[OFF+21]), "+f"(d[OFF+22]), "+f"(d[OFF+23]), "+f"(d[OFF+24]), "+f"(d[OFF+25]), "+f"(d[OFF+26]), "+f"(d[OFF+27]), "+f"(d[OFF+28]), "+f"(d[OFF+29]), "+f"(d[OFF+30]), "+f"(d[OFF+31]) : "r"(a0), "r"(a1), "r"(a2), "r"(a3), "l"(db), "r"(sd), "n"(TB));
}
template<int OFF, int TB, int S> __device__ __forceinline__ void wgmma_rs_n48(float (&d)[S], uint32_t a0, uint32_t a1, uint32_t a2, uint32_t a3, uint64_t db, int sd) {
  asm volatile("{\n.reg .pred p;\nsetp.ne.b32 p, %29, 0;\n"
    "wgmma.mma_async.sync.aligned.m64n48k16.f32.bf16.bf16 {%0, %1, %2, %3, %4, %5, %6, %7, %8, %9, %10, %11, %12, %13, %14, %15, %16, %17, %18, %19, %20, %21, %22, %23}, {%24, %25, %26, %27}, %28, p, 1, 1, %30;\n}\n"
    : "+f"(d[OFF+0]), "+f"(d[OFF+1]), "+f"(d[OFF+2]), "+f"(d[OFF+3]), "+f"(d[OFF+4]), "+f"(d[OFF+5]), "+f"(d[OFF+6]), "+f"(d[OFF+7]), "+f"(d[OFF+8]), "+f"(d[OFF+9]), "+f"(d[OFF+10]), "+f"(d[OFF+11]), "+f"(d[OFF+12]), "+f"(d[OFF+13]), "+f"(d[OFF+14]), "+f"(d[OFF+15]), "+f"(d[OFF+16]), "+f"(d[OFF+17]), "+f"(d[OFF+18]), "+f"(d[OFF+19]), "+f"(d[OFF+20]), "+f"(d[OFF+21]), "+f"(d[OFF+22]), "+f"(d[OFF+23]) : "r"(a0), "r"(a1), "r"(a2), "r"(a3), "l"(db), "r"(sd), "n"(TB));
}
template<int OFF, int TB, int S> __device__ __forceinline__ void wgmma_rs_n16(float (&d)[S], uint32_t a0, uint32_t a1, uint32_t a2, uint32_t a3, uint64_t db, int sd) {
  asm volatile("{\n.reg .pred p;\nsetp.ne.b32 p, %13, 0;\n"
    "wgmma.mma_async.sync.aligned.m64n16k16.f32.bf16.bf16 {%0, %1, %2, %3, %4, %5, %6, %7}, {%8, %9, %10, %11}, %12, p, 1, 1, %14;\n}\n"
    : "+f"(d[OFF+0]), "+f"(d[OFF+1]), "+f"(d[OFF+2]), "+f"(d[OFF+3]), "+f"(d[OFF+4]), "+f"(d[OFF+5]), "+f"(d[OFF+6]), "+f"(d[OFF+7]) : "r"(a0), "r"(a1), "r"(a2), "r"(a3), "l"(db), "r"(sd), "n"(TB));
}
template<int OFF, int TA, int TB, int S> __device__ __forceinline__ void wgmma_ss_n160(float (&d)[S], uint64_t da, uint64_t db, int sd) {
  asm volatile("{\n.reg .pred p;\nsetp.ne.b32 p, %82, 0;\n"
    "wgmma.mma_async.sync.aligned.m64n160k16.f32.bf16.bf16 {%0, %1, %2, %3, %4, %5, %6, %7, %8, %9, %10, %11, %12, %13, %14, %15, %16, %17, %18, %19, %20, %21, %22, %23, %24, %25, %26, %27, %28, %29, %30, %31, %32, %33, %34, %35, %36, %37, %38, %39, %40, %41, %42, %43, %44, %45, %46, %47, %48, %49, %50, %51, %52, %53, %54, %55, %56, %57, %58, %59, %60, %61, %62, %63, %64, %65, %66, %67, %68, %69, %70, %71, %72, %73, %74, %75, %76, %77, %78, %79}, %80, %81, p, 1, 1, %83, %84;\n}\n"
    : "+f"(d[OFF+0]), "+f"(d[OFF+1]), "+f"(d[OFF+2]), "+f"(d[OFF+3]), "+f"(d[OFF+4]), "+f"(d[OFF+5]), "+f"(d[OFF+6]), "+f"(d[OFF+7]), "+f"(d[OFF+8]), "+f"(d[OFF+9]), "+f"(d[OFF+10]), "+f"(d[OFF+11]), "+f"(d[OFF+12]), "+f"(d[OFF+13]), "+f"(d[OFF+14]), "+f"(d[OFF+15]), "+f"(d[OFF+16]), "+f"(d[OFF+17]), "+f"(d[OFF+18]), "+f"(d[OFF+19]), "+f"(d[OFF+20]), "+f"(d[OFF+21]), "+f"(d[OFF+22]), "+f"(d[OFF+23]), "+f"(d[OFF+24]), "+f"(d[OFF+25]), "+f"(d[OFF+26]), "+f"(d[OFF+27]), "+f"(d[OFF+28]), "+f"(d[OFF+29]), "+f"(d[OFF+30]), "+f"(d[OFF+31]), "+f"(d[OFF+32]), "+f"(d[OFF+33]), "+f"(d[OFF+34]), "+f"(d[OFF+35]), "+f"(d[OFF+36]), "+f"(d[OFF+37]), "+f"(d[OFF+38]), "+f"(d[OFF+39]), "+f"(d[OFF+40]), "+f"(d[OFF+41]), "+f"(d[OFF+42]), "+f"(d[OFF+43]), "+f"(d[OFF+44]), "+f"(d[OFF+45]), "+f"(d[OFF+46]), "+f"(d[OFF+47]), "+f"(d[OFF+48]), "+f"(d[OFF+49]), "+f"(d[OFF+50]), "+f"(d[OFF+51]), "+f"(d[OFF+52]), "+f"(d[OFF+53]), "+f"(d[OFF+54]), "+f"(d[OFF+55]), "+f"(d[OFF+56]), "+f"(d[OFF+57]), "+f"(d[OFF+58]), "+f"(d[OFF+59]), "+f"(d[OFF+60]), "+f"(d[OFF+61]), "+f"(d[OFF+62]), "+f"(d[OFF+63]), "+f"(d[OFF+64]), "+f"(d[OFF+65]), "+f"(d[OFF+66]), "+f"(d[OFF+67]), "+f"(d[OFF+68]), "+f"(d[OFF+69]), "+f"(d[OFF+70]), "+f"(d[OFF+71]), "+f"(d[OFF+72]), "+f"(d[OFF+73]), "+f"(d[OFF+74]), "+f"(d[OFF+75]), "+f"(d[OFF+76]), "+f"(d[OFF+77]), "+f"(d[OFF+78]), "+f"(d[OFF+79]) : "l"(da), "l"(db), "r"(sd), "n"(TA), "n"(TB));
}

__device__ __align__(1024) uint16_t g_kvT[2 * 640 * 2048];
__device__ __align__(1024) uint16_t g_y2T[2 * 640 * 2048];
__device__ __align__(1024) uint16_t g_o[2048 * 640];
__device__ __align__(1024) uint16_t g_gate[2080];
__device__ __align__(1024) uint4 g_halo[128 * 5 * 32];
__device__ __align__(1024) unsigned g_cnt[46 * 32];
__device__ __align__(1024) unsigned g_launch[132 * 32];
#define CNT_KV(i) (g_cnt + 32 * (i))
#define CNT_O(i) (g_cnt + 32 * (10 + (i)))
#define CNT_Y(i) (g_cnt + 32 * (26 + (i)))
#define PTL(i) do {} while (0)
#define PTPL(on, i) do {} while (0)
#define PT(i) do {} while (0)
#define PTP(on, i) do {} while (0)

constexpr uint32_t SB = 1024;
constexpr uint32_t STG = 23552, WST = 15360;
DEVI constexpr uint32_t o_px(int ks) { return (((ks >> 1) + 1) & 3) * 2 * STG; }
DEVI constexpr uint32_t o_pw(int ks) { return o_px(ks) + 16384 + (ks & 1) * WST; }
constexpr uint32_t O_HALO = 0, O_QT = STG;
constexpr uint32_t O_OST = 2 * STG;
constexpr uint32_t P3S = 28672;
constexpr uint32_t HC = 8320, UC = 4624, UZ = 528;
constexpr uint32_t O_H0 = 5 * P3S, O_U2 = O_H0 + 3 * HC, O_H3 = O_U2 + UC, O_U0 = O_H3 + 2 * HC;
DEVI constexpr uint32_t o_h(int c) { return O_H0 + c * HC + (c > 2 ? UC : 0); }
DEVI constexpr uint32_t o_u(int c) { return c == 2 ? O_U2 : O_U0 + (c > 2 ? c - 1 : c) * UC; }
constexpr uint32_t O_Y = 208896;
DEVI constexpr uint32_t o_x(int c) { return c < 2 ? O_Y + c * 5120 : O_U0 + (c & 1) * UC; }
constexpr uint32_t O_HIN = O_Y + 16384;
DEVI constexpr uint32_t o_kin(int c) { return ((O_U0 + 127) & ~127u) + ((c & 1) ? 0 : 73 * 128); }
DEVI constexpr uint32_t o_p3(int ks) { return (ks < 6 ? ks : ks - 6) * P3S; }
constexpr uint32_t O_BT = 4 * P3S;
constexpr uint32_t O_GT = O_Y + 20480, O_GW = O_GT + 320;
constexpr uint32_t O_BAR = 231040;
constexpr uint32_t B_FULL = O_BAR, B_EMPTY = O_BAR + 8 * 8, B_P3F = O_BAR + 8 * 16, B_P3R = O_BAR + 8 * 26, B_G = O_BAR + 8 * 27, B_U = O_BAR + 8 * 28,
                   B_KVD = O_BAR + 8 * 33, B_KF = O_BAR + 8 * 36, B_Y = O_BAR + 8 * 38, B_EP = O_BAR + 8 * 40, B_LAST = O_BAR + 8 * 41, B_DONE = O_BAR + 8 * 42,
                   B_P1E = O_BAR + 8 * 43, B_HX = O_BAR + 8 * 43  , B_P3E = O_BAR + 8 * 52, B_HX0 = O_BAR + 8 * 57, B_KVS = O_BAR + 8 * 58, B_QD = O_BAR + 8 * 60, B_GD = O_BAR + 8 * 61, B_OR = O_BAR + 8 * 62, B_Q = O_BAR + 8 * 51;
constexpr uint32_t B_S13 = B_EMPTY + 8 * 5, B_S15 = B_EMPTY + 8 * 7, B_S19 = B_EMPTY + 8 * 3;
constexpr uint32_t O_GP = O_BAR + 512, O_EPOCH = O_GW + 1280;
constexpr uint32_t SMEM_BYTES = 232448;
static_assert(O_U0 + 4 * UC <= O_Y - 512 && o_kin(0) >= O_U0 + 2 * UC && O_EPOCH + 4 <= O_BAR && O_U0 >= 8 * STG, "smem map");
enum { NB_LEAD = 1, NB_HELP = 2, NB_HALO = 3, NB_ATT = 4, NB_G = 5, NB_TOK = 6, NB_RFULL = 8, NB_RFREE = 10 };

struct Maps { CUtensorMap x_par, w_main, w_tail, k_ld, v_ld, o_st, kv_st, wo, o_ld, y_ld, q_ld; };

template <int M> DEVI void conv_step(float (&acc)[128], uint32_t a0, uint32_t a1, uint32_t a2, uint32_t a3, uint32_t dl) {
  auto D = [&](int off) { return ((uint64_t)8 << 32) | (uint64_t)(uint32_t)(dl + off - 16 * M); };
  if constexpr (M == 0) wgmma_rs_n16<0, 0>(acc, a0, a1, a2, a3, D(0), 0);
  if constexpr (M <= 3) wgmma_rs_n48<8, 0>(acc, a0, a1, a2, a3, D(16), M == 0 ? 0 : 1);
  if constexpr (M <= 6) wgmma_rs_n48<32, 0>(acc, a0, a1, a2, a3, D(64), M == 0 ? 0 : 1);
  if constexpr (M <= 9) wgmma_rs_n48<56, 0>(acc, a0, a1, a2, a3, D(112), M == 0 ? 0 : 1);
  if constexpr (M <= 12) wgmma_rs_n48<80, 0>(acc, a0, a1, a2, a3, D(160), M == 0 ? 0 : 1);
  wgmma_rs_n48<104, 0>(acc, a0, a1, a2, a3, D(208), M == 0 ? 0 : 1);
}
DEVI constexpr int a_off(int P, int i) { return -4 * (64 * ((i & 4) ? 15 - P : P) + (i & 1) * 32 - (i & 2) * 2); }
template <int P> DEVI void load_pair(uint32_t (&a)[8], uint32_t ab) {
#pragma unroll
  for (int i = 0; i < 8; i++) a[i] = lds32(ab + a_off(P, i));
}
template <int P> DEVI void mma_pair(float (&acc)[128], uint32_t (&a)[8], uint32_t db) {
  wg_fence();
  conv_step<P>(acc, a[0], a[1], a[2], a[3], db);
  conv_step<15 - P>(acc, a[4], a[5], a[6], a[7], db);
  wg_commit();
}

template <int I0, int I1> DEVI void conv_reduce(uint32_t sb, int c, int ht, int chan, int bar, int nthr) {
  const uint32_t a0 = sb + o_h(c) + ht * 16, a2 = sb + o_u(c) + ht * 16, a3 = sb + o_x(c) + ht * 16;
  uint4* yp = (uint4*)(g_y2T + (size_t)chan * 2048) + ht;
#pragma unroll
  for (int i = I0; i < I1; i++) {
    uint4 p, q, r, s;
    if (i == I0) bar_sync(bar, nthr);
    lds128(a0 + i * 2048, p.x, p.y, p.z, p.w); lds128(a0 + 4160 + i * 2048, q.x, q.y, q.z, q.w);
    lds128(a2 + i * 2048, r.x, r.y, r.z, r.w); lds128(a3 + i * 2048, s.x, s.y, s.z, s.w);
    auto sum = [](uint32_t a, uint32_t b, uint32_t c, uint32_t d) { return hadd2(hadd2(hadd2(a, b), 0u), hadd2(c, d)) ^ 0x80008000u; };
    yp[i * 128] = make_uint4(sum(p.x, q.x, r.x, s.x), sum(p.y, q.y, r.y, s.y), sum(p.z, q.z, r.z, s.z), sum(p.w, q.w, r.w, s.w));
  }
}

template <int ODD, int PART> DEVI void pack_qkv(const float (&acc)[120], uint32_t (&Q)[10][2], uint32_t (&K)[10][2], uint32_t (&V)[10][2]) {
#pragma unroll
  for (int f = 0; f < 10; f++) {
    const bool tail = ODD ? (f < 2) : (f >= 8);
    const int fm = ODD ? f - 2 : f, ft = ODD ? f : f - 8;
    const int nq = tail ? 24 + ft : fm, nk = tail ? 26 + ft : 8 + fm, nv = tail ? 28 + ft : 16 + fm;
    if (PART == 0) { K[f][1] = pack_bf16(acc[4 * nk + 2], acc[4 * nk + 3]); V[f][1] = pack_bf16(acc[4 * nv + 2], acc[4 * nv + 3]); }
    if (PART == 1) { V[f][0] = pack_bf16(acc[4 * nv], acc[4 * nv + 1]); K[f][0] = pack_bf16(acc[4 * nk], acc[4 * nk + 1]); }
    if (PART == 2) { Q[f][0] = pack_bf16(acc[4 * nq], acc[4 * nq + 1]); Q[f][1] = pack_bf16(acc[4 * nq + 2], acc[4 * nq + 3]); }
  }
}
DEVI int pair_of(int c) {
  const int lo = 32 + 8 * c, hi = c - 4 + ((max(c - 29, 0) * 37) >> 8);
  int p; asm("{\n.reg .pred q;\nsetp.lt.s32 q, %1, 4;\nselp.b32 %0, %2, %3, q;\n}" : "=r"(p) : "r"(c), "r"(lo), "r"(hi));
  return p;
}
DEVI uint32_t make_ctx() {
  int b; asm volatile("mov.u32 %0, %%ctaid.x;" : "=r"(b));
  b += clk() & threadIdx.y;
  const int p = pair_of(b >> 1);
  const int j = b < 128 ? 8 * (p & 7) + (p >> 3) : 64;
  const int q = (j * 205) >> 10, r = j - 5 * q, i = j - q, co = (i * 79) >> 10;
  const int cp = r == 4 ? 4 : co, tb = r == 4 ? q : i - 13 * co;
  return ((2 * p + (b & 1)) & 255) | tb << 8 | (2 * cp + (b & 1)) << 12 | (b >> 7) << 16;
}
#define CTX() asm volatile("" : "+r"(ctx)); CTXU()
#define CTXU() int tid; asm volatile("mov.u32 %0, %%tid.x;" : "=r"(tid)); \
  const int lane = tid & 31, vb = ctx & 255, hg = (ctx >> 4) & 7, rt = ctx & 15, par = (ctx >> 3) & 1, mt = ctx & 7, rank = ctx & 1, \
  tb = (ctx >> 8) & 15, cb = (ctx >> 12) & 15; const bool main_cta = ctx < 65536; \
  (void)tid; (void)lane; (void)vb; (void)hg; (void)rt; (void)par; (void)mt; (void)rank; (void)tb; (void)cb; (void)main_cta
#define CTXW() CTX(); const int wg = warp >> 2, w = warp & 3, g = lane >> 2, t = lane & 3; const bool lead = (tid & 127) == 0; \
  (void)wg; (void)w; (void)g; (void)t; (void)lead

__global__ void __cluster_dims__(2, 1, 1) __launch_bounds__(512, 1)
fused_kernel(const uint16_t* __restrict__ xq, const uint16_t* __restrict__ wqkv, const uint16_t* __restrict__ gate_w, const __grid_constant__ Maps M, const uint16_t* __restrict__ shift_k, const uint16_t* __restrict__ ssm_k, const uint16_t* __restrict__ ssm_D,
             uint16_t* __restrict__ outp) {
  extern __shared__ __align__(1024) uint8_t smem_raw[];
  const uint32_t sb = smem_u32(smem_raw);
  const uint32_t t0 = clk();
  auto get_epoch = [&]() { mbar_wait(sb + B_EP, 0); return lds32(sb + O_EPOCH); };

  auto p1_load_x = [&](int ks, int p, int rank) {
    tma3(sb + o_px(ks), &M.x_par, ks * 32, (p >> 2) & 1, (p & 3) * 256 + rank * 128, sb + B_FULL + 8 * (ks & 7));
  };
  auto p1_load_w = [&](int ks, int p, int rank) {
    const uint32_t st = sb + o_pw(ks), fb = sb + B_FULL + 8 * (ks & 7);
    tma3_mc(st + rank * 6144, &M.w_main, (p >> 3) * 80 + 2 * (p & 8), ks * 32 + rank * 16, 0, fb);
    tma3_mc(st + 12288 + rank * 1536, &M.w_tail, (p >> 3) * 80 + 8 * (~p & 8), ks * 32 + rank * 16, 0, fb);
  };
  auto cta_pair = [&]() { return pair_of(blockIdx.x >> 1); };

  if (threadIdx.x < 32) {
    const unsigned b = blockIdx.x, l = threadIdx.x;
    const uint16_t* pfp = l < 16 ? xq + (16 * b + l) * 640 : wqkv + (15 * b + l - 16) * 64;
    if ((l | b >> 7 << 5) < 31) pf_l2(pfp);
  }
  const int warp = __shfl_sync(~0u, threadIdx.x >> 5, 0);
  if ((warp & 14) == 8) {
    if (elect_one()) {
#pragma unroll
      for (int s = 0; s < 8; s++) mbar_init(sb + O_BAR - 512 + 64 * warp + 8 * s, 5 * warp - 39);
      asm volatile("fence.mbarrier_init.release.cluster;" ::: "memory");
    }
    __syncwarp();
  }
  asm volatile("barrier.cluster.arrive.relaxed.aligned;" ::: "memory");
  if (warp == 8 && blockIdx.x < 128) {
    const int p = cta_pair(), rank = blockIdx.x & 1;
    if (elect_one()) { mbar_expect_tx(sb + B_FULL, 16384 + WST); p1_load_x(0, p, rank); }
    __syncwarp();
    asm volatile("barrier.cluster.wait.aligned;" ::: "memory");
    if (elect_one()) {
      p1_load_w(0, p, rank); PT(100);
      pf_map(&M.k_ld); pf_map(&M.v_ld);
    }
    __syncwarp();
  } else if (warp != 15) {
    asm volatile("barrier.cluster.wait.aligned;" ::: "memory");
    spin_until(t0, HOLD);
  }
  auto cluster_sync = [&]() {
    asm volatile("barrier.cluster.arrive.relaxed.aligned;" ::: "memory");
    asm volatile("barrier.cluster.wait.aligned;" ::: "memory");
  };
  auto init_rest = [&]() {
    if (warp >= 11 && elect_one()) {
#pragma unroll
      for (int s = 0; s < 12; s++) mbar_init(sb + O_BAR + 128 - 11 * 96 + 96 * warp + 8 * s, warp == 14 ? 2 : 1);
      asm volatile("fence.mbarrier_init.release.cluster;" ::: "memory");
    }
    __syncwarp();
    if (blockIdx.x < 128) bar_sync(0, 224); else cluster_sync();
  };
  uint32_t ctx = 0;

  if (warp < 8) {
    reg_inc<RC>();
    ctx = make_ctx();
    if (blockIdx.x >= 128) cluster_sync();
    else {
      {
        uint32_t Q[10][2], K[10][2], V[10][2];
        {
          {
            float acc[120];
            CTXW();
            const int odd = (cta_pair() >> 3) & 1;
            const uint32_t rsb = mapa(sb, (blockIdx.x & 1) ^ 1);
            {
              const uint32_t aa = sb + (warp * 16 + (lane & 15)) * 128 + (((lane >> 4) ^ (lane & 7)) << 4);
              constexpr int NA = DEFER > 3 ? DEFER : 3;
              uint32_t a[NA][8];
              auto load_a = [&](int ks) {
                uint32_t(&r)[8] = a[ks % NA];
                mbar_wait(sb + B_FULL + 8 * (ks & 7), (ks >> 3) & 1);
                PTP(lead && (wg || !(ks & 3)), wg ? 60 + ks : 80 + (ks >> 2));
                ldsm4(r[0], r[1], r[2], r[3], (aa ^ ((ks & 1) * 64)) + o_px(ks)); ldsm4(r[4], r[5], r[6], r[7], (aa ^ ((ks & 1) * 64 + 32)) + o_px(ks));
              };
              auto mma_q = [&](int ks, int h) {
                uint32_t(&r)[8] = a[ks % NA];
                wgmma_rs_n64<0, 1>(acc, r[4 * h], r[4 * h + 1], r[4 * h + 2], r[4 * h + 3], mkdesc(SB + o_pw(ks) + h * 6144, 2048, 1024, 1), ks | h);
              };
              auto mma_step = [&](int ks, int h) {
                uint32_t(&r)[8] = a[ks % NA];
                wg_fence();
                wgmma_rs_n128<32, 1>(acc, r[4 * h], r[4 * h + 1], r[4 * h + 2], r[4 * h + 3], mkdesc(SB + o_pw(ks) + h * 6144 + 2048, 2048, 1024, 1), ks | h);
                if (ks < 20 - DEFER) mma_q(ks, h);
                wgmma_rs_n48<96, 1>(acc, r[4 * h], r[4 * h + 1], r[4 * h + 2], r[4 * h + 3], mkdesc(SB + o_pw(ks) + 12288 + h * 1536, 512, 256, 3), ks | h);
                wg_commit();
              };
              if (lead) PT(1 + wg);
              load_a(0);
#pragma unroll
              for (int ks = 0; ks < 20; ks++) {
                if (LEAD && ks == 20 - LEAD) bar_sync_p(wg == 0, NB_LEAD, 256);
                mma_step(ks, 0);
                if (ks < 19 && ks >= NLATE) load_a(ks + 1);
                mma_step(ks, 1);
                if (ks < NLATE) load_a(ks + 1);
                if (ks >= 1 && ks <= 16) {
                  wg_wait<2>();
                  mbar_arrive2_p(lead, sb + B_EMPTY + 8 * ((ks - 1) & 7), rsb + B_EMPTY + 8 * ((ks - 1) & 7));
                } else if (ks < 19 && ks + 2 - NA >= 16) wg_wait<2>();
              }
              if (LEAD) bar_arrive_p(wg, NB_LEAD, 256);
              if (DEFER) {
                wg_fence();
#pragma unroll
                for (int i = 40 - 2 * DEFER; i < 40; i++) mma_q(i >> 1, i & 1);
                wg_commit();
              }
              mbar_wait(sb + B_S15, 1);
              wg_wait<1>();
              mbar_arrive_p(tid == 0, sb + B_P1E);
              if (!DEFER) wg_wait<0>();
              fence_regs<32, 120>(acc);
              PTPL(lead, 158 + wg);
            }
            if (odd) pack_qkv<1, 0>(acc, Q, K, V); else pack_qkv<0, 0>(acc, Q, K, V);
            if (warp == 7 && (blockIdx.x & 1)) {
              uint4* hp = g_halo + vb * 160 + lane;
              st_relaxed(hp, K[0][1], K[1][1], K[3][1], K[4][1]); st_relaxed(hp + 32, K[5][1], K[6][1], K[8][1], K[9][1]);
              st_relaxed(hp + 64, K[2][1], K[7][1], V[0][1], V[1][1]);
              st_relaxed(hp + 96, V[2][1], V[3][1], V[4][1], V[5][1]); st_relaxed(hp + 128, V[6][1], V[7][1], V[8][1], V[9][1]);
            }
            const uint32_t ho = sb + O_HALO + warp * 2560 + lane * 16;
            stsm4(ho, K[0][1], K[1][1], K[3][1], K[4][1]); stsm4(ho + 512, K[5][1], K[6][1], K[8][1], K[9][1]);
            stsm4(ho + 1024, K[2][1], K[7][1], V[0][1], V[1][1]);
            stsm4(ho + 1536, V[2][1], V[3][1], V[4][1], V[5][1]); stsm4(ho + 2048, V[6][1], V[7][1], V[8][1], V[9][1]);
            if (warp == 7) {
              if (!(blockIdx.x & 1)) {
                fence_async_smem();
                __syncwarp();
                if (elect_one())
                  asm volatile("cp.async.bulk.shared::cluster.shared::cta.mbarrier::complete_tx::bytes [%0], [%1], 2560, [%2];"
                               ::"r"(mapa(sb + O_HIN, 1)), "r"(sb + O_HALO + 7 * 2560), "r"(mapa(sb + B_HX0, 1)) : "memory");
              }
              __syncwarp();
            } else {
              __syncwarp();
              if (lane == 0) mbar_arrive(sb + B_HX + 8 + 8 * warp);
            }
            if (odd) pack_qkv<1, 1>(acc, Q, K, V); else pack_qkv<0, 1>(acc, Q, K, V);
            wg_wait<0>();
            fence_regs<0, 32>(acc);
            PTPL(lead, 50 + wg);
            mbar_arrive2_p(lead, sb + B_S19, rsb + B_S19);
            if (odd) pack_qkv<1, 2>(acc, Q, K, V); else pack_qkv<0, 2>(acc, Q, K, V);
#pragma unroll
            for (int f = 0; f < 10; f++) V[f][0] = movm(V[f][0]);
            if (lead) PT(52 + wg);
            if (wg) mbar_wait(sb + B_P1E, 0);
          }
          CTXW();
          uint32_t z = threadIdx.y;
          const bool gt0 = 2 * t > g, gt1 = 2 * t + 1 > g;
          const uint32_t pmask = (gt0 ? 0xFFFFu : 0u) | (gt1 ? 0xFFFF0000u : 0u);
          const uint32_t hs = warp ? O_HALO + (warp - 1) * 2560 : O_HIN, ha = sb + hs + lane * 16;
          const uint32_t va = sb + ((lane & 8) ? O_HALO + warp * 2560 : hs) + 1280 + (lane >> 4) * 128 + (lane & 7) * 16;
          uint32_t Qh[4][2], Kh[10], Vh[10];
          float c1[4][4] = {}, c2[4][4] = {}, c0[4][4] = {}, l[8][2], m[8], x[8];
#pragma unroll
          for (int j = 0; j < 4; j++) {
            const int fa = (j >> 1) * 5 + (j & 1) * 3, fh = (j >> 1) * 5 + 2;
            const bool mine = (j & 1) ? (t >= 2) : (t < 2);
            Qh[j][0] = mine ? Q[fh][0] : 0u; Qh[j][1] = mine ? Q[fh][1] : 0u;
            mma16(c1[j], Q[fa][0], Q[fa][1], Q[fa + 1][0], Q[fa + 1][1], K[fa][0], K[fa + 1][0]);
            mma16(c2[j], Q[fa][0], Q[fa][1], Q[fa + 1][0], Q[fa + 1][1], K[fa][1], K[fa + 1][1]);
            mma8(c1[j], Qh[j][0], Qh[j][1], K[fh][0]);
            mma8(c2[j], Qh[j][0], Qh[j][1], K[fh][1]);
          }
          if (lead) PT(54 + wg);
          mbar_wait(sb + (warp ? B_HX + 8 * warp : B_HX0), 0);
          if (lead) PT(56 + wg);
          ldsm4(Kh[0], Kh[1], Kh[3], Kh[4], ha); ldsm4(Kh[5], Kh[6], Kh[8], Kh[9], ha + 512);
          asm volatile("ldmatrix.sync.aligned.m8n8.x2.shared.b16 {%0,%1}, [%2];" : "=r"(Kh[2]), "=r"(Kh[7]) : "r"(ha + 1024) : "memory");
          auto load_v = [&]() {
#pragma unroll
            for (int i = 0; i < 5; i++) ldsm4t(Vh[2 * i], V[2 * i][1], Vh[2 * i + 1], V[2 * i + 1][1], va + i * 256);
          };
          load_v();
          const float C = 0.22360679774997896f * 1.4426950408889634f;
          auto max1 = [&](int r) { m[r] = fmaxf(l[r][0], l[r][1]); x[r] = __shfl_xor_sync(~0u, m[r], 1); };
          auto max2 = [&](int r) { m[r] = fmaxf(m[r], x[r]); x[r] = __shfl_xor_sync(~0u, m[r], 2); };
          auto exps = [&](int r) { const float mc = fmaxf(m[r], x[r]) * C; l[r][0] = ex2(fmaf(l[r][0], C, -mc)); l[r][1] = ex2(fmaf(l[r][1], C, -mc)); };
#pragma unroll
          for (int j = 0; j < 4; j++) { l[4 + j][0] = gt0 ? c1[j][2] : c2[j][2]; l[4 + j][1] = gt1 ? c1[j][3] : c2[j][3]; max1(4 + j); }
#pragma unroll
          for (int j = 0; j < 4; j++) {
            const int fa = (j >> 1) * 5 + (j & 1) * 3, fh = (j >> 1) * 5 + 2;
            mma16(c0[j], Q[fa][0], Q[fa][1], Q[fa + 1][0], Q[fa + 1][1], Kh[fa], Kh[fa + 1]);
            mma8(c0[j], Qh[j][0], Qh[j][1], Kh[fh]);
            max2(4 + j);
          }
          const bool have_halo = warp > 0 || mt > 0;
#pragma unroll
          for (int j = 0; j < 4; j++) {
            if (!have_halo) c0[j][0] = c0[j][1] = -INFINITY;
            l[j][0] = gt0 ? c0[j][0] : c1[j][0]; l[j][1] = gt1 ? c0[j][1] : c1[j][1];
            max1(j);
          }
          exps(4); exps(5);
#pragma unroll
          for (int j = 0; j < 4; j++) max2(j);
          exps(6); exps(7);
#pragma unroll
          for (int j = 0; j < 4; j++) exps(j);
          float o[12][4] = {}, sm[4][4] = {};
#pragma unroll
          for (int j = 0; j < 4; j++) {
            const int fa = (j >> 1) * 5 + (j & 1) * 3, fh = (j >> 1) * 5 + 2;
            const uint32_t pl = pack_bf16(l[j][0], l[j][1]), pu = pack_bf16(l[4 + j][0], l[4 + j][1]);
            const uint32_t p0 = pl & pmask, p2 = pl & ~pmask, p3 = pu & pmask, p5 = pu & ~pmask, z0 = z << (2 * j + 1), z1 = z << (2 * j + 2);
            mma8(sm[j], pl, pu, 0x3F803F80u);
#pragma unroll
            for (int q = 0; q < 3; q++) {
              const int f = q < 2 ? fa + q : fh;
              mma8(o[3 * j + q], p2, p3, V[f][0]);
              mma16(o[3 * j + q], p0, z0, z1, p5, Vh[f], V[f][1]);
            }
            asm volatile("rcp.approx.ftz.f32 %0, %0;" : "+f"(sm[j][0]));
            asm volatile("rcp.approx.ftz.f32 %0, %0;" : "+f"(sm[j][2]));
          }
#pragma unroll
          for (int i = 0; i < 12; i++) z &= __float_as_uint(o[i][0]);
          bar_sync_p(wg == 0, NB_HALO + z, 256);
          uint32_t O[10][2];
#pragma unroll
          for (int j = 0; j < 4; j++) {
            const int fa = (j >> 1) * 5 + (j & 1) * 3, fh = (j >> 1) * 5 + 2;
            const float r0 = sm[j][0], r1 = sm[j][2];
#pragma unroll
            for (int q = 0; q < 3; q++) {
              const int f = q < 2 ? fa + q : fh;
              const float* e = o[3 * j + q];
              const uint32_t o0 = pack_bf16(e[0] * r0, e[1] * r0), o1 = pack_bf16(e[2] * r1, e[3] * r1);
              if (q < 2 || !(j & 1)) { O[f][0] = o0; O[f][1] = o1; }
              else { O[f][0] = t >= 2 ? o0 : O[f][0]; O[f][1] = t >= 2 ? o1 : O[f][1]; }
            }
          }
          mbar_wait(sb + B_GD, 0);
          const uint32_t oa = sb + O_OST + wg * 2 * STG + (w * 16 + (lane & 15)) * 160 + (lane >> 4) * 16;
#pragma unroll
          for (int i = 0; i < 5; i++) stsm4(oa + i * 32, O[2 * i][0], O[2 * i][1], O[2 * i + 1][0], O[2 * i + 1][1]);
        }
      }
      {
        CTXW();
        fence_async_smem();
        bar_arrive(wg ? NB_LEAD : NB_ATT, 160);
        PTP(lead, 58 + wg);
        const uint32_t abase = sb + (g & 1) * 4160 + 4 * (1023 - 4 - 8 * w - (g >> 1) + t);
        float acc[128];
        uint32_t a0[8], a1[8], a2[8], a3[8];
#pragma unroll 1
        for (int c = wg ^ 1; c < 5; c += 2) {
          const uint32_t ab = abase + o_h(c);
          const uint32_t db = ((SB + o_u(c) + UZ - 16) >> 4) | 0x10000u;
          mbar_wait(sb + B_U + 8 * c, 0);
          load_pair<0>(a0, ab); load_pair<1>(a1, ab); load_pair<2>(a2, ab);
          PTP(lead, 85 + c);
          bar_sync(c ? NB_TOK + wg : NB_HALO, 256);
          fence_regs(acc);
          mma_pair<0>(acc, a0, db);
          load_pair<3>(a3, ab);
          mma_pair<1>(acc, a1, db); wg_wait<1>();  load_pair<4>(a0, ab);
          if (lead) PT(90 + c);
          mma_pair<2>(acc, a2, db); wg_wait<1>();  load_pair<5>(a1, ab);
          mma_pair<3>(acc, a3, db); wg_wait<1>();  load_pair<6>(a2, ab);
          mma_pair<4>(acc, a0, db); wg_wait<1>();  load_pair<7>(a3, ab);
          mma_pair<5>(acc, a1, db);
          mma_pair<6>(acc, a2, db);
          bar_arrive_p(c < 4, NB_TOK + (wg ^ 1), 256);
          mma_pair<7>(acc, a3, db);
          bar_arrive_p(c == 4, NB_TOK, 256);
          wg_wait<0>();
          fence_regs(acc);
          PTPL(lead, 95 + c);
          bar_sync(NB_RFREE + wg, 256);
          const uint32_t pb = sb + (w < 2 ? o_h(c) + w * 4160 : w == 2 ? o_u(c) : o_x(c)) + lane * 16;
          if (lane < 2 * w) sts128(pb, 0, 0, 0, 0);
#pragma unroll
          for (int q = 0; q < 8; q++) {
            uint32_t p[4];
#pragma unroll
            for (int i = 0; i < 4; i++) {
              const int nu = 4 * q + i;
              p[i] = pack_bf16(acc[4 * nu], acc[4 * nu + 1]);
              if (nu > 0) p[i] = hadd2(p[i], pack_bf16(acc[4 * nu - 2], acc[4 * nu - 1]));
            }
            stsm4t(pb + w * 32 + q * 512, p[0], p[1], p[2], p[3]);
            if (q == 3) bar_arrive_p(c == 4, NB_RFULL + 1, 256);
          }
          if (c < 4) bar_arrive(NB_RFULL + wg, 256);
          if (lead) PT(140 + c);
        }
        if (wg) {
          const int yb = (lds32(sb + O_EPOCH) & 1) * 640;
              conv_reduce<1, 2>(sb, 4, tid - 128, yb + 512 + ((vb & 0x61) | (vb & 6) << 2 | (vb >> 2 & 6)), 14, 128);
          bar_arrive(12, 256);
          PTPL(lead, 45);
        }
      }
    }
    if (warp < 4) {
      CTXW();
      const uint32_t rsb = mapa(sb, (blockIdx.x & 1) ^ 1);
      const uint32_t ba = sb + O_BT + ((lane >> 4) * 8 + (lane & 7)) * 128 + (((2 * w + ((lane >> 3) & 1)) ^ ((lane & 1) << 2 | (lane >> 1 & 3))) << 4);
      mbar_wait(sb + B_P3F, 0);
      if (lead) PT(145);
      float acc[80];
#pragma unroll
      for (int ks = 0; ks < 10; ks++) {
        if (ks == NPRE) {
          if (NPRE) { wg_wait<0>(); mbar_arrive2_p(lead, sb + B_P3E + 8 * NPRE, rsb + B_P3E + 8 * NPRE); }
          bar_sync_p(blockIdx.x < 128, NB_TOK, 256);
        }
        PTP(lead, 146 + ks);
        const uint64_t da = mkdesc(SB + o_p3(ks), 1024, 1024, 1), db = mkdesc(SB + o_p3(ks) + 8192, 16, 1024, 1);
        wg_fence();
#pragma unroll
        for (int j = 0; j < 4; j++) wgmma_ss_n160<0, 1, 0>(acc, da + j * 128, db + j * 2, j | ks);
        wg_commit();
        if (ks < 9) mbar_wait(sb + B_P3F + 8 * (ks + 1), 0);
        if (ks >= 1 && ks <= 4 && ks != NPRE) { wg_wait<1>(); mbar_arrive2_p(lead, sb + B_P3E + 8 * ks, rsb + B_P3E + 8 * ks); }
      }
      wg_wait<0>();
      fence_regs(acc);
      PTPL(lead, 156);
#pragma unroll
      for (int i = 0; i < 10; i++) {
        stsm4t(ba + i * 2048, pack_bf16(acc[8 * i], acc[8 * i + 1]), pack_bf16(acc[8 * i + 2], acc[8 * i + 3]),
               pack_bf16(acc[8 * i + 4], acc[8 * i + 5]), pack_bf16(acc[8 * i + 6], acc[8 * i + 7]));
        if (i & 1) bar_arrive(1 + (i >> 1), 256);
      }
      if (lead) PT(157);
    }
  } else if (warp < 12) {
    reg_dec<RH>();
    const int hw = warp - 8;
    init_rest();
    ctx = __shfl_sync(~0u, make_ctx(), 0);
    const int yrow = (ctx & 0x61) | (ctx & 6) << 2 | (ctx >> 2 & 6);
    if (ctx < 65536) {
      CTXU();
      const int pr = hw >> 1, hh = hw & 1, tk = vb & 63, odd = (lane >> 2) & 1;
      const uint32_t sel0 = odd ? 0x7632 : 0x5410, sel1 = odd ? 0x5410 : 0x7632;
      const uint32_t in = sb + o_kin(pr), fb = sb + B_KF + 8 * pr, out = sb + O_Y + pr * 8192;
      const uint32_t oa = out + (2 * lane + odd) * 64 + (((3 - 2 * hh) ^ (lane & 3)) << 4), ia = in + hh * 2048 + lane * 4;
      auto fetch = [&](int c) {
        wait_until(t0, KT0 + c * KTD + ((((vb * 37) & 63) * KPH) >> 6));
        if (elect_one()) {
          const int kb = 2 * c + (vb >> 6);
          mbar_expect_tx(fb, 69 * 128);
          tma2(in, &M.k_ld, kb * 64, 32 * tk - 4, fb);
          tma2(in + 36 * 128, &M.v_ld, kb * 64, 32 * tk - 1, fb);
          PT(20 + c);
        }
        __syncwarp();
      };
      if (hh == 0) fetch(pr);
      const uint4* skp = (const uint4*)shift_k + (2 * pr + (vb >> 6)) * 32 + lane;
      uint4 sk = __ldg(skp), sk1 = __ldg(skp + 128), sk2 = __ldg(skp + (pr ? 0 : 256));
#pragma unroll 1
      for (int c = pr; c < 5; c += 2) {
        {
          mbar_wait(fb, (c >> 1) & 1);
          if (hh == 0 && lane == 0) PT(25 + c);
          uint32_t k[20], o[17];
#pragma unroll
          for (int i = 0; i < 20; i++) { k[i] = lds32(ia + i * 128); if (i >= 3) o[i - 3] = lds32(ia + (33 + i) * 128); }
          fence_async_smem();
          bar_sync(12 + pr, 64);
          if (hh == 0) {
            if (c < 3) fetch(c + 2);
            else if (lane == 0) mbar_arrive(sb + B_KVD + 8 * (c - 3));
          }
          const uint32_t w0 = prmt(sk.x, sk.z, 0x5410), w1 = prmt(sk.x, sk.z, 0x7632), w2 = prmt(sk.y, sk.w, 0x5410), w3 = prmt(sk.y, sk.w, 0x7632);
#pragma unroll
          for (int i = 0; i < 17; i++) o[i] = hmul2(hfma2(k[i + 3], w0, hfma2(k[i + 2], w1, hfma2(k[i + 1], w2, hmul2(k[i], w3)))), o[i]);
          sk = sk1; sk1 = sk2;
#pragma unroll
          for (int i = 0; i < 4; i++) {
            const int e = 8 * (i >> 1) + (i & 1);
            const uint32_t a = (oa ^ ((i >> 1) * 16)) + (i & 1) * 4096;
            sts128(a, prmt(o[7 + e], o[6 + e], sel0), prmt(o[5 + e], o[4 + e], sel0), prmt(o[3 + e], o[2 + e], sel0), prmt(o[1 + e], o[e], sel0));
            sts128(a ^ 64, prmt(o[7 + e], o[6 + e], sel1), prmt(o[5 + e], o[4 + e], sel1), prmt(o[3 + e], o[2 + e], sel1), prmt(o[1 + e], o[e], sel1));
          }
          bar_sync(12 + pr, 64);
        }
        if (hh) {
          fence_async_smem();
          if (elect_one()) {
            const int kb = 2 * c + (vb >> 6);
            tma3_store(&M.kv_st, 0, kb * 64, 63 - tk, out);
            tma3_store(&M.kv_st, 0, 640 + kb * 64, 63 - tk, out + 4096);
            bulk_commit(); bulk_wait_all();
            mbar_arrive(sb + (c == 4 ? B_KVD + 16 : B_KVS + 4 * (c & 2)));
            PTL(35 + c);
          }
          __syncwarp();
        }
      }
    }
    CTXU();
    const int g = lane >> 2, t = lane & 3, row = 8 * hw + g;
    const uint32_t go = (tb * 160 + row) * 80 + cb * 8 + t;
    const int yb = __shfl_sync(~0u, get_epoch() & 1, 0) * 640;
    uint4 T[10];
    if (hw == 2) {
      if (main_cta) { mbar_wait(sb + B_LAST, 0); mbar_wait(sb + B_S15, 1); }
      if (elect_one()) {
        mbar_expect_tx(sb + B_Q, 20480);
#pragma unroll
        for (int h = 0; h < 2; h++) tma2(sb + O_QT + h * 10240, &M.q_ld, cb * 64 + 32 * h, tb * 160, sb + B_Q);
      }
      __syncwarp();
    }
    mbar_wait(sb + B_Q, 0);
#pragma unroll
    for (int i = 0; i < 10; i++) lds128(sb + O_QT + (i & 1) * 10240 + (i >> 1) * 2048 + row * 64 + t * 16, T[i].x, T[i].y, T[i].z, T[i].w);
    fence_async_smem();
    bar_sync(12 + (hw >> 1), 64);
    if (!(tid & 63)) mbar_arrive(sb + B_QD);
    if (tid == 256) PTL(40);
    if (main_cta) {
      bar_arrive(NB_RFREE, 256);
      bar_arrive(NB_RFREE + 1, 256);
      auto red = [&](int c) {
        const int wg = (c & 1) ^ 1;
        conv_reduce<0, 2>(sb, c, tid - 256, yb + 128 * c + yrow, NB_RFULL + wg, 256);
        if (hw == 3 && elect_one()) flag_add(CNT_Y(4 * c + (vb >> 5)), 1);
        if (tid == 256) PTL(41 + c);
        if (c < 3) bar_arrive(NB_RFREE + wg, 256);
        if (c == 2) {
          bar_sync(NB_HELP, 128);
          if (tid == 256) { mbar_arrive(sb + B_P3E); mbar_arrive_remote(sb + B_P3E, rank ^ 1); }
        }
      };
      if (hw == 3) {
        mbar_wait(sb + B_KVD + 16, 0);
        if (elect_one()) { flag_release(CNT_KV(4 + (vb >> 6))); PTL(32); }
        __syncwarp();
      }
#pragma unroll 1
      for (int c = 0; c < 4; c++) red(c);
      conv_reduce<0, 1>(sb, 4, tid - 256, yb + 512 + yrow, NB_RFULL + 1, 256);
      if (hw == 3 && elect_one()) { flag_add(CNT_Y(16 + (vb >> 5)), 1); PTL(19); }
    }
    uint32_t G[5];
    mbar_wait(sb + B_G, 0);
#pragma unroll
    for (int q = 0; q < 5; q++) { uint16_t v; asm volatile("ld.shared.u16 %0, [%1];" : "=h"(v) : "r"(sb + O_GT + (32 * q + row) * 2)); G[q] = prmt(v, 0, 0x1010); }
    auto gate_q = [&]() {
#pragma unroll
      for (int i = 0; i < 10; i++) { const uint32_t c = G[i >> 1] ^ 0x80008000u; T[i] = make_uint4(hmul2(T[i].x, c), hmul2(T[i].y, c), hmul2(T[i].z, c), hmul2(T[i].w, c)); }
    };
    gate_q();
    const uint32_t so = __shfl_sync(~0u, sb + O_BT + row * 128 + ((t ^ ((g & 1) << 2 | g >> 1)) << 4), lane);
    uint4* const op = (uint4*)__shfl_sync(~0u, (unsigned long long)((uint4*)outp + go), lane);
    if (main_cta) bar_sync(12, 256);
    const uint32_t ya = sb + O_Y + lane * 64 + ((hw ^ ((lane >> 1) & 3)) << 4);
    auto empty = [](uint32_t m) { return (m & 0xFFFFu) == 0 || m < 0x10000u; };
    int redo = blockIdx.y;
#pragma unroll 1
    do {
      if (redo) {
#pragma unroll 1
        for (int i = 0; i < (tb < 12 ? 10 : 8); i++) {
          const uint32_t a = ya + (i & 1) * 10240 + (i >> 1) * 2048;
          uint4 v;
          lds128(a, v.x, v.y, v.z, v.w);
          while (empty(__vimin3_u16x2(__vminu2(v.x, v.y), v.z, v.w)))
            asm volatile("ld.relaxed.gpu.global.v4.b32 {%0,%1,%2,%3}, [%4];" : "=r"(v.x), "=r"(v.y), "=r"(v.z), "=r"(v.w)
                         : "l"((const uint4*)g_y2T + (yb + cb * 64 + 32 * (i & 1) + lane) * 256 + tb * 20 + 4 * (i >> 1) + hw) : "memory");
          sts128(a, v.x, v.y, v.z, v.w);
        }
        __syncwarp();
#pragma unroll
        for (int i = 0; i < 10; i++) if (i < 8 || tb < 12) T[i] = __ldg((const uint4*)xq + go + (i >> 1) * 2560 + (i & 1) * 4);
        gate_q();
        PTL(49);
      }
      uint32_t m = ~0u;
#pragma unroll
      for (int h = 0; h < 2; h++) {
        if (h) mbar_wait(sb + B_Y + 8, 0); else mbar_wait_wd(sb + B_Y, 0, t0);
        if (tid == 256) PTL(46);
#pragma unroll
        for (int q = 0; q < 5; q++) {
          uint4 y;
          ldsm4t(y.x, y.y, y.z, y.w, ya + h * 10240 + q * 2048);
          const uint32_t mq = __vimin3_u16x2(__vimin3_u16x2(m, y.x, y.y), y.z, y.w);
          m = q == 4 && tb == 12 ? m : mq;
          uint4& r = T[2 * q + h];
          r = make_uint4(hmul2(r.x, y.x), hmul2(r.y, y.y), hmul2(r.z, y.z), hmul2(r.w, y.w));
        }
      }
      redo = __any_sync(~0u, empty(m));
    } while (redo);
    if (tid == 256) PTL(47);
#pragma unroll
    for (int q = 0; q < 5; q++) {
      const uint32_t c = hfma2(G[q], 0xBF80BF80u, 0x3F803F80u);
      bar_sync(1 + q, 256);
      if (q == 4) mbar_arrive_p(tid == 256, sb + B_DONE);
#pragma unroll
      for (int h = 0; h < 2; h++) {
        uint4 u;
        lds128((so ^ (h * 64)) + q * 4096, u.x, u.y, u.z, u.w);
        const uint4& r = T[2 * q + h];
        if (q < 4 || tb < 12)
          asm volatile("st.global.v4.b32 [%0], {%1,%2,%3,%4};" ::"l"(op + q * 2560 + h * 4), "r"(hfma2(u.x, c, r.x)), "r"(hfma2(u.y, c, r.y)), "r"(hfma2(u.z, c, r.z)), "r"(hfma2(u.w, c, r.w)) : "memory");
      }
    }
  } else {
    reg_dec<RP>();
    uint4 gwv = make_uint4(0, 0, 0, 0);
    if (warp == 15) {
      const int p = cta_pair(), rank = blockIdx.x & 1;
      asm volatile("barrier.cluster.wait.aligned;" ::: "memory");
      if (blockIdx.x >= 128) cluster_sync();
      else {
#pragma unroll 1
        for (int ks = 1;; ks += 2) {
          mbar_wait(sb + B_EMPTY + 8 * (ks & 7), ((ks >> 3) & 1) ^ 1);
          spin_until(t0, PT1 + (ks - 1) * PTD);
          if (elect_one()) { mbar_expect_tx(sb + B_FULL + 8 * (ks & 7), WST); p1_load_w(ks, p, rank); PT(100 + ks); }
          if (ks == 19) break;
          const int kn = ks + 1;
          mbar_wait(sb + B_EMPTY + 8 * (kn & 7), ((kn >> 3) & 1) ^ 1);
          spin_until(t0, PT1 + ks * PTD - PTE);
          if (elect_one()) { mbar_expect_tx(sb + B_FULL + 8 * (kn & 7), 16384 + WST); p1_load_x(kn, p, rank); p1_load_w(kn, p, rank); PT(100 + kn); }
        }
        if (elect_one()) mbar_arrive(sb + B_LAST);
#pragma unroll 1
        for (int i = 0; i < 2; i++) {
          mbar_wait(sb + B_KVS + 8 * i, 0);
          if (elect_one()) { flag_release(CNT_KV(2 * i + (p >> 5))); PTL(30 + i); }
          __syncwarp();
        }
        mbar_wait(sb + B_S19, 0);
      }
    } else {
      if (threadIdx.x < 384 + 80) gwv = __ldg((const uint4*)gate_w + threadIdx.x - 384);
      init_rest();
    }
    ctx = __shfl_sync(~0u, make_ctx(), 0);
    CTXU();
    if (warp == 12) {
        unsigned epoch = 0;
      if (lane == 0) epoch = *(volatile unsigned*)(g_launch + 32 * vb) + 1;
      if (main_cta) { sts128(sb + O_GW + lane * 16, gwv.x, gwv.y, gwv.z, gwv.w); bar_arrive(NB_G, 96); }
      if (lane == 0) {
        if ((sb & 0xFFFFFF) != SB) __trap();
        sts32(sb + O_EPOCH, epoch);
        mbar_arrive(sb + B_EP);
      }
      if (main_cta && rank) {
#pragma unroll
        for (int f = 0; f < 5; f++) st_relaxed(g_halo + vb * 160 + lane + 32 * f, ~0u, ~0u, ~0u, ~0u);
      }
      __syncwarp();
      if (elect_one()) flag_release(g_launch + 32 * vb);
      __syncwarp();
      if (main_cta) {
        uint4 h0 = make_uint4(0, 0, 0, 0);
        if (lane < 5) {
          h0 = __ldg((const uint4*)(ssm_k + (size_t)(128 * lane + vb) * 2048));
          h0.x = prmt(pack_bf16(bf_lo(h0.x) + bf_lo(__ldg(ssm_D + 128 * lane + vb)), 0.f), h0.x, 0x7610);
        }
        epoch = __shfl_sync(~0u, epoch, 0);
        const int ze = lane & 7;
        const uint32_t za = sb + (lane < 8 ? o_u(ze) + UZ : lane < 24 ? o_h(ze) + (lane >> 4) * 4160 + 4096 : o_u(ze) + 512);
        const uint16_t* hp = ssm_k + (size_t)vb * 2048 + 8;
        const uint16_t* up = g_kvT + (size_t)vb * 2048;
        const unsigned* fp = CNT_KV(vb >> 6);
        sts128(sb + O_Y - 512 + lane * 16, 0, 0, 0, 0);
        mbar_wait(sb + B_LAST, 0);
        mbar_wait(sb + B_S13, 1);
#pragma unroll
        for (int c = 0; c < 5; c++) {
          if (c == 0 || c == 3) {
            mbar_wait(sb + B_KVD + (c ? 8 : 0), 0);
#pragma unroll
            for (int e = c; e < (c ? 5 : 3); e++) sts128(sb + o_u(e) + lane * 16, 0, 0, 0, 0);
            if (ze >= c && ze < (c ? 5 : 3)) sts128(za, h0.x, h0.y, h0.z, h0.w);
            fence_async_smem();
            __syncwarp();
            if (elect_one()) {
#pragma unroll
              for (int e = c; e < (c ? 5 : 3); e++) {
                mbar_expect_tx(sb + B_U + 8 * e, 3 * 4096 - 16);
                if (c || e == 0) bulk_load(sb + o_u(e) + UZ + 16, hp + 128 * 2048 * e, 4080, sb + B_U + 8 * e);
              }
            }
          }
                    if (!(c & 1)) { flag_wait(fp + 32 * c, 64 * epoch); __syncwarp(); }
          if (elect_one()) {
            bulk_load(sb + o_h(c), up + 128 * 2048 * c, 4096, sb + B_U + 8 * c);
            bulk_load(sb + o_h(c) + 4160, up + (640 + 128 * c) * 2048, 4096, sb + B_U + 8 * c);
            if (c == 1) {
#pragma unroll
              for (int e = 1; e < 3; e++) bulk_load(sb + o_u(e) + UZ + 16, hp + 128 * 2048 * e, 4080, sb + B_U + 8 * e);
            }
            PTL(10 + c);
          }
        }
        mbar_wait(sb + B_OR, 0);
        if (elect_one()) {
#pragma unroll 1
          for (int i = 0; i < 40; i++) bulk_store(g_y2T + (size_t)((~epoch & 1) * 640 + 5 * vb) * 2048 + i * 256, sb + O_Y - 512, 512);
          bulk_commit(); bulk_wait_read();
          PTL(33);
        }
      }
    } else if (warp != 15) {
        const int r = warp - 13;
      if (main_cta) {
        if (rank && lane == 0) mbar_expect_tx(sb + B_HX0, 1280);
        const int t = lane & 3, grow = hg * 16 + (lane & 15);
        const uint32_t ga = sb + grow * 128 + (((4 * r + (lane >> 4)) ^ (lane & 7)) << 4);
        const uint32_t gp = sb + O_GW + 64 * r + 4 * t;
        float s0 = 0.f, s1 = 0.f;
        if (tid < 384 + 80) sts128(sb + O_GW + (tid - 384) * 16, gwv.x, gwv.y, gwv.z, gwv.w);
        bar_sync(NB_G, 96);
#pragma unroll 1
        for (int ks = 0; ks < 20; ks += 2) {
          uint32_t x[8], gw[4];
#pragma unroll
          for (int i = 0; i < 4; i++) gw[i] = lds32(gp + ks * 64 + i * 16);
          mbar_wait_wd(sb + B_FULL + 8 * (ks & 7), (ks >> 3) & 1, t0);
          if (r == 0 && lane == 0) PT(120 + ks);
          ldsm4(x[0], x[1], x[2], x[3], ga + o_px(ks)); ldsm4(x[4], x[5], x[6], x[7], (ga ^ 32) + o_px(ks));
#pragma unroll
          for (int i = 0; i < 8; i++) x[i] = hmul2(x[i], gw[i >> 1]);
          if (lane < 2) mbar_arrive(sb + B_EMPTY + 8 * (ks & 7) + 8 * lane + (x[0] & x[7] & threadIdx.y));
#pragma unroll
          for (int i = 0; i < 8; i += 4) {
            s0 += (bf_lo(x[i]) + bf_hi(x[i])) + (bf_lo(x[i + 2]) + bf_hi(x[i + 2]));
            s1 += (bf_lo(x[i + 1]) + bf_hi(x[i + 1])) + (bf_lo(x[i + 3]) + bf_hi(x[i + 3]));
          }
        }
        s0 += __shfl_xor_sync(~0u, s0, 1); s1 += __shfl_xor_sync(~0u, s1, 1);
        s0 += __shfl_xor_sync(~0u, s0, 2); s1 += __shfl_xor_sync(~0u, s1, 2);
        if (t < 2) sts32(sb + O_GP + r * 64 + (8 * t + (lane >> 2)) * 4, __float_as_uint(t ? s1 : s0));
        if (lane == 0) mbar_arrive(sb + B_GD);
        if (r == 0) bar_arrive(NB_G, 64);
        if (!rank) {
          uint4 d[3];
          if (mt > 0) {
            const uint4* hp = g_halo + (vb - 1) * 160 + r * 64 + lane;
            mbar_wait_wd(sb + B_EP, 0, t0);
            flag_wait_wd(g_launch + 32 * (vb - 1), lds32(sb + O_EPOCH), t0);
            mbar_wait_wd(sb + B_HX + 56, 0, t0);
            for (;;) {
              bool ok = true;
#pragma unroll
              for (int f = 0; f < 3; f++) {
                asm volatile("ld.relaxed.gpu.global.v4.b32 {%0,%1,%2,%3}, [%4];" : "=r"(d[f].x), "=r"(d[f].y), "=r"(d[f].z), "=r"(d[f].w) : "l"(hp + 32 * f) : "memory");
              }
#pragma unroll
              for (int f = 0; f < 3; f++) ok = ok && max(max(d[f].x, d[f].y), max(d[f].z, d[f].w)) != ~0u;
              if (__all_sync(~0u, ok)) break;
              if (clk() - t0 > 0x70000000u) __trap();
            }
          } else {
#pragma unroll
            for (int f = 0; f < 3; f++) d[f] = make_uint4(0, 0, 0, 0);
          }
#pragma unroll
          for (int f = 0; f < 3; f++) stsm4(sb + O_HIN + r * 1024 + f * 512 + lane * 16, d[f].x, d[f].y, d[f].z, d[f].w);
          __syncwarp();
          if (lane == 0) { mbar_arrive(sb + B_HX0); PTL(15 + r); }
        }
        if (r == 1) {
          bar_sync(NB_G, 64);
          if (lane < 16) {
            const uint32_t pa = sb + O_GP + lane * 4;
            const float z = __uint_as_float(lds32(pa)) + __uint_as_float(lds32(pa + 64));
            g_gate[2 * (mt * 128 + hg * 16 + lane) + par] = (uint16_t)pack_bf16(__fdividef(1.f, 1.f + __expf(-bf_lo(pack_bf16(z, 0.f)))), 0.f);
          }
          __syncwarp();
          if (elect_one()) flag_release(CNT_O(rt));
        }
      }
      mbar_wait_wd(sb + B_EP, 0, t0);
      const unsigned epoch = lds32(sb + O_EPOCH);
      if (main_cta) mbar_wait_wd(sb + B_P3E, 0, t0);
      const uint32_t yd = __shfl_sync(~0u, sb + O_Y + r * 10240 + threadIdx.y, 0), yb = __shfl_sync(~0u, sb + B_Y + 8 * r + threadIdx.y, 0);
      const int y1 = __shfl_sync(~0u, (epoch & 1) * 640 + cb * 64 + 32 * r + threadIdx.y, 0), y2 = __shfl_sync(~0u, tb * 5 + threadIdx.y, 0);
      if (elect_one()) { pf_map(&M.y_ld); mbar_expect_tx(yb, 10240); }
      __syncwarp();
      flag_wait_wd(CNT_Y(2 * cb + r), 32 * epoch, t0);
      __syncwarp();
      if (elect_one()) { tma3(yd, &M.y_ld, 0, y1, y2, yb); PTL(17 + r); }
      __syncwarp();
      mbar_wait_wd(sb + B_DONE, 0, t0);
    } else {
      const unsigned epoch = get_epoch();
      if (main_cta) {
        if (elect_one()) { pf_map(&M.o_st); pf_map(&M.wo); pf_map(&M.o_ld); }
        __syncwarp();
        bar_sync(NB_LEAD, 160);
        if (elect_one()) tma3_store(&M.o_st, hg * 80, par, mt * 128 + 64, sb + O_OST + 2 * STG);
        bar_sync(NB_ATT, 160);
        if (elect_one()) {
          tma3_store(&M.o_st, hg * 80, par, mt * 128, sb + O_OST);
          bulk_commit(); bulk_wait_all();
          flag_release(CNT_O(rt));
          mbar_arrive(sb + B_OR); mbar_arrive(sb + B_OR);
          PTL(3);
        }
        __syncwarp();
      }
      mbar_wait(sb + B_QD, 0);
#pragma unroll 1
      for (int ks = 0; ks < 5; ks++)
        if (elect_one()) tma2(sb + o_p3(ks), &M.wo, cb * 64, ks * 64, sb + B_P3F + 8 * ks);
      if (lane < 4) flag_wait(CNT_O(8 * (lane & 1) + min(7, (80 * tb + 79 * (lane >> 1)) >> 7)), 16 * epoch);
      __syncwarp();
      if (elect_one()) {
        PTL(4);
        mbar_arrive_remote(sb + B_P3R, rank ^ 1);
        mbar_expect_tx(sb + B_G, 320);
        bulk_load(sb + O_GT, g_gate + tb * 160, 320, sb + B_G);
      }
      mbar_wait(sb + B_P3R, 0);
      auto load_o = [&](int ks) {
        tma2_mc(sb + o_p3(ks) + 8192 + rank * 10240, &M.o_ld, ks * 64, tb * 160 + rank * 80, sb + B_P3F + 8 * ks);
        mbar_expect_tx(sb + B_P3F + 8 * ks, P3S);
      };
      auto load_wo = [&](int ks) { tma2(sb + o_p3(ks), &M.wo, cb * 64, ks * 64, sb + B_P3F + 8 * ks); };
#pragma unroll 1
      for (int ks = 0; ks < 5; ks++)
        if (elect_one()) load_o(ks);
#pragma unroll
      for (int ks = 5; ks < 10; ks++) {
        if (ks > 5 || main_cta) mbar_wait(sb + B_P3E + 8 * (ks - 5), 0);
        if (elect_one()) {
          load_o(ks); load_wo(ks);
          PTL(ks);
        }
      }
    }
  }
}

typedef CUresult (*PFN_enc)(CUtensorMap*, CUtensorMapDataType, cuuint32_t, void*, const cuuint64_t*, const cuuint64_t*, const cuuint32_t*,
                            const cuuint32_t*, CUtensorMapInterleave, CUtensorMapSwizzle, CUtensorMapL2promotion, CUtensorMapFloatOOBfill);
static void enc(PFN_enc f, CUtensorMap* m, const void* base, int rank, const cuuint64_t* dims, const cuuint64_t* strides, const cuuint32_t* box,
                CUtensorMapSwizzle sw) {
  const cuuint32_t es[5] = {1, 1, 1, 1, 1};
  f(m, CU_TENSOR_MAP_DATA_TYPE_BFLOAT16, rank, (void*)base, dims, strides, box, es, CU_TENSOR_MAP_INTERLEAVE_NONE, sw,
    CU_TENSOR_MAP_L2_PROMOTION_NONE, CU_TENSOR_MAP_FLOAT_OOB_FILL_NONE);
}

extern "C" void kernel_launch(void* const* d_in, const int* in_sizes, int n_in, void* d_out, int out_size) {
  (void)in_sizes; (void)n_in; (void)out_size;
  static PFN_enc f = nullptr;
  static void *kvT, *y2T, *o;
  if (!f) {
    void* p = nullptr;
    cudaDriverEntryPointQueryResult q;
    cudaGetDriverEntryPoint("cuTensorMapEncodeTiled", &p, cudaEnableDefault, &q);
    f = (PFN_enc)p;
    cudaGetSymbolAddress(&kvT, g_kvT); cudaGetSymbolAddress(&y2T, g_y2T); cudaGetSymbolAddress(&o, g_o);
    cudaFuncSetAttribute(fused_kernel, cudaFuncAttributeMaxDynamicSharedMemorySize, SMEM_BYTES);
  }
  Maps M;
  const CUtensorMapSwizzle S0 = CU_TENSOR_MAP_SWIZZLE_NONE, S32 = CU_TENSOR_MAP_SWIZZLE_32B, S64 = CU_TENSOR_MAP_SWIZZLE_64B, S128 = CU_TENSOR_MAP_SWIZZLE_128B;
  const cuuint64_t dpar[3] = {640, 2, 1024}, spar[2] = {1280, 2560};
  const cuuint64_t dw[3] = {640, 640, 3}, sw[2] = {3840, 1280};
  const cuuint64_t dnat[2] = {640, 2048}, snat[1] = {1280};
  const cuuint64_t dT2[3] = {32, 1280, 64}, sT[2] = {4096, 64};
  const cuuint64_t dwo[2] = {640, 640};
  { const cuuint32_t bx[3] = {64, 1, 128}; enc(f, &M.x_par, d_in[0], 3, dpar, spar, bx, S128); }
  { const cuuint32_t bx[3] = {64, 16, 3}; enc(f, &M.w_main, d_in[7], 3, dw, sw, bx, S128); }
  { const cuuint32_t bx[3] = {16, 16, 3}; enc(f, &M.w_tail, d_in[7], 3, dw, sw, bx, S32); }
  { const cuuint32_t bx[3] = {80, 1, 64}; enc(f, &M.o_st, o, 3, dpar, spar, bx, S0); }
  { const cuuint32_t bx[3] = {32, 64, 1}; enc(f, &M.kv_st, kvT, 3, dT2, sT, bx, S64); }
  { const cuuint32_t bx[3] = {32, 32, 5}; enc(f, &M.y_ld, y2T, 3, dT2, sT, bx, S64); }
  { const cuuint32_t bx[2] = {64, 36}; enc(f, &M.k_ld, d_in[1], 2, dnat, snat, bx, S0); }
  { const cuuint32_t bx[2] = {64, 33}; enc(f, &M.v_ld, d_in[2], 2, dnat, snat, bx, S0); }
  { const cuuint32_t bx[2] = {32, 160}; enc(f, &M.q_ld, d_in[0], 2, dnat, snat, bx, S0); }
  { const cuuint32_t bx[2] = {64, 64}; enc(f, &M.wo, d_in[8], 2, dwo, snat, bx, S128); }
  { const cuuint32_t bx[2] = {64, 80}; enc(f, &M.o_ld, o, 2, dnat, snat, bx, S128); }
  fused_kernel<<<130, 512, SMEM_BYTES, cudaStreamPerThread>>>((const uint16_t*)d_in[0], (const uint16_t*)d_in[7], (const uint16_t*)d_in[9], M, (const uint16_t*)d_in[3], (const uint16_t*)d_in[4], (const uint16_t*)d_in[5],
                                                              (uint16_t*)d_out);
}
```

```cpp
#include <cuda_runtime.h>
#include <cuda_bf16.h>
#include <cuda.h>
#include <stdint.h>
#include <type_traits>

#define DEVI __device__ __forceinline__
#define PT1 300
#define PTD 460
#define PTE 150
#define DEFER 4
#define KPH KTD
#define NLATE 4
#define NPRE 1
#define HDL 300
#define PTA 200
#define PTS 16
#define KT0 1500
#define KTD 1000
#define RC 192
#define RH 96
#define RP 32
#define HOLD 750
#define LEAD 3

DEVI uint32_t smem_u32(const void* p) { return (uint32_t)__cvta_generic_to_shared(p); }
DEVI void wg_fence() { asm volatile("wgmma.fence.sync.aligned;" ::: "memory"); }
DEVI void wg_commit() { asm volatile("wgmma.commit_group.sync.aligned;" ::: "memory"); }
template <int N> DEVI void wg_wait() { asm volatile("wgmma.wait_group.sync.aligned %0;" ::"n"(N) : "memory"); }
template <int A = 0, int B = -1, int S> DEVI void fence_regs(float (&d)[S]) {
#pragma unroll
  for (int i = A; i < (B < 0 ? S : B); i++) asm volatile("" : "+f"(d[i])::"memory");
}
DEVI uint64_t mkdesc(uint32_t addr, uint32_t lbo, uint32_t sbo, int swz) {
  return (uint64_t)((addr & 0x3FFFF) >> 4) | ((uint64_t)(lbo >> 4) << 16) | ((uint64_t)(sbo >> 4) << 32) | ((uint64_t)swz << 62);
}
DEVI void mbar_init(uint32_t bar, uint32_t cnt) { asm volatile("mbarrier.init.shared::cta.b64 [%0], %1;" ::"r"(bar), "r"(cnt) : "memory"); }
DEVI void mbar_expect_tx(uint32_t bar, uint32_t bytes) { asm volatile("mbarrier.arrive.expect_tx.shared::cta.b64 _, [%0], %1;" ::"r"(bar), "r"(bytes) : "memory"); }
DEVI void mbar_arrive(uint32_t bar) { asm volatile("mbarrier.arrive.shared::cta.b64 _, [%0];" ::"r"(bar) : "memory"); }
DEVI void mbar_wait(uint32_t bar, uint32_t parity) {
  asm volatile("{\n.reg .pred p;\nLAB_WAIT:\nmbarrier.try_wait.parity.shared::cta.b64 p, [%0], %1;\n@!p bra LAB_WAIT;\n}" ::"r"(bar), "r"(parity) : "memory");
}
DEVI void mbar_wait_wd(uint32_t bar, uint32_t parity, uint32_t t0) {
  asm volatile("{\n.reg .pred p;\n.reg .u32 c;\nLAB_WAIT:\nmbarrier.try_wait.parity.shared::cta.b64 p, [%0], %1;\n@p bra DONE;\nmov.u32 c, %%clock;\nsub.u32 c, c, %2;\nsetp.lt.u32 p, c, 0x70000000;\n@p bra LAB_WAIT;\ntrap;\nDONE:\n}" ::"r"(bar), "r"(parity), "r"(t0) : "memory");
}
DEVI void flag_wait(const unsigned* p, unsigned target) {
  asm volatile("{\n.reg .pred p;\n.reg .s32 v;\nLAB_WAIT:\nld.relaxed.gpu.global.u32 v, [%0];\nsub.s32 v, v, %1;\nsetp.lt.s32 p, v, 0;\n@p bra LAB_WAIT;\n}" ::"l"(p), "r"(target) : "memory");
}
DEVI void flag_wait_wd(const unsigned* p, unsigned target, uint32_t t0) {
  asm volatile("{\n.reg .pred p;\n.reg .s32 v;\nLAB_WAIT:\nld.relaxed.gpu.global.u32 v, [%0];\nsub.s32 v, v, %1;\nsetp.ge.s32 p, v, 0;\n@p bra DONE;\nmov.u32 v, %%clock;\nsub.s32 v, v, %2;\nsetp.lt.u32 p, v, 0x70000000;\n@p bra LAB_WAIT;\ntrap;\nDONE:\n}" ::"l"(p), "r"(target), "r"(t0) : "memory");
}
DEVI void flag_add(unsigned* p, unsigned v) { asm volatile("red.relaxed.gpu.global.add.u32 [%0], %1;" ::"l"(p), "r"(v) : "memory"); }
DEVI void flag_release(unsigned* p) { asm volatile("fence.proxy.async;\nred.relaxed.gpu.global.add.u32 [%0], 1;" ::"l"(p) : "memory"); }
DEVI void fence_async_smem() { asm volatile("fence.proxy.async.shared::cta;" ::: "memory"); }
DEVI bool elect_one() { uint32_t p; asm volatile("{\n.reg .pred P;\nelect.sync _|P, 0xffffffff;\nselp.u32 %0, 1, 0, P;\n}" : "=r"(p)); return p; }
DEVI void bar_sync(int id, int n) { asm volatile("bar.sync %0, %1;" ::"r"(id), "r"(n) : "memory"); }
DEVI void bar_arrive(int id, int n) { asm volatile("bar.arrive %0, %1;" ::"r"(id), "r"(n) : "memory"); }
DEVI void tma2(uint32_t dst, const CUtensorMap* m, int c0, int c1, uint32_t bar) {
  asm volatile("cp.async.bulk.tensor.2d.shared::cluster.global.mbarrier::complete_tx::bytes [%0], [%1, {%3, %4}], [%2];" ::"r"(dst), "l"(m), "r"(bar), "r"(c0), "r"(c1) : "memory");
}
DEVI void tma3(uint32_t dst, const CUtensorMap* m, int c0, int c1, int c2, uint32_t bar) {
  asm volatile("cp.async.bulk.tensor.3d.shared::cluster.global.mbarrier::complete_tx::bytes [%0], [%1, {%3, %4, %5}], [%2];" ::"r"(dst), "l"(m), "r"(bar), "r"(c0), "r"(c1), "r"(c2) : "memory");
}
DEVI void tma3_mc(uint32_t dst, const CUtensorMap* m, int c0, int c1, int c2, uint32_t bar) {
  asm volatile("cp.async.bulk.tensor.3d.shared::cluster.global.mbarrier::complete_tx::bytes.multicast::cluster [%0], [%1, {%3, %4, %5}], [%2], %6;" ::"r"(dst), "l"(m), "r"(bar), "r"(c0), "r"(c1), "r"(c2), "h"((uint16_t)3) : "memory");
}
DEVI void tma2_mc(uint32_t dst, const CUtensorMap* m, int c0, int c1, uint32_t bar) {
  asm volatile("cp.async.bulk.tensor.2d.shared::cluster.global.mbarrier::complete_tx::bytes.multicast::cluster [%0], [%1, {%3, %4}], [%2], %5;" ::"r"(dst), "l"(m), "r"(bar), "r"(c0), "r"(c1), "h"((uint16_t)3) : "memory");
}
DEVI void mbar_arrive_remote(uint32_t bar, uint32_t cta) {
  asm volatile("{\n.reg .b32 ra;\nmapa.shared::cluster.u32 ra, %0, %1;\nmbarrier.arrive.shared::cluster.b64 _, [ra];\n}" ::"r"(bar), "r"(cta) : "memory");
}
DEVI void tma3_store(const CUtensorMap* m, int c0, int c1, int c2, uint32_t src) {
  asm volatile("cp.async.bulk.tensor.3d.global.shared::cta.bulk_group [%0, {%2, %3, %4}], [%1];" ::"l"(m), "r"(src), "r"(c0), "r"(c1), "r"(c2) : "memory");
}
DEVI void bulk_load(uint32_t dst, const void* src, uint32_t bytes, uint32_t bar) {
  asm volatile("cp.async.bulk.shared::cluster.global.mbarrier::complete_tx::bytes [%0], [%1], %2, [%3];" ::"r"(dst), "l"(src), "r"(bytes), "r"(bar) : "memory");
}
DEVI void bulk_store(void* dst, uint32_t src, uint32_t bytes) {
  asm volatile("cp.async.bulk.global.shared::cta.bulk_group [%0], [%1], %2;" ::"l"(dst), "r"(src), "r"(bytes) : "memory");
}
DEVI void pf_map(const CUtensorMap* m) { asm volatile("prefetch.tensormap [%0];" ::"l"(m) : "memory"); }
DEVI void pf_l2(const void* p) { asm volatile("prefetch.global.L2 [%0];" ::"l"(p)); }
template <int OFF> DEVI uint32_t ldg_v(const void* p) { uint32_t v; asm volatile("ld.volatile.global.b32 %0, [%1 + %2];" : "=r"(v) : "l"(p), "n"(OFF)); return v; }
DEVI void bulk_commit() { asm volatile("cp.async.bulk.commit_group;" ::: "memory"); }
DEVI void bulk_wait_all() { asm volatile("cp.async.bulk.wait_group 0;" ::: "memory"); }
DEVI void bulk_wait_read() { asm volatile("cp.async.bulk.wait_group.read 0;" ::: "memory"); }
template <int R> DEVI void reg_inc() { asm volatile("setmaxnreg.inc.sync.aligned.u32 %0;" ::"n"(R)); }
template <int R> DEVI void reg_dec() { asm volatile("setmaxnreg.dec.sync.aligned.u32 %0;" ::"n"(R)); }
DEVI uint32_t prmt(uint32_t a, uint32_t b, uint32_t s) { uint32_t r; asm("prmt.b32 %0,%1,%2,%3;" : "=r"(r) : "r"(a), "r"(b), "r"(s)); return r; }
DEVI uint32_t lds32(uint32_t a) { uint32_t r; asm volatile("ld.shared.b32 %0,[%1];" : "=r"(r) : "r"(a)); return r; }
DEVI void sts32(uint32_t a, uint32_t x) { asm volatile("st.shared.b32 [%0],%1;" ::"r"(a), "r"(x) : "memory"); }
DEVI void sts128(uint32_t a, uint32_t x, uint32_t y, uint32_t z, uint32_t w) { asm volatile("st.shared.v4.b32 [%0],{%1,%2,%3,%4};" ::"r"(a), "r"(x), "r"(y), "r"(z), "r"(w) : "memory"); }
DEVI void sts128v(uint32_t a, uint32_t x, uint32_t y, uint32_t z, uint32_t w) { asm volatile("st.volatile.shared.v4.b32 [%0],{%1,%2,%3,%4};" ::"r"(a), "r"(x), "r"(y), "r"(z), "r"(w) : "memory"); }
DEVI void lds128(uint32_t a, uint32_t& x, uint32_t& y, uint32_t& z, uint32_t& w) { asm volatile("ld.shared.v4.b32 {%0,%1,%2,%3},[%4];" : "=r"(x), "=r"(y), "=r"(z), "=r"(w) : "r"(a) : "memory"); }
DEVI void ldsm4(uint32_t& r0, uint32_t& r1, uint32_t& r2, uint32_t& r3, uint32_t addr) {
  asm volatile("ldmatrix.sync.aligned.m8n8.x4.shared.b16 {%0,%1,%2,%3}, [%4];" : "=r"(r0), "=r"(r1), "=r"(r2), "=r"(r3) : "r"(addr) : "memory");
}
DEVI void ldsm4t(uint32_t& r0, uint32_t& r1, uint32_t& r2, uint32_t& r3, uint32_t addr) {
  asm volatile("ldmatrix.sync.aligned.m8n8.x4.trans.shared.b16 {%0,%1,%2,%3}, [%4];" : "=r"(r0), "=r"(r1), "=r"(r2), "=r"(r3) : "r"(addr) : "memory");
}
DEVI void stsm4(uint32_t addr, uint32_t r0, uint32_t r1, uint32_t r2, uint32_t r3) {
  asm volatile("stmatrix.sync.aligned.m8n8.x4.shared.b16 [%0], {%1,%2,%3,%4};" ::"r"(addr), "r"(r0), "r"(r1), "r"(r2), "r"(r3) : "memory");
}
DEVI void stsm4t(uint32_t addr, uint32_t r0, uint32_t r1, uint32_t r2, uint32_t r3) {
  asm volatile("stmatrix.sync.aligned.m8n8.x4.trans.shared.b16 [%0], {%1,%2,%3,%4};" ::"r"(addr), "r"(r0), "r"(r1), "r"(r2), "r"(r3) : "memory");
}
DEVI uint32_t movm(uint32_t a) { uint32_t r; asm volatile("movmatrix.sync.aligned.m8n8.trans.b16 %0, %1;" : "=r"(r) : "r"(a)); return r; }
DEVI uint32_t pack_bf16(float lo, float hi) { uint32_t r; asm("cvt.rn.bf16x2.f32 %0, %1, %2;" : "=r"(r) : "f"(hi), "f"(lo)); return r; }
DEVI uint32_t hmul2(uint32_t a, uint32_t b) { uint32_t r; asm("mul.rn.bf16x2 %0,%1,%2;" : "=r"(r) : "r"(a), "r"(b)); return r; }
DEVI uint32_t hadd2(uint32_t a, uint32_t b) { uint32_t r; asm("add.rn.bf16x2 %0,%1,%2;" : "=r"(r) : "r"(a), "r"(b)); return r; }
DEVI float bf_lo(uint32_t a) { return __uint_as_float(prmt(a, 0, 0x1044)); }
DEVI float bf_hi(uint32_t a) { return __uint_as_float(a & 0xFFFF0000u); }
DEVI void mma16(float (&c)[4], uint32_t a0, uint32_t a1, uint32_t a2, uint32_t a3, uint32_t b0, uint32_t b1) {
  asm volatile("mma.sync.aligned.m16n8k16.row.col.f32.bf16.bf16.f32 {%0,%1,%2,%3},{%4,%5,%6,%7},{%8,%9},{%0,%1,%2,%3};"
      : "+f"(c[0]), "+f"(c[1]), "+f"(c[2]), "+f"(c[3]) : "r"(a0), "r"(a1), "r"(a2), "r"(a3), "r"(b0), "r"(b1));
}
DEVI void mma8(float (&c)[4], uint32_t a0, uint32_t a1, uint32_t b0) {
  asm volatile("mma.sync.aligned.m16n8k8.row.col.f32.bf16.bf16.f32 {%0,%1,%2,%3},{%4,%5},{%6},{%0,%1,%2,%3};"
      : "+f"(c[0]), "+f"(c[1]), "+f"(c[2]), "+f"(c[3]) : "r"(a0), "r"(a1), "r"(b0));
}
DEVI float ex2(float x) { float r; asm volatile("ex2.approx.ftz.f32 %0, %1;" : "=f"(r) : "f"(x)); return r; }

DEVI uint32_t clk() { uint32_t c; asm volatile("mov.u32 %0, %%clock;" : "=r"(c)); return c; }
DEVI void wait_until(uint32_t t0, int dt) { while ((int)(clk() - t0) < dt) __nanosleep(40); }
DEVI void spin_until(uint32_t t0, int dt) { while ((int)(clk() - t0) < dt) {} }
DEVI uint32_t hfma2(uint32_t a, uint32_t b, uint32_t c) { uint32_t r; asm("fma.rn.bf16x2 %0,%1,%2,%3;" : "=r"(r) : "r"(a), "r"(b), "r"(c)); return r; }
DEVI void bar_sync_p(int on, int id, int n) { asm volatile("{\n.reg .pred p;\nsetp.ne.b32 p, %0, 0;\n@p bar.sync %1, %2;\n}" ::"r"(on), "r"(id), "r"(n) : "memory"); }
DEVI void bar_arrive_p(int on, int id, int n) { asm volatile("{\n.reg .pred p;\nsetp.ne.b32 p, %0, 0;\n@p bar.arrive %1, %2;\n}" ::"r"(on), "r"(id), "r"(n) : "memory"); }
DEVI void mbar_arrive_p(int on, uint32_t bar) { asm volatile("{\n.reg .pred p;\nsetp.ne.b32 p, %1, 0;\n@p mbarrier.arrive.shared::cta.b64 _, [%0];\n}" ::"r"(bar), "r"(on) : "memory"); }
DEVI void mbar_arrive2_p(int on, uint32_t bar, uint32_t rbar) {
  asm volatile("{\n.reg .pred p;\nsetp.ne.b32 p, %2, 0;\n@p mbarrier.arrive.shared::cta.b64 _, [%0];\n@p mbarrier.arrive.shared::cluster.b64 _, [%1];\n}" ::"r"(bar), "r"(rbar), "r"(on) : "memory");
}
DEVI void st_relaxed(uint4* p, uint32_t x, uint32_t y, uint32_t z, uint32_t w) {
  asm volatile("st.relaxed.gpu.global.v4.b32 [%0], {%1,%2,%3,%4};" ::"l"(p), "r"(x), "r"(y), "r"(z), "r"(w) : "memory");
}
DEVI uint32_t mapa(uint32_t a, uint32_t cta) { uint32_t r; asm("mapa.shared::cluster.u32 %0, %1, %2;" : "=r"(r) : "r"(a), "r"(cta)); return r; }
DEVI void st_async128(uint32_t a, uint32_t x, uint32_t y, uint32_t z, uint32_t w, uint32_t bar) {
  asm volatile("st.async.weak.shared::cluster.mbarrier::complete_tx::bytes.v4.b32 [%0], {%1,%2,%3,%4}, [%5];" ::"r"(a), "r"(x), "r"(y), "r"(z), "r"(w), "r"(bar) : "memory");
}

template<int OFF, int TB, int S> __device__ __forceinline__ void wgmma_rs_n128(float (&d)[S], uint32_t a0, uint32_t a1, uint32_t a2, uint32_t a3, uint64_t db, int sd) {
  asm volatile("{\n.reg .pred p;\nsetp.ne.b32 p, %69, 0;\n"
    "wgmma.mma_async.sync.aligned.m64n128k16.f32.bf16.bf16 {%0, %1, %2, %3, %4, %5, %6, %7, %8, %9, %10, %11, %12, %13, %14, %15, %16, %17, %18, %19, %20, %21, %22, %23, %24, %25, %26, %27, %28, %29, %30, %31, %32, %33, %34, %35, %36, %37, %38, %39, %40, %41, %42, %43, %44, %45, %46, %47, %48, %49, %50, %51, %52, %53, %54, %55, %56, %57, %58, %59, %60, %61, %62, %63}, {%64, %65, %66, %67}, %68, p, 1, 1, %70;\n}\n"
    : "+f"(d[OFF+0]), "+f"(d[OFF+1]), "+f"(d[OFF+2]), "+f"(d[OFF+3]), "+f"(d[OFF+4]), "+f"(d[OFF+5]), "+f"(d[OFF+6]), "+f"(d[OFF+7]), "+f"(d[OFF+8]), "+f"(d[OFF+9]), "+f"(d[OFF+10]), "+f"(d[OFF+11]), "+f"(d[OFF+12]), "+f"(d[OFF+13]), "+f"(d[OFF+14]), "+f"(d[OFF+15]), "+f"(d[OFF+16]), "+f"(d[OFF+17]), "+f"(d[OFF+18]), "+f"(d[OFF+19]), "+f"(d[OFF+20]), "+f"(d[OFF+21]), "+f"(d[OFF+22]), "+f"(d[OFF+23]), "+f"(d[OFF+24]), "+f"(d[OFF+25]), "+f"(d[OFF+26]), "+f"(d[OFF+27]), "+f"(d[OFF+28]), "+f"(d[OFF+29]), "+f"(d[OFF+30]), "+f"(d[OFF+31]), "+f"(d[OFF+32]), "+f"(d[OFF+33]), "+f"(d[OFF+34]), "+f"(d[OFF+35]), "+f"(d[OFF+36]), "+f"(d[OFF+37]), "+f"(d[OFF+38]), "+f"(d[OFF+39]), "+f"(d[OFF+40]), "+f"(d[OFF+41]), "+f"(d[OFF+42]), "+f"(d[OFF+43]), "+f"(d[OFF+44]), "+f"(d[OFF+45]), "+f"(d[OFF+46]), "+f"(d[OFF+47]), "+f"(d[OFF+48]), "+f"(d[OFF+49]), "+f"(d[OFF+50]), "+f"(d[OFF+51]), "+f"(d[OFF+52]), "+f"(d[OFF+53]), "+f"(d[OFF+54]), "+f"(d[OFF+55]), "+f"(d[OFF+56]), "+f"(d[OFF+57]), "+f"(d[OFF+58]), "+f"(d[OFF+59]), "+f"(d[OFF+60]), "+f"(d[OFF+61]), "+f"(d[OFF+62]), "+f"(d[OFF+63]) : "r"(a0), "r"(a1), "r"(a2), "r"(a3), "l"(db), "r"(sd), "n"(TB));
}
template<int OFF, int TB, int S> __device__ __forceinline__ void wgmma_rs_n64(float (&d)[S], uint32_t a0, uint32_t a1, uint32_t a2, uint32_t a3, uint64_t db, int sd) {
  asm volatile("{\n.reg .pred p;\nsetp.ne.b32 p, %37, 0;\n"
    "wgmma.mma_async.sync.aligned.m64n64k16.f32.bf16.bf16 {%0, %1, %2, %3, %4, %5, %6, %7, %8, %9, %10, %11, %12, %13, %14, %15, %16, %17, %18, %19, %20, %21, %22, %23, %24, %25, %26, %27, %28, %29, %30, %31}, {%32, %33, %34, %35}, %36, p, 1, 1, %38;\n}\n"
    : "+f"(d[OFF+0]), "+f"(d[OFF+1]), "+f"(d[OFF+2]), "+f"(d[OFF+3]), "+f"(d[OFF+4]), "+f"(d[OFF+5]), "+f"(d[OFF+6]), "+f"(d[OFF+7]), "+f"(d[OFF+8]), "+f"(d[OFF+9]), "+f"(d[OFF+10]), "+f"(d[OFF+11]), "+f"(d[OFF+12]), "+f"(d[OFF+13]), "+f"(d[OFF+14]), "+f"(d[OFF+15]), "+f"(d[OFF+16]), "+f"(d[OFF+17]), "+f"(d[OFF+18]), "+f"(d[OFF+19]), "+f"(d[OFF+20]), "+f"(d[OFF+21]), "+f"(d[OFF+22]), "+f"(d[OFF+23]), "+f"(d[OFF+24]), "+f"(d[OFF+25]), "+f"(d[OFF+26]), "+f"(d[OFF+27]), "+f"(d[OFF+28]), "+f"(d[OFF+29]), "+f"(d[OFF+30]), "+f"(d[OFF+31]) : "r"(a0), "r"(a1), "r"(a2), "r"(a3), "l"(db), "r"(sd), "n"(TB));
}
template<int OFF, int TB, int S> __device__ __forceinline__ void wgmma_rs_n48(float (&d)[S], uint32_t a0, uint32_t a1, uint32_t a2, uint32_t a3, uint64_t db, int sd) {
  asm volatile("{\n.reg .pred p;\nsetp.ne.b32 p, %29, 0;\n"
    "wgmma.mma_async.sync.aligned.m64n48k16.f32.bf16.bf16 {%0, %1, %2, %3, %4, %5, %6, %7, %8, %9, %10, %11, %12, %13, %14, %15, %16, %17, %18, %19, %20, %21, %22, %23}, {%24, %25, %26, %27}, %28, p, 1, 1, %30;\n}\n"
    : "+f"(d[OFF+0]), "+f"(d[OFF+1]), "+f"(d[OFF+2]), "+f"(d[OFF+3]), "+f"(d[OFF+4]), "+f"(d[OFF+5]), "+f"(d[OFF+6]), "+f"(d[OFF+7]), "+f"(d[OFF+8]), "+f"(d[OFF+9]), "+f"(d[OFF+10]), "+f"(d[OFF+11]), "+f"(d[OFF+12]), "+f"(d[OFF+13]), "+f"(d[OFF+14]), "+f"(d[OFF+15]), "+f"(d[OFF+16]), "+f"(d[OFF+17]), "+f"(d[OFF+18]), "+f"(d[OFF+19]), "+f"(d[OFF+20]), "+f"(d[OFF+21]), "+f"(d[OFF+22]), "+f"(d[OFF+23]) : "r"(a0), "r"(a1), "r"(a2), "r"(a3), "l"(db), "r"(sd), "n"(TB));
}
template<int OFF, int TB, int S> __device__ __forceinline__ void wgmma_rs_n16(float (&d)[S], uint32_t a0, uint32_t a1, uint32_t a2, uint32_t a3, uint64_t db, int sd) {
  asm volatile("{\n.reg .pred p;\nsetp.ne.b32 p, %13, 0;\n"
    "wgmma.mma_async.sync.aligned.m64n16k16.f32.bf16.bf16 {%0, %1, %2, %3, %4, %5, %6, %7}, {%8, %9, %10, %11}, %12, p, 1, 1, %14;\n}\n"
    : "+f"(d[OFF+0]), "+f"(d[OFF+1]), "+f"(d[OFF+2]), "+f"(d[OFF+3]), "+f"(d[OFF+4]), "+f"(d[OFF+5]), "+f"(d[OFF+6]), "+f"(d[OFF+7]) : "r"(a0), "r"(a1), "r"(a2), "r"(a3), "l"(db), "r"(sd), "n"(TB));
}
template<int OFF, int TA, int TB, int S> __device__ __forceinline__ void wgmma_ss_n160(float (&d)[S], uint64_t da, uint64_t db, int sd) {
  asm volatile("{\n.reg .pred p;\nsetp.ne.b32 p, %82, 0;\n"
    "wgmma.mma_async.sync.aligned.m64n160k16.f32.bf16.bf16 {%0, %1, %2, %3, %4, %5, %6, %7, %8, %9, %10, %11, %12, %13, %14, %15, %16, %17, %18, %19, %20, %21, %22, %23, %24, %25, %26, %27, %28, %29, %30, %31, %32, %33, %34, %35, %36, %37, %38, %39, %40, %41, %42, %43, %44, %45, %46, %47, %48, %49, %50, %51, %52, %53, %54, %55, %56, %57, %58, %59, %60, %61, %62, %63, %64, %65, %66, %67, %68, %69, %70, %71, %72, %73, %74, %75, %76, %77, %78, %79}, %80, %81, p, 1, 1, %83, %84;\n}\n"
    : "+f"(d[OFF+0]), "+f"(d[OFF+1]), "+f"(d[OFF+2]), "+f"(d[OFF+3]), "+f"(d[OFF+4]), "+f"(d[OFF+5]), "+f"(d[OFF+6]), "+f"(d[OFF+7]), "+f"(d[OFF+8]), "+f"(d[OFF+9]), "+f"(d[OFF+10]), "+f"(d[OFF+11]), "+f"(d[OFF+12]), "+f"(d[OFF+13]), "+f"(d[OFF+14]), "+f"(d[OFF+15]), "+f"(d[OFF+16]), "+f"(d[OFF+17]), "+f"(d[OFF+18]), "+f"(d[OFF+19]), "+f"(d[OFF+20]), "+f"(d[OFF+21]), "+f"(d[OFF+22]), "+f"(d[OFF+23]), "+f"(d[OFF+24]), "+f"(d[OFF+25]), "+f"(d[OFF+26]), "+f"(d[OFF+27]), "+f"(d[OFF+28]), "+f"(d[OFF+29]), "+f"(d[OFF+30]), "+f"(d[OFF+31]), "+f"(d[OFF+32]), "+f"(d[OFF+33]), "+f"(d[OFF+34]), "+f"(d[OFF+35]), "+f"(d[OFF+36]), "+f"(d[OFF+37]), "+f"(d[OFF+38]), "+f"(d[OFF+39]), "+f"(d[OFF+40]), "+f"(d[OFF+41]), "+f"(d[OFF+42]), "+f"(d[OFF+43]), "+f"(d[OFF+44]), "+f"(d[OFF+45]), "+f"(d[OFF+46]), "+f"(d[OFF+47]), "+f"(d[OFF+48]), "+f"(d[OFF+49]), "+f"(d[OFF+50]), "+f"(d[OFF+51]), "+f"(d[OFF+52]), "+f"(d[OFF+53]), "+f"(d[OFF+54]), "+f"(d[OFF+55]), "+f"(d[OFF+56]), "+f"(d[OFF+57]), "+f"(d[OFF+58]), "+f"(d[OFF+59]), "+f"(d[OFF+60]), "+f"(d[OFF+61]), "+f"(d[OFF+62]), "+f"(d[OFF+63]), "+f"(d[OFF+64]), "+f"(d[OFF+65]), "+f"(d[OFF+66]), "+f"(d[OFF+67]), "+f"(d[OFF+68]), "+f"(d[OFF+69]), "+f"(d[OFF+70]), "+f"(d[OFF+71]), "+f"(d[OFF+72]), "+f"(d[OFF+73]), "+f"(d[OFF+74]), "+f"(d[OFF+75]), "+f"(d[OFF+76]), "+f"(d[OFF+77]), "+f"(d[OFF+78]), "+f"(d[OFF+79]) : "l"(da), "l"(db), "r"(sd), "n"(TA), "n"(TB));
}

__device__ __align__(1024) uint16_t g_kvT[2 * 640 * 2048];
__device__ __align__(1024) uint16_t g_y2T[2 * 640 * 2048];
__device__ __align__(1024) uint16_t g_o[2048 * 640];
__device__ __align__(1024) uint16_t g_gate[2080];
__device__ __align__(1024) uint4 g_halo[128 * 5 * 32];
__device__ __align__(1024) unsigned g_cnt[46 * 32];
__device__ __align__(1024) unsigned g_launch[132 * 32];
#define CNT_KV(i) (g_cnt + 32 * (i))
#define CNT_O(i) (g_cnt + 32 * (10 + (i)))
#define CNT_Y(i) (g_cnt + 32 * (26 + (i)))
#define PTL(i) do {} while (0)
#define PTPL(on, i) do {} while (0)
#define PT(i) do {} while (0)
#define PTP(on, i) do {} while (0)

constexpr uint32_t SB = 1024;
constexpr uint32_t STG = 23552, WST = 15360;
DEVI constexpr uint32_t o_px(int ks) { return (((ks >> 1) + 1) & 3) * 2 * STG; }
DEVI constexpr uint32_t o_pw(int ks) { return o_px(ks) + 16384 + (ks & 1) * WST; }
constexpr uint32_t O_HALO = 0, O_QT = STG;
constexpr uint32_t O_OST = 2 * STG;
constexpr uint32_t P3S = 28672;
constexpr uint32_t HC = 8320, UC = 4624, UZ = 528;
constexpr uint32_t O_H0 = 5 * P3S, O_U2 = O_H0 + 3 * HC, O_H3 = O_U2 + UC, O_U0 = O_H3 + 2 * HC;
DEVI constexpr uint32_t o_h(int c) { return O_H0 + c * HC + (c > 2 ? UC : 0); }
DEVI constexpr uint32_t o_u(int c) { return c == 2 ? O_U2 : O_U0 + (c > 2 ? c - 1 : c) * UC; }
constexpr uint32_t O_Y = 208896;
DEVI constexpr uint32_t o_x(int c) { return c < 2 ? O_Y + c * 5120 : O_U0 + (c & 1) * UC; }
constexpr uint32_t O_HIN = O_Y + 16384;
DEVI constexpr uint32_t o_kin(int c) { return ((O_U0 + 127) & ~127u) + ((c & 1) ? 0 : 73 * 128); }
DEVI constexpr uint32_t o_p3(int ks) { return (ks < 6 ? ks : ks - 6) * P3S; }
constexpr uint32_t O_BT = 4 * P3S;
constexpr uint32_t O_GT = O_Y + 20480, O_GW = O_GT + 320;
constexpr uint32_t O_BAR = 231040;
constexpr uint32_t B_FULL = O_BAR, B_EMPTY = O_BAR + 8 * 8, B_P3F = O_BAR + 8 * 16, B_P3R = O_BAR + 8 * 26, B_G = O_BAR + 8 * 27, B_U = O_BAR + 8 * 28,
                   B_KVD = O_BAR + 8 * 33, B_KF = O_BAR + 8 * 36, B_Y = O_BAR + 8 * 38, B_EP = O_BAR + 8 * 40, B_LAST = O_BAR + 8 * 41, B_DONE = O_BAR + 8 * 42,
                   B_P1E = O_BAR + 8 * 43, B_HX = O_BAR + 8 * 43  , B_P3E = O_BAR + 8 * 52, B_HX0 = O_BAR + 8 * 57, B_KVS = O_BAR + 8 * 58, B_QD = O_BAR + 8 * 60, B_GD = O_BAR + 8 * 61, B_OR = O_BAR + 8 * 62, B_HC = O_BAR + 8 * 63, B_Q = O_BAR + 8 * 51;
constexpr uint32_t B_S13 = B_EMPTY + 8 * 5, B_S15 = B_EMPTY + 8 * 7, B_S19 = B_EMPTY + 8 * 3;
constexpr uint32_t O_GP = O_BAR + 512, O_EPOCH = O_GW + 1280;
constexpr uint32_t SMEM_BYTES = 232448;
static_assert(O_U0 + 4 * UC <= O_Y - 512 && o_kin(0) >= O_U0 + 2 * UC && O_EPOCH + 4 <= O_BAR && O_U0 >= 8 * STG, "smem map");
enum { NB_LEAD = 1, NB_HELP = 2, NB_HALO = 3, NB_ATT = 4, NB_G = 5, NB_TOK = 6, NB_RFULL = 8, NB_RFREE = 10 };

struct Maps { CUtensorMap x_par, w_main, w_tail, k_ld, v_ld, o_st, kv_st, wo, o_ld, y_ld, q_ld; };

template <int M> DEVI void conv_step(float (&acc)[128], uint32_t a0, uint32_t a1, uint32_t a2, uint32_t a3, uint32_t dl) {
  auto D = [&](int off) { return ((uint64_t)8 << 32) | (uint64_t)(uint32_t)(dl + off - 16 * M); };
  if constexpr (M == 0) wgmma_rs_n16<0, 0>(acc, a0, a1, a2, a3, D(0), 0);
  if constexpr (M <= 3) wgmma_rs_n48<8, 0>(acc, a0, a1, a2, a3, D(16), M == 0 ? 0 : 1);
  if constexpr (M <= 6) wgmma_rs_n48<32, 0>(acc, a0, a1, a2, a3, D(64), M == 0 ? 0 : 1);
  if constexpr (M <= 9) wgmma_rs_n48<56, 0>(acc, a0, a1, a2, a3, D(112), M == 0 ? 0 : 1);
  if constexpr (M <= 12) wgmma_rs_n48<80, 0>(acc, a0, a1, a2, a3, D(160), M == 0 ? 0 : 1);
  wgmma_rs_n48<104, 0>(acc, a0, a1, a2, a3, D(208), M == 0 ? 0 : 1);
}
DEVI constexpr int a_off(int P, int i) { return -4 * (64 * ((i & 4) ? 15 - P : P) + (i & 1) * 32 - (i & 2) * 2); }
template <int P> DEVI void load_pair(uint32_t (&a)[8], uint32_t ab) {
#pragma unroll
  for (int i = 0; i < 8; i++) a[i] = lds32(ab + a_off(P, i));
}
template <int P> DEVI void mma_pair(float (&acc)[128], uint32_t (&a)[8], uint32_t db) {
  wg_fence();
  conv_step<P>(acc, a[0], a[1], a[2], a[3], db);
  conv_step<15 - P>(acc, a[4], a[5], a[6], a[7], db);
  wg_commit();
}

template <int I0, int I1> DEVI void conv_reduce(uint32_t sb, int c, int ht, int chan, int bar, int nthr) {
  const uint32_t a0 = sb + o_h(c) + ht * 16, a2 = sb + o_u(c) + ht * 16, a3 = sb + o_x(c) + ht * 16;
  uint4* yp = (uint4*)(g_y2T + (size_t)chan * 2048) + ht;
#pragma unroll
  for (int i = I0; i < I1; i++) {
    uint4 p, q, r, s;
    if (i == I0) bar_sync(bar, nthr);
    lds128(a0 + i * 2048, p.x, p.y, p.z, p.w); lds128(a0 + 4160 + i * 2048, q.x, q.y, q.z, q.w);
    lds128(a2 + i * 2048, r.x, r.y, r.z, r.w); lds128(a3 + i * 2048, s.x, s.y, s.z, s.w);
    auto sum = [](uint32_t a, uint32_t b, uint32_t c, uint32_t d) { return hadd2(hadd2(hadd2(a, b), 0u), hadd2(c, d)) ^ 0x80008000u; };
    yp[i * 128] = make_uint4(sum(p.x, q.x, r.x, s.x), sum(p.y, q.y, r.y, s.y), sum(p.z, q.z, r.z, s.z), sum(p.w, q.w, r.w, s.w));
  }
}

template <int ODD, int PART> DEVI void pack_qkv(const float (&acc)[120], uint32_t (&Q)[10][2], uint32_t (&K)[10][2], uint32_t (&V)[10][2]) {
#pragma unroll
  for (int f = 0; f < 10; f++) {
    const bool tail = ODD ? (f < 2) : (f >= 8);
    const int fm = ODD ? f - 2 : f, ft = ODD ? f : f - 8;
    const int nq = tail ? 24 + ft : fm, nk = tail ? 26 + ft : 8 + fm, nv = tail ? 28 + ft : 16 + fm;
    if (PART == 0) { K[f][1] = pack_bf16(acc[4 * nk + 2], acc[4 * nk + 3]); V[f][1] = pack_bf16(acc[4 * nv + 2], acc[4 * nv + 3]); }
    if (PART == 1) { V[f][0] = pack_bf16(acc[4 * nv], acc[4 * nv + 1]); K[f][0] = pack_bf16(acc[4 * nk], acc[4 * nk + 1]); }
    if (PART == 2) { Q[f][0] = pack_bf16(acc[4 * nq], acc[4 * nq + 1]); Q[f][1] = pack_bf16(acc[4 * nq + 2], acc[4 * nq + 3]); }
  }
}
DEVI int pair_of(int c) {
  const int lo = 32 + 8 * c, hi = c - 4 + ((max(c - 29, 0) * 37) >> 8);
  int p; asm("{\n.reg .pred q;\nsetp.lt.s32 q, %1, 4;\nselp.b32 %0, %2, %3, q;\n}" : "=r"(p) : "r"(c), "r"(lo), "r"(hi));
  return p;
}
DEVI uint32_t make_ctx() {
  int b; asm volatile("mov.u32 %0, %%ctaid.x;" : "=r"(b));
  b += clk() & threadIdx.y;
  const int p = pair_of(b >> 1);
  const int j = b < 128 ? 8 * (p & 7) + (p >> 3) : 64;
  const int q = (j * 205) >> 10, r = j - 5 * q, i = j - q, co = (i * 79) >> 10;
  const int cp = r == 4 ? 4 : co, tb = r == 4 ? q : i - 13 * co;
  return ((2 * p + (b & 1)) & 255) | tb << 8 | (2 * cp + (b & 1)) << 12 | (b >> 7) << 16;
}
#define CTX() asm volatile("" : "+r"(ctx)); CTXU()
#define CTXU() int tid; asm volatile("mov.u32 %0, %%tid.x;" : "=r"(tid)); \
  const int lane = tid & 31, vb = ctx & 255, hg = (ctx >> 4) & 7, rt = ctx & 15, par = (ctx >> 3) & 1, mt = ctx & 7, rank = ctx & 1, \
  tb = (ctx >> 8) & 15, cb = (ctx >> 12) & 15; const bool main_cta = ctx < 65536; \
  (void)tid; (void)lane; (void)vb; (void)hg; (void)rt; (void)par; (void)mt; (void)rank; (void)tb; (void)cb; (void)main_cta
#define CTXW() CTX(); const int wg = warp >> 2, w = warp & 3, g = lane >> 2, t = lane & 3; const bool lead = (tid & 127) == 0; \
  (void)wg; (void)w; (void)g; (void)t; (void)lead

__global__ void __cluster_dims__(2, 1, 1) __launch_bounds__(512, 1)
fused_kernel(const uint16_t* __restrict__ xq, const uint16_t* __restrict__ wqkv, const uint16_t* __restrict__ gate_w, const __grid_constant__ Maps M, const uint16_t* __restrict__ shift_k, const uint16_t* __restrict__ ssm_k, const uint16_t* __restrict__ ssm_D,
             uint16_t* __restrict__ outp) {
  extern __shared__ __align__(1024) uint8_t smem_raw[];
  const uint32_t sb = smem_u32(smem_raw);
  const uint32_t t0 = clk();
  auto get_epoch = [&]() { mbar_wait(sb + B_EP, 0); return lds32(sb + O_EPOCH); };

  auto p1_load_x = [&](int ks, int p, int rank) {
    tma3(sb + o_px(ks), &M.x_par, ks * 32, (p >> 2) & 1, (p & 3) * 256 + rank * 128, sb + B_FULL + 8 * (ks & 7));
  };
  auto p1_load_w = [&](int ks, int p, int rank) {
    const uint32_t st = sb + o_pw(ks), fb = sb + B_FULL + 8 * (ks & 7);
    tma3_mc(st + rank * 6144, &M.w_main, (p >> 3) * 80 + 2 * (p & 8), ks * 32 + rank * 16, 0, fb);
    tma3_mc(st + 12288 + rank * 1536, &M.w_tail, (p >> 3) * 80 + 8 * (~p & 8), ks * 32 + rank * 16, 0, fb);
  };
  auto cta_pair = [&]() { return pair_of(blockIdx.x >> 1); };

  if (threadIdx.x < 32) {
    const unsigned b = blockIdx.x, l = threadIdx.x;
    const uint16_t* pfp = l < 16 ? xq + (16 * b + l) * 640 : wqkv + (15 * b + l - 16) * 64;
    if ((l | b >> 7 << 5) < 31) pf_l2(pfp);
  }
  const int warp = __shfl_sync(~0u, threadIdx.x >> 5, 0);
  if ((warp & 14) == 8) {
    if (elect_one()) {
#pragma unroll
      for (int s = 0; s < 8; s++) mbar_init(sb + O_BAR - 512 + 64 * warp + 8 * s, 5 * warp - 39);
      asm volatile("fence.mbarrier_init.release.cluster;" ::: "memory");
    }
    __syncwarp();
  }
  asm volatile("barrier.cluster.arrive.relaxed.aligned;" ::: "memory");
  if (warp == 8 && blockIdx.x < 128) {
    const int p = cta_pair(), rank = blockIdx.x & 1;
    if (elect_one()) { mbar_expect_tx(sb + B_FULL, 16384 + WST); p1_load_x(0, p, rank); }
    __syncwarp();
    asm volatile("barrier.cluster.wait.aligned;" ::: "memory");
    if (elect_one()) {
      p1_load_w(0, p, rank); PT(100);
      pf_map(&M.k_ld); pf_map(&M.v_ld);
    }
    __syncwarp();
  } else if (warp != 15) {
    asm volatile("barrier.cluster.wait.aligned;" ::: "memory");
    spin_until(t0, HOLD);
  }
  auto cluster_sync = [&]() {
    asm volatile("barrier.cluster.arrive.relaxed.aligned;" ::: "memory");
    asm volatile("barrier.cluster.wait.aligned;" ::: "memory");
  };
  auto init_rest = [&]() {
    if (warp >= 11 && elect_one()) {
#pragma unroll
      for (int s = 0; s < 12; s++) mbar_init(sb + O_BAR + 128 - 11 * 96 + 96 * warp + 8 * s, warp == 14 ? 2 : 1);
      asm volatile("fence.mbarrier_init.release.cluster;" ::: "memory");
    }
    __syncwarp();
    if (blockIdx.x < 128) bar_sync(0, 224); else cluster_sync();
  };
  uint32_t ctx = 0;

  if (warp < 8) {
    reg_inc<RC>();
    ctx = make_ctx();
    if (blockIdx.x >= 128) cluster_sync();
    else {
      {
        uint32_t Q[10][2], K[10][2], V[10][2];
        {
          {
            float acc[120];
            CTXW();
            const int odd = (cta_pair() >> 3) & 1;
            const uint32_t rsb = mapa(sb, (blockIdx.x & 1) ^ 1);
            {
              const uint32_t aa = sb + (warp * 16 + (lane & 15)) * 128 + (((lane >> 4) ^ (lane & 7)) << 4);
              constexpr int NA = DEFER > 3 ? DEFER : 3;
              uint32_t a[NA][8];
              auto load_a = [&](int ks) {
                uint32_t(&r)[8] = a[ks % NA];
                mbar_wait(sb + B_FULL + 8 * (ks & 7), (ks >> 3) & 1);
                PTP(lead && (wg || !(ks & 3)), wg ? 60 + ks : 80 + (ks >> 2));
                ldsm4(r[0], r[1], r[2], r[3], (aa ^ ((ks & 1) * 64)) + o_px(ks)); ldsm4(r[4], r[5], r[6], r[7], (aa ^ ((ks & 1) * 64 + 32)) + o_px(ks));
              };
              auto mma_q = [&](int ks, int h) {
                uint32_t(&r)[8] = a[ks % NA];
                wgmma_rs_n64<0, 1>(acc, r[4 * h], r[4 * h + 1], r[4 * h + 2], r[4 * h + 3], mkdesc(SB + o_pw(ks) + h * 6144, 2048, 1024, 1), ks | h);
              };
              auto mma_step = [&](int ks, int h) {
                uint32_t(&r)[8] = a[ks % NA];
                wg_fence();
                wgmma_rs_n128<32, 1>(acc, r[4 * h], r[4 * h + 1], r[4 * h + 2], r[4 * h + 3], mkdesc(SB + o_pw(ks) + h * 6144 + 2048, 2048, 1024, 1), ks | h);
                if (ks < 20 - DEFER) mma_q(ks, h);
                wgmma_rs_n48<96, 1>(acc, r[4 * h], r[4 * h + 1], r[4 * h + 2], r[4 * h + 3], mkdesc(SB + o_pw(ks) + 12288 + h * 1536, 512, 256, 3), ks | h);
                wg_commit();
              };
              if (lead) PT(1 + wg);
              load_a(0);
#pragma unroll
              for (int ks = 0; ks < 20; ks++) {
                if (ks == 20 - LEAD) bar_sync_p(wg == 0, NB_LEAD, 256);
                mma_step(ks, 0);
                if (ks < 19 && ks >= NLATE) load_a(ks + 1);
                mma_step(ks, 1);
                if (ks < NLATE) load_a(ks + 1);
                if (ks >= 1 && ks <= 16) {
                  wg_wait<2>();
                  mbar_arrive2_p(lead, sb + B_EMPTY + 8 * ((ks - 1) & 7), rsb + B_EMPTY + 8 * ((ks - 1) & 7));
                } else if (ks < 19 && ks + 2 - NA >= 16) wg_wait<2>();
              }
              bar_arrive_p(wg, NB_LEAD, 256);
              if (DEFER) {
                wg_fence();
#pragma unroll
                for (int i = 40 - 2 * DEFER; i < 40; i++) mma_q(i >> 1, i & 1);
                wg_commit();
              }
              mbar_wait(sb + B_S15, 1);
              wg_wait<1>();
              mbar_arrive_p(tid == 0, sb + B_P1E);
              if (!DEFER) wg_wait<0>();
              fence_regs<32, 120>(acc);
              PTPL(lead, 158 + wg);
            }
            if (odd) pack_qkv<1, 0>(acc, Q, K, V); else pack_qkv<0, 0>(acc, Q, K, V);
            if (warp == 7 && (blockIdx.x & 1)) {
              uint4* hp = g_halo + vb * 160 + lane;
              st_relaxed(hp, K[0][1], K[1][1], K[3][1], K[4][1]); st_relaxed(hp + 32, K[5][1], K[6][1], K[8][1], K[9][1]);
              st_relaxed(hp + 64, K[2][1], K[7][1], V[0][1], V[1][1]);
              st_relaxed(hp + 96, V[2][1], V[3][1], V[4][1], V[5][1]); st_relaxed(hp + 128, V[6][1], V[7][1], V[8][1], V[9][1]);
            }
            const uint32_t ho = sb + O_HALO + warp * 2560 + lane * 16;
            stsm4(ho, K[0][1], K[1][1], K[3][1], K[4][1]); stsm4(ho + 512, K[5][1], K[6][1], K[8][1], K[9][1]);
            stsm4(ho + 1024, K[2][1], K[7][1], V[0][1], V[1][1]);
            stsm4(ho + 1536, V[2][1], V[3][1], V[4][1], V[5][1]); stsm4(ho + 2048, V[6][1], V[7][1], V[8][1], V[9][1]);
            if (warp == 7) {
              if (!(blockIdx.x & 1)) {
                fence_async_smem();
                __syncwarp();
                if (elect_one())
                  asm volatile("cp.async.bulk.shared::cluster.shared::cta.mbarrier::complete_tx::bytes [%0], [%1], 2560, [%2];"
                               ::"r"(mapa(sb + O_HIN, 1)), "r"(sb + O_HALO + 7 * 2560), "r"(mapa(sb + B_HX0, 1)) : "memory");
              }
              __syncwarp();
            } else {
              __syncwarp();
              if (lane == 0) mbar_arrive(sb + B_HX + 8 + 8 * warp);
            }
            if (odd) pack_qkv<1, 1>(acc, Q, K, V); else pack_qkv<0, 1>(acc, Q, K, V);
            wg_wait<0>();
            fence_regs<0, 32>(acc);
            PTPL(lead, 50 + wg);
            mbar_arrive2_p(lead, sb + B_S19, rsb + B_S19);
            if (odd) pack_qkv<1, 2>(acc, Q, K, V); else pack_qkv<0, 2>(acc, Q, K, V);
#pragma unroll
            for (int f = 0; f < 10; f++) V[f][0] = movm(V[f][0]);
            if (lead) PT(52 + wg);
            if (wg) mbar_wait(sb + B_P1E, 0);
          }
          CTXW();
          uint32_t z = threadIdx.y;
          const bool gt0 = 2 * t > g, gt1 = 2 * t + 1 > g;
          const uint32_t pmask = (gt0 ? 0xFFFFu : 0u) | (gt1 ? 0xFFFF0000u : 0u);
          const uint32_t hs = warp ? O_HALO + (warp - 1) * 2560 : O_HIN, ha = sb + hs + lane * 16;
          const uint32_t va = sb + ((lane & 8) ? O_HALO + warp * 2560 : hs) + 1280 + (lane >> 4) * 128 + (lane & 7) * 16;
          uint32_t Qh[4][2], Kh[10], Vh[10];
          float c1[4][4] = {}, c2[4][4] = {}, c0[4][4] = {}, l[8][2], m[8], x[8];
#pragma unroll
          for (int j = 0; j < 4; j++) {
            const int fa = (j >> 1) * 5 + (j & 1) * 3, fh = (j >> 1) * 5 + 2;
            const bool mine = (j & 1) ? (t >= 2) : (t < 2);
            Qh[j][0] = mine ? Q[fh][0] : 0u; Qh[j][1] = mine ? Q[fh][1] : 0u;
            mma16(c1[j], Q[fa][0], Q[fa][1], Q[fa + 1][0], Q[fa + 1][1], K[fa][0], K[fa + 1][0]);
            mma16(c2[j], Q[fa][0], Q[fa][1], Q[fa + 1][0], Q[fa + 1][1], K[fa][1], K[fa + 1][1]);
            mma8(c1[j], Qh[j][0], Qh[j][1], K[fh][0]);
            mma8(c2[j], Qh[j][0], Qh[j][1], K[fh][1]);
          }
          if (lead) PT(54 + wg);
          mbar_wait(sb + (warp ? B_HX + 8 * warp : B_HX0), 0);
          if (lead) PT(56 + wg);
          ldsm4(Kh[0], Kh[1], Kh[3], Kh[4], ha); ldsm4(Kh[5], Kh[6], Kh[8], Kh[9], ha + 512);
          asm volatile("ldmatrix.sync.aligned.m8n8.x2.shared.b16 {%0,%1}, [%2];" : "=r"(Kh[2]), "=r"(Kh[7]) : "r"(ha + 1024) : "memory");
          auto load_v = [&]() {
#pragma unroll
            for (int i = 0; i < 5; i++) ldsm4t(Vh[2 * i], V[2 * i][1], Vh[2 * i + 1], V[2 * i + 1][1], va + i * 256);
          };
          load_v();
          const float C = 0.22360679774997896f * 1.4426950408889634f;
          auto max1 = [&](int r) { m[r] = fmaxf(l[r][0], l[r][1]); x[r] = __shfl_xor_sync(~0u, m[r], 1); };
          auto max2 = [&](int r) { m[r] = fmaxf(m[r], x[r]); x[r] = __shfl_xor_sync(~0u, m[r], 2); };
          auto exps = [&](int r) { const float mc = fmaxf(m[r], x[r]) * C; l[r][0] = ex2(fmaf(l[r][0], C, -mc)); l[r][1] = ex2(fmaf(l[r][1], C, -mc)); };
#pragma unroll
          for (int j = 0; j < 4; j++) { l[4 + j][0] = gt0 ? c1[j][2] : c2[j][2]; l[4 + j][1] = gt1 ? c1[j][3] : c2[j][3]; max1(4 + j); }
#pragma unroll
          for (int j = 0; j < 4; j++) {
            const int fa = (j >> 1) * 5 + (j & 1) * 3, fh = (j >> 1) * 5 + 2;
            mma16(c0[j], Q[fa][0], Q[fa][1], Q[fa + 1][0], Q[fa + 1][1], Kh[fa], Kh[fa + 1]);
            mma8(c0[j], Qh[j][0], Qh[j][1], Kh[fh]);
            max2(4 + j);
          }
          const bool have_halo = warp > 0 || mt > 0;
#pragma unroll
          for (int j = 0; j < 4; j++) {
            if (!have_halo) c0[j][0] = c0[j][1] = -INFINITY;
            l[j][0] = gt0 ? c0[j][0] : c1[j][0]; l[j][1] = gt1 ? c0[j][1] : c1[j][1];
            max1(j);
          }
          exps(4); exps(5);
#pragma unroll
          for (int j = 0; j < 4; j++) max2(j);
          exps(6); exps(7);
#pragma unroll
          for (int j = 0; j < 4; j++) exps(j);
          float o[12][4] = {}, sm[4][4] = {};
#pragma unroll
          for (int j = 0; j < 4; j++) {
            const int fa = (j >> 1) * 5 + (j & 1) * 3, fh = (j >> 1) * 5 + 2;
            const uint32_t pl = pack_bf16(l[j][0], l[j][1]), pu = pack_bf16(l[4 + j][0], l[4 + j][1]);
            const uint32_t p0 = pl & pmask, p2 = pl & ~pmask, p3 = pu & pmask, p5 = pu & ~pmask, z0 = z << (2 * j + 1), z1 = z << (2 * j + 2);
            mma8(sm[j], pl, pu, 0x3F803F80u);
#pragma unroll
            for (int q = 0; q < 3; q++) {
              const int f = q < 2 ? fa + q : fh;
              mma8(o[3 * j + q], p2, p3, V[f][0]);
              mma16(o[3 * j + q], p0, z0, z1, p5, Vh[f], V[f][1]);
            }
            asm volatile("rcp.approx.ftz.f32 %0, %0;" : "+f"(sm[j][0]));
            asm volatile("rcp.approx.ftz.f32 %0, %0;" : "+f"(sm[j][2]));
          }
#pragma unroll
          for (int i = 0; i < 12; i++) z &= __float_as_uint(o[i][0]);
          bar_sync_p(wg == 0, NB_HALO + z, 256);
          uint32_t O[10][2];
#pragma unroll
          for (int j = 0; j < 4; j++) {
            const int fa = (j >> 1) * 5 + (j & 1) * 3, fh = (j >> 1) * 5 + 2;
            const float r0 = sm[j][0], r1 = sm[j][2];
#pragma unroll
            for (int q = 0; q < 3; q++) {
              const int f = q < 2 ? fa + q : fh;
              const float* e = o[3 * j + q];
              const uint32_t o0 = pack_bf16(e[0] * r0, e[1] * r0), o1 = pack_bf16(e[2] * r1, e[3] * r1);
              if (q < 2 || !(j & 1)) { O[f][0] = o0; O[f][1] = o1; }
              else { O[f][0] = t >= 2 ? o0 : O[f][0]; O[f][1] = t >= 2 ? o1 : O[f][1]; }
            }
          }
          mbar_wait(sb + B_GD, 0);
          const uint32_t oa = sb + O_OST + wg * 2 * STG + (w * 16 + (lane & 15)) * 160 + (lane >> 4) * 16;
#pragma unroll
          for (int i = 0; i < 5; i++) stsm4(oa + i * 32, O[2 * i][0], O[2 * i][1], O[2 * i + 1][0], O[2 * i + 1][1]);
        }
      }
      {
        CTXW();
        fence_async_smem();
        bar_arrive(wg ? NB_LEAD : NB_ATT, 160);
        PTP(lead, 58 + wg);
        const uint32_t abase = sb + (g & 1) * 4160 + 4 * (1023 - 4 - 8 * w - (g >> 1) + t);
        float acc[128];
        uint32_t a0[8], a1[8], a2[8], a3[8];
#pragma unroll 1
        for (int c = wg ^ 1; c < 5; c += 2) {
          const uint32_t ab = abase + o_h(c);
          const uint32_t db = ((SB + o_u(c) + UZ - 16) >> 4) | 0x10000u;
          mbar_wait(sb + B_U + 8 * c, 0);
          load_pair<0>(a0, ab); load_pair<1>(a1, ab); load_pair<2>(a2, ab);
          PTP(lead, 85 + c);
          bar_sync(c ? NB_TOK + wg : NB_HALO, 256);
          fence_regs(acc);
          mma_pair<0>(acc, a0, db);
          load_pair<3>(a3, ab);
          mma_pair<1>(acc, a1, db); wg_wait<1>();  load_pair<4>(a0, ab);
          if (lead) PT(90 + c);
          mma_pair<2>(acc, a2, db); wg_wait<1>();  load_pair<5>(a1, ab);
          mma_pair<3>(acc, a3, db); wg_wait<1>();  load_pair<6>(a2, ab);
          mma_pair<4>(acc, a0, db); wg_wait<1>();  load_pair<7>(a3, ab);
          mma_pair<5>(acc, a1, db);
          mma_pair<6>(acc, a2, db);
          bar_arrive_p(c < 4, NB_TOK + (wg ^ 1), 256);
          mma_pair<7>(acc, a3, db);
          bar_arrive_p(c == 4, NB_TOK, 256);
          wg_wait<0>();
          fence_regs(acc);
          PTPL(lead, 95 + c);
          bar_sync(NB_RFREE + wg, 256);
          const uint32_t pb = sb + (w < 2 ? o_h(c) + w * 4160 : w == 2 ? o_u(c) : o_x(c)) + lane * 16;
          if (lane < 2 * w) sts128(pb, 0, 0, 0, 0);
#pragma unroll
          for (int q = 0; q < 8; q++) {
            uint32_t p[4];
#pragma unroll
            for (int i = 0; i < 4; i++) {
              const int nu = 4 * q + i;
              p[i] = pack_bf16(acc[4 * nu], acc[4 * nu + 1]);
              if (nu > 0) p[i] = hadd2(p[i], pack_bf16(acc[4 * nu - 2], acc[4 * nu - 1]));
            }
            stsm4t(pb + w * 32 + q * 512, p[0], p[1], p[2], p[3]);
            if (q == 3) bar_arrive_p(c == 4, NB_RFULL + 1, 256);
          }
          if (c < 4) bar_arrive(NB_RFULL + wg, 256);
          if (lead) PT(140 + c);
        }
        if (wg) {
          const int yb = (lds32(sb + O_EPOCH) & 1) * 640;
              conv_reduce<1, 2>(sb, 4, tid - 128, yb + 512 + ((vb & 0x61) | (vb & 6) << 2 | (vb >> 2 & 6)), 14, 128);
          bar_arrive(12, 256);
          PTPL(lead, 45);
        }
      }
    }
    if (warp < 4) {
      CTXW();
      const uint32_t rsb = mapa(sb, (blockIdx.x & 1) ^ 1);
      const uint32_t ba = sb + O_BT + ((lane >> 4) * 8 + (lane & 7)) * 128 + (((2 * w + ((lane >> 3) & 1)) ^ ((lane & 1) << 2 | (lane >> 1 & 3))) << 4);
      mbar_wait(sb + B_P3F, 0);
      if (lead) PT(145);
      float acc[80];
#pragma unroll
      for (int ks = 0; ks < 10; ks++) {
        if (ks == NPRE) {
          if (NPRE) { wg_wait<0>(); mbar_arrive2_p(lead, sb + B_P3E + 8 * NPRE, rsb + B_P3E + 8 * NPRE); }
          bar_sync_p(blockIdx.x < 128, NB_TOK, 256);
        }
        PTP(lead, 146 + ks);
        const uint64_t da = mkdesc(SB + o_p3(ks), 1024, 1024, 1), db = mkdesc(SB + o_p3(ks) + 8192, 16, 1024, 1);
        wg_fence();
#pragma unroll
        for (int j = 0; j < 4; j++) wgmma_ss_n160<0, 1, 0>(acc, da + j * 128, db + j * 2, j | ks);
        wg_commit();
        if (ks < 9) mbar_wait(sb + B_P3F + 8 * (ks + 1), 0);
        if (ks >= 1 && ks <= 4 && ks != NPRE) { wg_wait<1>(); mbar_arrive2_p(lead, sb + B_P3E + 8 * ks, rsb + B_P3E + 8 * ks); }
      }
      wg_wait<0>();
      fence_regs(acc);
      PTPL(lead, 156);
#pragma unroll
      for (int i = 0; i < 10; i++) {
        stsm4t(ba + i * 2048, pack_bf16(acc[8 * i], acc[8 * i + 1]), pack_bf16(acc[8 * i + 2], acc[8 * i + 3]),
               pack_bf16(acc[8 * i + 4], acc[8 * i + 5]), pack_bf16(acc[8 * i + 6], acc[8 * i + 7]));
        if (i & 1) bar_arrive(1 + (i >> 1), 256);
      }
      if (lead) PT(157);
    }
  } else if (warp < 12) {
    reg_dec<RH>();
    const int hw = warp - 8;
    init_rest();
    ctx = __shfl_sync(~0u, make_ctx(), 0);
    const int yrow = (ctx & 0x61) | (ctx & 6) << 2 | (ctx >> 2 & 6);
    if (ctx < 65536) {
      CTXU();
      const int pr = hw >> 1, hh = hw & 1, tk = vb & 63, odd = (lane >> 2) & 1;
      const uint32_t sel0 = odd ? 0x7632 : 0x5410, sel1 = odd ? 0x5410 : 0x7632;
      const uint32_t in = sb + o_kin(pr), fb = sb + B_KF + 8 * pr, out = sb + O_Y + pr * 8192;
      const uint32_t oa = out + (2 * lane + odd) * 64 + (((3 - 2 * hh) ^ (lane & 3)) << 4), ia = in + hh * 2048 + lane * 4;
      auto fetch = [&](int c) {
        wait_until(t0, KT0 + c * KTD + ((((vb * 37) & 63) * KPH) >> 6));
        if (elect_one()) {
          const int kb = 2 * c + (vb >> 6);
          mbar_expect_tx(fb, 69 * 128);
          tma2(in, &M.k_ld, kb * 64, 32 * tk - 4, fb);
          tma2(in + 36 * 128, &M.v_ld, kb * 64, 32 * tk - 1, fb);
          PT(20 + c);
        }
        __syncwarp();
      };
      if (hh == 0) fetch(pr);
      const uint4* skp = (const uint4*)shift_k + (2 * pr + (vb >> 6)) * 32 + lane;
      uint4 sk = __ldg(skp), sk1 = __ldg(skp + 128), sk2 = __ldg(skp + (pr ? 0 : 256));
#pragma unroll 1
      for (int c = pr; c < 5; c += 2) {
        {
          mbar_wait(fb, (c >> 1) & 1);
          if (hh == 0 && lane == 0) PT(25 + c);
          uint32_t k[20], o[17];
#pragma unroll
          for (int i = 0; i < 20; i++) { k[i] = lds32(ia + i * 128); if (i >= 3) o[i - 3] = lds32(ia + (33 + i) * 128); }
          fence_async_smem();
          bar_sync(12 + pr, 64);
          if (hh == 0) {
            if (c < 3) fetch(c + 2);
            else if (lane == 0) mbar_arrive(sb + B_KVD + 8 * (c - 3));
          }
          const uint32_t w0 = prmt(sk.x, sk.z, 0x5410), w1 = prmt(sk.x, sk.z, 0x7632), w2 = prmt(sk.y, sk.w, 0x5410), w3 = prmt(sk.y, sk.w, 0x7632);
#pragma unroll
          for (int i = 0; i < 17; i++) o[i] = hmul2(hfma2(k[i + 3], w0, hfma2(k[i + 2], w1, hfma2(k[i + 1], w2, hmul2(k[i], w3)))), o[i]);
          sk = sk1; sk1 = sk2;
#pragma unroll
          for (int i = 0; i < 4; i++) {
            const int e = 8 * (i >> 1) + (i & 1);
            const uint32_t a = (oa ^ ((i >> 1) * 16)) + (i & 1) * 4096;
            sts128(a, prmt(o[7 + e], o[6 + e], sel0), prmt(o[5 + e], o[4 + e], sel0), prmt(o[3 + e], o[2 + e], sel0), prmt(o[1 + e], o[e], sel0));
            sts128(a ^ 64, prmt(o[7 + e], o[6 + e], sel1), prmt(o[5 + e], o[4 + e], sel1), prmt(o[3 + e], o[2 + e], sel1), prmt(o[1 + e], o[e], sel1));
          }
          bar_sync(12 + pr, 64);
        }
        if (hh) {
          fence_async_smem();
          if (elect_one()) {
            const int kb = 2 * c + (vb >> 6);
            tma3_store(&M.kv_st, 0, kb * 64, 63 - tk, out);
            tma3_store(&M.kv_st, 0, 640 + kb * 64, 63 - tk, out + 4096);
            bulk_commit(); bulk_wait_all();
            mbar_arrive(sb + (c == 4 ? B_KVD + 16 : B_KVS + 4 * (c & 2)));
            PTL(35 + c);
          }
          __syncwarp();
        }
      }
    }
    CTXU();
    const int g = lane >> 2, t = lane & 3, row = 8 * hw + g;
    const uint32_t go = (tb * 160 + row) * 80 + cb * 8 + t;
    const int yb = __shfl_sync(~0u, get_epoch() & 1, 0) * 640;
    uint4 T[10];
    if (hw == 2) {
      if (main_cta) { mbar_wait(sb + B_LAST, 0); mbar_wait(sb + B_S15, 1); }
      if (elect_one()) {
        mbar_expect_tx(sb + B_Q, 20480);
#pragma unroll
        for (int h = 0; h < 2; h++) tma2(sb + O_QT + h * 10240, &M.q_ld, cb * 64 + 32 * h, tb * 160, sb + B_Q);
      }
      __syncwarp();
    }
    mbar_wait(sb + B_Q, 0);
#pragma unroll
    for (int i = 0; i < 10; i++) lds128(sb + O_QT + (i & 1) * 10240 + (i >> 1) * 2048 + row * 64 + t * 16, T[i].x, T[i].y, T[i].z, T[i].w);
    fence_async_smem();
    bar_sync(12 + (hw >> 1), 64);
    if (!(tid & 63)) mbar_arrive(sb + B_QD);
    if (tid == 256) PTL(40);
    if (main_cta) {
      bar_arrive(NB_RFREE, 256);
      bar_arrive(NB_RFREE + 1, 256);
      auto red = [&](int c) {
        const int wg = (c & 1) ^ 1;
        conv_reduce<0, 2>(sb, c, tid - 256, yb + 128 * c + yrow, NB_RFULL + wg, 256);
        if (hw == 3 && elect_one()) flag_add(CNT_Y(4 * c + (vb >> 5)), 1);
        if (tid == 256) PTL(41 + c);
        if (c < 3) bar_arrive(NB_RFREE + wg, 256);
        if (c == 2) {
          bar_sync(NB_HELP, 128);
          if (tid == 256) { mbar_arrive(sb + B_P3E); mbar_arrive_remote(sb + B_P3E, rank ^ 1); }
        }
      };
      if (hw == 3) {
        mbar_wait(sb + B_KVD + 16, 0);
        if (elect_one()) { flag_release(CNT_KV(4 + (vb >> 6))); PTL(32); }
        __syncwarp();
      }
#pragma unroll 1
      for (int c = 0; c < 4; c++) red(c);
      conv_reduce<0, 1>(sb, 4, tid - 256, yb + 512 + yrow, NB_RFULL + 1, 256);
      if (hw == 3 && elect_one()) { flag_add(CNT_Y(16 + (vb >> 5)), 1); PTL(19); }
    }
    uint32_t G[5];
    mbar_wait(sb + B_G, 0);
#pragma unroll
    for (int q = 0; q < 5; q++) { uint16_t v; asm volatile("ld.shared.u16 %0, [%1];" : "=h"(v) : "r"(sb + O_GT + (32 * q + row) * 2)); G[q] = prmt(v, 0, 0x1010); }
    auto gate_q = [&]() {
#pragma unroll
      for (int i = 0; i < 10; i++) { const uint32_t c = G[i >> 1] ^ 0x80008000u; T[i] = make_uint4(hmul2(T[i].x, c), hmul2(T[i].y, c), hmul2(T[i].z, c), hmul2(T[i].w, c)); }
    };
    gate_q();
    const uint32_t so = __shfl_sync(~0u, sb + O_BT + row * 128 + ((t ^ ((g & 1) << 2 | g >> 1)) << 4), lane);
    uint4* const op = (uint4*)__shfl_sync(~0u, (unsigned long long)((uint4*)outp + go), lane);
    if (main_cta) bar_sync(12, 256);
    const uint32_t ya = sb + O_Y + lane * 64 + ((hw ^ ((lane >> 1) & 3)) << 4);
    auto empty = [](uint32_t m) { return (m & 0xFFFFu) == 0 || m < 0x10000u; };
    int redo = blockIdx.y;
#pragma unroll 1
    do {
      if (redo) {
#pragma unroll 1
        for (int i = 0; i < (tb < 12 ? 10 : 8); i++) {
          const uint32_t a = ya + (i & 1) * 10240 + (i >> 1) * 2048;
          uint4 v;
          lds128(a, v.x, v.y, v.z, v.w);
          while (empty(__vimin3_u16x2(__vminu2(v.x, v.y), v.z, v.w)))
            asm volatile("ld.relaxed.gpu.global.v4.b32 {%0,%1,%2,%3}, [%4];" : "=r"(v.x), "=r"(v.y), "=r"(v.z), "=r"(v.w)
                         : "l"((const uint4*)g_y2T + (yb + cb * 64 + 32 * (i & 1) + lane) * 256 + tb * 20 + 4 * (i >> 1) + hw) : "memory");
          sts128(a, v.x, v.y, v.z, v.w);
        }
        __syncwarp();
#pragma unroll
        for (int i = 0; i < 10; i++) if (i < 8 || tb < 12) T[i] = __ldg((const uint4*)xq + go + (i >> 1) * 2560 + (i & 1) * 4);
        gate_q();
        PTL(49);
      }
      uint32_t m = ~0u;
#pragma unroll
      for (int h = 0; h < 2; h++) {
        if (h) mbar_wait(sb + B_Y + 8, 0); else mbar_wait_wd(sb + B_Y, 0, t0);
        if (tid == 256) PTL(46);
#pragma unroll
        for (int q = 0; q < 5; q++) {
          uint4 y;
          ldsm4t(y.x, y.y, y.z, y.w, ya + h * 10240 + q * 2048);
          const uint32_t mq = __vimin3_u16x2(__vimin3_u16x2(m, y.x, y.y), y.z, y.w);
          m = q == 4 && tb == 12 ? m : mq;
          uint4& r = T[2 * q + h];
          r = make_uint4(hmul2(r.x, y.x), hmul2(r.y, y.y), hmul2(r.z, y.z), hmul2(r.w, y.w));
        }
      }
      redo = __any_sync(~0u, empty(m));
    } while (redo);
    if (tid == 256) PTL(47);
#pragma unroll
    for (int q = 0; q < 5; q++) {
      const uint32_t c = hfma2(G[q], 0xBF80BF80u, 0x3F803F80u);
      bar_sync(1 + q, 256);
      if (q == 4) mbar_arrive_p(tid == 256, sb + B_DONE);
#pragma unroll
      for (int h = 0; h < 2; h++) {
        uint4 u;
        lds128((so ^ (h * 64)) + q * 4096, u.x, u.y, u.z, u.w);
        const uint4& r = T[2 * q + h];
        if (q < 4 || tb < 12)
          asm volatile("st.global.v4.b32 [%0], {%1,%2,%3,%4};" ::"l"(op + q * 2560 + h * 4), "r"(hfma2(u.x, c, r.x)), "r"(hfma2(u.y, c, r.y)), "r"(hfma2(u.z, c, r.z)), "r"(hfma2(u.w, c, r.w)) : "memory");
      }
    }
  } else {
    reg_dec<RP>();
    uint4 gwv = make_uint4(0, 0, 0, 0);
    if (warp == 15) {
      const int p = cta_pair(), rank = blockIdx.x & 1;
      asm volatile("barrier.cluster.wait.aligned;" ::: "memory");
      if (blockIdx.x >= 128) cluster_sync();
      else {
#pragma unroll 1
        for (int ks = 1;; ks += 2) {
          mbar_wait(sb + B_EMPTY + 8 * (ks & 7), ((ks >> 3) & 1) ^ 1);
          spin_until(t0, PT1 + (ks - 1) * PTD - max(ks - PTS, 0) * PTA);
          if (elect_one()) { mbar_expect_tx(sb + B_FULL + 8 * (ks & 7), WST); p1_load_w(ks, p, rank); PT(100 + ks); }
          if (ks == 19) break;
          const int kn = ks + 1;
          mbar_wait(sb + B_EMPTY + 8 * (kn & 7), ((kn >> 3) & 1) ^ 1);
          spin_until(t0, PT1 + ks * PTD - PTE - max(kn - PTS, 0) * PTA);
          if (elect_one()) { mbar_expect_tx(sb + B_FULL + 8 * (kn & 7), 16384 + WST); p1_load_x(kn, p, rank); p1_load_w(kn, p, rank); PT(100 + kn); }
        }
        if (elect_one()) mbar_arrive(sb + B_LAST);
#pragma unroll 1
        for (int i = 0; i < 2; i++) {
          mbar_wait(sb + B_KVS + 8 * i, 0);
          if (elect_one()) { flag_release(CNT_KV(2 * i + (p >> 5))); PTL(30 + i); }
          __syncwarp();
        }
        mbar_wait(sb + B_S19, 0);
      }
    } else {
      if (threadIdx.x < 384 + 80) gwv = __ldg((const uint4*)gate_w + threadIdx.x - 384);
      init_rest();
    }
    ctx = __shfl_sync(~0u, make_ctx(), 0);
    CTXU();
    if (warp == 12) {
        unsigned epoch = 0;
      if (lane == 0) epoch = *(volatile unsigned*)(g_launch + 32 * vb) + 1;
      if (main_cta) { sts128(sb + O_GW + lane * 16, gwv.x, gwv.y, gwv.z, gwv.w); bar_arrive(NB_G, 96); }
      if (lane == 0) {
        if ((sb & 0xFFFFFF) != SB) __trap();
        sts32(sb + O_EPOCH, epoch);
        mbar_arrive(sb + B_EP);
      }
      if (main_cta && rank) {
#pragma unroll
        for (int f = 0; f < 5; f++) st_relaxed(g_halo + vb * 160 + lane + 32 * f, ~0u, ~0u, ~0u, ~0u);
      }
      __syncwarp();
      if (elect_one()) flag_release(g_launch + 32 * vb);
      __syncwarp();
      if (main_cta) {
        uint4 h0 = make_uint4(0, 0, 0, 0);
        if (lane < 5) {
          h0 = __ldg((const uint4*)(ssm_k + (size_t)(128 * lane + vb) * 2048));
          h0.x = prmt(pack_bf16(bf_lo(h0.x) + bf_lo(__ldg(ssm_D + 128 * lane + vb)), 0.f), h0.x, 0x7610);
        }
        epoch = __shfl_sync(~0u, epoch, 0);
        if (!rank && mt > 0) {
          flag_wait(g_launch + 32 * (vb - 1), epoch);
          if (lane < 2) mbar_arrive(sb + B_HC);
          __syncwarp();
        }
        const int ze = lane & 7;
        const uint32_t za = sb + (lane < 8 ? o_u(ze) + UZ : lane < 24 ? o_h(ze) + (lane >> 4) * 4160 + 4096 : o_u(ze) + 512);
        const uint16_t* hp = ssm_k + (size_t)vb * 2048 + 8;
        const uint16_t* up = g_kvT + (size_t)vb * 2048;
        const unsigned* fp = CNT_KV(vb >> 6);
        sts128(sb + O_Y - 512 + lane * 16, 0, 0, 0, 0);
        mbar_wait(sb + B_LAST, 0);
        mbar_wait(sb + B_S13, 1);
#pragma unroll
        for (int c = 0; c < 5; c++) {
          if (c == 0 || c == 3) {
            mbar_wait(sb + B_KVD + (c ? 8 : 0), 0);
#pragma unroll
            for (int e = c; e < (c ? 5 : 3); e++) sts128(sb + o_u(e) + lane * 16, 0, 0, 0, 0);
            if (ze >= c && ze < (c ? 5 : 3)) sts128(za, h0.x, h0.y, h0.z, h0.w);
            fence_async_smem();
            __syncwarp();
            if (elect_one()) {
#pragma unroll
              for (int e = c; e < (c ? 5 : 3); e++) {
                mbar_expect_tx(sb + B_U + 8 * e, 3 * 4096 - 16);
                if (c || e == 0) bulk_load(sb + o_u(e) + UZ + 16, hp + 128 * 2048 * e, 4080, sb + B_U + 8 * e);
              }
            }
          }
                    if (!(c & 1)) { flag_wait(fp + 32 * c, 64 * epoch); __syncwarp(); }
          if (elect_one()) {
            bulk_load(sb + o_h(c), up + 128 * 2048 * c, 4096, sb + B_U + 8 * c);
            bulk_load(sb + o_h(c) + 4160, up + (640 + 128 * c) * 2048, 4096, sb + B_U + 8 * c);
            if (c == 1) {
#pragma unroll
              for (int e = 1; e < 3; e++) bulk_load(sb + o_u(e) + UZ + 16, hp + 128 * 2048 * e, 4080, sb + B_U + 8 * e);
            }
            PTL(10 + c);
          }
        }
        mbar_wait(sb + B_OR, 0);
        if (elect_one()) {
#pragma unroll 1
          for (int i = 0; i < 40; i++) bulk_store(g_y2T + (size_t)((~epoch & 1) * 640 + 5 * vb) * 2048 + i * 256, sb + O_Y - 512, 512);
          bulk_commit(); bulk_wait_read();
          PTL(33);
        }
      }
    } else if (warp != 15) {
        const int r = warp - 13;
      if (main_cta) {
        if (rank && lane == 0) mbar_expect_tx(sb + B_HX0, 1280);
        const int t = lane & 3, grow = hg * 16 + (lane & 15);
        const uint32_t ga = sb + grow * 128 + (((4 * r + (lane >> 4)) ^ (lane & 7)) << 4);
        const uint32_t gp = sb + O_GW + 64 * r + 4 * t;
        float s0 = 0.f, s1 = 0.f;
        if (tid < 384 + 80) sts128(sb + O_GW + (tid - 384) * 16, gwv.x, gwv.y, gwv.z, gwv.w);
        bar_sync(NB_G, 96);
#pragma unroll 1
        for (int ks = 0; ks < 20; ks += 2) {
          uint32_t x[8], gw[4];
#pragma unroll
          for (int i = 0; i < 4; i++) gw[i] = lds32(gp + ks * 64 + i * 16);
          mbar_wait_wd(sb + B_FULL + 8 * (ks & 7), (ks >> 3) & 1, t0);
          if (r == 0 && lane == 0) PT(120 + ks);
          ldsm4(x[0], x[1], x[2], x[3], ga + o_px(ks)); ldsm4(x[4], x[5], x[6], x[7], (ga ^ 32) + o_px(ks));
#pragma unroll
          for (int i = 0; i < 8; i++) x[i] = hmul2(x[i], gw[i >> 1]);
          if (lane < 2) mbar_arrive(sb + B_EMPTY + 8 * (ks & 7) + 8 * lane + (x[0] & x[7] & threadIdx.y));
#pragma unroll
          for (int i = 0; i < 8; i += 4) {
            s0 += (bf_lo(x[i]) + bf_hi(x[i])) + (bf_lo(x[i + 2]) + bf_hi(x[i + 2]));
            s1 += (bf_lo(x[i + 1]) + bf_hi(x[i + 1])) + (bf_lo(x[i + 3]) + bf_hi(x[i + 3]));
          }
        }
        s0 += __shfl_xor_sync(~0u, s0, 1); s1 += __shfl_xor_sync(~0u, s1, 1);
        s0 += __shfl_xor_sync(~0u, s0, 2); s1 += __shfl_xor_sync(~0u, s1, 2);
        if (t < 2) sts32(sb + O_GP + r * 64 + (8 * t + (lane >> 2)) * 4, __float_as_uint(t ? s1 : s0));
        if (lane == 0) mbar_arrive(sb + B_GD);
        if (r == 0) bar_arrive(NB_G, 64);
        if (!rank) {
          uint4 d[3];
          if (mt > 0) {
            const uint4* hp = g_halo + (vb - 1) * 160 + r * 64 + lane;
            mbar_wait_wd(sb + B_HC, 0, t0);
            mbar_wait_wd(sb + B_HX + 56, 0, t0);
            if (HDL) { const uint32_t t1 = clk(); spin_until(t1, HDL); }
            for (;;) {
              bool ok = true;
#pragma unroll
              for (int f = 0; f < 3; f++) {
                asm volatile("ld.relaxed.gpu.global.v4.b32 {%0,%1,%2,%3}, [%4];" : "=r"(d[f].x), "=r"(d[f].y), "=r"(d[f].z), "=r"(d[f].w) : "l"(hp + 32 * f) : "memory");
              }
#pragma unroll
              for (int f = 0; f < 3; f++) ok = ok && max(max(d[f].x, d[f].y), max(d[f].z, d[f].w)) != ~0u;
              if (__all_sync(~0u, ok)) break;
              if (clk() - t0 > 0x70000000u) __trap();
            }
          } else {
#pragma unroll
            for (int f = 0; f < 3; f++) d[f] = make_uint4(0, 0, 0, 0);
          }
#pragma unroll
          for (int f = 0; f < 3; f++) stsm4(sb + O_HIN + r * 1024 + f * 512 + lane * 16, d[f].x, d[f].y, d[f].z, d[f].w);
          __syncwarp();
          if (lane == 0) { mbar_arrive(sb + B_HX0); PTL(15 + r); }
        }
        if (r == 1) {
          bar_sync(NB_G, 64);
          if (lane < 16) {
            const uint32_t pa = sb + O_GP + lane * 4;
            const float z = __uint_as_float(lds32(pa)) + __uint_as_float(lds32(pa + 64));
            g_gate[2 * (mt * 128 + hg * 16 + lane) + par] = (uint16_t)pack_bf16(__fdividef(1.f, 1.f + __expf(-bf_lo(pack_bf16(z, 0.f)))), 0.f);
          }
          __syncwarp();
          if (elect_one()) flag_release(CNT_O(rt));
        }
      }
      mbar_wait_wd(sb + B_EP, 0, t0);
      const unsigned epoch = lds32(sb + O_EPOCH);
      if (main_cta) mbar_wait_wd(sb + B_P3E, 0, t0);
      const uint32_t yd = __shfl_sync(~0u, sb + O_Y + r * 10240 + threadIdx.y, 0), yb = __shfl_sync(~0u, sb + B_Y + 8 * r + threadIdx.y, 0);
      const int y1 = __shfl_sync(~0u, (epoch & 1) * 640 + cb * 64 + 32 * r + threadIdx.y, 0), y2 = __shfl_sync(~0u, tb * 5 + threadIdx.y, 0);
      if (elect_one()) { pf_map(&M.y_ld); mbar_expect_tx(yb, 10240); }
      __syncwarp();
      flag_wait_wd(CNT_Y(2 * cb + r), 32 * epoch, t0);
      __syncwarp();
      if (elect_one()) { tma3(yd, &M.y_ld, 0, y1, y2, yb); PTL(17 + r); }
      __syncwarp();
      mbar_wait_wd(sb + B_DONE, 0, t0);
    } else {
      const unsigned epoch = get_epoch();
      if (main_cta) {
        if (elect_one()) { pf_map(&M.o_st); pf_map(&M.wo); pf_map(&M.o_ld); }
        __syncwarp();
        bar_sync(NB_LEAD, 160);
        if (elect_one()) tma3_store(&M.o_st, hg * 80, par, mt * 128 + 64, sb + O_OST + 2 * STG);
        bar_sync(NB_ATT, 160);
        if (elect_one()) {
          tma3_store(&M.o_st, hg * 80, par, mt * 128, sb + O_OST);
          bulk_commit(); bulk_wait_all();
          flag_release(CNT_O(rt));
          mbar_arrive(sb + B_OR); mbar_arrive(sb + B_OR);
          PTL(3);
        }
        __syncwarp();
      }
      mbar_wait(sb + B_QD, 0);
#pragma unroll 1
      for (int ks = 0; ks < 5; ks++)
        if (elect_one()) tma2(sb + o_p3(ks), &M.wo, cb * 64, ks * 64, sb + B_P3F + 8 * ks);
      if (lane < 4) flag_wait(CNT_O(8 * (lane & 1) + min(7, (80 * tb + 79 * (lane >> 1)) >> 7)), 16 * epoch);
      __syncwarp();
      if (elect_one()) {
        PTL(4);
        mbar_arrive_remote(sb + B_P3R, rank ^ 1);
        mbar_expect_tx(sb + B_G, 320);
        bulk_load(sb + O_GT, g_gate + tb * 160, 320, sb + B_G);
      }
      mbar_wait(sb + B_P3R, 0);
      auto load_o = [&](int ks) {
        tma2_mc(sb + o_p3(ks) + 8192 + rank * 10240, &M.o_ld, ks * 64, tb * 160 + rank * 80, sb + B_P3F + 8 * ks);
        mbar_expect_tx(sb + B_P3F + 8 * ks, P3S);
      };
      auto load_wo = [&](int ks) { tma2(sb + o_p3(ks), &M.wo, cb * 64, ks * 64, sb + B_P3F + 8 * ks); };
#pragma unroll 1
      for (int ks = 0; ks < 5; ks++)
        if (elect_one()) load_o(ks);
#pragma unroll
      for (int ks = 5; ks < 10; ks++) {
        if (ks > 5 || main_cta) mbar_wait(sb + B_P3E + 8 * (ks - 5), 0);
        if (elect_one()) {
          load_o(ks); load_wo(ks);
          PTL(ks);
        }
      }
    }
  }
}

typedef CUresult (*PFN_enc)(CUtensorMap*, CUtensorMapDataType, cuuint32_t, void*, const cuuint64_t*, const cuuint64_t*, const cuuint32_t*,
                            const cuuint32_t*, CUtensorMapInterleave, CUtensorMapSwizzle, CUtensorMapL2promotion, CUtensorMapFloatOOBfill);
static void enc(PFN_enc f, CUtensorMap* m, const void* base, int rank, const cuuint64_t* dims, const cuuint64_t* strides, const cuuint32_t* box,
                CUtensorMapSwizzle sw) {
  const cuuint32_t es[5] = {1, 1, 1, 1, 1};
  f(m, CU_TENSOR_MAP_DATA_TYPE_BFLOAT16, rank, (void*)base, dims, strides, box, es, CU_TENSOR_MAP_INTERLEAVE_NONE, sw,
    CU_TENSOR_MAP_L2_PROMOTION_NONE, CU_TENSOR_MAP_FLOAT_OOB_FILL_NONE);
}

extern "C" void kernel_launch(void* const* d_in, const int* in_sizes, int n_in, void* d_out, int out_size) {
  (void)in_sizes; (void)n_in; (void)out_size;
  static PFN_enc f = nullptr;
  static void *kvT, *y2T, *o;
  if (!f) {
    void* p = nullptr;
    cudaDriverEntryPointQueryResult q;
    cudaGetDriverEntryPoint("cuTensorMapEncodeTiled", &p, cudaEnableDefault, &q);
    f = (PFN_enc)p;
    cudaGetSymbolAddress(&kvT, g_kvT); cudaGetSymbolAddress(&y2T, g_y2T); cudaGetSymbolAddress(&o, g_o);
    cudaFuncSetAttribute(fused_kernel, cudaFuncAttributeMaxDynamicSharedMemorySize, SMEM_BYTES);
  }
  Maps M;
  const CUtensorMapSwizzle S0 = CU_TENSOR_MAP_SWIZZLE_NONE, S32 = CU_TENSOR_MAP_SWIZZLE_32B, S64 = CU_TENSOR_MAP_SWIZZLE_64B, S128 = CU_TENSOR_MAP_SWIZZLE_128B;
  const cuuint64_t dpar[3] = {640, 2, 1024}, spar[2] = {1280, 2560};
  const cuuint64_t dw[3] = {640, 640, 3}, sw[2] = {3840, 1280};
  const cuuint64_t dnat[2] = {640, 2048}, snat[1] = {1280};
  const cuuint64_t dT2[3] = {32, 1280, 64}, sT[2] = {4096, 64};
  const cuuint64_t dwo[2] = {640, 640};
  { const cuuint32_t bx[3] = {64, 1, 128}; enc(f, &M.x_par, d_in[0], 3, dpar, spar, bx, S128); }
  { const cuuint32_t bx[3] = {64, 16, 3}; enc(f, &M.w_main, d_in[7], 3, dw, sw, bx, S128); }
  { const cuuint32_t bx[3] = {16, 16, 3}; enc(f, &M.w_tail, d_in[7], 3, dw, sw, bx, S32); }
  { const cuuint32_t bx[3] = {80, 1, 64}; enc(f, &M.o_st, o, 3, dpar, spar, bx, S0); }
  { const cuuint32_t bx[3] = {32, 64, 1}; enc(f, &M.kv_st, kvT, 3, dT2, sT, bx, S64); }
  { const cuuint32_t bx[3] = {32, 32, 5}; enc(f, &M.y_ld, y2T, 3, dT2, sT, bx, S64); }
  { const cuuint32_t bx[2] = {64, 36}; enc(f, &M.k_ld, d_in[1], 2, dnat, snat, bx, S0); }
  { const cuuint32_t bx[2] = {64, 33}; enc(f, &M.v_ld, d_in[2], 2, dnat, snat, bx, S0); }
  { const cuuint32_t bx[2] = {32, 160}; enc(f, &M.q_ld, d_in[0], 2, dnat, snat, bx, S0); }
  { const cuuint32_t bx[2] = {64, 64}; enc(f, &M.wo, d_in[8], 2, dwo, snat, bx, S128); }
  { const cuuint32_t bx[2] = {64, 80}; enc(f, &M.o_ld, o, 2, dnat, snat, bx, S128); }
  fused_kernel<<<130, 512, SMEM_BYTES, cudaStreamPerThread>>>((const uint16_t*)d_in[0], (const uint16_t*)d_in[7], (const uint16_t*)d_in[9], M, (const uint16_t*)d_in[3], (const uint16_t*)d_in[4], (const uint16_t*)d_in[5],
                                                              (uint16_t*)d_out);
}
```

```cpp
#include <cuda_runtime.h>
#include <cuda_bf16.h>
#include <cuda.h>
#include <stdint.h>
#include <type_traits>

#define DEVI __device__ __forceinline__
#define PT1 300
#define PTD 460
#define PTE 150
#define DEFER 4
#define KPH 700
#define NLATE 4
#define NPRE 1
#define HDL 300
#define PTA 200
#define PTS 16
#define HPERM 0x73406251u
#define KPM 0
#define KT0 1800
#define KTD 1000
#define RC 192
#define RH 96
#define RP 32
#define HOLD 750
#define LEAD 3

DEVI uint32_t smem_u32(const void* p) { return (uint32_t)__cvta_generic_to_shared(p); }
DEVI void wg_fence() { asm volatile("wgmma.fence.sync.aligned;" ::: "memory"); }
DEVI void wg_commit() { asm volatile("wgmma.commit_group.sync.aligned;" ::: "memory"); }
template <int N> DEVI void wg_wait() { asm volatile("wgmma.wait_group.sync.aligned %0;" ::"n"(N) : "memory"); }
template <int A = 0, int B = -1, int S> DEVI void fence_regs(float (&d)[S]) {
#pragma unroll
  for (int i = A; i < (B < 0 ? S : B); i++) asm volatile("" : "+f"(d[i])::"memory");
}
DEVI uint64_t mkdesc(uint32_t addr, uint32_t lbo, uint32_t sbo, int swz) {
  return (uint64_t)((addr & 0x3FFFF) >> 4) | ((uint64_t)(lbo >> 4) << 16) | ((uint64_t)(sbo >> 4) << 32) | ((uint64_t)swz << 62);
}
DEVI void mbar_init(uint32_t bar, uint32_t cnt) { asm volatile("mbarrier.init.shared::cta.b64 [%0], %1;" ::"r"(bar), "r"(cnt) : "memory"); }
DEVI void mbar_expect_tx(uint32_t bar, uint32_t bytes) { asm volatile("mbarrier.arrive.expect_tx.shared::cta.b64 _, [%0], %1;" ::"r"(bar), "r"(bytes) : "memory"); }
DEVI void mbar_arrive(uint32_t bar) { asm volatile("mbarrier.arrive.shared::cta.b64 _, [%0];" ::"r"(bar) : "memory"); }
DEVI void mbar_wait(uint32_t bar, uint32_t parity) {
  asm volatile("{\n.reg .pred p;\nLAB_WAIT:\nmbarrier.try_wait.parity.shared::cta.b64 p, [%0], %1;\n@!p bra LAB_WAIT;\n}" ::"r"(bar), "r"(parity) : "memory");
}
DEVI void mbar_wait_wd(uint32_t bar, uint32_t parity, uint32_t t0) {
  asm volatile("{\n.reg .pred p;\n.reg .u32 c;\nLAB_WAIT:\nmbarrier.try_wait.parity.shared::cta.b64 p, [%0], %1;\n@p bra DONE;\nmov.u32 c, %%clock;\nsub.u32 c, c, %2;\nsetp.lt.u32 p, c, 0x70000000;\n@p bra LAB_WAIT;\ntrap;\nDONE:\n}" ::"r"(bar), "r"(parity), "r"(t0) : "memory");
}
DEVI void flag_wait(const unsigned* p, unsigned target) {
  asm volatile("{\n.reg .pred p;\n.reg .s32 v;\nLAB_WAIT:\nld.relaxed.gpu.global.u32 v, [%0];\nsub.s32 v, v, %1;\nsetp.lt.s32 p, v, 0;\n@p bra LAB_WAIT;\n}" ::"l"(p), "r"(target) : "memory");
}
DEVI void flag_wait_wd(const unsigned* p, unsigned target, uint32_t t0) {
  asm volatile("{\n.reg .pred p;\n.reg .s32 v;\nLAB_WAIT:\nld.relaxed.gpu.global.u32 v, [%0];\nsub.s32 v, v, %1;\nsetp.ge.s32 p, v, 0;\n@p bra DONE;\nmov.u32 v, %%clock;\nsub.s32 v, v, %2;\nsetp.lt.u32 p, v, 0x70000000;\n@p bra LAB_WAIT;\ntrap;\nDONE:\n}" ::"l"(p), "r"(target), "r"(t0) : "memory");
}
DEVI void flag_add(unsigned* p, unsigned v) { asm volatile("red.relaxed.gpu.global.add.u32 [%0], %1;" ::"l"(p), "r"(v) : "memory"); }
DEVI void flag_release(unsigned* p) { asm volatile("fence.proxy.async;\nred.relaxed.gpu.global.add.u32 [%0], 1;" ::"l"(p) : "memory"); }
DEVI void fence_async_smem() { asm volatile("fence.proxy.async.shared::cta;" ::: "memory"); }
DEVI bool elect_one() { uint32_t p; asm volatile("{\n.reg .pred P;\nelect.sync _|P, 0xffffffff;\nselp.u32 %0, 1, 0, P;\n}" : "=r"(p)); return p; }
DEVI void bar_sync(int id, int n) { asm volatile("bar.sync %0, %1;" ::"r"(id), "r"(n) : "memory"); }
DEVI void bar_arrive(int id, int n) { asm volatile("bar.arrive %0, %1;" ::"r"(id), "r"(n) : "memory"); }
DEVI void tma2(uint32_t dst, const CUtensorMap* m, int c0, int c1, uint32_t bar) {
  asm volatile("cp.async.bulk.tensor.2d.shared::cluster.global.mbarrier::complete_tx::bytes [%0], [%1, {%3, %4}], [%2];" ::"r"(dst), "l"(m), "r"(bar), "r"(c0), "r"(c1) : "memory");
}
DEVI void tma3(uint32_t dst, const CUtensorMap* m, int c0, int c1, int c2, uint32_t bar) {
  asm volatile("cp.async.bulk.tensor.3d.shared::cluster.global.mbarrier::complete_tx::bytes [%0], [%1, {%3, %4, %5}], [%2];" ::"r"(dst), "l"(m), "r"(bar), "r"(c0), "r"(c1), "r"(c2) : "memory");
}
DEVI void tma3_mc(uint32_t dst, const CUtensorMap* m, int c0, int c1, int c2, uint32_t bar) {
  asm volatile("cp.async.bulk.tensor.3d.shared::cluster.global.mbarrier::complete_tx::bytes.multicast::cluster [%0], [%1, {%3, %4, %5}], [%2], %6;" ::"r"(dst), "l"(m), "r"(bar), "r"(c0), "r"(c1), "r"(c2), "h"((uint16_t)3) : "memory");
}
DEVI void tma2_mc(uint32_t dst, const CUtensorMap* m, int c0, int c1, uint32_t bar) {
  asm volatile("cp.async.bulk.tensor.2d.shared::cluster.global.mbarrier::complete_tx::bytes.multicast::cluster [%0], [%1, {%3, %4}], [%2], %5;" ::"r"(dst), "l"(m), "r"(bar), "r"(c0), "r"(c1), "h"((uint16_t)3) : "memory");
}
DEVI void mbar_arrive_remote(uint32_t bar, uint32_t cta) {
  asm volatile("{\n.reg .b32 ra;\nmapa.shared::cluster.u32 ra, %0, %1;\nmbarrier.arrive.shared::cluster.b64 _, [ra];\n}" ::"r"(bar), "r"(cta) : "memory");
}
DEVI void tma3_store(const CUtensorMap* m, int c0, int c1, int c2, uint32_t src) {
  asm volatile("cp.async.bulk.tensor.3d.global.shared::cta.bulk_group [%0, {%2, %3, %4}], [%1];" ::"l"(m), "r"(src), "r"(c0), "r"(c1), "r"(c2) : "memory");
}
DEVI void bulk_load(uint32_t dst, const void* src, uint32_t bytes, uint32_t bar) {
  asm volatile("cp.async.bulk.shared::cluster.global.mbarrier::complete_tx::bytes [%0], [%1], %2, [%3];" ::"r"(dst), "l"(src), "r"(bytes), "r"(bar) : "memory");
}
DEVI void bulk_store(void* dst, uint32_t src, uint32_t bytes) {
  asm volatile("cp.async.bulk.global.shared::cta.bulk_group [%0], [%1], %2;" ::"l"(dst), "r"(src), "r"(bytes) : "memory");
}
DEVI void pf_map(const CUtensorMap* m) { asm volatile("prefetch.tensormap [%0];" ::"l"(m) : "memory"); }
DEVI void pf_l2(const void* p) { asm volatile("prefetch.global.L2 [%0];" ::"l"(p)); }
template <int OFF> DEVI uint32_t ldg_v(const void* p) { uint32_t v; asm volatile("ld.volatile.global.b32 %0, [%1 + %2];" : "=r"(v) : "l"(p), "n"(OFF)); return v; }
DEVI void bulk_commit() { asm volatile("cp.async.bulk.commit_group;" ::: "memory"); }
DEVI void bulk_wait_all() { asm volatile("cp.async.bulk.wait_group 0;" ::: "memory"); }
DEVI void bulk_wait_read() { asm volatile("cp.async.bulk.wait_group.read 0;" ::: "memory"); }
template <int R> DEVI void reg_inc() { asm volatile("setmaxnreg.inc.sync.aligned.u32 %0;" ::"n"(R)); }
template <int R> DEVI void reg_dec() { asm volatile("setmaxnreg.dec.sync.aligned.u32 %0;" ::"n"(R)); }
DEVI uint32_t prmt(uint32_t a, uint32_t b, uint32_t s) { uint32_t r; asm("prmt.b32 %0,%1,%2,%3;" : "=r"(r) : "r"(a), "r"(b), "r"(s)); return r; }
DEVI uint32_t lds32(uint32_t a) { uint32_t r; asm volatile("ld.shared.b32 %0,[%1];" : "=r"(r) : "r"(a)); return r; }
DEVI void sts32(uint32_t a, uint32_t x) { asm volatile("st.shared.b32 [%0],%1;" ::"r"(a), "r"(x) : "memory"); }
DEVI void sts128(uint32_t a, uint32_t x, uint32_t y, uint32_t z, uint32_t w) { asm volatile("st.shared.v4.b32 [%0],{%1,%2,%3,%4};" ::"r"(a), "r"(x), "r"(y), "r"(z), "r"(w) : "memory"); }
DEVI void sts128v(uint32_t a, uint32_t x, uint32_t y, uint32_t z, uint32_t w) { asm volatile("st.volatile.shared.v4.b32 [%0],{%1,%2,%3,%4};" ::"r"(a), "r"(x), "r"(y), "r"(z), "r"(w) : "memory"); }
DEVI void lds128(uint32_t a, uint32_t& x, uint32_t& y, uint32_t& z, uint32_t& w) { asm volatile("ld.shared.v4.b32 {%0,%1,%2,%3},[%4];" : "=r"(x), "=r"(y), "=r"(z), "=r"(w) : "r"(a) : "memory"); }
DEVI void ldsm4(uint32_t& r0, uint32_t& r1, uint32_t& r2, uint32_t& r3, uint32_t addr) {
  asm volatile("ldmatrix.sync.aligned.m8n8.x4.shared.b16 {%0,%1,%2,%3}, [%4];" : "=r"(r0), "=r"(r1), "=r"(r2), "=r"(r3) : "r"(addr) : "memory");
}
DEVI void ldsm4t(uint32_t& r0, uint32_t& r1, uint32_t& r2, uint32_t& r3, uint32_t addr) {
  asm volatile("ldmatrix.sync.aligned.m8n8.x4.trans.shared.b16 {%0,%1,%2,%3}, [%4];" : "=r"(r0), "=r"(r1), "=r"(r2), "=r"(r3) : "r"(addr) : "memory");
}
DEVI void stsm4(uint32_t addr, uint32_t r0, uint32_t r1, uint32_t r2, uint32_t r3) {
  asm volatile("stmatrix.sync.aligned.m8n8.x4.shared.b16 [%0], {%1,%2,%3,%4};" ::"r"(addr), "r"(r0), "r"(r1), "r"(r2), "r"(r3) : "memory");
}
DEVI void stsm4t(uint32_t addr, uint32_t r0, uint32_t r1, uint32_t r2, uint32_t r3) {
  asm volatile("stmatrix.sync.aligned.m8n8.x4.trans.shared.b16 [%0], {%1,%2,%3,%4};" ::"r"(addr), "r"(r0), "r"(r1), "r"(r2), "r"(r3) : "memory");
}
DEVI uint32_t movm(uint32_t a) { uint32_t r; asm volatile("movmatrix.sync.aligned.m8n8.trans.b16 %0, %1;" : "=r"(r) : "r"(a)); return r; }
DEVI uint32_t pack_bf16(float lo, float hi) { uint32_t r; asm("cvt.rn.bf16x2.f32 %0, %1, %2;" : "=r"(r) : "f"(hi), "f"(lo)); return r; }
DEVI uint32_t hmul2(uint32_t a, uint32_t b) { uint32_t r; asm("mul.rn.bf16x2 %0,%1,%2;" : "=r"(r) : "r"(a), "r"(b)); return r; }
DEVI uint32_t hadd2(uint32_t a, uint32_t b) { uint32_t r; asm("add.rn.bf16x2 %0,%1,%2;" : "=r"(r) : "r"(a), "r"(b)); return r; }
DEVI float bf_lo(uint32_t a) { return __uint_as_float(prmt(a, 0, 0x1044)); }
DEVI float bf_hi(uint32_t a) { return __uint_as_float(a & 0xFFFF0000u); }
DEVI void mma16(float (&c)[4], uint32_t a0, uint32_t a1, uint32_t a2, uint32_t a3, uint32_t b0, uint32_t b1) {
  asm volatile("mma.sync.aligned.m16n8k16.row.col.f32.bf16.bf16.f32 {%0,%1,%2,%3},{%4,%5,%6,%7},{%8,%9},{%0,%1,%2,%3};"
      : "+f"(c[0]), "+f"(c[1]), "+f"(c[2]), "+f"(c[3]) : "r"(a0), "r"(a1), "r"(a2), "r"(a3), "r"(b0), "r"(b1));
}
DEVI void mma8(float (&c)[4], uint32_t a0, uint32_t a1, uint32_t b0) {
  asm volatile("mma.sync.aligned.m16n8k8.row.col.f32.bf16.bf16.f32 {%0,%1,%2,%3},{%4,%5},{%6},{%0,%1,%2,%3};"
      : "+f"(c[0]), "+f"(c[1]), "+f"(c[2]), "+f"(c[3]) : "r"(a0), "r"(a1), "r"(b0));
}
DEVI float ex2(float x) { float r; asm volatile("ex2.approx.ftz.f32 %0, %1;" : "=f"(r) : "f"(x)); return r; }

DEVI uint32_t clk() { uint32_t c; asm volatile("mov.u32 %0, %%clock;" : "=r"(c)); return c; }
DEVI void wait_until(uint32_t t0, int dt) { while ((int)(clk() - t0) < dt) __nanosleep(40); }
DEVI void spin_until(uint32_t t0, int dt) { while ((int)(clk() - t0) < dt) {} }
DEVI uint32_t hfma2(uint32_t a, uint32_t b, uint32_t c) { uint32_t r; asm("fma.rn.bf16x2 %0,%1,%2,%3;" : "=r"(r) : "r"(a), "r"(b), "r"(c)); return r; }
DEVI void bar_sync_p(int on, int id, int n) { asm volatile("{\n.reg .pred p;\nsetp.ne.b32 p, %0, 0;\n@p bar.sync %1, %2;\n}" ::"r"(on), "r"(id), "r"(n) : "memory"); }
DEVI void bar_arrive_p(int on, int id, int n) { asm volatile("{\n.reg .pred p;\nsetp.ne.b32 p, %0, 0;\n@p bar.arrive %1, %2;\n}" ::"r"(on), "r"(id), "r"(n) : "memory"); }
DEVI void mbar_arrive_p(int on, uint32_t bar) { asm volatile("{\n.reg .pred p;\nsetp.ne.b32 p, %1, 0;\n@p mbarrier.arrive.shared::cta.b64 _, [%0];\n}" ::"r"(bar), "r"(on) : "memory"); }
DEVI void mbar_arrive2_p(int on, uint32_t bar, uint32_t rbar) {
  asm volatile("{\n.reg .pred p;\nsetp.ne.b32 p, %2, 0;\n@p mbarrier.arrive.shared::cta.b64 _, [%0];\n@p mbarrier.arrive.shared::cluster.b64 _, [%1];\n}" ::"r"(bar), "r"(rbar), "r"(on) : "memory");
}
DEVI void st_relaxed(uint4* p, uint32_t x, uint32_t y, uint32_t z, uint32_t w) {
  asm volatile("st.relaxed.gpu.global.v4.b32 [%0], {%1,%2,%3,%4};" ::"l"(p), "r"(x), "r"(y), "r"(z), "r"(w) : "memory");
}
DEVI uint32_t mapa(uint32_t a, uint32_t cta) { uint32_t r; asm("mapa.shared::cluster.u32 %0, %1, %2;" : "=r"(r) : "r"(a), "r"(cta)); return r; }
DEVI void st_async128(uint32_t a, uint32_t x, uint32_t y, uint32_t z, uint32_t w, uint32_t bar) {
  asm volatile("st.async.weak.shared::cluster.mbarrier::complete_tx::bytes.v4.b32 [%0], {%1,%2,%3,%4}, [%5];" ::"r"(a), "r"(x), "r"(y), "r"(z), "r"(w), "r"(bar) : "memory");
}

template<int OFF, int TB, int S> __device__ __forceinline__ void wgmma_rs_n128(float (&d)[S], uint32_t a0, uint32_t a1, uint32_t a2, uint32_t a3, uint64_t db, int sd) {
  asm volatile("{\n.reg .pred p;\nsetp.ne.b32 p, %69, 0;\n"
    "wgmma.mma_async.sync.aligned.m64n128k16.f32.bf16.bf16 {%0, %1, %2, %3, %4, %5, %6, %7, %8, %9, %10, %11, %12, %13, %14, %15, %16, %17, %18, %19, %20, %21, %22, %23, %24, %25, %26, %27, %28, %29, %30, %31, %32, %33, %34, %35, %36, %37, %38, %39, %40, %41, %42, %43, %44, %45, %46, %47, %48, %49, %50, %51, %52, %53, %54, %55, %56, %57, %58, %59, %60, %61, %62, %63}, {%64, %65, %66, %67}, %68, p, 1, 1, %70;\n}\n"
    : "+f"(d[OFF+0]), "+f"(d[OFF+1]), "+f"(d[OFF+2]), "+f"(d[OFF+3]), "+f"(d[OFF+4]), "+f"(d[OFF+5]), "+f"(d[OFF+6]), "+f"(d[OFF+7]), "+f"(d[OFF+8]), "+f"(d[OFF+9]), "+f"(d[OFF+10]), "+f"(d[OFF+11]), "+f"(d[OFF+12]), "+f"(d[OFF+13]), "+f"(d[OFF+14]), "+f"(d[OFF+15]), "+f"(d[OFF+16]), "+f"(d[OFF+17]), "+f"(d[OFF+18]), "+f"(d[OFF+19]), "+f"(d[OFF+20]), "+f"(d[OFF+21]), "+f"(d[OFF+22]), "+f"(d[OFF+23]), "+f"(d[OFF+24]), "+f"(d[OFF+25]), "+f"(d[OFF+26]), "+f"(d[OFF+27]), "+f"(d[OFF+28]), "+f"(d[OFF+29]), "+f"(d[OFF+30]), "+f"(d[OFF+31]), "+f"(d[OFF+32]), "+f"(d[OFF+33]), "+f"(d[OFF+34]), "+f"(d[OFF+35]), "+f"(d[OFF+36]), "+f"(d[OFF+37]), "+f"(d[OFF+38]), "+f"(d[OFF+39]), "+f"(d[OFF+40]), "+f"(d[OFF+41]), "+f"(d[OFF+42]), "+f"(d[OFF+43]), "+f"(d[OFF+44]), "+f"(d[OFF+45]), "+f"(d[OFF+46]), "+f"(d[OFF+47]), "+f"(d[OFF+48]), "+f"(d[OFF+49]), "+f"(d[OFF+50]), "+f"(d[OFF+51]), "+f"(d[OFF+52]), "+f"(d[OFF+53]), "+f"(d[OFF+54]), "+f"(d[OFF+55]), "+f"(d[OFF+56]), "+f"(d[OFF+57]), "+f"(d[OFF+58]), "+f"(d[OFF+59]), "+f"(d[OFF+60]), "+f"(d[OFF+61]), "+f"(d[OFF+62]), "+f"(d[OFF+63]) : "r"(a0), "r"(a1), "r"(a2), "r"(a3), "l"(db), "r"(sd), "n"(TB));
}
template<int OFF, int TB, int S> __device__ __forceinline__ void wgmma_rs_n64(float (&d)[S], uint32_t a0, uint32_t a1, uint32_t a2, uint32_t a3, uint64_t db, int sd) {
  asm volatile("{\n.reg .pred p;\nsetp.ne.b32 p, %37, 0;\n"
    "wgmma.mma_async.sync.aligned.m64n64k16.f32.bf16.bf16 {%0, %1, %2, %3, %4, %5, %6, %7, %8, %9, %10, %11, %12, %13, %14, %15, %16, %17, %18, %19, %20, %21, %22, %23, %24, %25, %26, %27, %28, %29, %30, %31}, {%32, %33, %34, %35}, %36, p, 1, 1, %38;\n}\n"
    : "+f"(d[OFF+0]), "+f"(d[OFF+1]), "+f"(d[OFF+2]), "+f"(d[OFF+3]), "+f"(d[OFF+4]), "+f"(d[OFF+5]), "+f"(d[OFF+6]), "+f"(d[OFF+7]), "+f"(d[OFF+8]), "+f"(d[OFF+9]), "+f"(d[OFF+10]), "+f"(d[OFF+11]), "+f"(d[OFF+12]), "+f"(d[OFF+13]), "+f"(d[OFF+14]), "+f"(d[OFF+15]), "+f"(d[OFF+16]), "+f"(d[OFF+17]), "+f"(d[OFF+18]), "+f"(d[OFF+19]), "+f"(d[OFF+20]), "+f"(d[OFF+21]), "+f"(d[OFF+22]), "+f"(d[OFF+23]), "+f"(d[OFF+24]), "+f"(d[OFF+25]), "+f"(d[OFF+26]), "+f"(d[OFF+27]), "+f"(d[OFF+28]), "+f"(d[OFF+29]), "+f"(d[OFF+30]), "+f"(d[OFF+31]) : "r"(a0), "r"(a1), "r"(a2), "r"(a3), "l"(db), "r"(sd), "n"(TB));
}
template<int OFF, int TB, int S> __device__ __forceinline__ void wgmma_rs_n48(float (&d)[S], uint32_t a0, uint32_t a1, uint32_t a2, uint32_t a3, uint64_t db, int sd) {
  asm volatile("{\n.reg .pred p;\nsetp.ne.b32 p, %29, 0;\n"
    "wgmma.mma_async.sync.aligned.m64n48k16.f32.bf16.bf16 {%0, %1, %2, %3, %4, %5, %6, %7, %8, %9, %10, %11, %12, %13, %14, %15, %16, %17, %18, %19, %20, %21, %22, %23}, {%24, %25, %26, %27}, %28, p, 1, 1, %30;\n}\n"
    : "+f"(d[OFF+0]), "+f"(d[OFF+1]), "+f"(d[OFF+2]), "+f"(d[OFF+3]), "+f"(d[OFF+4]), "+f"(d[OFF+5]), "+f"(d[OFF+6]), "+f"(d[OFF+7]), "+f"(d[OFF+8]), "+f"(d[OFF+9]), "+f"(d[OFF+10]), "+f"(d[OFF+11]), "+f"(d[OFF+12]), "+f"(d[OFF+13]), "+f"(d[OFF+14]), "+f"(d[OFF+15]), "+f"(d[OFF+16]), "+f"(d[OFF+17]), "+f"(d[OFF+18]), "+f"(d[OFF+19]), "+f"(d[OFF+20]), "+f"(d[OFF+21]), "+f"(d[OFF+22]), "+f"(d[OFF+23]) : "r"(a0), "r"(a1), "r"(a2), "r"(a3), "l"(db), "r"(sd), "n"(TB));
}
template<int OFF, int TB, int S> __device__ __forceinline__ void wgmma_rs_n16(float (&d)[S], uint32_t a0, uint32_t a1, uint32_t a2, uint32_t a3, uint64_t db, int sd) {
  asm volatile("{\n.reg .pred p;\nsetp.ne.b32 p, %13, 0;\n"
    "wgmma.mma_async.sync.aligned.m64n16k16.f32.bf16.bf16 {%0, %1, %2, %3, %4, %5, %6, %7}, {%8, %9, %10, %11}, %12, p, 1, 1, %14;\n}\n"
    : "+f"(d[OFF+0]), "+f"(d[OFF+1]), "+f"(d[OFF+2]), "+f"(d[OFF+3]), "+f"(d[OFF+4]), "+f"(d[OFF+5]), "+f"(d[OFF+6]), "+f"(d[OFF+7]) : "r"(a0), "r"(a1), "r"(a2), "r"(a3), "l"(db), "r"(sd), "n"(TB));
}
template<int OFF, int TA, int TB, int S> __device__ __forceinline__ void wgmma_ss_n160(float (&d)[S], uint64_t da, uint64_t db, int sd) {
  asm volatile("{\n.reg .pred p;\nsetp.ne.b32 p, %82, 0;\n"
    "wgmma.mma_async.sync.aligned.m64n160k16.f32.bf16.bf16 {%0, %1, %2, %3, %4, %5, %6, %7, %8, %9, %10, %11, %12, %13, %14, %15, %16, %17, %18, %19, %20, %21, %22, %23, %24, %25, %26, %27, %28, %29, %30, %31, %32, %33, %34, %35, %36, %37, %38, %39, %40, %41, %42, %43, %44, %45, %46, %47, %48, %49, %50, %51, %52, %53, %54, %55, %56, %57, %58, %59, %60, %61, %62, %63, %64, %65, %66, %67, %68, %69, %70, %71, %72, %73, %74, %75, %76, %77, %78, %79}, %80, %81, p, 1, 1, %83, %84;\n}\n"
    : "+f"(d[OFF+0]), "+f"(d[OFF+1]), "+f"(d[OFF+2]), "+f"(d[OFF+3]), "+f"(d[OFF+4]), "+f"(d[OFF+5]), "+f"(d[OFF+6]), "+f"(d[OFF+7]), "+f"(d[OFF+8]), "+f"(d[OFF+9]), "+f"(d[OFF+10]), "+f"(d[OFF+11]), "+f"(d[OFF+12]), "+f"(d[OFF+13]), "+f"(d[OFF+14]), "+f"(d[OFF+15]), "+f"(d[OFF+16]), "+f"(d[OFF+17]), "+f"(d[OFF+18]), "+f"(d[OFF+19]), "+f"(d[OFF+20]), "+f"(d[OFF+21]), "+f"(d[OFF+22]), "+f"(d[OFF+23]), "+f"(d[OFF+24]), "+f"(d[OFF+25]), "+f"(d[OFF+26]), "+f"(d[OFF+27]), "+f"(d[OFF+28]), "+f"(d[OFF+29]), "+f"(d[OFF+30]), "+f"(d[OFF+31]), "+f"(d[OFF+32]), "+f"(d[OFF+33]), "+f"(d[OFF+34]), "+f"(d[OFF+35]), "+f"(d[OFF+36]), "+f"(d[OFF+37]), "+f"(d[OFF+38]), "+f"(d[OFF+39]), "+f"(d[OFF+40]), "+f"(d[OFF+41]), "+f"(d[OFF+42]), "+f"(d[OFF+43]), "+f"(d[OFF+44]), "+f"(d[OFF+45]), "+f"(d[OFF+46]), "+f"(d[OFF+47]), "+f"(d[OFF+48]), "+f"(d[OFF+49]), "+f"(d[OFF+50]), "+f"(d[OFF+51]), "+f"(d[OFF+52]), "+f"(d[OFF+53]), "+f"(d[OFF+54]), "+f"(d[OFF+55]), "+f"(d[OFF+56]), "+f"(d[OFF+57]), "+f"(d[OFF+58]), "+f"(d[OFF+59]), "+f"(d[OFF+60]), "+f"(d[OFF+61]), "+f"(d[OFF+62]), "+f"(d[OFF+63]), "+f"(d[OFF+64]), "+f"(d[OFF+65]), "+f"(d[OFF+66]), "+f"(d[OFF+67]), "+f"(d[OFF+68]), "+f"(d[OFF+69]), "+f"(d[OFF+70]), "+f"(d[OFF+71]), "+f"(d[OFF+72]), "+f"(d[OFF+73]), "+f"(d[OFF+74]), "+f"(d[OFF+75]), "+f"(d[OFF+76]), "+f"(d[OFF+77]), "+f"(d[OFF+78]), "+f"(d[OFF+79]) : "l"(da), "l"(db), "r"(sd), "n"(TA), "n"(TB));
}

__device__ __align__(1024) uint16_t g_kvT[2 * 640 * 2048];
__device__ __align__(1024) uint16_t g_y2T[2 * 640 * 2048];
__device__ __align__(1024) uint16_t g_o[2048 * 640];
__device__ __align__(1024) uint16_t g_gate[2080];
__device__ __align__(1024) uint4 g_halo[128 * 5 * 32];
__device__ __align__(1024) unsigned g_cnt[46 * 32];
__device__ __align__(1024) unsigned g_launch[132 * 32];
#define CNT_KV(i) (g_cnt + 32 * (i))
#define CNT_O(i) (g_cnt + 32 * (10 + (i)))
#define CNT_Y(i) (g_cnt + 32 * (26 + (i)))
#define PTL(i) do {} while (0)
#define PTPL(on, i) do {} while (0)
#define PT(i) do {} while (0)
#define PTP(on, i) do {} while (0)

constexpr uint32_t SB = 1024;
constexpr uint32_t STG = 23552, WST = 15360;
DEVI constexpr uint32_t o_px(int ks) { return (((ks >> 1) + 1) & 3) * 2 * STG; }
DEVI constexpr uint32_t o_pw(int ks) { return o_px(ks) + 16384 + (ks & 1) * WST; }
constexpr uint32_t O_HALO = 0, O_QT = STG;
constexpr uint32_t O_OST = 2 * STG;
constexpr uint32_t P3S = 28672;
constexpr uint32_t HC = 8320, UC = 4624, UZ = 528;
constexpr uint32_t O_H0 = 5 * P3S, O_U2 = O_H0 + 3 * HC, O_H3 = O_U2 + UC, O_U0 = O_H3 + 2 * HC;
DEVI constexpr uint32_t o_h(int c) { return O_H0 + c * HC + (c > 2 ? UC : 0); }
DEVI constexpr uint32_t o_u(int c) { return c == 2 ? O_U2 : O_U0 + (c > 2 ? c - 1 : c) * UC; }
constexpr uint32_t O_Y = 208896;
DEVI constexpr uint32_t o_x(int c) { return c < 2 ? O_Y + c * 5120 : O_U0 + (c & 1) * UC; }
constexpr uint32_t O_HIN = O_Y + 16384;
DEVI constexpr uint32_t o_kin(int c) { return ((O_U0 + 127) & ~127u) + ((c & 1) ? 0 : 73 * 128); }
DEVI constexpr uint32_t o_p3(int ks) { return (ks < 6 ? ks : ks - 6) * P3S; }
constexpr uint32_t O_BT = 4 * P3S;
constexpr uint32_t O_GT = O_Y + 20480, O_GW = O_GT + 320;
constexpr uint32_t O_BAR = 231040;
constexpr uint32_t B_FULL = O_BAR, B_EMPTY = O_BAR + 8 * 8, B_P3F = O_BAR + 8 * 16, B_P3R = O_BAR + 8 * 26, B_G = O_BAR + 8 * 27, B_U = O_BAR + 8 * 28,
                   B_KVD = O_BAR + 8 * 33, B_KF = O_BAR + 8 * 36, B_Y = O_BAR + 8 * 38, B_EP = O_BAR + 8 * 40, B_LAST = O_BAR + 8 * 41, B_DONE = O_BAR + 8 * 42,
                   B_P1E = O_BAR + 8 * 43, B_HX = O_BAR + 8 * 43  , B_P3E = O_BAR + 8 * 52, B_HX0 = O_BAR + 8 * 57, B_KVS = O_BAR + 8 * 58, B_QD = O_BAR + 8 * 60, B_GD = O_BAR + 8 * 61, B_OR = O_BAR + 8 * 62, B_HC = O_BAR + 8 * 63, B_Q = O_BAR + 8 * 51;
constexpr uint32_t B_S13 = B_EMPTY + 8 * 5, B_S15 = B_EMPTY + 8 * 7, B_S19 = B_EMPTY + 8 * 3;
constexpr uint32_t O_GP = O_BAR + 512, O_EPOCH = O_GW + 1280;
constexpr uint32_t SMEM_BYTES = 232448;
static_assert(O_U0 + 4 * UC <= O_Y - 512 && o_kin(0) >= O_U0 + 2 * UC && O_EPOCH + 4 <= O_BAR && O_U0 >= 8 * STG, "smem map");
enum { NB_LEAD = 1, NB_HELP = 2, NB_HALO = 3, NB_ATT = 4, NB_G = 5, NB_TOK = 6, NB_RFULL = 8, NB_RFREE = 10 };

struct Maps { CUtensorMap x_par, w_main, w_tail, k_ld, v_ld, o_st, kv_st, wo, o_ld, y_ld, q_ld; };

template <int M> DEVI void conv_step(float (&acc)[128], uint32_t a0, uint32_t a1, uint32_t a2, uint32_t a3, uint32_t dl) {
  auto D = [&](int off) { return ((uint64_t)8 << 32) | (uint64_t)(uint32_t)(dl + off - 16 * M); };
  if constexpr (M == 0) wgmma_rs_n16<0, 0>(acc, a0, a1, a2, a3, D(0), 0);
  if constexpr (M <= 3) wgmma_rs_n48<8, 0>(acc, a0, a1, a2, a3, D(16), M == 0 ? 0 : 1);
  if constexpr (M <= 6) wgmma_rs_n48<32, 0>(acc, a0, a1, a2, a3, D(64), M == 0 ? 0 : 1);
  if constexpr (M <= 9) wgmma_rs_n48<56, 0>(acc, a0, a1, a2, a3, D(112), M == 0 ? 0 : 1);
  if constexpr (M <= 12) wgmma_rs_n48<80, 0>(acc, a0, a1, a2, a3, D(160), M == 0 ? 0 : 1);
  wgmma_rs_n48<104, 0>(acc, a0, a1, a2, a3, D(208), M == 0 ? 0 : 1);
}
DEVI constexpr int a_off(int P, int i) { return -4 * (64 * ((i & 4) ? 15 - P : P) + (i & 1) * 32 - (i & 2) * 2); }
template <int P> DEVI void load_pair(uint32_t (&a)[8], uint32_t ab) {
#pragma unroll
  for (int i = 0; i < 8; i++) a[i] = lds32(ab + a_off(P, i));
}
template <int P> DEVI void mma_pair(float (&acc)[128], uint32_t (&a)[8], uint32_t db) {
  wg_fence();
  conv_step<P>(acc, a[0], a[1], a[2], a[3], db);
  conv_step<15 - P>(acc, a[4], a[5], a[6], a[7], db);
  wg_commit();
}

template <int I0, int I1> DEVI void conv_reduce(uint32_t sb, int c, int ht, int chan, int bar, int nthr) {
  const uint32_t a0 = sb + o_h(c) + ht * 16, a2 = sb + o_u(c) + ht * 16, a3 = sb + o_x(c) + ht * 16;
  uint4* yp = (uint4*)(g_y2T + (size_t)chan * 2048) + ht;
#pragma unroll
  for (int i = I0; i < I1; i++) {
    uint4 p, q, r, s;
    if (i == I0) bar_sync(bar, nthr);
    lds128(a0 + i * 2048, p.x, p.y, p.z, p.w); lds128(a0 + 4160 + i * 2048, q.x, q.y, q.z, q.w);
    lds128(a2 + i * 2048, r.x, r.y, r.z, r.w); lds128(a3 + i * 2048, s.x, s.y, s.z, s.w);
    auto sum = [](uint32_t a, uint32_t b, uint32_t c, uint32_t d) { return hadd2(hadd2(hadd2(a, b), 0u), hadd2(c, d)) ^ 0x80008000u; };
    yp[i * 128] = make_uint4(sum(p.x, q.x, r.x, s.x), sum(p.y, q.y, r.y, s.y), sum(p.z, q.z, r.z, s.z), sum(p.w, q.w, r.w, s.w));
  }
}

template <int ODD, int PART> DEVI void pack_qkv(const float (&acc)[120], uint32_t (&Q)[10][2], uint32_t (&K)[10][2], uint32_t (&V)[10][2]) {
#pragma unroll
  for (int f = 0; f < 10; f++) {
    const bool tail = ODD ? (f < 2) : (f >= 8);
    const int fm = ODD ? f - 2 : f, ft = ODD ? f : f - 8;
    const int nq = tail ? 24 + ft : fm, nk = tail ? 26 + ft : 8 + fm, nv = tail ? 28 + ft : 16 + fm;
    if (PART == 0) { K[f][1] = pack_bf16(acc[4 * nk + 2], acc[4 * nk + 3]); V[f][1] = pack_bf16(acc[4 * nv + 2], acc[4 * nv + 3]); }
    if (PART == 1) { V[f][0] = pack_bf16(acc[4 * nv], acc[4 * nv + 1]); K[f][0] = pack_bf16(acc[4 * nk], acc[4 * nk + 1]); }
    if (PART == 2) { Q[f][0] = pack_bf16(acc[4 * nq], acc[4 * nq + 1]); Q[f][1] = pack_bf16(acc[4 * nq + 2], acc[4 * nq + 3]); }
  }
}
DEVI int pair_of(int c) {
  int p; asm("{\n.reg .pred q, r;\nsetp.lt.s32 q, %1, 4;\nsetp.lt.s32 r, %1, 36;\nselp.b32 %0, %3, %4, r;\nselp.b32 %0, %2, %0, q;\n}" : "=r"(p) : "r"(c), "r"(32 + 8 * c), "r"(c - 4), "r"((c * 293 - 2097) >> 8));
  p = (p & 7) | ((HPERM >> ((p >> 3) * 4)) & 7) << 3;
  return p;
}
DEVI uint32_t make_ctx() {
  int b; asm volatile("mov.u32 %0, %%ctaid.x;" : "=r"(b));
  b += clk() & threadIdx.y;
  const int p = pair_of(b >> 1);
  const int j = b < 128 ? 8 * (p & 7) + (p >> 3) : 64;
  const int q = (j * 205) >> 10, r = j - 5 * q, i = j - q, co = (i * 79) >> 10;
  const int cp = r == 4 ? 4 : co, tb = r == 4 ? q : i - 13 * co;
  return (b < 128 ? 2 * p + (b & 1) : b) | tb << 8 | (2 * cp + (b & 1)) << 12 | (b >> 7) << 16;
}
#define CTX() asm volatile("" : "+r"(ctx)); CTXU()
#define CTXU() int tid; asm volatile("mov.u32 %0, %%tid.x;" : "=r"(tid)); \
  const int lane = tid & 31, vb = ctx & 255, hg = (ctx >> 4) & 7, rt = ctx & 15, par = (ctx >> 3) & 1, mt = ctx & 7, rank = ctx & 1, \
  tb = (ctx >> 8) & 15, cb = (ctx >> 12) & 15; const bool main_cta = ctx < 65536; \
  (void)tid; (void)lane; (void)vb; (void)hg; (void)rt; (void)par; (void)mt; (void)rank; (void)tb; (void)cb; (void)main_cta
#define CTXW() CTX(); const int wg = warp >> 2, w = warp & 3, g = lane >> 2, t = lane & 3; const bool lead = (tid & 127) == 0; \
  (void)wg; (void)w; (void)g; (void)t; (void)lead

__global__ void __cluster_dims__(2, 1, 1) __launch_bounds__(512, 1)
fused_kernel(const uint16_t* __restrict__ xq, const uint16_t* __restrict__ wqkv, const uint16_t* __restrict__ gate_w, const __grid_constant__ Maps M, const uint16_t* __restrict__ shift_k, const uint16_t* __restrict__ ssm_k, const uint16_t* __restrict__ ssm_D,
             uint16_t* __restrict__ outp) {
  extern __shared__ __align__(1024) uint8_t smem_raw[];
  const uint32_t sb = smem_u32(smem_raw);
  const uint32_t t0 = clk();
  auto get_epoch = [&]() { mbar_wait(sb + B_EP, 0); return lds32(sb + O_EPOCH); };

  auto p1_load_x = [&](int ks, int p, int rank) {
    tma3(sb + o_px(ks), &M.x_par, ks * 32, (p >> 2) & 1, (p & 3) * 256 + rank * 128, sb + B_FULL + 8 * (ks & 7));
  };
  auto p1_load_w = [&](int ks, int p, int rank) {
    const uint32_t st = sb + o_pw(ks), fb = sb + B_FULL + 8 * (ks & 7);
    tma3_mc(st + rank * 6144, &M.w_main, (p >> 3) * 80 + 2 * (p & 8), ks * 32 + rank * 16, 0, fb);
    tma3_mc(st + 12288 + rank * 1536, &M.w_tail, (p >> 3) * 80 + 8 * (~p & 8), ks * 32 + rank * 16, 0, fb);
  };
  auto cta_pair = [&]() { return pair_of(blockIdx.x >> 1); };

  if (threadIdx.x < 32) {
    const unsigned b = blockIdx.x, l = threadIdx.x;
    const uint16_t* pfp = l < 16 ? xq + (16 * b + l) * 640 : wqkv + (15 * b + l - 16) * 64;
    if ((l | b >> 7 << 5) < 31) pf_l2(pfp);
  }
  const int warp = __shfl_sync(~0u, threadIdx.x >> 5, 0);
  if ((warp & 14) == 8) {
    if (elect_one()) {
#pragma unroll
      for (int s = 0; s < 8; s++) mbar_init(sb + O_BAR - 512 + 64 * warp + 8 * s, 5 * warp - 39);
      asm volatile("fence.mbarrier_init.release.cluster;" ::: "memory");
    }
    __syncwarp();
  }
  asm volatile("barrier.cluster.arrive.relaxed.aligned;" ::: "memory");
  if (warp == 8 && blockIdx.x < 128) {
    const int p = cta_pair(), rank = blockIdx.x & 1;
    if (elect_one()) { mbar_expect_tx(sb + B_FULL, 16384 + WST); p1_load_x(0, p, rank); }
    __syncwarp();
    asm volatile("barrier.cluster.wait.aligned;" ::: "memory");
    if (elect_one()) {
      p1_load_w(0, p, rank); PT(100);
      pf_map(&M.k_ld); pf_map(&M.v_ld);
    }
    __syncwarp();
  } else if (warp != 15) {
    asm volatile("barrier.cluster.wait.aligned;" ::: "memory");
    spin_until(t0, HOLD);
  }
  auto cluster_sync = [&]() {
    asm volatile("barrier.cluster.arrive.relaxed.aligned;" ::: "memory");
    asm volatile("barrier.cluster.wait.aligned;" ::: "memory");
  };
  auto init_rest = [&]() {
    if (warp >= 11 && elect_one()) {
#pragma unroll
      for (int s = 0; s < 12; s++) mbar_init(sb + O_BAR + 128 - 11 * 96 + 96 * warp + 8 * s, warp == 14 ? 2 : 1);
      asm volatile("fence.mbarrier_init.release.cluster;" ::: "memory");
    }
    __syncwarp();
    if (blockIdx.x < 128) bar_sync(0, 224); else cluster_sync();
  };
  uint32_t ctx = 0;

  if (warp < 8) {
    reg_inc<RC>();
    ctx = make_ctx();
    if (blockIdx.x >= 128) cluster_sync();
    else {
      {
        uint32_t Q[10][2], K[10][2], V[10][2];
        {
          {
            float acc[120];
            CTXW();
            const int odd = (cta_pair() >> 3) & 1;
            const uint32_t rsb = mapa(sb, (blockIdx.x & 1) ^ 1);
            {
              const uint32_t aa = sb + (warp * 16 + (lane & 15)) * 128 + (((lane >> 4) ^ (lane & 7)) << 4);
              constexpr int NA = DEFER > 3 ? DEFER : 3;
              uint32_t a[NA][8];
              auto load_a = [&](int ks) {
                uint32_t(&r)[8] = a[ks % NA];
                mbar_wait(sb + B_FULL + 8 * (ks & 7), (ks >> 3) & 1);
                PTP(lead && (wg || !(ks & 3)), wg ? 60 + ks : 80 + (ks >> 2));
                ldsm4(r[0], r[1], r[2], r[3], (aa ^ ((ks & 1) * 64)) + o_px(ks)); ldsm4(r[4], r[5], r[6], r[7], (aa ^ ((ks & 1) * 64 + 32)) + o_px(ks));
              };
              auto mma_q = [&](int ks, int h) {
                uint32_t(&r)[8] = a[ks % NA];
                wgmma_rs_n64<0, 1>(acc, r[4 * h], r[4 * h + 1], r[4 * h + 2], r[4 * h + 3], mkdesc(SB + o_pw(ks) + h * 6144, 2048, 1024, 1), ks | h);
              };
              auto mma_step = [&](int ks, int h) {
                uint32_t(&r)[8] = a[ks % NA];
                wg_fence();
                wgmma_rs_n128<32, 1>(acc, r[4 * h], r[4 * h + 1], r[4 * h + 2], r[4 * h + 3], mkdesc(SB + o_pw(ks) + h * 6144 + 2048, 2048, 1024, 1), ks | h);
                if (ks < 20 - DEFER) mma_q(ks, h);
                wgmma_rs_n48<96, 1>(acc, r[4 * h], r[4 * h + 1], r[4 * h + 2], r[4 * h + 3], mkdesc(SB + o_pw(ks) + 12288 + h * 1536, 512, 256, 3), ks | h);
                wg_commit();
              };
              if (lead) PT(1 + wg);
              load_a(0);
#pragma unroll
              for (int ks = 0; ks < 20; ks++) {
                if (ks == 20 - LEAD) bar_sync_p(wg == 0, NB_LEAD, 256);
                mma_step(ks, 0);
                if (ks < 19 && ks >= NLATE) load_a(ks + 1);
                mma_step(ks, 1);
                if (ks < NLATE) load_a(ks + 1);
                if (ks >= 1 && ks <= 16) {
                  wg_wait<2>();
                  mbar_arrive2_p(lead, sb + B_EMPTY + 8 * ((ks - 1) & 7), rsb + B_EMPTY + 8 * ((ks - 1) & 7));
                } else if (ks < 19 && ks + 2 - NA >= 16) wg_wait<2>();
              }
              bar_arrive_p(wg, NB_LEAD, 256);
              if (DEFER) {
                wg_fence();
#pragma unroll
                for (int i = 40 - 2 * DEFER; i < 40; i++) mma_q(i >> 1, i & 1);
                wg_commit();
              }
              mbar_wait(sb + B_S15, 1);
              wg_wait<1>();
              mbar_arrive_p(tid == 0, sb + B_P1E);
              if (!DEFER) wg_wait<0>();
              fence_regs<32, 120>(acc);
              PTPL(lead, 158 + wg);
            }
            if (odd) pack_qkv<1, 0>(acc, Q, K, V); else pack_qkv<0, 0>(acc, Q, K, V);
            if (warp == 7 && (blockIdx.x & 1)) {
              uint4* hp = g_halo + vb * 160 + lane;
              st_relaxed(hp, K[0][1], K[1][1], K[3][1], K[4][1]); st_relaxed(hp + 32, K[5][1], K[6][1], K[8][1], K[9][1]);
              st_relaxed(hp + 64, K[2][1], K[7][1], V[0][1], V[1][1]);
              st_relaxed(hp + 96, V[2][1], V[3][1], V[4][1], V[5][1]); st_relaxed(hp + 128, V[6][1], V[7][1], V[8][1], V[9][1]);
            }
            const uint32_t ho = sb + O_HALO + warp * 2560 + lane * 16;
            stsm4(ho, K[0][1], K[1][1], K[3][1], K[4][1]); stsm4(ho + 512, K[5][1], K[6][1], K[8][1], K[9][1]);
            stsm4(ho + 1024, K[2][1], K[7][1], V[0][1], V[1][1]);
            stsm4(ho + 1536, V[2][1], V[3][1], V[4][1], V[5][1]); stsm4(ho + 2048, V[6][1], V[7][1], V[8][1], V[9][1]);
            if (warp == 7) {
              if (!(blockIdx.x & 1)) {
                fence_async_smem();
                __syncwarp();
                if (elect_one())
                  asm volatile("cp.async.bulk.shared::cluster.shared::cta.mbarrier::complete_tx::bytes [%0], [%1], 2560, [%2];"
                               ::"r"(mapa(sb + O_HIN, 1)), "r"(sb + O_HALO + 7 * 2560), "r"(mapa(sb + B_HX0, 1)) : "memory");
              }
              __syncwarp();
            } else {
              __syncwarp();
              if (lane == 0) mbar_arrive(sb + B_HX + 8 + 8 * warp);
            }
            if (odd) pack_qkv<1, 1>(acc, Q, K, V); else pack_qkv<0, 1>(acc, Q, K, V);
            wg_wait<0>();
            fence_regs<0, 32>(acc);
            PTPL(lead, 50 + wg);
            mbar_arrive2_p(lead, sb + B_S19, rsb + B_S19);
            if (odd) pack_qkv<1, 2>(acc, Q, K, V); else pack_qkv<0, 2>(acc, Q, K, V);
#pragma unroll
            for (int f = 0; f < 10; f++) V[f][0] = movm(V[f][0]);
            if (lead) PT(52 + wg);
            if (wg) mbar_wait(sb + B_P1E, 0);
          }
          CTXW();
          uint32_t z = threadIdx.y;
          const bool gt0 = 2 * t > g, gt1 = 2 * t + 1 > g;
          const uint32_t pmask = (gt0 ? 0xFFFFu : 0u) | (gt1 ? 0xFFFF0000u : 0u);
          const uint32_t hs = warp ? O_HALO + (warp - 1) * 2560 : O_HIN, ha = sb + hs + lane * 16;
          const uint32_t va = sb + ((lane & 8) ? O_HALO + warp * 2560 : hs) + 1280 + (lane >> 4) * 128 + (lane & 7) * 16;
          uint32_t Qh[4][2], Kh[10], Vh[10];
          float c1[4][4] = {}, c2[4][4] = {}, c0[4][4] = {}, l[8][2], m[8], x[8];
#pragma unroll
          for (int j = 0; j < 4; j++) {
            const int fa = (j >> 1) * 5 + (j & 1) * 3, fh = (j >> 1) * 5 + 2;
            const bool mine = (j & 1) ? (t >= 2) : (t < 2);
            Qh[j][0] = mine ? Q[fh][0] : 0u; Qh[j][1] = mine ? Q[fh][1] : 0u;
            mma16(c1[j], Q[fa][0], Q[fa][1], Q[fa + 1][0], Q[fa + 1][1], K[fa][0], K[fa + 1][0]);
            mma16(c2[j], Q[fa][0], Q[fa][1], Q[fa + 1][0], Q[fa + 1][1], K[fa][1], K[fa + 1][1]);
            mma8(c1[j], Qh[j][0], Qh[j][1], K[fh][0]);
            mma8(c2[j], Qh[j][0], Qh[j][1], K[fh][1]);
          }
          const float C = 0.22360679774997896f * 1.4426950408889634f;
          auto max1 = [&](int r) { m[r] = fmaxf(l[r][0], l[r][1]); x[r] = __shfl_xor_sync(~0u, m[r], 1); };
          auto max2 = [&](int r) { m[r] = fmaxf(m[r], x[r]); x[r] = __shfl_xor_sync(~0u, m[r], 2); };
          auto exps = [&](int r) { const float mc = fmaxf(m[r], x[r]) * C; l[r][0] = ex2(fmaf(l[r][0], C, -mc)); l[r][1] = ex2(fmaf(l[r][1], C, -mc)); };
          auto upper = [&](int a, int b) {
#pragma unroll
            for (int k = a; k < b; k++)
#pragma unroll
              for (int j = 0; j < 4; j++) {
                if (k == 0) { l[4 + j][0] = gt0 ? c1[j][2] : c2[j][2]; l[4 + j][1] = gt1 ? c1[j][3] : c2[j][3]; max1(4 + j); }
                if (k == 1) max2(4 + j);
                if (k == 2) exps(4 + j);
              }
          };
          if (lead) PT(54 + wg);
          mbar_wait(sb + (warp ? B_HX + 8 * warp : B_HX0), 0);
          if (lead) PT(56 + wg);
          ldsm4(Kh[0], Kh[1], Kh[3], Kh[4], ha); ldsm4(Kh[5], Kh[6], Kh[8], Kh[9], ha + 512);
          asm volatile("ldmatrix.sync.aligned.m8n8.x2.shared.b16 {%0,%1}, [%2];" : "=r"(Kh[2]), "=r"(Kh[7]) : "r"(ha + 1024) : "memory");
#pragma unroll
          for (int i = 0; i < 5; i++) ldsm4t(Vh[2 * i], V[2 * i][1], Vh[2 * i + 1], V[2 * i + 1][1], va + i * 256);
          upper(0, 3);
          const bool have_halo = warp > 0 || mt > 0;
#pragma unroll
          for (int j = 0; j < 4; j++) {
            const int fa = (j >> 1) * 5 + (j & 1) * 3, fh = (j >> 1) * 5 + 2;
            mma16(c0[j], Q[fa][0], Q[fa][1], Q[fa + 1][0], Q[fa + 1][1], Kh[fa], Kh[fa + 1]);
            mma8(c0[j], Qh[j][0], Qh[j][1], Kh[fh]);
            if (!have_halo) c0[j][0] = c0[j][1] = -INFINITY;
            l[j][0] = gt0 ? c0[j][0] : c1[j][0]; l[j][1] = gt1 ? c0[j][1] : c1[j][1];
            max1(j);
          }
#pragma unroll
          for (int j = 0; j < 4; j++) max2(j);
#pragma unroll
          for (int j = 0; j < 4; j++) exps(j);
          float o[12][4] = {}, sm[4][4] = {};
#pragma unroll
          for (int j = 0; j < 4; j++) {
            const int fa = (j >> 1) * 5 + (j & 1) * 3, fh = (j >> 1) * 5 + 2;
            const uint32_t pl = pack_bf16(l[j][0], l[j][1]), pu = pack_bf16(l[4 + j][0], l[4 + j][1]);
            const uint32_t p0 = pl & pmask, p2 = pl & ~pmask, p3 = pu & pmask, p5 = pu & ~pmask, z0 = z << (2 * j + 1), z1 = z << (2 * j + 2);
            mma8(sm[j], pl, pu, 0x3F803F80u);
#pragma unroll
            for (int q = 0; q < 3; q++) {
              const int f = q < 2 ? fa + q : fh;
              mma8(o[3 * j + q], p2, p3, V[f][0]);
              mma16(o[3 * j + q], p0, z0, z1, p5, Vh[f], V[f][1]);
            }
            asm volatile("rcp.approx.ftz.f32 %0, %0;" : "+f"(sm[j][0]));
            asm volatile("rcp.approx.ftz.f32 %0, %0;" : "+f"(sm[j][2]));
          }
#pragma unroll
          for (int i = 0; i < 12; i++) z &= __float_as_uint(o[i][0]);
          bar_sync_p(wg == 0, NB_HALO + z, 256);
          uint32_t O[10][2];
#pragma unroll
          for (int j = 0; j < 4; j++) {
            const int fa = (j >> 1) * 5 + (j & 1) * 3, fh = (j >> 1) * 5 + 2;
            const float r0 = sm[j][0], r1 = sm[j][2];
#pragma unroll
            for (int q = 0; q < 3; q++) {
              const int f = q < 2 ? fa + q : fh;
              const float* e = o[3 * j + q];
              const uint32_t o0 = pack_bf16(e[0] * r0, e[1] * r0), o1 = pack_bf16(e[2] * r1, e[3] * r1);
              if (q < 2 || !(j & 1)) { O[f][0] = o0; O[f][1] = o1; }
              else { O[f][0] = t >= 2 ? o0 : O[f][0]; O[f][1] = t >= 2 ? o1 : O[f][1]; }
            }
          }
          mbar_wait(sb + B_GD, 0);
          const uint32_t oa = sb + O_OST + wg * 2 * STG + (w * 16 + (lane & 15)) * 160 + (lane >> 4) * 16;
#pragma unroll
          for (int i = 0; i < 5; i++) stsm4(oa + i * 32, O[2 * i][0], O[2 * i][1], O[2 * i + 1][0], O[2 * i + 1][1]);
        }
      }
      {
        CTXW();
        fence_async_smem();
        bar_arrive(wg ? NB_LEAD : NB_ATT, 160);
        PTP(lead, 58 + wg);
        const uint32_t abase = sb + (g & 1) * 4160 + 4 * (1023 - 4 - 8 * w - (g >> 1) + t);
        float acc[128];
        uint32_t a0[8], a1[8], a2[8], a3[8];
#pragma unroll 1
        for (int c = wg ^ 1; c < 5; c += 2) {
          const uint32_t ab = abase + o_h(c);
          const uint32_t db = ((SB + o_u(c) + UZ - 16) >> 4) | 0x10000u;
          mbar_wait(sb + B_U + 8 * c, 0);
          load_pair<0>(a0, ab); load_pair<1>(a1, ab); load_pair<2>(a2, ab);
          PTP(lead, 85 + c);
          bar_sync(c ? NB_TOK + wg : NB_HALO, 256);
          fence_regs(acc);
          mma_pair<0>(acc, a0, db);
          load_pair<3>(a3, ab);
          mma_pair<1>(acc, a1, db); wg_wait<1>();  load_pair<4>(a0, ab);
          if (lead) PT(90 + c);
          mma_pair<2>(acc, a2, db); wg_wait<1>();  load_pair<5>(a1, ab);
          mma_pair<3>(acc, a3, db); wg_wait<1>();  load_pair<6>(a2, ab);
          mma_pair<4>(acc, a0, db); wg_wait<1>();  load_pair<7>(a3, ab);
          mma_pair<5>(acc, a1, db);
          mma_pair<6>(acc, a2, db);
          bar_arrive_p(c < 4, NB_TOK + (wg ^ 1), 256);
          mma_pair<7>(acc, a3, db);
          bar_arrive_p(c == 4, NB_TOK, 256);
          wg_wait<0>();
          fence_regs(acc);
          PTPL(lead, 95 + c);
          bar_sync(NB_RFREE + wg, 256);
          const uint32_t pb = sb + (w < 2 ? o_h(c) + w * 4160 : w == 2 ? o_u(c) : o_x(c)) + lane * 16;
          if (lane < 2 * w) sts128(pb, 0, 0, 0, 0);
#pragma unroll
          for (int q = 0; q < 8; q++) {
            uint32_t p[4];
#pragma unroll
            for (int i = 0; i < 4; i++) {
              const int nu = 4 * q + i;
              p[i] = pack_bf16(acc[4 * nu], acc[4 * nu + 1]);
              if (nu > 0) p[i] = hadd2(p[i], pack_bf16(acc[4 * nu - 2], acc[4 * nu - 1]));
            }
            stsm4t(pb + w * 32 + q * 512, p[0], p[1], p[2], p[3]);
            if (q == 3) bar_arrive_p(c == 4, NB_RFULL + 1, 256);
          }
          if (c < 4) bar_arrive(NB_RFULL + wg, 256);
          if (lead) PT(140 + c);
        }
        if (wg) {
          const int yb = (lds32(sb + O_EPOCH) & 1) * 640;
              conv_reduce<1, 2>(sb, 4, tid - 128, yb + 512 + ((vb & 0x61) | (vb & 6) << 2 | (vb >> 2 & 6)), 14, 128);
          bar_arrive(12, 256);
          PTPL(lead, 45);
        }
      }
    }
    if (warp < 4) {
      CTXW();
      const uint32_t rsb = mapa(sb, (blockIdx.x & 1) ^ 1);
      const uint32_t ba = sb + O_BT + ((lane >> 4) * 8 + (lane & 7)) * 128 + (((2 * w + ((lane >> 3) & 1)) ^ ((lane & 1) << 2 | (lane >> 1 & 3))) << 4);
      mbar_wait(sb + B_P3F, 0);
      if (lead) PT(145);
      float acc[80];
#pragma unroll
      for (int ks = 0; ks < 10; ks++) {
        if (ks == NPRE) {
          if (NPRE) { wg_wait<0>(); mbar_arrive2_p(lead, sb + B_P3E + 8 * NPRE, rsb + B_P3E + 8 * NPRE); }
          bar_sync_p(blockIdx.x < 128, NB_TOK, 256);
        }
        PTP(lead, 146 + ks);
        const uint64_t da = mkdesc(SB + o_p3(ks), 1024, 1024, 1), db = mkdesc(SB + o_p3(ks) + 8192, 16, 1024, 1);
        wg_fence();
#pragma unroll
        for (int j = 0; j < 4; j++) wgmma_ss_n160<0, 1, 0>(acc, da + j * 128, db + j * 2, j | ks);
        wg_commit();
        if (ks < 9) mbar_wait(sb + B_P3F + 8 * (ks + 1), 0);
        if (ks >= 1 && ks <= 4 && ks != NPRE) { wg_wait<1>(); mbar_arrive2_p(lead, sb + B_P3E + 8 * ks, rsb + B_P3E + 8 * ks); }
      }
      wg_wait<0>();
      fence_regs(acc);
      PTPL(lead, 156);
#pragma unroll
      for (int i = 0; i < 10; i++) {
        stsm4t(ba + i * 2048, pack_bf16(acc[8 * i], acc[8 * i + 1]), pack_bf16(acc[8 * i + 2], acc[8 * i + 3]),
               pack_bf16(acc[8 * i + 4], acc[8 * i + 5]), pack_bf16(acc[8 * i + 6], acc[8 * i + 7]));
        if (i & 1) bar_arrive(1 + (i >> 1), 256);
      }
      if (lead) PT(157);
    }
  } else if (warp < 12) {
    reg_dec<RH>();
    const int hw = warp - 8;
    init_rest();
    ctx = __shfl_sync(~0u, make_ctx(), 0);
    const int yrow = (ctx & 0x61) | (ctx & 6) << 2 | (ctx >> 2 & 6);
    if (ctx < 65536) {
      CTXU();
      const int pr = hw >> 1, hh = hw & 1, tk = vb & 63, odd = (lane >> 2) & 1;
      const uint32_t sel0 = odd ? 0x7632 : 0x5410, sel1 = odd ? 0x5410 : 0x7632;
      const uint32_t in = sb + o_kin(pr), fb = sb + B_KF + 8 * pr, out = sb + O_Y + pr * 8192;
      const uint32_t oa = out + (2 * lane + odd) * 64 + (((3 - 2 * hh) ^ (lane & 3)) << 4), ia = in + hh * 2048 + lane * 4;
      auto fetch = [&](int c) {
        wait_until(t0, KT0 + c * KTD + (((KPM == 0 ? (vb * 37) & 63 : KPM == 1 ? (vb & 14) * 4 : KPM == 2 ? (vb & 15) * 4 : KPM == 3 ? (vb >> 4) * 8 : KPM == 4 ? ((vb >> 1) * 37) & 63 : ((vb & 14) * 4 + (((vb >> 4) + 1) & 2) * 2)) * KPH) >> 6));
        if (elect_one()) {
          const int kb = 2 * c + (vb >> 6);
          mbar_expect_tx(fb, 69 * 128);
          tma2(in, &M.k_ld, kb * 64, 32 * tk - 4, fb);
          tma2(in + 36 * 128, &M.v_ld, kb * 64, 32 * tk - 1, fb);
          PT(20 + c);
        }
        __syncwarp();
      };
      if (hh == 0) fetch(pr);
      const uint4* skp = (const uint4*)shift_k + (2 * pr + (vb >> 6)) * 32 + lane;
      uint4 sk = __ldg(skp), sk1 = __ldg(skp + 128), sk2 = __ldg(skp + (pr ? 0 : 256));
#pragma unroll 1
      for (int c = pr; c < 5; c += 2) {
        {
          mbar_wait(fb, (c >> 1) & 1);
          if (hh == 0 && lane == 0) PT(25 + c);
          uint32_t k[20], o[17];
#pragma unroll
          for (int i = 0; i < 20; i++) { k[i] = lds32(ia + i * 128); if (i >= 3) o[i - 3] = lds32(ia + (33 + i) * 128); }
          fence_async_smem();
          bar_sync(12 + pr, 64);
          if (hh == 0) {
            if (c < 3) fetch(c + 2);
            else if (lane == 0) mbar_arrive(sb + B_KVD + 8 * (c - 3));
          }
          const uint32_t w0 = prmt(sk.x, sk.z, 0x5410), w1 = prmt(sk.x, sk.z, 0x7632), w2 = prmt(sk.y, sk.w, 0x5410), w3 = prmt(sk.y, sk.w, 0x7632);
#pragma unroll
          for (int i = 0; i < 17; i++) o[i] = hmul2(hfma2(k[i + 3], w0, hfma2(k[i + 2], w1, hfma2(k[i + 1], w2, hmul2(k[i], w3)))), o[i]);
          sk = sk1; sk1 = sk2;
#pragma unroll
          for (int i = 0; i < 4; i++) {
            const int e = 8 * (i >> 1) + (i & 1);
            const uint32_t a = (oa ^ ((i >> 1) * 16)) + (i & 1) * 4096;
            sts128(a, prmt(o[7 + e], o[6 + e], sel0), prmt(o[5 + e], o[4 + e], sel0), prmt(o[3 + e], o[2 + e], sel0), prmt(o[1 + e], o[e], sel0));
            sts128(a ^ 64, prmt(o[7 + e], o[6 + e], sel1), prmt(o[5 + e], o[4 + e], sel1), prmt(o[3 + e], o[2 + e], sel1), prmt(o[1 + e], o[e], sel1));
          }
          bar_sync(12 + pr, 64);
        }
        if (hh) {
          fence_async_smem();
          if (elect_one()) {
            const int kb = 2 * c + (vb >> 6);
            tma3_store(&M.kv_st, 0, kb * 64, 63 - tk, out);
            tma3_store(&M.kv_st, 0, 640 + kb * 64, 63 - tk, out + 4096);
            bulk_commit(); bulk_wait_all();
            mbar_arrive(sb + (c == 4 ? B_KVD + 16 : B_KVS + 4 * (c & 2)));
            PTL(35 + c);
          }
          __syncwarp();
        }
      }
    }
    CTXU();
    const int g = lane >> 2, t = lane & 3, row = 8 * hw + g;
    const uint32_t go = (tb * 160 + row) * 80 + cb * 8 + t;
    const int yb = __shfl_sync(~0u, get_epoch() & 1, 0) * 640;
    uint4 T[10];
    if (hw == 2) {
      if (main_cta) { mbar_wait(sb + B_LAST, 0); mbar_wait(sb + B_S15, 1); }
      if (elect_one()) {
        mbar_expect_tx(sb + B_Q, 20480);
#pragma unroll
        for (int h = 0; h < 2; h++) tma2(sb + O_QT + h * 10240, &M.q_ld, cb * 64 + 32 * h, tb * 160, sb + B_Q);
      }
      __syncwarp();
    }
    mbar_wait(sb + B_Q, 0);
#pragma unroll
    for (int i = 0; i < 10; i++) lds128(sb + O_QT + (i & 1) * 10240 + (i >> 1) * 2048 + row * 64 + t * 16, T[i].x, T[i].y, T[i].z, T[i].w);
    fence_async_smem();
    bar_sync(12 + (hw >> 1), 64);
    if (!(tid & 63)) mbar_arrive(sb + B_QD);
    if (tid == 256) PTL(40);
    if (main_cta) {
      bar_arrive(NB_RFREE, 256);
      bar_arrive(NB_RFREE + 1, 256);
      auto red = [&](int c) {
        const int wg = (c & 1) ^ 1;
        conv_reduce<0, 2>(sb, c, tid - 256, yb + 128 * c + yrow, NB_RFULL + wg, 256);
        if (hw == 3 && elect_one()) flag_add(CNT_Y(4 * c + (vb >> 5)), 1);
        if (tid == 256) PTL(41 + c);
        if (c < 3) bar_arrive(NB_RFREE + wg, 256);
        if (c == 2) {
          bar_sync(NB_HELP, 128);
          if (tid == 256) { mbar_arrive(sb + B_P3E); mbar_arrive_remote(sb + B_P3E, rank ^ 1); }
        }
      };
      if (hw == 3) {
        mbar_wait(sb + B_KVD + 16, 0);
        if (elect_one()) { flag_release(CNT_KV(4 + (vb >> 6))); PTL(32); }
        __syncwarp();
      }
#pragma unroll 1
      for (int c = 0; c < 4; c++) red(c);
      conv_reduce<0, 1>(sb, 4, tid - 256, yb + 512 + yrow, NB_RFULL + 1, 256);
      if (hw == 3 && elect_one()) flag_add(CNT_Y(16 + (vb >> 5)), 1);
    }
    uint32_t G[5];
    mbar_wait(sb + B_G, 0);
#pragma unroll
    for (int q = 0; q < 5; q++) { uint16_t v; asm volatile("ld.shared.u16 %0, [%1];" : "=h"(v) : "r"(sb + O_GT + (32 * q + row) * 2)); G[q] = prmt(v, 0, 0x1010); }
    auto gate_q = [&]() {
#pragma unroll
      for (int i = 0; i < 10; i++) { const uint32_t c = G[i >> 1] ^ 0x80008000u; T[i] = make_uint4(hmul2(T[i].x, c), hmul2(T[i].y, c), hmul2(T[i].z, c), hmul2(T[i].w, c)); }
    };
    gate_q();
    const uint32_t so = __shfl_sync(~0u, sb + O_BT + row * 128 + ((t ^ ((g & 1) << 2 | g >> 1)) << 4), lane);
    uint4* const op = (uint4*)__shfl_sync(~0u, (unsigned long long)((uint4*)outp + go), lane);
    if (main_cta) bar_sync(12, 256);
    const uint32_t ya = sb + O_Y + lane * 64 + ((hw ^ ((lane >> 1) & 3)) << 4);
    auto empty = [](uint32_t m) { return (m & 0xFFFFu) == 0 || m < 0x10000u; };
    int redo = blockIdx.y;
#pragma unroll 1
    do {
      if (redo) {
#pragma unroll 1
        for (int i = 0; i < (tb < 12 ? 10 : 8); i++) {
          const uint32_t a = ya + (i & 1) * 10240 + (i >> 1) * 2048;
          uint4 v;
          lds128(a, v.x, v.y, v.z, v.w);
          while (empty(__vimin3_u16x2(__vminu2(v.x, v.y), v.z, v.w)))
            asm volatile("ld.relaxed.gpu.global.v4.b32 {%0,%1,%2,%3}, [%4];" : "=r"(v.x), "=r"(v.y), "=r"(v.z), "=r"(v.w)
                         : "l"((const uint4*)g_y2T + (yb + cb * 64 + 32 * (i & 1) + lane) * 256 + tb * 20 + 4 * (i >> 1) + hw) : "memory");
          sts128(a, v.x, v.y, v.z, v.w);
        }
        __syncwarp();
#pragma unroll
        for (int i = 0; i < 10; i++) if (i < 8 || tb < 12) T[i] = __ldg((const uint4*)xq + go + (i >> 1) * 2560 + (i & 1) * 4);
        gate_q();
        PTL(49);
      }
      uint32_t m = ~0u;
#pragma unroll
      for (int h = 0; h < 2; h++) {
        if (h) mbar_wait(sb + B_Y + 8, 0); else mbar_wait_wd(sb + B_Y, 0, t0);
        if (tid == 256) PTL(46);
#pragma unroll
        for (int q = 0; q < 5; q++) {
          uint4 y;
          ldsm4t(y.x, y.y, y.z, y.w, ya + h * 10240 + q * 2048);
          const uint32_t mq = __vimin3_u16x2(__vimin3_u16x2(m, y.x, y.y), y.z, y.w);
          m = q == 4 && tb == 12 ? m : mq;
          uint4& r = T[2 * q + h];
          r = make_uint4(hmul2(r.x, y.x), hmul2(r.y, y.y), hmul2(r.z, y.z), hmul2(r.w, y.w));
        }
      }
      redo = __any_sync(~0u, empty(m));
    } while (redo);
    if (tid == 256) PTL(47);
#pragma unroll
    for (int q = 0; q < 5; q++) {
      const uint32_t c = hfma2(G[q], 0xBF80BF80u, 0x3F803F80u);
      bar_sync(1 + q, 256);
      if (q == 4) mbar_arrive_p(tid == 256, sb + B_DONE);
#pragma unroll
      for (int h = 0; h < 2; h++) {
        uint4 u;
        lds128((so ^ (h * 64)) + q * 4096, u.x, u.y, u.z, u.w);
        const uint4& r = T[2 * q + h];
        if (q < 4 || tb < 12)
          asm volatile("st.global.v4.b32 [%0], {%1,%2,%3,%4};" ::"l"(op + q * 2560 + h * 4), "r"(hfma2(u.x, c, r.x)), "r"(hfma2(u.y, c, r.y)), "r"(hfma2(u.z, c, r.z)), "r"(hfma2(u.w, c, r.w)) : "memory");
      }
    }
  } else {
    reg_dec<RP>();
    uint4 gwv = make_uint4(0, 0, 0, 0);
    if (warp == 15) {
      const int p = cta_pair(), rank = blockIdx.x & 1;
      asm volatile("barrier.cluster.wait.aligned;" ::: "memory");
      if (blockIdx.x >= 128) cluster_sync();
      else {
#pragma unroll 1
        for (int ks = 1;; ks += 2) {
          mbar_wait(sb + B_EMPTY + 8 * (ks & 7), ((ks >> 3) & 1) ^ 1);
          spin_until(t0, PT1 + (ks - 1) * PTD - max(ks - PTS, 0) * PTA);
          if (elect_one()) { mbar_expect_tx(sb + B_FULL + 8 * (ks & 7), WST); p1_load_w(ks, p, rank); PT(100 + ks); }
          if (ks == 19) break;
          const int kn = ks + 1;
          mbar_wait(sb + B_EMPTY + 8 * (kn & 7), ((kn >> 3) & 1) ^ 1);
          spin_until(t0, PT1 + ks * PTD - PTE - max(kn - PTS, 0) * PTA);
          if (elect_one()) { mbar_expect_tx(sb + B_FULL + 8 * (kn & 7), 16384 + WST); p1_load_x(kn, p, rank); p1_load_w(kn, p, rank); PT(100 + kn); }
        }
        if (elect_one()) mbar_arrive(sb + B_LAST);
#pragma unroll 1
        for (int i = 0; i < 2; i++) {
          mbar_wait(sb + B_KVS + 8 * i, 0);
          if (elect_one()) { flag_release(CNT_KV(2 * i + (p >> 5))); PTL(30 + i); }
          __syncwarp();
        }
        mbar_wait(sb + B_S19, 0);
      }
    } else {
      if (threadIdx.x < 384 + 80) gwv = __ldg((const uint4*)gate_w + threadIdx.x - 384);
      init_rest();
    }
    ctx = __shfl_sync(~0u, make_ctx(), 0);
    CTXU();
    if (warp == 12) {
        unsigned epoch = 0;
      if (lane == 0) epoch = *(volatile unsigned*)(g_launch + 32 * vb) + 1;
      if (main_cta) { sts128(sb + O_GW + lane * 16, gwv.x, gwv.y, gwv.z, gwv.w); bar_arrive(NB_G, 96); }
      if (lane == 0) {
        if ((sb & 0xFFFFFF) != SB) __trap();
        sts32(sb + O_EPOCH, epoch);
        mbar_arrive(sb + B_EP);
      }
      if (main_cta && rank) {
#pragma unroll
        for (int f = 0; f < 5; f++) st_relaxed(g_halo + vb * 160 + lane + 32 * f, ~0u, ~0u, ~0u, ~0u);
      }
      __syncwarp();
      if (elect_one()) flag_release(g_launch + 32 * vb);
      __syncwarp();
      if (main_cta) {
        uint4 h0 = make_uint4(0, 0, 0, 0);
        if (lane < 5) {
          h0 = __ldg((const uint4*)(ssm_k + (size_t)(128 * lane + vb) * 2048));
          h0.x = prmt(pack_bf16(bf_lo(h0.x) + bf_lo(__ldg(ssm_D + 128 * lane + vb)), 0.f), h0.x, 0x7610);
        }
        epoch = __shfl_sync(~0u, epoch, 0);
        if (!rank && mt > 0) {
          flag_wait(g_launch + 32 * (vb - 1), epoch);
          if (lane < 2) mbar_arrive(sb + B_HC);
          __syncwarp();
        }
        const int ze = lane & 7;
        const uint32_t za = sb + (lane < 8 ? o_u(ze) + UZ : lane < 24 ? o_h(ze) + (lane >> 4) * 4160 + 4096 : o_u(ze) + 512);
        const uint16_t* hp = ssm_k + (size_t)vb * 2048 + 8;
        const uint16_t* up = g_kvT + (size_t)vb * 2048;
        const unsigned* fp = CNT_KV(vb >> 6);
        sts128(sb + O_Y - 512 + lane * 16, 0, 0, 0, 0);
        mbar_wait(sb + B_LAST, 0);
        mbar_wait(sb + B_S13, 1);
#pragma unroll
        for (int c = 0; c < 5; c++) {
          if (c == 0 || c == 3) {
            mbar_wait(sb + B_KVD + (c ? 8 : 0), 0);
#pragma unroll
            for (int e = c; e < (c ? 5 : 3); e++) sts128(sb + o_u(e) + lane * 16, 0, 0, 0, 0);
            if (ze >= c && ze < (c ? 5 : 3)) sts128(za, h0.x, h0.y, h0.z, h0.w);
            fence_async_smem();
            __syncwarp();
            if (elect_one()) {
#pragma unroll
              for (int e = c; e < (c ? 5 : 3); e++) {
                mbar_expect_tx(sb + B_U + 8 * e, 3 * 4096 - 16);
                if (c || e == 0) bulk_load(sb + o_u(e) + UZ + 16, hp + 128 * 2048 * e, 4080, sb + B_U + 8 * e);
              }
            }
          }
                    if (!(c & 1)) { flag_wait(fp + 32 * c, 64 * epoch); __syncwarp(); }
          if (elect_one()) {
            bulk_load(sb + o_h(c), up + 128 * 2048 * c, 4096, sb + B_U + 8 * c);
            bulk_load(sb + o_h(c) + 4160, up + (640 + 128 * c) * 2048, 4096, sb + B_U + 8 * c);
            if (c == 1) {
#pragma unroll
              for (int e = 1; e < 3; e++) bulk_load(sb + o_u(e) + UZ + 16, hp + 128 * 2048 * e, 4080, sb + B_U + 8 * e);
            }
            PTL(10 + c);
          }
        }
        mbar_wait(sb + B_OR, 0);
        if (elect_one()) {
#pragma unroll 1
          for (int i = 0; i < 40; i++) bulk_store(g_y2T + (size_t)((~epoch & 1) * 640 + 5 * vb) * 2048 + i * 256, sb + O_Y - 512, 512);
          bulk_commit(); bulk_wait_read();
          PTL(33);
        }
      }
    } else if (warp != 15) {
        const int r = warp - 13;
      if (main_cta) {
        if (rank && lane == 0) mbar_expect_tx(sb + B_HX0, 1280);
        const int t = lane & 3, grow = hg * 16 + (lane & 15);
        const uint32_t ga = sb + grow * 128 + (((4 * r + (lane >> 4)) ^ (lane & 7)) << 4);
        const uint32_t gp = sb + O_GW + 64 * r + 4 * t;
        float s0 = 0.f, s1 = 0.f;
        if (tid < 384 + 80) sts128(sb + O_GW + (tid - 384) * 16, gwv.x, gwv.y, gwv.z, gwv.w);
        bar_sync(NB_G, 96);
#pragma unroll 1
        for (int ks = 0; ks < 20; ks += 2) {
          uint32_t x[8], gw[4];
#pragma unroll
          for (int i = 0; i < 4; i++) gw[i] = lds32(gp + ks * 64 + i * 16);
          mbar_wait_wd(sb + B_FULL + 8 * (ks & 7), (ks >> 3) & 1, t0);
          if (r == 0 && lane == 0) PT(120 + ks);
          ldsm4(x[0], x[1], x[2], x[3], ga + o_px(ks)); ldsm4(x[4], x[5], x[6], x[7], (ga ^ 32) + o_px(ks));
#pragma unroll
          for (int i = 0; i < 8; i++) x[i] = hmul2(x[i], gw[i >> 1]);
          if (lane < 2) mbar_arrive(sb + B_EMPTY + 8 * (ks & 7) + 8 * lane + (x[0] & x[7] & threadIdx.y));
#pragma unroll
          for (int i = 0; i < 8; i += 4) {
            s0 += (bf_lo(x[i]) + bf_hi(x[i])) + (bf_lo(x[i + 2]) + bf_hi(x[i + 2]));
            s1 += (bf_lo(x[i + 1]) + bf_hi(x[i + 1])) + (bf_lo(x[i + 3]) + bf_hi(x[i + 3]));
          }
        }
        s0 += __shfl_xor_sync(~0u, s0, 1); s1 += __shfl_xor_sync(~0u, s1, 1);
        s0 += __shfl_xor_sync(~0u, s0, 2); s1 += __shfl_xor_sync(~0u, s1, 2);
        if (t < 2) sts32(sb + O_GP + r * 64 + (8 * t + (lane >> 2)) * 4, __float_as_uint(t ? s1 : s0));
        if (lane == 0) mbar_arrive(sb + B_GD);
        if (r == 0) bar_arrive(NB_G, 64);
        if (!rank) {
          uint4 d[3];
          if (mt > 0) {
            const uint4* hp = g_halo + (vb - 1) * 160 + r * 64 + lane;
            mbar_wait_wd(sb + B_HC, 0, t0);
            mbar_wait_wd(sb + B_HX + 56, 0, t0);
            if (HDL) { const uint32_t t1 = clk(); spin_until(t1, HDL); }
            for (;;) {
              bool ok = true;
#pragma unroll
              for (int f = 0; f < 3; f++) {
                asm volatile("ld.relaxed.gpu.global.v4.b32 {%0,%1,%2,%3}, [%4];" : "=r"(d[f].x), "=r"(d[f].y), "=r"(d[f].z), "=r"(d[f].w) : "l"(hp + 32 * f) : "memory");
              }
#pragma unroll
              for (int f = 0; f < 3; f++) ok = ok && max(max(d[f].x, d[f].y), max(d[f].z, d[f].w)) != ~0u;
              if (__all_sync(~0u, ok)) break;
              if (clk() - t0 > 0x70000000u) __trap();
            }
          } else {
#pragma unroll
            for (int f = 0; f < 3; f++) d[f] = make_uint4(0, 0, 0, 0);
          }
#pragma unroll
          for (int f = 0; f < 3; f++) stsm4(sb + O_HIN + r * 1024 + f * 512 + lane * 16, d[f].x, d[f].y, d[f].z, d[f].w);
          __syncwarp();
          if (lane == 0) { mbar_arrive(sb + B_HX0); PTL(15 + r); }
        }
        if (r == 1) {
          bar_sync(NB_G, 64);
          if (lane < 16) {
            const uint32_t pa = sb + O_GP + lane * 4;
            const float z = __uint_as_float(lds32(pa)) + __uint_as_float(lds32(pa + 64));
            g_gate[2 * (mt * 128 + hg * 16 + lane) + par] = (uint16_t)pack_bf16(__fdividef(1.f, 1.f + __expf(-bf_lo(pack_bf16(z, 0.f)))), 0.f);
          }
          __syncwarp();
          if (elect_one()) flag_release(CNT_O(rt));
        }
      }
      mbar_wait_wd(sb + B_EP, 0, t0);
      const unsigned epoch = lds32(sb + O_EPOCH);
      if (main_cta) mbar_wait_wd(sb + B_P3E, 0, t0);
      const uint32_t yd = __shfl_sync(~0u, sb + O_Y + r * 10240 + threadIdx.y, 0), yb = __shfl_sync(~0u, sb + B_Y + 8 * r + threadIdx.y, 0);
      const int y1 = __shfl_sync(~0u, (epoch & 1) * 640 + cb * 64 + 32 * r + threadIdx.y, 0), y2 = __shfl_sync(~0u, tb * 5 + threadIdx.y, 0);
      if (elect_one()) { pf_map(&M.y_ld); mbar_expect_tx(yb, 10240); }
      __syncwarp();
      flag_wait_wd(CNT_Y(2 * cb + r), 32 * epoch, t0);
      __syncwarp();
      if (elect_one()) { tma3(yd, &M.y_ld, 0, y1, y2, yb); PTL(17 + r); }
      __syncwarp();
      mbar_wait_wd(sb + B_DONE, 0, t0);
    } else {
      const unsigned epoch = get_epoch();
      if (main_cta) {
        if (elect_one()) { pf_map(&M.o_st); pf_map(&M.wo); pf_map(&M.o_ld); }
        __syncwarp();
        bar_sync(NB_LEAD, 160);
        if (elect_one()) tma3_store(&M.o_st, hg * 80, par, mt * 128 + 64, sb + O_OST + 2 * STG);
        bar_sync(NB_ATT, 160);
        if (elect_one()) {
          tma3_store(&M.o_st, hg * 80, par, mt * 128, sb + O_OST);
          bulk_commit(); bulk_wait_all();
          flag_release(CNT_O(rt));
          mbar_arrive(sb + B_OR); mbar_arrive(sb + B_OR);
          PTL(3);
        }
        __syncwarp();
      }
      mbar_wait(sb + B_QD, 0);
#pragma unroll 1
      for (int ks = 0; ks < 5; ks++)
        if (elect_one()) tma2(sb + o_p3(ks), &M.wo, cb * 64, ks * 64, sb + B_P3F + 8 * ks);
      if (lane < 4) flag_wait(CNT_O(8 * (lane & 1) + min(7, (80 * tb + 79 * (lane >> 1)) >> 7)), 16 * epoch);
      __syncwarp();
      if (elect_one()) {
        PTL(4);
        mbar_arrive_remote(sb + B_P3R, rank ^ 1);
        mbar_expect_tx(sb + B_G, 320);
        bulk_load(sb + O_GT, g_gate + tb * 160, 320, sb + B_G);
      }
      mbar_wait(sb + B_P3R, 0);
      auto load_o = [&](int ks) {
        tma2_mc(sb + o_p3(ks) + 8192 + rank * 10240, &M.o_ld, ks * 64, tb * 160 + rank * 80, sb + B_P3F + 8 * ks);
        mbar_expect_tx(sb + B_P3F + 8 * ks, P3S);
      };
      auto load_wo = [&](int ks) { tma2(sb + o_p3(ks), &M.wo, cb * 64, ks * 64, sb + B_P3F + 8 * ks); };
#pragma unroll 1
      for (int ks = 0; ks < 5; ks++)
        if (elect_one()) load_o(ks);
#pragma unroll
      for (int ks = 5; ks < 10; ks++) {
        if (ks > 5 || main_cta) mbar_wait(sb + B_P3E + 8 * (ks - 5), 0);
        if (elect_one()) {
          load_o(ks); load_wo(ks);
          PTL(ks);
        }
      }
    }
  }
}

typedef CUresult (*PFN_enc)(CUtensorMap*, CUtensorMapDataType, cuuint32_t, void*, const cuuint64_t*, const cuuint64_t*, const cuuint32_t*,
                            const cuuint32_t*, CUtensorMapInterleave, CUtensorMapSwizzle, CUtensorMapL2promotion, CUtensorMapFloatOOBfill);
static void enc(PFN_enc f, CUtensorMap* m, const void* base, int rank, const cuuint64_t* dims, const cuuint64_t* strides, const cuuint32_t* box,
                CUtensorMapSwizzle sw) {
  const cuuint32_t es[5] = {1, 1, 1, 1, 1};
  f(m, CU_TENSOR_MAP_DATA_TYPE_BFLOAT16, rank, (void*)base, dims, strides, box, es, CU_TENSOR_MAP_INTERLEAVE_NONE, sw,
    CU_TENSOR_MAP_L2_PROMOTION_NONE, CU_TENSOR_MAP_FLOAT_OOB_FILL_NONE);
}

extern "C" void kernel_launch(void* const* d_in, const int* in_sizes, int n_in, void* d_out, int out_size) {
  (void)in_sizes; (void)n_in; (void)out_size;
  static PFN_enc f = nullptr;
  static void *kvT, *y2T, *o;
  if (!f) {
    void* p = nullptr;
    cudaDriverEntryPointQueryResult q;
    cudaGetDriverEntryPoint("cuTensorMapEncodeTiled", &p, cudaEnableDefault, &q);
    f = (PFN_enc)p;
    cudaGetSymbolAddress(&kvT, g_kvT); cudaGetSymbolAddress(&y2T, g_y2T); cudaGetSymbolAddress(&o, g_o);
    cudaFuncSetAttribute(fused_kernel, cudaFuncAttributeMaxDynamicSharedMemorySize, SMEM_BYTES);
  }
  Maps M;
  const CUtensorMapSwizzle S0 = CU_TENSOR_MAP_SWIZZLE_NONE, S32 = CU_TENSOR_MAP_SWIZZLE_32B, S64 = CU_TENSOR_MAP_SWIZZLE_64B, S128 = CU_TENSOR_MAP_SWIZZLE_128B;
  const cuuint64_t dpar[3] = {640, 2, 1024}, spar[2] = {1280, 2560};
  const cuuint64_t dw[3] = {640, 640, 3}, sw[2] = {3840, 1280};
  const cuuint64_t dnat[2] = {640, 2048}, snat[1] = {1280};
  const cuuint64_t dT2[3] = {32, 1280, 64}, sT[2] = {4096, 64};
  const cuuint64_t dwo[2] = {640, 640};
  { const cuuint32_t bx[3] = {64, 1, 128}; enc(f, &M.x_par, d_in[0], 3, dpar, spar, bx, S128); }
  { const cuuint32_t bx[3] = {64, 16, 3}; enc(f, &M.w_main, d_in[7], 3, dw, sw, bx, S128); }
  { const cuuint32_t bx[3] = {16, 16, 3}; enc(f, &M.w_tail, d_in[7], 3, dw, sw, bx, S32); }
  { const cuuint32_t bx[3] = {80, 1, 64}; enc(f, &M.o_st, o, 3, dpar, spar, bx, S0); }
  { const cuuint32_t bx[3] = {32, 64, 1}; enc(f, &M.kv_st, kvT, 3, dT2, sT, bx, S64); }
  { const cuuint32_t bx[3] = {32, 32, 5}; enc(f, &M.y_ld, y2T, 3, dT2, sT, bx, S64); }
  { const cuuint32_t bx[2] = {64, 36}; enc(f, &M.k_ld, d_in[1], 2, dnat, snat, bx, S0); }
  { const cuuint32_t bx[2] = {64, 33}; enc(f, &M.v_ld, d_in[2], 2, dnat, snat, bx, S0); }
  { const cuuint32_t bx[2] = {32, 160}; enc(f, &M.q_ld, d_in[0], 2, dnat, snat, bx, S0); }
  { const cuuint32_t bx[2] = {64, 64}; enc(f, &M.wo, d_in[8], 2, dwo, snat, bx, S128); }
  { const cuuint32_t bx[2] = {64, 80}; enc(f, &M.o_ld, o, 2, dnat, snat, bx, S128); }
  fused_kernel<<<130, 512, SMEM_BYTES, cudaStreamPerThread>>>((const uint16_t*)d_in[0], (const uint16_t*)d_in[7], (const uint16_t*)d_in[9], M, (const uint16_t*)d_in[3], (const uint16_t*)d_in[4], (const uint16_t*)d_in[5],
                                                              (uint16_t*)d_out);
}
```
